```python
import torch

def _softmax(x, axis=-1):
    return torch.softmax(x, dim=axis)

def _gelu(x):
    return torch.nn.functional.gelu(x, approximate='tanh')

def _silu(x):
    return torch.nn.functional.silu(x)

def _sigmoid(x):
    return torch.sigmoid(x)

def _layernorm(x, axis=-1, eps=1e-05):
    m = x.mean(dim=axis, keepdim=True)
    v = x.var(dim=axis, keepdim=True, unbiased=False)
    return (x - m) / torch.sqrt(v + eps)

def _scatter_add(tgt, idx, src, axis=0):
    return tgt.clone().index_add_(axis, idx, src)

def _segment_sum(src, seg, n):
    out = torch.zeros((n,) + src.shape[1:], dtype=src.dtype)
    return out.index_add_(0, seg, src)

def _pad(x, pw):
    flat = tuple((v for pair in reversed(pw) for v in pair))
    return torch.nn.functional.pad(x, flat)
kernel_name = 'gather_scatter__tensor_product_equiv_mace__graph'

def setup_inputs():

    _w = lambda a: (lambda t: t.to(torch.bfloat16) if t.is_floating_point() else t)(torch.as_tensor(a))
    N, deg = (10000, 32)
    Lmax, C, De = (1, 128, 16)
    M = (Lmax + 1) ** 2
    E = N * deg
    src = (lambda lo, hi, *s: torch.randint(lo, hi, s))(0, N, E).to(torch.int64)
    dst = (lambda lo, hi, *s: torch.randint(lo, hi, s))(0, N, E).to(torch.int64)
    r = (lambda *s: torch.randn(*s, dtype=torch.bfloat16) * 0.05)(E, 3).to(float)
    r = r / (torch.linalg.norm(r, dim=-1, keepdim=True).to(float) + 1e-06)
    rx, ry, rz = (r[:, 0].clone(), r[:, 1].clone(), r[:, 2].clone())
    x2, y2, z2 = (rx * rx, ry * ry, rz * rz)
    sh_list = [torch.ones_like(rx), rx, ry, rz, rx * ry, ry * rz, 2.0 * z2 - x2 - y2, rx * rz, x2 - y2, ry * (3.0 * x2 - y2), rx * ry * rz, ry * (4.0 * z2 - x2 - y2), rz * (2.0 * z2 - 3.0 * x2 - 3.0 * y2), rx * (4.0 * z2 - x2 - y2), rz * (x2 - y2), rx * (x2 - 3.0 * y2)]
    sh16 = torch.stack(sh_list, dim=-1).to(float)
    pad = max(0, M - 16)
    sh_full = torch.cat([sh16, torch.zeros((E, pad), dtype=float)], dim=-1)[:, :M]
    cg = ((lambda *s: torch.randn(*s, dtype=torch.bfloat16) * 0.05)(M, M, M) * (1.0 / float(M))).to(float)
    return {'x': _w(((lambda *s: torch.randn(*s, dtype=torch.bfloat16) * 0.05)(N, M, C) * 0.3).to(float)), 'src': _w(src), 'dst': _w(dst), 'sh': _w(sh_full.to(float)), 'edge_attr': _w(((lambda *s: torch.randn(*s, dtype=torch.bfloat16) * 0.05)(E, De) * 0.3).to(float)), 'cg': _w(cg), 'w_r': _w(((lambda *s: torch.randn(*s, dtype=torch.bfloat16) * 0.05)(De, C) * (1.0 / float(De) ** 0.5)).to(float)), 'w_out': _w(((lambda *s: torch.randn(*s, dtype=torch.bfloat16) * 0.05)(C, C) * (1.0 / float(C) ** 0.5)).to(float))}

def reference(x, src, dst, sh, edge_attr, cg, w_r, w_out):
    N = x.shape[0]
    M = x.shape[1]
    C = x.shape[2]
    h = x[src]
    tp = torch.einsum('uvw,euc,ev->ewc', cg, h, sh)
    rw = edge_attr @ w_r
    msg = tp * rw[:, None, :]
    msg2 = msg.reshape(-1, M * C)
    agg = _segment_sum(msg2, dst, N).reshape(N, M, C)
    out = torch.einsum('nmc,cd->nmd', agg, w_out)
    return out
```

```cpp
#include <cuda_runtime.h>
#include <cuda.h>
#include <cuda_bf16.h>
#include <stdint.h>
#include <stdlib.h>

#define NT 512
#define NCW 12
#define MAXB 144
#define MAXNPB 80
#define KE 5
#define SP 97
#define RECN 2816
#define RP 1512
#define OLN 80
#define NBAR 360
#define R0 168
#define R1 160
#define PREG 24
#define PACE 10.3
#define TDELAY 5400
#define POLLD 1100
#define FULLSEC 0xe0
#define BARPOS 1
#define WFPOS 0
#define WFT 80
#define SLIPTH 600
#define SLIPSUB 300
#define SLIPFROM 24
#define AHEAD 96
#define EARLY 32
#define RAMPF 0.1
#define SPRINT 0
#define SPRINTF 0.1
#define SLIPEND 640
#define RAMP 800

__device__ __align__(1024) uint4 g_cell[MAXB * MAXB * 24];
__device__ __align__(1024) uint4 g_wf[2048];
__device__ __align__(256) ulonglong2 g_sync;
__device__ __align__(256) unsigned g_epoch;
__device__ __align__(256) unsigned g_wfcnt;
#define TLSTAMP(i)
#define TLMAX(i)

constexpr uint32_t sb = 1024;
#define SM_R (2 * SP * 1024 + 128)
#define SM_CTR (SM_R + RP * 4)
#define SM_MISC (SM_CTR + 528)
#define SM_INV (SM_MISC + 80)
#define SM_OFF (SM_INV + 48)
#define SM_REC (SM_R + 0x2000 + RP * 4)
#define SM_OL (SM_REC + RECN * 4)
#define SM_BAR (SM_OL + NCW * OLN * 4)
#define SM_TOTAL (SM_BAR + (NBAR + 16) * 8)
static_assert(SM_TOTAL <= 232448 && SM_OFF + NBAR * 4 <= SM_R + 0x2000, "shared memory");
static_assert(4 + RECN / 2 + SP + 2 <= RP && RECN / 8 + 8 <= NBAR && NBAR % 24 == 0, "tables");
#define SC_STG 0
#define CP 400
#define SC_TMP ((MAXB + 1) * CP)
#define SC_TABB (SC_TMP + 3072 * 8)
#define SC_TABC (SC_TABB + 41 * 512)
#define SC_TABA (SC_TABC + NCW * 512)
#define SC_ZEND (SC_TABB + 4 * NT * 16)
#define SC_CNT SC_ZEND
#define SC_KEY (SC_CNT + 640)
#define SC_MAP (SC_KEY + 192)
#define WSL 5
#define SC_WR ((2 * SP - WSL) * 1024 + 128)
#define SC_CG (SC_WR + 16 * 272)
static_assert(SC_TABA + 2048 <= SC_ZEND && RECN <= 3072, "scratch");

__device__ __forceinline__ uint32_t pack_bf16(float lo, float hi) {
    uint32_t r;
    asm("cvt.rn.bf16x2.f32 %0, %1, %2;" : "=r"(r) : "f"(hi), "f"(lo));
    return r;
}
__device__ __forceinline__ uint32_t s2u(const void* p) { return (uint32_t)__cvta_generic_to_shared(p); }
__device__ __forceinline__ void mbar_wait0(uint32_t a) {
    asm volatile(
        "{\n.reg .pred p, q;\n.reg .u32 n;\nmov.u32 n, 0;\n"
        "LAB_WAIT:\nmbarrier.try_wait.parity.shared.b64 p, [%0], 0;\nadd.u32 n, n, 1;\nsetp.lt.and.u32 q, n, 1000000, !p;\n@q bra LAB_WAIT;\n}" ::"r"(a)
        : "memory");
}
__device__ __forceinline__ uint32_t lds8(uint32_t a) { uint32_t v; asm volatile("ld.shared.u8 %0, [%1];" : "=r"(v) : "r"(a) : "memory"); return v; }
__device__ __forceinline__ uint32_t lds16(uint32_t a) { uint32_t v; asm volatile("ld.shared.u16 %0, [%1];" : "=r"(v) : "r"(a) : "memory"); return v; }
__device__ __forceinline__ uint32_t lds32(uint32_t a) { uint32_t v; asm volatile("ld.shared.u32 %0, [%1];" : "=r"(v) : "r"(a) : "memory"); return v; }
__device__ __forceinline__ uint2 lds64(uint32_t a) {
    uint2 v; asm volatile("ld.shared.v2.u32 {%0,%1}, [%2];" : "=r"(v.x), "=r"(v.y) : "r"(a) : "memory"); return v;
}
__device__ __forceinline__ uint4 lds128(uint32_t a) {
    uint4 v; asm volatile("ld.volatile.shared.v4.u32 {%0,%1,%2,%3}, [%4];" : "=r"(v.x), "=r"(v.y), "=r"(v.z), "=r"(v.w) : "r"(a) : "memory"); return v;
}
__device__ __forceinline__ void sts16(uint32_t a, uint32_t v) { asm volatile("st.shared.u16 [%0], %1;" ::"r"(a), "h"((unsigned short)v) : "memory"); }
__device__ __forceinline__ void sts32(uint32_t a, uint32_t v) { asm volatile("st.shared.u32 [%0], %1;" ::"r"(a), "r"(v) : "memory"); }
__device__ __forceinline__ void sts64(uint32_t a, uint32_t x, uint32_t y) { asm volatile("st.shared.v2.u32 [%0], {%1,%2};" ::"r"(a), "r"(x), "r"(y) : "memory"); }
__device__ __forceinline__ void sts128(uint32_t a, uint32_t x, uint32_t y, uint32_t z, uint32_t w) {
    asm volatile("st.shared.v4.u32 [%0], {%1,%2,%3,%4};" ::"r"(a), "r"(x), "r"(y), "r"(z), "r"(w) : "memory");
}
__device__ __forceinline__ uint32_t atoms_add(uint32_t a, uint32_t v) {
    uint32_t r;
    asm volatile("atom.shared.add.u32 %0, [%1], %2;" : "=r"(r) : "r"(a), "r"(v) : "memory");
    return r;
}
__device__ __forceinline__ uint2 ld_hdr(const uint4* p) {
    uint2 v;
    asm volatile("{\n.reg .b64 a;\nld.relaxed.gpu.global.b64 a, [%2];\nmov.b64 {%0,%1}, a;\n}" : "=r"(v.x), "=r"(v.y) : "l"(p) : "memory");
    return v;
}
__device__ __forceinline__ uint4 ld_cell(const uint4* p) {
    uint4 v;
    asm volatile("{\n.reg .b64 a, b;\nld.relaxed.gpu.global.v2.b64 {a, b}, [%4];\nmov.b64 {%0,%1}, a;\nmov.b64 {%2,%3}, b;\n}"
                 : "=r"(v.x), "=r"(v.y), "=r"(v.z), "=r"(v.w) : "l"(p) : "memory");
    return v;
}
__device__ __forceinline__ void st_cell(uint4* p, const uint4& v) {
    asm volatile("{\n.reg .b64 a, b;\nmov.b64 a, {%1,%2};\nmov.b64 b, {%3,%4};\nst.relaxed.gpu.global.v2.b64 [%0], {a, b};\n}" ::"l"(p),
                 "r"(v.x), "r"(v.y), "r"(v.z), "r"(v.w) : "memory");
}
__device__ __forceinline__ uint32_t scan_step(uint32_t v, int o) {
    asm volatile("{\n.reg .pred p;\n.reg .b32 y;\nshfl.sync.up.b32 y|p, %0, %1, 0, 0xffffffff;\n@p add.u32 %0, %0, y;\n}" : "+r"(v) : "r"(o));
    return v;
}
__device__ __forceinline__ uint32_t bitsel(uint32_t a, uint32_t b) {
    uint32_t r;
    asm("lop3.b32 %0, %1, %2, 0x1ffc, 0xe4;" : "=r"(r) : "r"(a), "r"(b));
    return r;
}
__device__ __forceinline__ uint32_t movm(uint32_t a) {
    uint32_t r;
    asm volatile("movmatrix.sync.aligned.m8n8.trans.b16 %0, %1;" : "=r"(r) : "r"(a));
    return r;
}
__device__ __forceinline__ uint32_t gt_lo() {
    uint32_t t;
    asm volatile("mov.u32 %0, %globaltimer_lo;" : "=r"(t));
    return t;
}
__device__ __forceinline__ bool elect() {
    uint32_t p;
    asm volatile("{\n.reg .pred P;\nelect.sync _|P, 0xffffffff;\nselp.u32 %0, 1, 0, P;\n}" : "=r"(p));
    return p;
}
__device__ __forceinline__ void project64(float (&o)[32], const uint32_t (&a)[32], const uint4 (&c)[4]) {
    asm volatile(
        "{\n.reg .pred p0, p1;\n.reg .b32 t, h;\n.reg .b64 d<16>;\nsetp.ne.b32 p0, 0, 0;\nsetp.eq.b32 p1, 0, 0;\nmov.b32 h, 8;\n"
        "and.b32 t, %64, 0xffe;\nmad.lo.u32 t, t, 4, 0x200000;\nmov.b64 d0, {t, h};\n"
        "and.b32 t, %65, 0xffe;\nmad.lo.u32 t, t, 4, 0x200000;\nmov.b64 d1, {t, h};\n"
        "and.b32 t, %66, 0xffe;\nmad.lo.u32 t, t, 4, 0x200000;\nmov.b64 d2, {t, h};\n"
        "and.b32 t, %67, 0xffe;\nmad.lo.u32 t, t, 4, 0x200000;\nmov.b64 d3, {t, h};\n"
        "and.b32 t, %68, 0xffe;\nmad.lo.u32 t, t, 4, 0x200000;\nmov.b64 d4, {t, h};\n"
        "and.b32 t, %69, 0xffe;\nmad.lo.u32 t, t, 4, 0x200000;\nmov.b64 d5, {t, h};\n"
        "and.b32 t, %70, 0xffe;\nmad.lo.u32 t, t, 4, 0x200000;\nmov.b64 d6, {t, h};\n"
        "and.b32 t, %71, 0xffe;\nmad.lo.u32 t, t, 4, 0x200000;\nmov.b64 d7, {t, h};\n"
        "and.b32 t, %72, 0xffe;\nmad.lo.u32 t, t, 4, 0x200000;\nmov.b64 d8, {t, h};\n"
        "and.b32 t, %73, 0xffe;\nmad.lo.u32 t, t, 4, 0x200000;\nmov.b64 d9, {t, h};\n"
        "and.b32 t, %74, 0xffe;\nmad.lo.u32 t, t, 4, 0x200000;\nmov.b64 d10, {t, h};\n"
        "and.b32 t, %75, 0xffe;\nmad.lo.u32 t, t, 4, 0x200000;\nmov.b64 d11, {t, h};\n"
        "and.b32 t, %76, 0xffe;\nmad.lo.u32 t, t, 4, 0x200000;\nmov.b64 d12, {t, h};\n"
        "and.b32 t, %77, 0xffe;\nmad.lo.u32 t, t, 4, 0x200000;\nmov.b64 d13, {t, h};\n"
        "and.b32 t, %78, 0xffe;\nmad.lo.u32 t, t, 4, 0x200000;\nmov.b64 d14, {t, h};\n"
        "and.b32 t, %79, 0xffe;\nmad.lo.u32 t, t, 4, 0x200000;\nmov.b64 d15, {t, h};\n"
        "wgmma.fence.sync.aligned;\n"
        "wgmma.mma_async.sync.aligned.m64n32k16.f32.bf16.bf16 {%0,%1,%2,%3,%4,%5,%6,%7,%8,%9,%10,%11,%12,%13,%14,%15}, {%32,%33,%34,%35}, d0, p0, 1, 1, 1;\n"
        "wgmma.mma_async.sync.aligned.m64n32k16.f32.bf16.bf16 {%16,%17,%18,%19,%20,%21,%22,%23,%24,%25,%26,%27,%28,%29,%30,%31}, {%32,%33,%34,%35}, d8, p0, 1, 1, 1;\n"
        "wgmma.mma_async.sync.aligned.m64n32k16.f32.bf16.bf16 {%0,%1,%2,%3,%4,%5,%6,%7,%8,%9,%10,%11,%12,%13,%14,%15}, {%36,%37,%38,%39}, d1, p1, 1, 1, 1;\n"
        "wgmma.mma_async.sync.aligned.m64n32k16.f32.bf16.bf16 {%16,%17,%18,%19,%20,%21,%22,%23,%24,%25,%26,%27,%28,%29,%30,%31}, {%36,%37,%38,%39}, d9, p1, 1, 1, 1;\n"
        "wgmma.mma_async.sync.aligned.m64n32k16.f32.bf16.bf16 {%0,%1,%2,%3,%4,%5,%6,%7,%8,%9,%10,%11,%12,%13,%14,%15}, {%40,%41,%42,%43}, d2, p1, 1, 1, 1;\n"
        "wgmma.mma_async.sync.aligned.m64n32k16.f32.bf16.bf16 {%16,%17,%18,%19,%20,%21,%22,%23,%24,%25,%26,%27,%28,%29,%30,%31}, {%40,%41,%42,%43}, d10, p1, 1, 1, 1;\n"
        "wgmma.mma_async.sync.aligned.m64n32k16.f32.bf16.bf16 {%0,%1,%2,%3,%4,%5,%6,%7,%8,%9,%10,%11,%12,%13,%14,%15}, {%44,%45,%46,%47}, d3, p1, 1, 1, 1;\n"
        "wgmma.mma_async.sync.aligned.m64n32k16.f32.bf16.bf16 {%16,%17,%18,%19,%20,%21,%22,%23,%24,%25,%26,%27,%28,%29,%30,%31}, {%44,%45,%46,%47}, d11, p1, 1, 1, 1;\n"
        "wgmma.mma_async.sync.aligned.m64n32k16.f32.bf16.bf16 {%0,%1,%2,%3,%4,%5,%6,%7,%8,%9,%10,%11,%12,%13,%14,%15}, {%48,%49,%50,%51}, d4, p1, 1, 1, 1;\n"
        "wgmma.mma_async.sync.aligned.m64n32k16.f32.bf16.bf16 {%16,%17,%18,%19,%20,%21,%22,%23,%24,%25,%26,%27,%28,%29,%30,%31}, {%48,%49,%50,%51}, d12, p1, 1, 1, 1;\n"
        "wgmma.mma_async.sync.aligned.m64n32k16.f32.bf16.bf16 {%0,%1,%2,%3,%4,%5,%6,%7,%8,%9,%10,%11,%12,%13,%14,%15}, {%52,%53,%54,%55}, d5, p1, 1, 1, 1;\n"
        "wgmma.mma_async.sync.aligned.m64n32k16.f32.bf16.bf16 {%16,%17,%18,%19,%20,%21,%22,%23,%24,%25,%26,%27,%28,%29,%30,%31}, {%52,%53,%54,%55}, d13, p1, 1, 1, 1;\n"
        "wgmma.mma_async.sync.aligned.m64n32k16.f32.bf16.bf16 {%0,%1,%2,%3,%4,%5,%6,%7,%8,%9,%10,%11,%12,%13,%14,%15}, {%56,%57,%58,%59}, d6, p1, 1, 1, 1;\n"
        "wgmma.mma_async.sync.aligned.m64n32k16.f32.bf16.bf16 {%16,%17,%18,%19,%20,%21,%22,%23,%24,%25,%26,%27,%28,%29,%30,%31}, {%56,%57,%58,%59}, d14, p1, 1, 1, 1;\n"
        "wgmma.mma_async.sync.aligned.m64n32k16.f32.bf16.bf16 {%0,%1,%2,%3,%4,%5,%6,%7,%8,%9,%10,%11,%12,%13,%14,%15}, {%60,%61,%62,%63}, d7, p1, 1, 1, 1;\n"
        "wgmma.mma_async.sync.aligned.m64n32k16.f32.bf16.bf16 {%16,%17,%18,%19,%20,%21,%22,%23,%24,%25,%26,%27,%28,%29,%30,%31}, {%60,%61,%62,%63}, d15, p1, 1, 1, 1;\n"
        "wgmma.commit_group.sync.aligned;\nwgmma.wait_group.sync.aligned 0;\n}"
        : "=f"(o[0]), "=f"(o[1]), "=f"(o[2]), "=f"(o[3]), "=f"(o[4]), "=f"(o[5]), "=f"(o[6]), "=f"(o[7]), "=f"(o[8]), "=f"(o[9]),
          "=f"(o[10]), "=f"(o[11]), "=f"(o[12]), "=f"(o[13]), "=f"(o[14]), "=f"(o[15]), "=f"(o[16]), "=f"(o[17]), "=f"(o[18]), "=f"(o[19]),
          "=f"(o[20]), "=f"(o[21]), "=f"(o[22]), "=f"(o[23]), "=f"(o[24]), "=f"(o[25]), "=f"(o[26]), "=f"(o[27]), "=f"(o[28]), "=f"(o[29]),
          "=f"(o[30]), "=f"(o[31])
        : "r"(a[0]), "r"(a[1]), "r"(a[2]), "r"(a[3]), "r"(a[4]), "r"(a[5]), "r"(a[6]), "r"(a[7]), "r"(a[8]), "r"(a[9]), "r"(a[10]),
          "r"(a[11]), "r"(a[12]), "r"(a[13]), "r"(a[14]), "r"(a[15]), "r"(a[16]), "r"(a[17]), "r"(a[18]), "r"(a[19]), "r"(a[20]), "r"(a[21]),
          "r"(a[22]), "r"(a[23]), "r"(a[24]), "r"(a[25]), "r"(a[26]), "r"(a[27]), "r"(a[28]), "r"(a[29]), "r"(a[30]), "r"(a[31]),
          "r"(c[0].x), "r"(c[0].y), "r"(c[0].z), "r"(c[0].w), "r"(c[1].x), "r"(c[1].y), "r"(c[1].z), "r"(c[1].w), "r"(c[2].x), "r"(c[2].y),
          "r"(c[2].z), "r"(c[2].w), "r"(c[3].x), "r"(c[3].y), "r"(c[3].z), "r"(c[3].w)
        : "memory");
}
__device__ __forceinline__ int cta_id() {
    int v;
    asm volatile("mov.u32 %0, %ctaid.x;" : "=r"(v));
    return v;
}
__device__ __forceinline__ int thread_id() {
    int v;
    asm volatile("mov.u32 %0, %tid.x;" : "=r"(v));
    return v;
}

__device__ __forceinline__ void slow_edge(int ee, int s, float* accn, const __nv_bfloat16* __restrict__ x,
                                          const __nv_bfloat16* __restrict__ sh, const __nv_bfloat16* __restrict__ ea,
                                          const __nv_bfloat16* __restrict__ cg, const __nv_bfloat16* __restrict__ wr,
                                          int lane) {
    float rwv[4] = {0.f, 0.f, 0.f, 0.f};
#pragma unroll 4
    for (int d = 0; d < 16; d++) {
        const float a = __bfloat162float(ea[(size_t)ee * 16 + d]);
        const uint2 wv = *(const uint2*)(wr + d * 128 + lane * 4);
        rwv[0] += a * __uint_as_float(wv.x << 16);
        rwv[1] += a * __uint_as_float(wv.x & 0xffff0000u);
        rwv[2] += a * __uint_as_float(wv.y << 16);
        rwv[3] += a * __uint_as_float(wv.y & 0xffff0000u);
    }
    float A = 0.f;
#pragma unroll
    for (int v = 0; v < 4; v++)
        A += __bfloat162float(cg[((lane >> 2) & 3) * 16 + v * 4 + (lane & 3)]) * __bfloat162float(sh[(size_t)ee * 4 + v]);
    float m[4][4];
#pragma unroll
    for (int w = 0; w < 4; w++)
#pragma unroll
        for (int j = 0; j < 4; j++) m[w][j] = 0.f;
#pragma unroll
    for (int u = 0; u < 4; u++) {
        const uint2 xv = *(const uint2*)(x + (size_t)s * 512 + u * 128 + lane * 4);
        const float x0 = __uint_as_float(xv.x << 16), x1 = __uint_as_float(xv.x & 0xffff0000u);
        const float x2 = __uint_as_float(xv.y << 16), x3 = __uint_as_float(xv.y & 0xffff0000u);
#pragma unroll
        for (int w = 0; w < 4; w++) {
            const float a = __shfl_sync(0xffffffffu, A, u * 4 + w);
            m[w][0] += a * x0;
            m[w][1] += a * x1;
            m[w][2] += a * x2;
            m[w][3] += a * x3;
        }
    }
#pragma unroll
    for (int w = 0; w < 4; w++)
#pragma unroll
        for (int j = 0; j < 4; j++) atomicAdd(accn + w * 128 + lane * 4 + j, m[w][j] * rwv[j]);
}

__device__ __forceinline__ void slow_out(const float* accn, const __nv_bfloat16* __restrict__ wout,
                                         __nv_bfloat16* __restrict__ outn, int lane) {
    float o[4][4];
#pragma unroll
    for (int w = 0; w < 4; w++)
#pragma unroll
        for (int j = 0; j < 4; j++) o[w][j] = 0.f;
#pragma unroll 2
    for (int c = 0; c < 128; c++) {
        const uint2 wv = *(const uint2*)(wout + c * 128 + lane * 4);
        const float w0 = __uint_as_float(wv.x << 16), w1 = __uint_as_float(wv.x & 0xffff0000u);
        const float w2 = __uint_as_float(wv.y << 16), w3 = __uint_as_float(wv.y & 0xffff0000u);
#pragma unroll
        for (int w = 0; w < 4; w++) {
            const float a = __bfloat162float(__float2bfloat16(accn[w * 128 + c]));
            o[w][0] += a * w0;
            o[w][1] += a * w1;
            o[w][2] += a * w2;
            o[w][3] += a * w3;
        }
    }
#pragma unroll
    for (int w = 0; w < 4; w++)
        *(uint2*)(outn + w * 128 + lane * 4) = make_uint2(pack_bf16(o[w][0], o[w][1]), pack_bf16(o[w][2], o[w][3]));
}

__device__ __forceinline__ void consume4(uint32_t (&pk)[64], const uint32_t (&w)[36], uint32_t olp, uint32_t xa, uint32_t ln,
                                      uint32_t lc, uint32_t linc, uint32_t lt, const __nv_bfloat16* ea, const __nv_bfloat16* sh) {
    ea += lt * 4, sh += lt & 2;
    asm volatile(
        "{\n.reg .pred p, q, psw, prdy, ps1, ps2, ps3, pz;\n.reg .f32 d<32>, fz;\n"
        ".reg .b32 h<64>, x<32>, y<32>, ra<8>, rb<8>, bA0, bA1, bB0, bB1, c0, c1, c2, c3, e0, e1, s0, kept;\n"
        ".reg .b32 olp, v, vB, m, id, ida, bar, xb, pos, t0, t1, t2, t3, n, z<16>;\n.reg .b16 lo, hi, i16;\n.reg .b64 pa, pb;\nmov.f32 fz, 0f00000000;\n"
        "mov.b32 h0, 0;\nmov.b32 h1, 0;\nmov.b32 h2, 0;\nmov.b32 h3, 0;\nmov.b32 h4, 0;\nmov.b32 h5, 0;\nmov.b32 h6, 0;\nmov.b32 h7, 0;\nmov.b32 h8, 0;\n"
        "mov.b32 h9, 0;\nmov.b32 h10, 0;\nmov.b32 h11, 0;\nmov.b32 h12, 0;\nmov.b32 h13, 0;\nmov.b32 h14, 0;\nmov.b32 h15, 0;\nmov.b32 h16, 0;\nmov.b32 h17, 0;\n"
        "mov.b32 h18, 0;\nmov.b32 h19, 0;\nmov.b32 h20, 0;\nmov.b32 h21, 0;\nmov.b32 h22, 0;\nmov.b32 h23, 0;\nmov.b32 h24, 0;\nmov.b32 h25, 0;\n"
        "mov.b32 h26, 0;\nmov.b32 h27, 0;\nmov.b32 h28, 0;\nmov.b32 h29, 0;\nmov.b32 h30, 0;\nmov.b32 h31, 0;\nmov.b32 h32, 0;\nmov.b32 h33, 0;\n"
        "mov.b32 h34, 0;\nmov.b32 h35, 0;\nmov.b32 h36, 0;\nmov.b32 h37, 0;\nmov.b32 h38, 0;\nmov.b32 h39, 0;\nmov.b32 h40, 0;\nmov.b32 h41, 0;\n"
        "mov.b32 h42, 0;\nmov.b32 h43, 0;\nmov.b32 h44, 0;\nmov.b32 h45, 0;\nmov.b32 h46, 0;\nmov.b32 h47, 0;\nmov.b32 h48, 0;\nmov.b32 h49, 0;\n"
        "mov.b32 h50, 0;\nmov.b32 h51, 0;\nmov.b32 h52, 0;\nmov.b32 h53, 0;\nmov.b32 h54, 0;\nmov.b32 h55, 0;\nmov.b32 h56, 0;\nmov.b32 h57, 0;\n"
        "mov.b32 h58, 0;\nmov.b32 h59, 0;\nmov.b32 h60, 0;\nmov.b32 h61, 0;\nmov.b32 h62, 0;\nmov.b32 h63, 0;\nmov.b32 olp, %64;\nand.b32 t0, %66, 32;\n"
        "setp.ne.u32 psw, t0, 0;\nsetp.eq.u32 pz, %64, 0;\nvote.sync.any.pred pz, pz, 0xffffffff;\nld.shared.b32 t0, [olp];\nadd.u32 olp, olp, 8;\n"
        "lop3.b32 t1, t0, %66, 0x3ff0, 0xe4;\nld.shared.b32 t1, [t1+%72];\nlop3.b32 kept, t1, t0, 0x1ffc, 0xe4;\nlop3.b32 t2, t1, %67, 3, 0x80;\n"
        "setp.ne.u32 q, t2, 0;\nshr.u32 t2, t1, 13;\nmad.wide.u32 pa, t2, 32, %70;\nmad.wide.u32 pb, t2, 8, %71;\nmov.b32 s0, 0;\n"
        "ld.global.cg.v2.b32 {e0,e1}, [pa];\n@q ld.global.cg.b32 s0, [pb];\nshfl.sync.idx.b32 v, kept, %67, 0x1f, 0xffffffff;\nor.b32 t3, %67, 4;\n"
        "shfl.sync.idx.b32 vB, kept, t3, 0x1f, 0xffffffff;\nshr.u32 bar, v, 1;\nand.b32 bar, bar, 0xff8;\nmbarrier.test_wait.parity.shared.b64 p, [bar+%74], 0;\n"
        "lop3.b32 ida, v, %67, 0x1fff, 0xe4;\nld.volatile.shared.u16 id, [ida+%73];\nvote.sync.all.pred prdy, p, 0xffffffff;\n"
        "RW:\nmma.sync.aligned.m16n8k8.row.col.f32.bf16.bf16.f32 {d0,d1,d2,d3}, {%108,%109}, {s0}, {fz,fz,fz,fz};\n"
        "mma.sync.aligned.m16n8k8.row.col.f32.bf16.bf16.f32 {d4,d5,d6,d7}, {%110,%111}, {s0}, {fz,fz,fz,fz};\ncvt.rn.bf16x2.f32 c0, d2, d0;\n"
        "cvt.rn.bf16x2.f32 c1, d3, d1;\ncvt.rn.bf16x2.f32 c2, d6, d4;\ncvt.rn.bf16x2.f32 c3, d7, d5;\nselp.b32 bA0, c2, c0, psw;\nselp.b32 bA1, c0, c2, psw;\n"
        "selp.b32 bB0, c3, c1, psw;\nselp.b32 bB1, c1, c3, psw;\n"
        "mma.sync.aligned.m16n8k16.row.col.f32.bf16.bf16.f32 {d0,d1,d2,d3}, {%76,%77,%78,%79}, {e0,e1}, {fz,fz,fz,fz};\ncvt.rn.bf16x2.f32 ra0, d2, d0;\n"
        "cvt.rn.bf16x2.f32 rb0, d3, d1;\nmma.sync.aligned.m16n8k16.row.col.f32.bf16.bf16.f32 {d4,d5,d6,d7}, {%80,%81,%82,%83}, {e0,e1}, {fz,fz,fz,fz};\n"
        "cvt.rn.bf16x2.f32 ra1, d6, d4;\ncvt.rn.bf16x2.f32 rb1, d7, d5;\n"
        "mma.sync.aligned.m16n8k16.row.col.f32.bf16.bf16.f32 {d8,d9,d10,d11}, {%84,%85,%86,%87}, {e0,e1}, {fz,fz,fz,fz};\ncvt.rn.bf16x2.f32 ra2, d10, d8;\n"
        "cvt.rn.bf16x2.f32 rb2, d11, d9;\nmma.sync.aligned.m16n8k16.row.col.f32.bf16.bf16.f32 {d12,d13,d14,d15}, {%88,%89,%90,%91}, {e0,e1}, {fz,fz,fz,fz};\n"
        "cvt.rn.bf16x2.f32 ra3, d14, d12;\ncvt.rn.bf16x2.f32 rb3, d15, d13;\n"
        "mma.sync.aligned.m16n8k16.row.col.f32.bf16.bf16.f32 {d16,d17,d18,d19}, {%92,%93,%94,%95}, {e0,e1}, {fz,fz,fz,fz};\ncvt.rn.bf16x2.f32 ra4, d18, d16;\n"
        "cvt.rn.bf16x2.f32 rb4, d19, d17;\nmma.sync.aligned.m16n8k16.row.col.f32.bf16.bf16.f32 {d20,d21,d22,d23}, {%96,%97,%98,%99}, {e0,e1}, {fz,fz,fz,fz};\n"
        "cvt.rn.bf16x2.f32 ra5, d22, d20;\ncvt.rn.bf16x2.f32 rb5, d23, d21;\n"
        "mma.sync.aligned.m16n8k16.row.col.f32.bf16.bf16.f32 {d24,d25,d26,d27}, {%100,%101,%102,%103}, {e0,e1}, {fz,fz,fz,fz};\n"
        "cvt.rn.bf16x2.f32 ra6, d26, d24;\ncvt.rn.bf16x2.f32 rb6, d27, d25;\n"
        "mma.sync.aligned.m16n8k16.row.col.f32.bf16.bf16.f32 {d28,d29,d30,d31}, {%104,%105,%106,%107}, {e0,e1}, {fz,fz,fz,fz};\n"
        "cvt.rn.bf16x2.f32 ra7, d30, d28;\ncvt.rn.bf16x2.f32 rb7, d31, d29;\nld.shared.b32 t0, [olp];\nadd.u32 olp, olp, 8;\n"
        "lop3.b32 t1, t0, %66, 0x3ff0, 0xe4;\nld.shared.b32 t1, [t1+%72];\nlop3.b32 kept, t1, t0, 0x1ffc, 0xe4;\nlop3.b32 t2, t1, %67, 3, 0x80;\n"
        "setp.ne.u32 q, t2, 0;\nshr.u32 t2, t1, 13;\nmad.wide.u32 pa, t2, 32, %70;\nmad.wide.u32 pb, t2, 8, %71;\nmov.b32 s0, 0;\n"
        "ld.global.cg.v2.b32 {e0,e1}, [pa];\n@q ld.global.cg.b32 s0, [pb];\n@!prdy bra.uni WA;\n"
        "HA:\nmad.lo.u32 xb, id, 64, %65;\ncvt.u16.u32 i16, id;\nldmatrix.sync.aligned.m8n8.x4.trans.shared.b16 {x0,x1,x2,x3}, [xb];\nxor.b32 t1, xb, 16;\n"
        "ldmatrix.sync.aligned.m8n8.x4.trans.shared.b16 {x4,x5,x6,x7}, [t1];\nxor.b32 t1, xb, 32;\n"
        "ldmatrix.sync.aligned.m8n8.x4.trans.shared.b16 {x8,x9,x10,x11}, [t1];\nxor.b32 t1, xb, 48;\n"
        "ldmatrix.sync.aligned.m8n8.x4.trans.shared.b16 {x12,x13,x14,x15}, [t1];\nxor.b32 t1, xb, 64;\n"
        "ldmatrix.sync.aligned.m8n8.x4.trans.shared.b16 {x16,x17,x18,x19}, [t1];\n@pz bra.uni DONE;\natom.shared.add.u32 pos, [%66+%75], %68;\n"
        "xor.b32 t1, xb, 80;\nldmatrix.sync.aligned.m8n8.x4.trans.shared.b16 {x20,x21,x22,x23}, [t1];\nxor.b32 t1, xb, 96;\n"
        "ldmatrix.sync.aligned.m8n8.x4.trans.shared.b16 {x24,x25,x26,x27}, [t1];\nxor.b32 t1, xb, 112;\n"
        "ldmatrix.sync.aligned.m8n8.x4.trans.shared.b16 {x28,x29,x30,x31}, [t1];\nst.volatile.shared.u16 [pos], i16;\nand.b32 t0, v, 268435456;\n"
        "setp.ne.u32 ps1, t0, 0;\nvote.sync.any.pred ps1, ps1, 0xffffffff;\nand.b32 t0, v, 536870912;\nsetp.ne.u32 ps2, t0, 0;\n"
        "vote.sync.any.pred ps2, ps2, 0xffffffff;\nmov.b32 v, vB;\nshr.u32 bar, v, 1;\nand.b32 bar, bar, 0xff8;\n"
        "mbarrier.test_wait.parity.shared.b64 p, [bar+%74], 0;\nlop3.b32 ida, v, %67, 0x1fff, 0xe4;\nld.volatile.shared.u16 id, [ida+%73];\n"
        "vote.sync.all.pred prdy, p, 0xffffffff;\nmov.b32 {lo, hi}, ra0;\nmov.b32 t2, {lo, lo};\nmul.rn.bf16x2 y0, x0, t2;\nmul.rn.bf16x2 y2, x2, t2;\n"
        "mov.b32 t2, {hi, hi};\nmul.rn.bf16x2 y1, x1, t2;\nmul.rn.bf16x2 y3, x3, t2;\n"
        "mma.sync.aligned.m16n8k16.row.col.f32.bf16.bf16.f32 {d0,d1,d2,d3}, {y0,y1,y2,y3}, {bA0,bA1}, {fz,fz,fz,fz};\ncvt.rn.bf16x2.f32 z0, d1, d0;\n"
        "cvt.rn.bf16x2.f32 z1, d3, d2;\nmov.b32 {lo, hi}, ra1;\nmov.b32 t2, {lo, lo};\nmul.rn.bf16x2 y4, x4, t2;\nmul.rn.bf16x2 y6, x6, t2;\n"
        "mov.b32 t2, {hi, hi};\nmul.rn.bf16x2 y5, x5, t2;\nmul.rn.bf16x2 y7, x7, t2;\n"
        "mma.sync.aligned.m16n8k16.row.col.f32.bf16.bf16.f32 {d4,d5,d6,d7}, {y4,y5,y6,y7}, {bA0,bA1}, {fz,fz,fz,fz};\ncvt.rn.bf16x2.f32 z2, d5, d4;\n"
        "cvt.rn.bf16x2.f32 z3, d7, d6;\nmov.b32 {lo, hi}, ra2;\nmov.b32 t2, {lo, lo};\nmul.rn.bf16x2 y8, x8, t2;\nmul.rn.bf16x2 y10, x10, t2;\n"
        "mov.b32 t2, {hi, hi};\nmul.rn.bf16x2 y9, x9, t2;\nmul.rn.bf16x2 y11, x11, t2;\n"
        "mma.sync.aligned.m16n8k16.row.col.f32.bf16.bf16.f32 {d8,d9,d10,d11}, {y8,y9,y10,y11}, {bA0,bA1}, {fz,fz,fz,fz};\ncvt.rn.bf16x2.f32 z4, d9, d8;\n"
        "cvt.rn.bf16x2.f32 z5, d11, d10;\nmov.b32 {lo, hi}, ra3;\nmov.b32 t2, {lo, lo};\nmul.rn.bf16x2 y12, x12, t2;\nmul.rn.bf16x2 y14, x14, t2;\n"
        "mov.b32 t2, {hi, hi};\nmul.rn.bf16x2 y13, x13, t2;\nmul.rn.bf16x2 y15, x15, t2;\n"
        "mma.sync.aligned.m16n8k16.row.col.f32.bf16.bf16.f32 {d12,d13,d14,d15}, {y12,y13,y14,y15}, {bA0,bA1}, {fz,fz,fz,fz};\ncvt.rn.bf16x2.f32 z6, d13, d12;\n"
        "cvt.rn.bf16x2.f32 z7, d15, d14;\nmov.b32 {lo, hi}, ra4;\nmov.b32 t2, {lo, lo};\nmul.rn.bf16x2 y16, x16, t2;\nmul.rn.bf16x2 y18, x18, t2;\n"
        "mov.b32 t2, {hi, hi};\nmul.rn.bf16x2 y17, x17, t2;\nmul.rn.bf16x2 y19, x19, t2;\n"
        "mma.sync.aligned.m16n8k16.row.col.f32.bf16.bf16.f32 {d16,d17,d18,d19}, {y16,y17,y18,y19}, {bA0,bA1}, {fz,fz,fz,fz};\ncvt.rn.bf16x2.f32 z8, d17, d16;\n"
        "cvt.rn.bf16x2.f32 z9, d19, d18;\nmov.b32 {lo, hi}, ra5;\nmov.b32 t2, {lo, lo};\nmul.rn.bf16x2 y20, x20, t2;\nmul.rn.bf16x2 y22, x22, t2;\n"
        "mov.b32 t2, {hi, hi};\nmul.rn.bf16x2 y21, x21, t2;\nmul.rn.bf16x2 y23, x23, t2;\n"
        "mma.sync.aligned.m16n8k16.row.col.f32.bf16.bf16.f32 {d20,d21,d22,d23}, {y20,y21,y22,y23}, {bA0,bA1}, {fz,fz,fz,fz};\ncvt.rn.bf16x2.f32 z10, d21, d20;\n"
        "cvt.rn.bf16x2.f32 z11, d23, d22;\nmov.b32 {lo, hi}, ra6;\nmov.b32 t2, {lo, lo};\nmul.rn.bf16x2 y24, x24, t2;\nmul.rn.bf16x2 y26, x26, t2;\n"
        "mov.b32 t2, {hi, hi};\nmul.rn.bf16x2 y25, x25, t2;\nmul.rn.bf16x2 y27, x27, t2;\n"
        "mma.sync.aligned.m16n8k16.row.col.f32.bf16.bf16.f32 {d24,d25,d26,d27}, {y24,y25,y26,y27}, {bA0,bA1}, {fz,fz,fz,fz};\ncvt.rn.bf16x2.f32 z12, d25, d24;\n"
        "cvt.rn.bf16x2.f32 z13, d27, d26;\nmov.b32 {lo, hi}, ra7;\nmov.b32 t2, {lo, lo};\nmul.rn.bf16x2 y28, x28, t2;\nmul.rn.bf16x2 y30, x30, t2;\n"
        "mov.b32 t2, {hi, hi};\nmul.rn.bf16x2 y29, x29, t2;\nmul.rn.bf16x2 y31, x31, t2;\n"
        "mma.sync.aligned.m16n8k16.row.col.f32.bf16.bf16.f32 {d28,d29,d30,d31}, {y28,y29,y30,y31}, {bA0,bA1}, {fz,fz,fz,fz};\ncvt.rn.bf16x2.f32 z14, d29, d28;\n"
        "cvt.rn.bf16x2.f32 z15, d31, d30;\n@ps2 bra.uni TA2;\n@ps1 bra.uni TA1;\n"
        "TA0:\nadd.rn.bf16x2 h0, h0, z0;\nadd.rn.bf16x2 h1, h1, z1;\nadd.rn.bf16x2 h2, h2, z2;\nadd.rn.bf16x2 h3, h3, z3;\nadd.rn.bf16x2 h4, h4, z4;\n"
        "add.rn.bf16x2 h5, h5, z5;\nadd.rn.bf16x2 h6, h6, z6;\nadd.rn.bf16x2 h7, h7, z7;\nadd.rn.bf16x2 h8, h8, z8;\nadd.rn.bf16x2 h9, h9, z9;\n"
        "add.rn.bf16x2 h10, h10, z10;\nadd.rn.bf16x2 h11, h11, z11;\nadd.rn.bf16x2 h12, h12, z12;\nadd.rn.bf16x2 h13, h13, z13;\nadd.rn.bf16x2 h14, h14, z14;\n"
        "add.rn.bf16x2 h15, h15, z15;\n@prdy bra.uni HB;\nbra.uni WB;\n"
        "TA1:\nadd.rn.bf16x2 h16, h16, z0;\nadd.rn.bf16x2 h17, h17, z1;\nadd.rn.bf16x2 h18, h18, z2;\nadd.rn.bf16x2 h19, h19, z3;\nadd.rn.bf16x2 h20, h20, z4;\n"
        "add.rn.bf16x2 h21, h21, z5;\nadd.rn.bf16x2 h22, h22, z6;\nadd.rn.bf16x2 h23, h23, z7;\nadd.rn.bf16x2 h24, h24, z8;\nadd.rn.bf16x2 h25, h25, z9;\n"
        "add.rn.bf16x2 h26, h26, z10;\nadd.rn.bf16x2 h27, h27, z11;\nadd.rn.bf16x2 h28, h28, z12;\nadd.rn.bf16x2 h29, h29, z13;\nadd.rn.bf16x2 h30, h30, z14;\n"
        "add.rn.bf16x2 h31, h31, z15;\n@prdy bra.uni HB;\nbra.uni WB;\n"
        "TA2:\n@ps1 bra.uni TA3;\nadd.rn.bf16x2 h32, h32, z0;\nadd.rn.bf16x2 h33, h33, z1;\nadd.rn.bf16x2 h34, h34, z2;\nadd.rn.bf16x2 h35, h35, z3;\n"
        "add.rn.bf16x2 h36, h36, z4;\nadd.rn.bf16x2 h37, h37, z5;\nadd.rn.bf16x2 h38, h38, z6;\nadd.rn.bf16x2 h39, h39, z7;\nadd.rn.bf16x2 h40, h40, z8;\n"
        "add.rn.bf16x2 h41, h41, z9;\nadd.rn.bf16x2 h42, h42, z10;\nadd.rn.bf16x2 h43, h43, z11;\nadd.rn.bf16x2 h44, h44, z12;\nadd.rn.bf16x2 h45, h45, z13;\n"
        "add.rn.bf16x2 h46, h46, z14;\nadd.rn.bf16x2 h47, h47, z15;\n@prdy bra.uni HB;\nbra.uni WB;\n"
        "TA3:\nadd.rn.bf16x2 h48, h48, z0;\nadd.rn.bf16x2 h49, h49, z1;\nadd.rn.bf16x2 h50, h50, z2;\nadd.rn.bf16x2 h51, h51, z3;\nadd.rn.bf16x2 h52, h52, z4;\n"
        "add.rn.bf16x2 h53, h53, z5;\nadd.rn.bf16x2 h54, h54, z6;\nadd.rn.bf16x2 h55, h55, z7;\nadd.rn.bf16x2 h56, h56, z8;\nadd.rn.bf16x2 h57, h57, z9;\n"
        "add.rn.bf16x2 h58, h58, z10;\nadd.rn.bf16x2 h59, h59, z11;\nadd.rn.bf16x2 h60, h60, z12;\nadd.rn.bf16x2 h61, h61, z13;\nadd.rn.bf16x2 h62, h62, z14;\n"
        "add.rn.bf16x2 h63, h63, z15;\n@prdy bra.uni HB;\nbra.uni WB;\n"
        "HB:\nmad.lo.u32 xb, id, 64, %65;\ncvt.u16.u32 i16, id;\natom.shared.add.u32 pos, [%66+%75], %68;\n"
        "ldmatrix.sync.aligned.m8n8.x4.trans.shared.b16 {x0,x1,x2,x3}, [xb];\nxor.b32 t1, xb, 16;\n"
        "ldmatrix.sync.aligned.m8n8.x4.trans.shared.b16 {x4,x5,x6,x7}, [t1];\nxor.b32 t1, xb, 32;\n"
        "ldmatrix.sync.aligned.m8n8.x4.trans.shared.b16 {x8,x9,x10,x11}, [t1];\nxor.b32 t1, xb, 48;\n"
        "ldmatrix.sync.aligned.m8n8.x4.trans.shared.b16 {x12,x13,x14,x15}, [t1];\nxor.b32 t1, xb, 64;\n"
        "ldmatrix.sync.aligned.m8n8.x4.trans.shared.b16 {x16,x17,x18,x19}, [t1];\nxor.b32 t1, xb, 80;\n"
        "ldmatrix.sync.aligned.m8n8.x4.trans.shared.b16 {x20,x21,x22,x23}, [t1];\nxor.b32 t1, xb, 96;\n"
        "ldmatrix.sync.aligned.m8n8.x4.trans.shared.b16 {x24,x25,x26,x27}, [t1];\nxor.b32 t1, xb, 112;\n"
        "ldmatrix.sync.aligned.m8n8.x4.trans.shared.b16 {x28,x29,x30,x31}, [t1];\nst.volatile.shared.u16 [pos], i16;\nand.b32 t0, v, 268435456;\n"
        "setp.ne.u32 ps1, t0, 0;\nvote.sync.any.pred ps1, ps1, 0xffffffff;\nand.b32 t0, v, 536870912;\nsetp.ne.u32 ps2, t0, 0;\n"
        "vote.sync.any.pred ps2, ps2, 0xffffffff;\nshfl.sync.idx.b32 v, kept, %67, 0x1f, 0xffffffff;\nor.b32 t3, %67, 4;\n"
        "shfl.sync.idx.b32 vB, kept, t3, 0x1f, 0xffffffff;\nshr.u32 bar, v, 1;\nand.b32 bar, bar, 0xff8;\nmbarrier.test_wait.parity.shared.b64 p, [bar+%74], 0;\n"
        "lop3.b32 ida, v, %67, 0x1fff, 0xe4;\nld.volatile.shared.u16 id, [ida+%73];\nvote.sync.all.pred prdy, p, 0xffffffff;\nmov.b32 {lo, hi}, rb0;\n"
        "mov.b32 t2, {lo, lo};\nmul.rn.bf16x2 y0, x0, t2;\nmul.rn.bf16x2 y2, x2, t2;\nmov.b32 t2, {hi, hi};\nmul.rn.bf16x2 y1, x1, t2;\n"
        "mul.rn.bf16x2 y3, x3, t2;\nmma.sync.aligned.m16n8k16.row.col.f32.bf16.bf16.f32 {d0,d1,d2,d3}, {y0,y1,y2,y3}, {bB0,bB1}, {fz,fz,fz,fz};\n"
        "cvt.rn.bf16x2.f32 z0, d1, d0;\ncvt.rn.bf16x2.f32 z1, d3, d2;\nmov.b32 {lo, hi}, rb1;\nmov.b32 t2, {lo, lo};\nmul.rn.bf16x2 y4, x4, t2;\n"
        "mul.rn.bf16x2 y6, x6, t2;\nmov.b32 t2, {hi, hi};\nmul.rn.bf16x2 y5, x5, t2;\nmul.rn.bf16x2 y7, x7, t2;\n"
        "mma.sync.aligned.m16n8k16.row.col.f32.bf16.bf16.f32 {d4,d5,d6,d7}, {y4,y5,y6,y7}, {bB0,bB1}, {fz,fz,fz,fz};\ncvt.rn.bf16x2.f32 z2, d5, d4;\n"
        "cvt.rn.bf16x2.f32 z3, d7, d6;\nmov.b32 {lo, hi}, rb2;\nmov.b32 t2, {lo, lo};\nmul.rn.bf16x2 y8, x8, t2;\nmul.rn.bf16x2 y10, x10, t2;\n"
        "mov.b32 t2, {hi, hi};\nmul.rn.bf16x2 y9, x9, t2;\nmul.rn.bf16x2 y11, x11, t2;\n"
        "mma.sync.aligned.m16n8k16.row.col.f32.bf16.bf16.f32 {d8,d9,d10,d11}, {y8,y9,y10,y11}, {bB0,bB1}, {fz,fz,fz,fz};\ncvt.rn.bf16x2.f32 z4, d9, d8;\n"
        "cvt.rn.bf16x2.f32 z5, d11, d10;\nmov.b32 {lo, hi}, rb3;\nmov.b32 t2, {lo, lo};\nmul.rn.bf16x2 y12, x12, t2;\nmul.rn.bf16x2 y14, x14, t2;\n"
        "mov.b32 t2, {hi, hi};\nmul.rn.bf16x2 y13, x13, t2;\nmul.rn.bf16x2 y15, x15, t2;\n"
        "mma.sync.aligned.m16n8k16.row.col.f32.bf16.bf16.f32 {d12,d13,d14,d15}, {y12,y13,y14,y15}, {bB0,bB1}, {fz,fz,fz,fz};\ncvt.rn.bf16x2.f32 z6, d13, d12;\n"
        "cvt.rn.bf16x2.f32 z7, d15, d14;\nmov.b32 {lo, hi}, rb4;\nmov.b32 t2, {lo, lo};\nmul.rn.bf16x2 y16, x16, t2;\nmul.rn.bf16x2 y18, x18, t2;\n"
        "mov.b32 t2, {hi, hi};\nmul.rn.bf16x2 y17, x17, t2;\nmul.rn.bf16x2 y19, x19, t2;\n"
        "mma.sync.aligned.m16n8k16.row.col.f32.bf16.bf16.f32 {d16,d17,d18,d19}, {y16,y17,y18,y19}, {bB0,bB1}, {fz,fz,fz,fz};\ncvt.rn.bf16x2.f32 z8, d17, d16;\n"
        "cvt.rn.bf16x2.f32 z9, d19, d18;\nmov.b32 {lo, hi}, rb5;\nmov.b32 t2, {lo, lo};\nmul.rn.bf16x2 y20, x20, t2;\nmul.rn.bf16x2 y22, x22, t2;\n"
        "mov.b32 t2, {hi, hi};\nmul.rn.bf16x2 y21, x21, t2;\nmul.rn.bf16x2 y23, x23, t2;\n"
        "mma.sync.aligned.m16n8k16.row.col.f32.bf16.bf16.f32 {d20,d21,d22,d23}, {y20,y21,y22,y23}, {bB0,bB1}, {fz,fz,fz,fz};\ncvt.rn.bf16x2.f32 z10, d21, d20;\n"
        "cvt.rn.bf16x2.f32 z11, d23, d22;\nmov.b32 {lo, hi}, rb6;\nmov.b32 t2, {lo, lo};\nmul.rn.bf16x2 y24, x24, t2;\nmul.rn.bf16x2 y26, x26, t2;\n"
        "mov.b32 t2, {hi, hi};\nmul.rn.bf16x2 y25, x25, t2;\nmul.rn.bf16x2 y27, x27, t2;\n"
        "mma.sync.aligned.m16n8k16.row.col.f32.bf16.bf16.f32 {d24,d25,d26,d27}, {y24,y25,y26,y27}, {bB0,bB1}, {fz,fz,fz,fz};\ncvt.rn.bf16x2.f32 z12, d25, d24;\n"
        "cvt.rn.bf16x2.f32 z13, d27, d26;\nmov.b32 {lo, hi}, rb7;\nmov.b32 t2, {lo, lo};\nmul.rn.bf16x2 y28, x28, t2;\nmul.rn.bf16x2 y30, x30, t2;\n"
        "mov.b32 t2, {hi, hi};\nmul.rn.bf16x2 y29, x29, t2;\nmul.rn.bf16x2 y31, x31, t2;\n"
        "mma.sync.aligned.m16n8k16.row.col.f32.bf16.bf16.f32 {d28,d29,d30,d31}, {y28,y29,y30,y31}, {bB0,bB1}, {fz,fz,fz,fz};\ncvt.rn.bf16x2.f32 z14, d29, d28;\n"
        "cvt.rn.bf16x2.f32 z15, d31, d30;\n@ps2 bra.uni TB2;\n@ps1 bra.uni TB1;\n"
        "TB0:\nadd.rn.bf16x2 h0, h0, z0;\nadd.rn.bf16x2 h1, h1, z1;\nadd.rn.bf16x2 h2, h2, z2;\nadd.rn.bf16x2 h3, h3, z3;\nadd.rn.bf16x2 h4, h4, z4;\n"
        "add.rn.bf16x2 h5, h5, z5;\nadd.rn.bf16x2 h6, h6, z6;\nadd.rn.bf16x2 h7, h7, z7;\nadd.rn.bf16x2 h8, h8, z8;\nadd.rn.bf16x2 h9, h9, z9;\n"
        "add.rn.bf16x2 h10, h10, z10;\nadd.rn.bf16x2 h11, h11, z11;\nadd.rn.bf16x2 h12, h12, z12;\nadd.rn.bf16x2 h13, h13, z13;\nadd.rn.bf16x2 h14, h14, z14;\n"
        "add.rn.bf16x2 h15, h15, z15;\nbra.uni RW;\n"
        "TB1:\nadd.rn.bf16x2 h16, h16, z0;\nadd.rn.bf16x2 h17, h17, z1;\nadd.rn.bf16x2 h18, h18, z2;\nadd.rn.bf16x2 h19, h19, z3;\nadd.rn.bf16x2 h20, h20, z4;\n"
        "add.rn.bf16x2 h21, h21, z5;\nadd.rn.bf16x2 h22, h22, z6;\nadd.rn.bf16x2 h23, h23, z7;\nadd.rn.bf16x2 h24, h24, z8;\nadd.rn.bf16x2 h25, h25, z9;\n"
        "add.rn.bf16x2 h26, h26, z10;\nadd.rn.bf16x2 h27, h27, z11;\nadd.rn.bf16x2 h28, h28, z12;\nadd.rn.bf16x2 h29, h29, z13;\nadd.rn.bf16x2 h30, h30, z14;\n"
        "add.rn.bf16x2 h31, h31, z15;\nbra.uni RW;\n"
        "TB2:\n@ps1 bra.uni TB3;\nadd.rn.bf16x2 h32, h32, z0;\nadd.rn.bf16x2 h33, h33, z1;\nadd.rn.bf16x2 h34, h34, z2;\nadd.rn.bf16x2 h35, h35, z3;\n"
        "add.rn.bf16x2 h36, h36, z4;\nadd.rn.bf16x2 h37, h37, z5;\nadd.rn.bf16x2 h38, h38, z6;\nadd.rn.bf16x2 h39, h39, z7;\nadd.rn.bf16x2 h40, h40, z8;\n"
        "add.rn.bf16x2 h41, h41, z9;\nadd.rn.bf16x2 h42, h42, z10;\nadd.rn.bf16x2 h43, h43, z11;\nadd.rn.bf16x2 h44, h44, z12;\nadd.rn.bf16x2 h45, h45, z13;\n"
        "add.rn.bf16x2 h46, h46, z14;\nadd.rn.bf16x2 h47, h47, z15;\nbra.uni RW;\n"
        "TB3:\nadd.rn.bf16x2 h48, h48, z0;\nadd.rn.bf16x2 h49, h49, z1;\nadd.rn.bf16x2 h50, h50, z2;\nadd.rn.bf16x2 h51, h51, z3;\nadd.rn.bf16x2 h52, h52, z4;\n"
        "add.rn.bf16x2 h53, h53, z5;\nadd.rn.bf16x2 h54, h54, z6;\nadd.rn.bf16x2 h55, h55, z7;\nadd.rn.bf16x2 h56, h56, z8;\nadd.rn.bf16x2 h57, h57, z9;\n"
        "add.rn.bf16x2 h58, h58, z10;\nadd.rn.bf16x2 h59, h59, z11;\nadd.rn.bf16x2 h60, h60, z12;\nadd.rn.bf16x2 h61, h61, z13;\nadd.rn.bf16x2 h62, h62, z14;\n"
        "add.rn.bf16x2 h63, h63, z15;\nbra.uni RW;\n"
        "WA:\nsetp.ge.u32 p, v, 1073741824;\nvote.sync.all.pred p, p, 0xffffffff;\n@p bra.uni DONE;\nmov.b32 n, 0;\nshr.u32 t2, v, 1;\nand.b32 t2, t2, 0xff8;\n"
        "WA3:\nmbarrier.try_wait.parity.shared.b64 p, [t2+%74], 0;\nvote.sync.all.pred p, p, 0xffffffff;\nadd.u32 n, n, 1;\nsetp.lt.and.u32 q, n, 1000000, !p;\n"
        "@q bra.uni WA3;\nlop3.b32 ida, v, %67, 0x1fff, 0xe4;\nld.volatile.shared.u16 id, [ida+%73];\nbra.uni HA;\n"
        "WB:\nsetp.ge.u32 p, v, 1073741824;\nvote.sync.all.pred p, p, 0xffffffff;\n@p bra.uni DONE;\nmov.b32 n, 0;\nshr.u32 t2, v, 1;\nand.b32 t2, t2, 0xff8;\n"
        "WB3:\nmbarrier.try_wait.parity.shared.b64 p, [t2+%74], 0;\nvote.sync.all.pred p, p, 0xffffffff;\nadd.u32 n, n, 1;\nsetp.lt.and.u32 q, n, 1000000, !p;\n"
        "@q bra.uni WB3;\nlop3.b32 ida, v, %67, 0x1fff, 0xe4;\nld.volatile.shared.u16 id, [ida+%73];\nbra.uni HB;\n"
        "DONE:\nmov.b32 %0, h0;\nmov.b32 %1, h1;\nmov.b32 %2, h2;\nmov.b32 %3, h3;\nmov.b32 %4, h4;\nmov.b32 %5, h5;\nmov.b32 %6, h6;\nmov.b32 %7, h7;\n"
        "mov.b32 %8, h8;\nmov.b32 %9, h9;\nmov.b32 %10, h10;\nmov.b32 %11, h11;\nmov.b32 %12, h12;\nmov.b32 %13, h13;\nmov.b32 %14, h14;\nmov.b32 %15, h15;\n"
        "mov.b32 %16, h16;\nmov.b32 %17, h17;\nmov.b32 %18, h18;\nmov.b32 %19, h19;\nmov.b32 %20, h20;\nmov.b32 %21, h21;\nmov.b32 %22, h22;\nmov.b32 %23, h23;\n"
        "mov.b32 %24, h24;\nmov.b32 %25, h25;\nmov.b32 %26, h26;\nmov.b32 %27, h27;\nmov.b32 %28, h28;\nmov.b32 %29, h29;\nmov.b32 %30, h30;\nmov.b32 %31, h31;\n"
        "mov.b32 %32, h32;\nmov.b32 %33, h33;\nmov.b32 %34, h34;\nmov.b32 %35, h35;\nmov.b32 %36, h36;\nmov.b32 %37, h37;\nmov.b32 %38, h38;\nmov.b32 %39, h39;\n"
        "mov.b32 %40, h40;\nmov.b32 %41, h41;\nmov.b32 %42, h42;\nmov.b32 %43, h43;\nmov.b32 %44, h44;\nmov.b32 %45, h45;\nmov.b32 %46, h46;\nmov.b32 %47, h47;\n"
        "mov.b32 %48, h48;\nmov.b32 %49, h49;\nmov.b32 %50, h50;\nmov.b32 %51, h51;\nmov.b32 %52, h52;\nmov.b32 %53, h53;\nmov.b32 %54, h54;\nmov.b32 %55, h55;\n"
        "mov.b32 %56, h56;\nmov.b32 %57, h57;\nmov.b32 %58, h58;\nmov.b32 %59, h59;\nmov.b32 %60, h60;\nmov.b32 %61, h61;\nmov.b32 %62, h62;\nmov.b32 %63, h63;\n"
        "}\n"
        : "=r"(pk[0]), "=r"(pk[1]), "=r"(pk[2]), "=r"(pk[3]), "=r"(pk[4]), "=r"(pk[5]), "=r"(pk[6]), "=r"(pk[7]), "=r"(pk[8]), "=r"(pk[9]),
          "=r"(pk[10]), "=r"(pk[11]), "=r"(pk[12]), "=r"(pk[13]), "=r"(pk[14]), "=r"(pk[15]), "=r"(pk[16]), "=r"(pk[17]), "=r"(pk[18]), "=r"(pk[19]),
          "=r"(pk[20]), "=r"(pk[21]), "=r"(pk[22]), "=r"(pk[23]), "=r"(pk[24]), "=r"(pk[25]), "=r"(pk[26]), "=r"(pk[27]), "=r"(pk[28]), "=r"(pk[29]),
          "=r"(pk[30]), "=r"(pk[31]), "=r"(pk[32]), "=r"(pk[33]), "=r"(pk[34]), "=r"(pk[35]), "=r"(pk[36]), "=r"(pk[37]), "=r"(pk[38]), "=r"(pk[39]),
          "=r"(pk[40]), "=r"(pk[41]), "=r"(pk[42]), "=r"(pk[43]), "=r"(pk[44]), "=r"(pk[45]), "=r"(pk[46]), "=r"(pk[47]), "=r"(pk[48]), "=r"(pk[49]),
          "=r"(pk[50]), "=r"(pk[51]), "=r"(pk[52]), "=r"(pk[53]), "=r"(pk[54]), "=r"(pk[55]), "=r"(pk[56]), "=r"(pk[57]), "=r"(pk[58]), "=r"(pk[59]),
          "=r"(pk[60]), "=r"(pk[61]), "=r"(pk[62]), "=r"(pk[63])
        : "r"(olp), "r"(xa), "r"(ln), "r"(lc), "r"(linc), "r"(lt), "l"(ea), "l"(sh),
          "n"(sb + SM_REC), "n"(sb + SM_R), "n"(sb + SM_BAR), "n"(sb + SM_CTR),
          "r"(w[0]), "r"(w[1]), "r"(w[2]), "r"(w[3]), "r"(w[4]), "r"(w[5]), "r"(w[6]), "r"(w[7]), "r"(w[8]), "r"(w[9]), "r"(w[10]), "r"(w[11]),
          "r"(w[12]), "r"(w[13]), "r"(w[14]), "r"(w[15]), "r"(w[16]), "r"(w[17]), "r"(w[18]), "r"(w[19]), "r"(w[20]), "r"(w[21]), "r"(w[22]),
          "r"(w[23]), "r"(w[24]), "r"(w[25]), "r"(w[26]), "r"(w[27]), "r"(w[28]), "r"(w[29]), "r"(w[30]), "r"(w[31]), "r"(w[32]), "r"(w[33]),
          "r"(w[34]), "r"(w[35])
        : "memory");
}
__device__ __forceinline__ void consume3(uint32_t (&pk)[48], const uint32_t (&w)[36], uint32_t olp, uint32_t xa, uint32_t ln,
                                      uint32_t lc, uint32_t linc, uint32_t lt, const __nv_bfloat16* ea, const __nv_bfloat16* sh) {
    ea += lt * 4, sh += lt & 2;
    asm volatile(
        "{\n.reg .pred p, q, psw, prdy, ps1, ps2, ps3, pz;\n.reg .f32 d<32>, fz;\n"
        ".reg .b32 h<48>, x<32>, y<32>, ra<8>, rb<8>, bA0, bA1, bB0, bB1, c0, c1, c2, c3, e0, e1, s0, kept;\n"
        ".reg .b32 olp, v, vB, m, id, ida, bar, xb, pos, t0, t1, t2, t3, n, z<16>;\n.reg .b16 lo, hi, i16;\n.reg .b64 pa, pb;\nmov.f32 fz, 0f00000000;\n"
        "mov.b32 h0, 0;\nmov.b32 h1, 0;\nmov.b32 h2, 0;\nmov.b32 h3, 0;\nmov.b32 h4, 0;\nmov.b32 h5, 0;\nmov.b32 h6, 0;\nmov.b32 h7, 0;\nmov.b32 h8, 0;\n"
        "mov.b32 h9, 0;\nmov.b32 h10, 0;\nmov.b32 h11, 0;\nmov.b32 h12, 0;\nmov.b32 h13, 0;\nmov.b32 h14, 0;\nmov.b32 h15, 0;\nmov.b32 h16, 0;\nmov.b32 h17, 0;\n"
        "mov.b32 h18, 0;\nmov.b32 h19, 0;\nmov.b32 h20, 0;\nmov.b32 h21, 0;\nmov.b32 h22, 0;\nmov.b32 h23, 0;\nmov.b32 h24, 0;\nmov.b32 h25, 0;\n"
        "mov.b32 h26, 0;\nmov.b32 h27, 0;\nmov.b32 h28, 0;\nmov.b32 h29, 0;\nmov.b32 h30, 0;\nmov.b32 h31, 0;\nmov.b32 h32, 0;\nmov.b32 h33, 0;\n"
        "mov.b32 h34, 0;\nmov.b32 h35, 0;\nmov.b32 h36, 0;\nmov.b32 h37, 0;\nmov.b32 h38, 0;\nmov.b32 h39, 0;\nmov.b32 h40, 0;\nmov.b32 h41, 0;\n"
        "mov.b32 h42, 0;\nmov.b32 h43, 0;\nmov.b32 h44, 0;\nmov.b32 h45, 0;\nmov.b32 h46, 0;\nmov.b32 h47, 0;\nmov.b32 olp, %48;\nand.b32 t0, %50, 32;\n"
        "setp.ne.u32 psw, t0, 0;\nsetp.eq.u32 pz, %48, 0;\nvote.sync.any.pred pz, pz, 0xffffffff;\nld.shared.b32 t0, [olp];\nadd.u32 olp, olp, 8;\n"
        "lop3.b32 t1, t0, %50, 0x3ff0, 0xe4;\nld.shared.b32 t1, [t1+%56];\nlop3.b32 kept, t1, t0, 0x1ffc, 0xe4;\nlop3.b32 t2, t1, %51, 3, 0x80;\n"
        "setp.ne.u32 q, t2, 0;\nshr.u32 t2, t1, 13;\nmad.wide.u32 pa, t2, 32, %54;\nmad.wide.u32 pb, t2, 8, %55;\nmov.b32 s0, 0;\n"
        "ld.global.cg.v2.b32 {e0,e1}, [pa];\n@q ld.global.cg.b32 s0, [pb];\nshfl.sync.idx.b32 v, kept, %51, 0x1f, 0xffffffff;\nor.b32 t3, %51, 4;\n"
        "shfl.sync.idx.b32 vB, kept, t3, 0x1f, 0xffffffff;\nshr.u32 bar, v, 1;\nand.b32 bar, bar, 0xff8;\nmbarrier.test_wait.parity.shared.b64 p, [bar+%58], 0;\n"
        "lop3.b32 ida, v, %51, 0x1fff, 0xe4;\nld.volatile.shared.u16 id, [ida+%57];\nvote.sync.all.pred prdy, p, 0xffffffff;\n"
        "RW:\nmma.sync.aligned.m16n8k8.row.col.f32.bf16.bf16.f32 {d0,d1,d2,d3}, {%92,%93}, {s0}, {fz,fz,fz,fz};\n"
        "mma.sync.aligned.m16n8k8.row.col.f32.bf16.bf16.f32 {d4,d5,d6,d7}, {%94,%95}, {s0}, {fz,fz,fz,fz};\ncvt.rn.bf16x2.f32 c0, d2, d0;\n"
        "cvt.rn.bf16x2.f32 c1, d3, d1;\ncvt.rn.bf16x2.f32 c2, d6, d4;\ncvt.rn.bf16x2.f32 c3, d7, d5;\nselp.b32 bA0, c2, c0, psw;\nselp.b32 bA1, c0, c2, psw;\n"
        "selp.b32 bB0, c3, c1, psw;\nselp.b32 bB1, c1, c3, psw;\n"
        "mma.sync.aligned.m16n8k16.row.col.f32.bf16.bf16.f32 {d0,d1,d2,d3}, {%60,%61,%62,%63}, {e0,e1}, {fz,fz,fz,fz};\ncvt.rn.bf16x2.f32 ra0, d2, d0;\n"
        "cvt.rn.bf16x2.f32 rb0, d3, d1;\nmma.sync.aligned.m16n8k16.row.col.f32.bf16.bf16.f32 {d4,d5,d6,d7}, {%64,%65,%66,%67}, {e0,e1}, {fz,fz,fz,fz};\n"
        "cvt.rn.bf16x2.f32 ra1, d6, d4;\ncvt.rn.bf16x2.f32 rb1, d7, d5;\n"
        "mma.sync.aligned.m16n8k16.row.col.f32.bf16.bf16.f32 {d8,d9,d10,d11}, {%68,%69,%70,%71}, {e0,e1}, {fz,fz,fz,fz};\ncvt.rn.bf16x2.f32 ra2, d10, d8;\n"
        "cvt.rn.bf16x2.f32 rb2, d11, d9;\nmma.sync.aligned.m16n8k16.row.col.f32.bf16.bf16.f32 {d12,d13,d14,d15}, {%72,%73,%74,%75}, {e0,e1}, {fz,fz,fz,fz};\n"
        "cvt.rn.bf16x2.f32 ra3, d14, d12;\ncvt.rn.bf16x2.f32 rb3, d15, d13;\n"
        "mma.sync.aligned.m16n8k16.row.col.f32.bf16.bf16.f32 {d16,d17,d18,d19}, {%76,%77,%78,%79}, {e0,e1}, {fz,fz,fz,fz};\ncvt.rn.bf16x2.f32 ra4, d18, d16;\n"
        "cvt.rn.bf16x2.f32 rb4, d19, d17;\nmma.sync.aligned.m16n8k16.row.col.f32.bf16.bf16.f32 {d20,d21,d22,d23}, {%80,%81,%82,%83}, {e0,e1}, {fz,fz,fz,fz};\n"
        "cvt.rn.bf16x2.f32 ra5, d22, d20;\ncvt.rn.bf16x2.f32 rb5, d23, d21;\n"
        "mma.sync.aligned.m16n8k16.row.col.f32.bf16.bf16.f32 {d24,d25,d26,d27}, {%84,%85,%86,%87}, {e0,e1}, {fz,fz,fz,fz};\ncvt.rn.bf16x2.f32 ra6, d26, d24;\n"
        "cvt.rn.bf16x2.f32 rb6, d27, d25;\nmma.sync.aligned.m16n8k16.row.col.f32.bf16.bf16.f32 {d28,d29,d30,d31}, {%88,%89,%90,%91}, {e0,e1}, {fz,fz,fz,fz};\n"
        "cvt.rn.bf16x2.f32 ra7, d30, d28;\ncvt.rn.bf16x2.f32 rb7, d31, d29;\nld.shared.b32 t0, [olp];\nadd.u32 olp, olp, 8;\n"
        "lop3.b32 t1, t0, %50, 0x3ff0, 0xe4;\nld.shared.b32 t1, [t1+%56];\nlop3.b32 kept, t1, t0, 0x1ffc, 0xe4;\nlop3.b32 t2, t1, %51, 3, 0x80;\n"
        "setp.ne.u32 q, t2, 0;\nshr.u32 t2, t1, 13;\nmad.wide.u32 pa, t2, 32, %54;\nmad.wide.u32 pb, t2, 8, %55;\nmov.b32 s0, 0;\n"
        "ld.global.cg.v2.b32 {e0,e1}, [pa];\n@q ld.global.cg.b32 s0, [pb];\n@!prdy bra.uni WA;\n"
        "HA:\nmad.lo.u32 xb, id, 64, %49;\ncvt.u16.u32 i16, id;\nldmatrix.sync.aligned.m8n8.x4.trans.shared.b16 {x0,x1,x2,x3}, [xb];\nxor.b32 t1, xb, 16;\n"
        "ldmatrix.sync.aligned.m8n8.x4.trans.shared.b16 {x4,x5,x6,x7}, [t1];\nxor.b32 t1, xb, 32;\n"
        "ldmatrix.sync.aligned.m8n8.x4.trans.shared.b16 {x8,x9,x10,x11}, [t1];\nxor.b32 t1, xb, 48;\n"
        "ldmatrix.sync.aligned.m8n8.x4.trans.shared.b16 {x12,x13,x14,x15}, [t1];\nxor.b32 t1, xb, 64;\n"
        "ldmatrix.sync.aligned.m8n8.x4.trans.shared.b16 {x16,x17,x18,x19}, [t1];\n@pz bra.uni DONE;\natom.shared.add.u32 pos, [%50+%59], %52;\n"
        "xor.b32 t1, xb, 80;\nldmatrix.sync.aligned.m8n8.x4.trans.shared.b16 {x20,x21,x22,x23}, [t1];\nxor.b32 t1, xb, 96;\n"
        "ldmatrix.sync.aligned.m8n8.x4.trans.shared.b16 {x24,x25,x26,x27}, [t1];\nxor.b32 t1, xb, 112;\n"
        "ldmatrix.sync.aligned.m8n8.x4.trans.shared.b16 {x28,x29,x30,x31}, [t1];\nst.volatile.shared.u16 [pos], i16;\nand.b32 t0, v, 268435456;\n"
        "setp.ne.u32 ps1, t0, 0;\nvote.sync.any.pred ps1, ps1, 0xffffffff;\nand.b32 t0, v, 536870912;\nsetp.ne.u32 ps2, t0, 0;\n"
        "vote.sync.any.pred ps2, ps2, 0xffffffff;\nmov.b32 v, vB;\nshr.u32 bar, v, 1;\nand.b32 bar, bar, 0xff8;\n"
        "mbarrier.test_wait.parity.shared.b64 p, [bar+%58], 0;\nlop3.b32 ida, v, %51, 0x1fff, 0xe4;\nld.volatile.shared.u16 id, [ida+%57];\n"
        "vote.sync.all.pred prdy, p, 0xffffffff;\nmov.b32 {lo, hi}, ra0;\nmov.b32 t2, {lo, lo};\nmul.rn.bf16x2 y0, x0, t2;\nmul.rn.bf16x2 y2, x2, t2;\n"
        "mov.b32 t2, {hi, hi};\nmul.rn.bf16x2 y1, x1, t2;\nmul.rn.bf16x2 y3, x3, t2;\n"
        "mma.sync.aligned.m16n8k16.row.col.f32.bf16.bf16.f32 {d0,d1,d2,d3}, {y0,y1,y2,y3}, {bA0,bA1}, {fz,fz,fz,fz};\ncvt.rn.bf16x2.f32 z0, d1, d0;\n"
        "cvt.rn.bf16x2.f32 z1, d3, d2;\nmov.b32 {lo, hi}, ra1;\nmov.b32 t2, {lo, lo};\nmul.rn.bf16x2 y4, x4, t2;\nmul.rn.bf16x2 y6, x6, t2;\n"
        "mov.b32 t2, {hi, hi};\nmul.rn.bf16x2 y5, x5, t2;\nmul.rn.bf16x2 y7, x7, t2;\n"
        "mma.sync.aligned.m16n8k16.row.col.f32.bf16.bf16.f32 {d4,d5,d6,d7}, {y4,y5,y6,y7}, {bA0,bA1}, {fz,fz,fz,fz};\ncvt.rn.bf16x2.f32 z2, d5, d4;\n"
        "cvt.rn.bf16x2.f32 z3, d7, d6;\nmov.b32 {lo, hi}, ra2;\nmov.b32 t2, {lo, lo};\nmul.rn.bf16x2 y8, x8, t2;\nmul.rn.bf16x2 y10, x10, t2;\n"
        "mov.b32 t2, {hi, hi};\nmul.rn.bf16x2 y9, x9, t2;\nmul.rn.bf16x2 y11, x11, t2;\n"
        "mma.sync.aligned.m16n8k16.row.col.f32.bf16.bf16.f32 {d8,d9,d10,d11}, {y8,y9,y10,y11}, {bA0,bA1}, {fz,fz,fz,fz};\ncvt.rn.bf16x2.f32 z4, d9, d8;\n"
        "cvt.rn.bf16x2.f32 z5, d11, d10;\nmov.b32 {lo, hi}, ra3;\nmov.b32 t2, {lo, lo};\nmul.rn.bf16x2 y12, x12, t2;\nmul.rn.bf16x2 y14, x14, t2;\n"
        "mov.b32 t2, {hi, hi};\nmul.rn.bf16x2 y13, x13, t2;\nmul.rn.bf16x2 y15, x15, t2;\n"
        "mma.sync.aligned.m16n8k16.row.col.f32.bf16.bf16.f32 {d12,d13,d14,d15}, {y12,y13,y14,y15}, {bA0,bA1}, {fz,fz,fz,fz};\ncvt.rn.bf16x2.f32 z6, d13, d12;\n"
        "cvt.rn.bf16x2.f32 z7, d15, d14;\nmov.b32 {lo, hi}, ra4;\nmov.b32 t2, {lo, lo};\nmul.rn.bf16x2 y16, x16, t2;\nmul.rn.bf16x2 y18, x18, t2;\n"
        "mov.b32 t2, {hi, hi};\nmul.rn.bf16x2 y17, x17, t2;\nmul.rn.bf16x2 y19, x19, t2;\n"
        "mma.sync.aligned.m16n8k16.row.col.f32.bf16.bf16.f32 {d16,d17,d18,d19}, {y16,y17,y18,y19}, {bA0,bA1}, {fz,fz,fz,fz};\ncvt.rn.bf16x2.f32 z8, d17, d16;\n"
        "cvt.rn.bf16x2.f32 z9, d19, d18;\nmov.b32 {lo, hi}, ra5;\nmov.b32 t2, {lo, lo};\nmul.rn.bf16x2 y20, x20, t2;\nmul.rn.bf16x2 y22, x22, t2;\n"
        "mov.b32 t2, {hi, hi};\nmul.rn.bf16x2 y21, x21, t2;\nmul.rn.bf16x2 y23, x23, t2;\n"
        "mma.sync.aligned.m16n8k16.row.col.f32.bf16.bf16.f32 {d20,d21,d22,d23}, {y20,y21,y22,y23}, {bA0,bA1}, {fz,fz,fz,fz};\ncvt.rn.bf16x2.f32 z10, d21, d20;\n"
        "cvt.rn.bf16x2.f32 z11, d23, d22;\nmov.b32 {lo, hi}, ra6;\nmov.b32 t2, {lo, lo};\nmul.rn.bf16x2 y24, x24, t2;\nmul.rn.bf16x2 y26, x26, t2;\n"
        "mov.b32 t2, {hi, hi};\nmul.rn.bf16x2 y25, x25, t2;\nmul.rn.bf16x2 y27, x27, t2;\n"
        "mma.sync.aligned.m16n8k16.row.col.f32.bf16.bf16.f32 {d24,d25,d26,d27}, {y24,y25,y26,y27}, {bA0,bA1}, {fz,fz,fz,fz};\ncvt.rn.bf16x2.f32 z12, d25, d24;\n"
        "cvt.rn.bf16x2.f32 z13, d27, d26;\nmov.b32 {lo, hi}, ra7;\nmov.b32 t2, {lo, lo};\nmul.rn.bf16x2 y28, x28, t2;\nmul.rn.bf16x2 y30, x30, t2;\n"
        "mov.b32 t2, {hi, hi};\nmul.rn.bf16x2 y29, x29, t2;\nmul.rn.bf16x2 y31, x31, t2;\n"
        "mma.sync.aligned.m16n8k16.row.col.f32.bf16.bf16.f32 {d28,d29,d30,d31}, {y28,y29,y30,y31}, {bA0,bA1}, {fz,fz,fz,fz};\ncvt.rn.bf16x2.f32 z14, d29, d28;\n"
        "cvt.rn.bf16x2.f32 z15, d31, d30;\n@ps2 bra.uni TA2;\n@ps1 bra.uni TA1;\n"
        "TA0:\nadd.rn.bf16x2 h0, h0, z0;\nadd.rn.bf16x2 h1, h1, z1;\nadd.rn.bf16x2 h2, h2, z2;\nadd.rn.bf16x2 h3, h3, z3;\nadd.rn.bf16x2 h4, h4, z4;\n"
        "add.rn.bf16x2 h5, h5, z5;\nadd.rn.bf16x2 h6, h6, z6;\nadd.rn.bf16x2 h7, h7, z7;\nadd.rn.bf16x2 h8, h8, z8;\nadd.rn.bf16x2 h9, h9, z9;\n"
        "add.rn.bf16x2 h10, h10, z10;\nadd.rn.bf16x2 h11, h11, z11;\nadd.rn.bf16x2 h12, h12, z12;\nadd.rn.bf16x2 h13, h13, z13;\nadd.rn.bf16x2 h14, h14, z14;\n"
        "add.rn.bf16x2 h15, h15, z15;\n@prdy bra.uni HB;\nbra.uni WB;\n"
        "TA1:\nadd.rn.bf16x2 h16, h16, z0;\nadd.rn.bf16x2 h17, h17, z1;\nadd.rn.bf16x2 h18, h18, z2;\nadd.rn.bf16x2 h19, h19, z3;\nadd.rn.bf16x2 h20, h20, z4;\n"
        "add.rn.bf16x2 h21, h21, z5;\nadd.rn.bf16x2 h22, h22, z6;\nadd.rn.bf16x2 h23, h23, z7;\nadd.rn.bf16x2 h24, h24, z8;\nadd.rn.bf16x2 h25, h25, z9;\n"
        "add.rn.bf16x2 h26, h26, z10;\nadd.rn.bf16x2 h27, h27, z11;\nadd.rn.bf16x2 h28, h28, z12;\nadd.rn.bf16x2 h29, h29, z13;\nadd.rn.bf16x2 h30, h30, z14;\n"
        "add.rn.bf16x2 h31, h31, z15;\n@prdy bra.uni HB;\nbra.uni WB;\n"
        "TA2:\nadd.rn.bf16x2 h32, h32, z0;\nadd.rn.bf16x2 h33, h33, z1;\nadd.rn.bf16x2 h34, h34, z2;\nadd.rn.bf16x2 h35, h35, z3;\nadd.rn.bf16x2 h36, h36, z4;\n"
        "add.rn.bf16x2 h37, h37, z5;\nadd.rn.bf16x2 h38, h38, z6;\nadd.rn.bf16x2 h39, h39, z7;\nadd.rn.bf16x2 h40, h40, z8;\nadd.rn.bf16x2 h41, h41, z9;\n"
        "add.rn.bf16x2 h42, h42, z10;\nadd.rn.bf16x2 h43, h43, z11;\nadd.rn.bf16x2 h44, h44, z12;\nadd.rn.bf16x2 h45, h45, z13;\nadd.rn.bf16x2 h46, h46, z14;\n"
        "add.rn.bf16x2 h47, h47, z15;\n@prdy bra.uni HB;\nbra.uni WB;\n"
        "HB:\nmad.lo.u32 xb, id, 64, %49;\ncvt.u16.u32 i16, id;\natom.shared.add.u32 pos, [%50+%59], %52;\n"
        "ldmatrix.sync.aligned.m8n8.x4.trans.shared.b16 {x0,x1,x2,x3}, [xb];\nxor.b32 t1, xb, 16;\n"
        "ldmatrix.sync.aligned.m8n8.x4.trans.shared.b16 {x4,x5,x6,x7}, [t1];\nxor.b32 t1, xb, 32;\n"
        "ldmatrix.sync.aligned.m8n8.x4.trans.shared.b16 {x8,x9,x10,x11}, [t1];\nxor.b32 t1, xb, 48;\n"
        "ldmatrix.sync.aligned.m8n8.x4.trans.shared.b16 {x12,x13,x14,x15}, [t1];\nxor.b32 t1, xb, 64;\n"
        "ldmatrix.sync.aligned.m8n8.x4.trans.shared.b16 {x16,x17,x18,x19}, [t1];\nxor.b32 t1, xb, 80;\n"
        "ldmatrix.sync.aligned.m8n8.x4.trans.shared.b16 {x20,x21,x22,x23}, [t1];\nxor.b32 t1, xb, 96;\n"
        "ldmatrix.sync.aligned.m8n8.x4.trans.shared.b16 {x24,x25,x26,x27}, [t1];\nxor.b32 t1, xb, 112;\n"
        "ldmatrix.sync.aligned.m8n8.x4.trans.shared.b16 {x28,x29,x30,x31}, [t1];\nst.volatile.shared.u16 [pos], i16;\nand.b32 t0, v, 268435456;\n"
        "setp.ne.u32 ps1, t0, 0;\nvote.sync.any.pred ps1, ps1, 0xffffffff;\nand.b32 t0, v, 536870912;\nsetp.ne.u32 ps2, t0, 0;\n"
        "vote.sync.any.pred ps2, ps2, 0xffffffff;\nshfl.sync.idx.b32 v, kept, %51, 0x1f, 0xffffffff;\nor.b32 t3, %51, 4;\n"
        "shfl.sync.idx.b32 vB, kept, t3, 0x1f, 0xffffffff;\nshr.u32 bar, v, 1;\nand.b32 bar, bar, 0xff8;\nmbarrier.test_wait.parity.shared.b64 p, [bar+%58], 0;\n"
        "lop3.b32 ida, v, %51, 0x1fff, 0xe4;\nld.volatile.shared.u16 id, [ida+%57];\nvote.sync.all.pred prdy, p, 0xffffffff;\nmov.b32 {lo, hi}, rb0;\n"
        "mov.b32 t2, {lo, lo};\nmul.rn.bf16x2 y0, x0, t2;\nmul.rn.bf16x2 y2, x2, t2;\nmov.b32 t2, {hi, hi};\nmul.rn.bf16x2 y1, x1, t2;\n"
        "mul.rn.bf16x2 y3, x3, t2;\nmma.sync.aligned.m16n8k16.row.col.f32.bf16.bf16.f32 {d0,d1,d2,d3}, {y0,y1,y2,y3}, {bB0,bB1}, {fz,fz,fz,fz};\n"
        "cvt.rn.bf16x2.f32 z0, d1, d0;\ncvt.rn.bf16x2.f32 z1, d3, d2;\nmov.b32 {lo, hi}, rb1;\nmov.b32 t2, {lo, lo};\nmul.rn.bf16x2 y4, x4, t2;\n"
        "mul.rn.bf16x2 y6, x6, t2;\nmov.b32 t2, {hi, hi};\nmul.rn.bf16x2 y5, x5, t2;\nmul.rn.bf16x2 y7, x7, t2;\n"
        "mma.sync.aligned.m16n8k16.row.col.f32.bf16.bf16.f32 {d4,d5,d6,d7}, {y4,y5,y6,y7}, {bB0,bB1}, {fz,fz,fz,fz};\ncvt.rn.bf16x2.f32 z2, d5, d4;\n"
        "cvt.rn.bf16x2.f32 z3, d7, d6;\nmov.b32 {lo, hi}, rb2;\nmov.b32 t2, {lo, lo};\nmul.rn.bf16x2 y8, x8, t2;\nmul.rn.bf16x2 y10, x10, t2;\n"
        "mov.b32 t2, {hi, hi};\nmul.rn.bf16x2 y9, x9, t2;\nmul.rn.bf16x2 y11, x11, t2;\n"
        "mma.sync.aligned.m16n8k16.row.col.f32.bf16.bf16.f32 {d8,d9,d10,d11}, {y8,y9,y10,y11}, {bB0,bB1}, {fz,fz,fz,fz};\ncvt.rn.bf16x2.f32 z4, d9, d8;\n"
        "cvt.rn.bf16x2.f32 z5, d11, d10;\nmov.b32 {lo, hi}, rb3;\nmov.b32 t2, {lo, lo};\nmul.rn.bf16x2 y12, x12, t2;\nmul.rn.bf16x2 y14, x14, t2;\n"
        "mov.b32 t2, {hi, hi};\nmul.rn.bf16x2 y13, x13, t2;\nmul.rn.bf16x2 y15, x15, t2;\n"
        "mma.sync.aligned.m16n8k16.row.col.f32.bf16.bf16.f32 {d12,d13,d14,d15}, {y12,y13,y14,y15}, {bB0,bB1}, {fz,fz,fz,fz};\ncvt.rn.bf16x2.f32 z6, d13, d12;\n"
        "cvt.rn.bf16x2.f32 z7, d15, d14;\nmov.b32 {lo, hi}, rb4;\nmov.b32 t2, {lo, lo};\nmul.rn.bf16x2 y16, x16, t2;\nmul.rn.bf16x2 y18, x18, t2;\n"
        "mov.b32 t2, {hi, hi};\nmul.rn.bf16x2 y17, x17, t2;\nmul.rn.bf16x2 y19, x19, t2;\n"
        "mma.sync.aligned.m16n8k16.row.col.f32.bf16.bf16.f32 {d16,d17,d18,d19}, {y16,y17,y18,y19}, {bB0,bB1}, {fz,fz,fz,fz};\ncvt.rn.bf16x2.f32 z8, d17, d16;\n"
        "cvt.rn.bf16x2.f32 z9, d19, d18;\nmov.b32 {lo, hi}, rb5;\nmov.b32 t2, {lo, lo};\nmul.rn.bf16x2 y20, x20, t2;\nmul.rn.bf16x2 y22, x22, t2;\n"
        "mov.b32 t2, {hi, hi};\nmul.rn.bf16x2 y21, x21, t2;\nmul.rn.bf16x2 y23, x23, t2;\n"
        "mma.sync.aligned.m16n8k16.row.col.f32.bf16.bf16.f32 {d20,d21,d22,d23}, {y20,y21,y22,y23}, {bB0,bB1}, {fz,fz,fz,fz};\ncvt.rn.bf16x2.f32 z10, d21, d20;\n"
        "cvt.rn.bf16x2.f32 z11, d23, d22;\nmov.b32 {lo, hi}, rb6;\nmov.b32 t2, {lo, lo};\nmul.rn.bf16x2 y24, x24, t2;\nmul.rn.bf16x2 y26, x26, t2;\n"
        "mov.b32 t2, {hi, hi};\nmul.rn.bf16x2 y25, x25, t2;\nmul.rn.bf16x2 y27, x27, t2;\n"
        "mma.sync.aligned.m16n8k16.row.col.f32.bf16.bf16.f32 {d24,d25,d26,d27}, {y24,y25,y26,y27}, {bB0,bB1}, {fz,fz,fz,fz};\ncvt.rn.bf16x2.f32 z12, d25, d24;\n"
        "cvt.rn.bf16x2.f32 z13, d27, d26;\nmov.b32 {lo, hi}, rb7;\nmov.b32 t2, {lo, lo};\nmul.rn.bf16x2 y28, x28, t2;\nmul.rn.bf16x2 y30, x30, t2;\n"
        "mov.b32 t2, {hi, hi};\nmul.rn.bf16x2 y29, x29, t2;\nmul.rn.bf16x2 y31, x31, t2;\n"
        "mma.sync.aligned.m16n8k16.row.col.f32.bf16.bf16.f32 {d28,d29,d30,d31}, {y28,y29,y30,y31}, {bB0,bB1}, {fz,fz,fz,fz};\ncvt.rn.bf16x2.f32 z14, d29, d28;\n"
        "cvt.rn.bf16x2.f32 z15, d31, d30;\n@ps2 bra.uni TB2;\n@ps1 bra.uni TB1;\n"
        "TB0:\nadd.rn.bf16x2 h0, h0, z0;\nadd.rn.bf16x2 h1, h1, z1;\nadd.rn.bf16x2 h2, h2, z2;\nadd.rn.bf16x2 h3, h3, z3;\nadd.rn.bf16x2 h4, h4, z4;\n"
        "add.rn.bf16x2 h5, h5, z5;\nadd.rn.bf16x2 h6, h6, z6;\nadd.rn.bf16x2 h7, h7, z7;\nadd.rn.bf16x2 h8, h8, z8;\nadd.rn.bf16x2 h9, h9, z9;\n"
        "add.rn.bf16x2 h10, h10, z10;\nadd.rn.bf16x2 h11, h11, z11;\nadd.rn.bf16x2 h12, h12, z12;\nadd.rn.bf16x2 h13, h13, z13;\nadd.rn.bf16x2 h14, h14, z14;\n"
        "add.rn.bf16x2 h15, h15, z15;\nbra.uni RW;\n"
        "TB1:\nadd.rn.bf16x2 h16, h16, z0;\nadd.rn.bf16x2 h17, h17, z1;\nadd.rn.bf16x2 h18, h18, z2;\nadd.rn.bf16x2 h19, h19, z3;\nadd.rn.bf16x2 h20, h20, z4;\n"
        "add.rn.bf16x2 h21, h21, z5;\nadd.rn.bf16x2 h22, h22, z6;\nadd.rn.bf16x2 h23, h23, z7;\nadd.rn.bf16x2 h24, h24, z8;\nadd.rn.bf16x2 h25, h25, z9;\n"
        "add.rn.bf16x2 h26, h26, z10;\nadd.rn.bf16x2 h27, h27, z11;\nadd.rn.bf16x2 h28, h28, z12;\nadd.rn.bf16x2 h29, h29, z13;\nadd.rn.bf16x2 h30, h30, z14;\n"
        "add.rn.bf16x2 h31, h31, z15;\nbra.uni RW;\n"
        "TB2:\nadd.rn.bf16x2 h32, h32, z0;\nadd.rn.bf16x2 h33, h33, z1;\nadd.rn.bf16x2 h34, h34, z2;\nadd.rn.bf16x2 h35, h35, z3;\nadd.rn.bf16x2 h36, h36, z4;\n"
        "add.rn.bf16x2 h37, h37, z5;\nadd.rn.bf16x2 h38, h38, z6;\nadd.rn.bf16x2 h39, h39, z7;\nadd.rn.bf16x2 h40, h40, z8;\nadd.rn.bf16x2 h41, h41, z9;\n"
        "add.rn.bf16x2 h42, h42, z10;\nadd.rn.bf16x2 h43, h43, z11;\nadd.rn.bf16x2 h44, h44, z12;\nadd.rn.bf16x2 h45, h45, z13;\nadd.rn.bf16x2 h46, h46, z14;\n"
        "add.rn.bf16x2 h47, h47, z15;\nbra.uni RW;\n"
        "WA:\nsetp.ge.u32 p, v, 805306368;\nvote.sync.all.pred p, p, 0xffffffff;\n@p bra.uni DONE;\nmov.b32 n, 0;\nshr.u32 t2, v, 1;\nand.b32 t2, t2, 0xff8;\n"
        "WA3:\nmbarrier.try_wait.parity.shared.b64 p, [t2+%58], 0;\nvote.sync.all.pred p, p, 0xffffffff;\nadd.u32 n, n, 1;\nsetp.lt.and.u32 q, n, 1000000, !p;\n"
        "@q bra.uni WA3;\nlop3.b32 ida, v, %51, 0x1fff, 0xe4;\nld.volatile.shared.u16 id, [ida+%57];\nbra.uni HA;\n"
        "WB:\nsetp.ge.u32 p, v, 805306368;\nvote.sync.all.pred p, p, 0xffffffff;\n@p bra.uni DONE;\nmov.b32 n, 0;\nshr.u32 t2, v, 1;\nand.b32 t2, t2, 0xff8;\n"
        "WB3:\nmbarrier.try_wait.parity.shared.b64 p, [t2+%58], 0;\nvote.sync.all.pred p, p, 0xffffffff;\nadd.u32 n, n, 1;\nsetp.lt.and.u32 q, n, 1000000, !p;\n"
        "@q bra.uni WB3;\nlop3.b32 ida, v, %51, 0x1fff, 0xe4;\nld.volatile.shared.u16 id, [ida+%57];\nbra.uni HB;\n"
        "DONE:\nmov.b32 %0, h0;\nmov.b32 %1, h1;\nmov.b32 %2, h2;\nmov.b32 %3, h3;\nmov.b32 %4, h4;\nmov.b32 %5, h5;\nmov.b32 %6, h6;\nmov.b32 %7, h7;\n"
        "mov.b32 %8, h8;\nmov.b32 %9, h9;\nmov.b32 %10, h10;\nmov.b32 %11, h11;\nmov.b32 %12, h12;\nmov.b32 %13, h13;\nmov.b32 %14, h14;\nmov.b32 %15, h15;\n"
        "mov.b32 %16, h16;\nmov.b32 %17, h17;\nmov.b32 %18, h18;\nmov.b32 %19, h19;\nmov.b32 %20, h20;\nmov.b32 %21, h21;\nmov.b32 %22, h22;\nmov.b32 %23, h23;\n"
        "mov.b32 %24, h24;\nmov.b32 %25, h25;\nmov.b32 %26, h26;\nmov.b32 %27, h27;\nmov.b32 %28, h28;\nmov.b32 %29, h29;\nmov.b32 %30, h30;\nmov.b32 %31, h31;\n"
        "mov.b32 %32, h32;\nmov.b32 %33, h33;\nmov.b32 %34, h34;\nmov.b32 %35, h35;\nmov.b32 %36, h36;\nmov.b32 %37, h37;\nmov.b32 %38, h38;\nmov.b32 %39, h39;\n"
        "mov.b32 %40, h40;\nmov.b32 %41, h41;\nmov.b32 %42, h42;\nmov.b32 %43, h43;\nmov.b32 %44, h44;\nmov.b32 %45, h45;\nmov.b32 %46, h46;\nmov.b32 %47, h47;\n"
        "}\n"
        : "=r"(pk[0]), "=r"(pk[1]), "=r"(pk[2]), "=r"(pk[3]), "=r"(pk[4]), "=r"(pk[5]), "=r"(pk[6]), "=r"(pk[7]), "=r"(pk[8]), "=r"(pk[9]),
          "=r"(pk[10]), "=r"(pk[11]), "=r"(pk[12]), "=r"(pk[13]), "=r"(pk[14]), "=r"(pk[15]), "=r"(pk[16]), "=r"(pk[17]), "=r"(pk[18]), "=r"(pk[19]),
          "=r"(pk[20]), "=r"(pk[21]), "=r"(pk[22]), "=r"(pk[23]), "=r"(pk[24]), "=r"(pk[25]), "=r"(pk[26]), "=r"(pk[27]), "=r"(pk[28]), "=r"(pk[29]),
          "=r"(pk[30]), "=r"(pk[31]), "=r"(pk[32]), "=r"(pk[33]), "=r"(pk[34]), "=r"(pk[35]), "=r"(pk[36]), "=r"(pk[37]), "=r"(pk[38]), "=r"(pk[39]),
          "=r"(pk[40]), "=r"(pk[41]), "=r"(pk[42]), "=r"(pk[43]), "=r"(pk[44]), "=r"(pk[45]), "=r"(pk[46]), "=r"(pk[47])
        : "r"(olp), "r"(xa), "r"(ln), "r"(lc), "r"(linc), "r"(lt), "l"(ea), "l"(sh),
          "n"(sb + SM_REC), "n"(sb + SM_R), "n"(sb + SM_BAR), "n"(sb + SM_CTR),
          "r"(w[0]), "r"(w[1]), "r"(w[2]), "r"(w[3]), "r"(w[4]), "r"(w[5]), "r"(w[6]), "r"(w[7]), "r"(w[8]), "r"(w[9]), "r"(w[10]), "r"(w[11]),
          "r"(w[12]), "r"(w[13]), "r"(w[14]), "r"(w[15]), "r"(w[16]), "r"(w[17]), "r"(w[18]), "r"(w[19]), "r"(w[20]), "r"(w[21]), "r"(w[22]),
          "r"(w[23]), "r"(w[24]), "r"(w[25]), "r"(w[26]), "r"(w[27]), "r"(w[28]), "r"(w[29]), "r"(w[30]), "r"(w[31]), "r"(w[32]), "r"(w[33]),
          "r"(w[34]), "r"(w[35])
        : "memory");
}

__device__ __forceinline__ void wf_done() {
    asm volatile("fence.proxy.async.global;\nred.release.gpu.global.add.u32 [%0], 1;" ::"l"(&g_wfcnt) : "memory");
}

template <int NS>
__device__ __forceinline__ void consumer(const __nv_bfloat16* __restrict__ sh,
                                         const __nv_bfloat16* __restrict__ ea, __nv_bfloat16* __restrict__ out, int N, int npb) {
    uint32_t pk[NS * 16];
    {
        const int lane = threadIdx.x & 31, warp = threadIdx.x >> 5;
        const int mi = lane >> 3, r = lane & 7, j = r >> 1;
        const int u = 2 * ((mi >> 1) ^ (j >> 1)) + (r & 1), L = 2 * u + (mi & 1), ph = (j ^ (j >> 1)) & 1;
        uint32_t w[36];
        {
            const uint32_t a = sb + SC_WR + (4 * j + (r & 1) + (mi & 2)) * 272 + (mi & 1) * 128;
#pragma unroll
            for (int c = 0; c < 8; c++)
                asm volatile("ldmatrix.sync.aligned.m8n8.x4.trans.shared.b16 {%0,%1,%2,%3}, [%4];"
                             : "=r"(w[4 * c]), "=r"(w[4 * c + 1]), "=r"(w[4 * c + 2]), "=r"(w[4 * c + 3]) : "r"(a + c * 16) : "memory");
            const uint32_t ca = sb + SC_CG + (lane & 2) * 8 + ((lane >> 2) & 3) * 2;
#pragma unroll
            for (int k = 0; k < 4; k++) {
                const uint32_t f = lds16(ca + 32 * k) | (lds16(ca + 32 * k + 8) << 16);
                w[32 + k] = (lane & 1) == (lane >> 4) ? f : 0;
            }
            asm volatile("fence.proxy.async.shared::cta;\nbar.sync 2, %0;" ::"n"(NCW * 32) : "memory");
            if (threadIdx.x < WSL) sts16(sb + SM_R + 0x2000 + (4 + SP - WSL + lane) * 4, (sb + SC_WR) / 64 + 1 + lane * 16);
        }
        if ((threadIdx.x >> 2) == WFT && blockIdx.x < 128) wf_done();
        if (threadIdx.x == NCW * 32 - 1) {
            const uint32_t target = lds32(sb + SM_MISC + 16);
            for (int n = 0; n < 1000000; n++) {
                uint32_t c;
                asm volatile("ld.acquire.gpu.global.u32 %0, [%1];" : "=r"(c) : "l"(&g_wfcnt) : "memory");
                if ((int)(c - target) >= 0) break;
            }
            asm volatile("st.release.cta.shared.u32 [%0], 1;" ::"r"(sb + SM_MISC + 24) : "memory");
        }
        __syncwarp();
        const uint32_t xa = __shfl_sync(0xffffffffu, L * 128 + (((L + ph) & 7) << 4) - 64, lane);
        const uint32_t ln = __shfl_sync(0xffffffffu, lane * 16 + (lane >> 3) * 4, lane);
        const uint32_t lc = __shfl_sync(0xffffffffu, j * 8 + (1 << (lane & 1)) + (ph << 13), lane);
        const uint32_t linc = __shfl_sync(0xffffffffu, (lane & 0x19) ? 0 : 8, lane);
        const uint32_t lt = __shfl_sync(0xffffffffu, lane & 3, lane);
        const uint32_t olp = sb + SM_OL + warp * (OLN * 4) + (lane & 4);
        if constexpr (NS == 4) consume4(pk, w, olp, xa, ln, lc, linc, lt, ea, sh);
        else consume3(pk, w, olp, xa, ln, lc, linc, lt, ea, sh);
    }
    TLMAX(10);
    const int tid = thread_id(), lane = tid & 31, warp = tid >> 5, g = lane >> 2, t = lane & 3;
    const uint32_t wc = lds32(sb + SM_MISC + 12) + 1;
    const uint32_t inv = lds32(sb + SM_INV + warp * 4);
    const int node0 = cta_id() * npb, nnodes = min(npb, N - node0);
#pragma unroll
    for (int s = 0; s < NS; s += 2) {
        uint32_t af[32];
#pragma unroll
        for (int i = 0; i < 16; i++) {
            af[2 * i] = movm(pk[s * 16 + i]);
            af[2 * i + 1] = movm(pk[(s + 1 < NS ? s + 1 : s) * 16 + i]);
        }
        if (s == 0) {
#pragma unroll
            for (int Q = 0; Q < 4; Q++) mbar_wait0(sb + SM_BAR + (wc + Q) * 8);
            TLMAX(11);
        }
        const int nl0 = ((inv >> (8 * s)) & 255) + (g >> 2) * 40, nl1 = ((inv >> (8 * s + 8)) & 255) + (g >> 2) * 40;
        uint4* op0 = (uint4*)(out + ((size_t)(node0 + nl0) * 4 + (g & 3)) * 128 + 8 * t);
        uint4* op1 = op0 + (nl1 - nl0) * 64;
#pragma unroll
        for (int H = 0; H < 2; H++) {
            float o[32];
            uint4 c[4];
#pragma unroll
            for (int k = 0; k < 4; k++) c[k] = lds128(sb + SM_R + (k & 1) * 0x2000 + (wc + 2 * H + (k >> 1)) * 16);
            project64(o, af, c);
#pragma unroll
            for (int Q = 0; Q < 2; Q++) {
                const float* q = o + Q * 16;
                if (nl0 < nnodes)
                    op0[H * 8 + Q * 4] =
                        make_uint4(pack_bf16(q[0], q[1]), pack_bf16(q[4], q[5]), pack_bf16(q[8], q[9]), pack_bf16(q[12], q[13]));
                if (s + 1 < NS && nl1 < nnodes)
                    op1[H * 8 + Q * 4] =
                        make_uint4(pack_bf16(q[2], q[3]), pack_bf16(q[6], q[7]), pack_bf16(q[10], q[11]), pack_bf16(q[14], q[15]));
            }
        }
    }
}

#define XSTR(x) XSTR2(x)
#define XSTR2(x) #x
__device__ __forceinline__ void producer(const CUtensorMap* tmx, int pw, int tau, int ramp, int rampn, int tdelay, int spr, int sprn) {
    const uint32_t nch = lds32(sb + SM_MISC + 12);
    {
        const uint32_t c = threadIdx.x & 127;
        int s[3];
#pragma unroll
        for (int k = 0; k < 3; k++)
            s[k] = max((int)lds32(sb + SM_R + (c + k * 128) * 16 + 4), (int)lds32(sb + SM_R + 0x2000 + (c + k * 128) * 16 + 4)) >> 16;
#pragma unroll
        for (int k = 0; k < 3; k++)
            if (k < 2 || c + 256 < NBAR) sts32(sb + SM_OFF + (c + k * 128) * 4, tdelay + ((s[k] * tau + min(s[k], rampn) * ramp - max(s[k] - sprn, 0) * spr) >> 10));
        asm volatile("bar.sync 1, 128;" ::: "memory");
    }
    if (elect()) {
        asm volatile(
            "{\n.reg .pred p, lead;\n.reg .b32 ra, oa, off, noff, due, now, a0, a1, a2, a3, b0, b1, b2, b3, d, r, z<8>, bar, t, n, tb, ta, prev;\n"
            ".reg .b64 lg, t64;\n"
            "mov.b32 ta, %5;\nld.volatile.shared.v4.b32 {z0,z1,z2,z3}, [ta+32];\nld.volatile.shared.v4.b32 {z4,z5,z6,z7}, [ta+32];\n"
            "mad.lo.u32 ra, %0, 16, %9;\n"
            "mov.b32 n, 0;\nld.volatile.shared.b32 prev, [ta];\nmov.b32 off, 1000000;\nsetp.eq.u32 lead, %0, 0;\n"
            "mov.u32 due, %%globaltimer_lo;\n"
            "setp.gt.u32 p, ra, %1;\n@p bra.uni END;\nbra.uni GO;\n"
            "LOOP:\n"
            "sub.u32 t, due, now;\nsetp.le.s32 p, t, %2;\n@p bra.uni GO;\n"
            "sub.u32 t, t, %2;\n"
            "WAIT:\n"
            "shr.u32 t, t, 1;\nnanosleep.u32 t;\n"
            "ld.volatile.shared.b32 tb, [ta];\nmov.u32 now, %%globaltimer_lo;\nadd.u32 due, tb, off;\nsub.u32 t, due, now;\n"
            "setp.gt.s32 p, t, %12;\n@p bra.uni WAIT;\n"
            "GO:\n"
            "mov.u32 now, %%globaltimer_lo;\n"
            "ld.volatile.shared.v4.b32 {a0,a1,a2,a3}, [ra];\nld.volatile.shared.v4.b32 {b0,b1,b2,b3}, [ra+0x2000];\n"
            "shr.u32 oa, ra, 2;\nshr.u32 bar, ra, 1;\nadd.u32 bar, bar, %10;\nld.shared.b32 noff, [oa+%11];\nld.volatile.shared.b32 tb, [ta];\n"
            "lop3.b32 t, a0, a1, a2, 0x80;\nlop3.b32 d, a3, b0, b1, 0x80;\nlop3.b32 t, t, d, b2, 0x80;\nand.b32 t, t, b3;\nand.b32 t, t, 1;\n"
            "setp.eq.u32 p, t, 0;\n"
            "@p bra.uni BACK;\nmbarrier.arrive.expect_tx.shared.b64 _, [bar], 8192;\n"
            "and.b32 d, a0, 0xffe;\nshl.b32 d, d, 6;\nshr.s32 r, a0, 13;\n"
            "cp.async.bulk.tensor.2d.shared::cluster.global.mbarrier::complete_tx::bytes [d], [%3, {z0, r}], [bar];\n"
            "and.b32 d, a1, 0xffe;\nshl.b32 d, d, 6;\nshr.s32 r, a1, 13;\n"
            "cp.async.bulk.tensor.2d.shared::cluster.global.mbarrier::complete_tx::bytes [d], [%3, {z1, r}], [bar];\n"
            "and.b32 d, a2, 0xffe;\nshl.b32 d, d, 6;\nshr.s32 r, a2, 13;\n"
            "cp.async.bulk.tensor.2d.shared::cluster.global.mbarrier::complete_tx::bytes [d], [%3, {z2, r}], [bar];\n"
            "and.b32 d, a3, 0xffe;\nshl.b32 d, d, 6;\nshr.s32 r, a3, 13;\n"
            "cp.async.bulk.tensor.2d.shared::cluster.global.mbarrier::complete_tx::bytes [d], [%3, {z3, r}], [bar];\n"
            "and.b32 d, b0, 0xffe;\nshl.b32 d, d, 6;\nshr.s32 r, b0, 13;\n"
            "cp.async.bulk.tensor.2d.shared::cluster.global.mbarrier::complete_tx::bytes [d], [%3, {z4, r}], [bar];\n"
            "and.b32 d, b1, 0xffe;\nshl.b32 d, d, 6;\nshr.s32 r, b1, 13;\n"
            "cp.async.bulk.tensor.2d.shared::cluster.global.mbarrier::complete_tx::bytes [d], [%3, {z5, r}], [bar];\n"
            "and.b32 d, b2, 0xffe;\nshl.b32 d, d, 6;\nshr.s32 r, b2, 13;\n"
            "cp.async.bulk.tensor.2d.shared::cluster.global.mbarrier::complete_tx::bytes [d], [%3, {z6, r}], [bar];\n"
            "and.b32 d, b3, 0xffe;\nshl.b32 d, d, 6;\nshr.s32 r, b3, 13;\n"
            "cp.async.bulk.tensor.2d.shared::cluster.global.mbarrier::complete_tx::bytes [d], [%3, {z7, r}], [bar];\n"
            "sub.u32 t, now, off;\nmov.b32 off, noff;\nadd.u32 due, off, tb;\n"
            "add.u32 ra, ra, 64;\nsetp.gt.u32 p, ra, %1;\n@p bra.uni END;\n@!lead bra.uni LOOP;\n"
            "add.u32 d, ta, 16;\ncp.async.bulk.shared::cluster.global.mbarrier::complete_tx::bytes [ta], [%4], 16, [d];\n"
            "sub.u32 d, prev, tb;\nsub.u32 r, t, tb;\nmin.s32 d, d, r;\nmov.b32 prev, t;\nsetp.le.s32 p, d, %6;\n@p bra.uni LOOP;\n"
            "setp.lt.u32 p, ra, %8;\n@p bra.uni LOOP;\nadd.u32 r, ra, " XSTR(SLIPEND) ";\nsetp.gt.u32 p, r, %1;\n@p bra.uni LOOP;\n"
            "ld.volatile.shared.b64 t64, [ta];\ncvt.u32.u64 r, t64;\nsub.u32 r, tb, r;\nsub.u32 d, d, %7;\nadd.s32 d, d, r;\n"
            "cvt.s64.s32 lg, d;\nadd.u64 t64, t64, lg;\n"
            "red.relaxed.gpu.global.max.u64 [%4], t64;\nbra.uni LOOP;\n"
            "BACK:\n"
            "nanosleep.u32 32;\nadd.u32 n, n, 1;\nsetp.lt.u32 p, n, 1000000;\n@p bra.uni GO;\n"
            "END:\n}" ::"r"(pw),
            "r"(sb + SM_R + nch * 16), "n"(AHEAD + EARLY), "l"(tmx), "l"(&g_sync), "n"(sb + SM_MISC + 32), "n"(SLIPTH), "n"(SLIPSUB),
            "n"(sb + SM_R + SLIPFROM * 16), "n"(sb + SM_R + 16), "n"(sb + SM_BAR - (sb + SM_R) / 2), "n"(sb + SM_OFF + 16 - (sb + SM_R) / 4), "n"(EARLY)
            : "memory");
        const uint32_t ra = sb + SM_R + (nch + 1 + pw) * 16, bar = sb + SM_BAR + (nch + 1 + pw) * 8;
        uint4 a, b;
        for (int n = 0; n < 1000000; n++) {
            uint32_t c;
            asm volatile("ld.acquire.cta.shared.u32 %0, [%1];" : "=r"(c) : "r"(sb + SM_MISC + 24) : "memory");
            a = lds128(ra), b = lds128(ra + 0x2000);
            if (a.x & a.y & a.z & a.w & b.x & b.y & b.z & b.w & c) break;
        }
        asm volatile("fence.proxy.async.global;" ::: "memory");
        asm volatile("mbarrier.arrive.expect_tx.shared.b64 _, [%0], 8192;" ::"r"(bar) : "memory");
        const uint32_t c[8] = {a.x, a.y, a.z, a.w, b.x, b.y, b.z, b.w};
#pragma unroll
        for (int i = 0; i < 8; i++)
            asm volatile("cp.async.bulk.shared::cluster.global.mbarrier::complete_tx::bytes [%0], [%1], 1024, [%2];" ::"r"(
                             (c[i] & 0xffe) << 6),
                         "l"(g_wf + (pw * 8 + i) * 64), "r"(bar)
                         : "memory");
    }
}

#define BARINIT(w, n)                                                                                              \
    if (elect()) {                                                                                                 \
        _Pragma("unroll") for (int k = 0; k < (NBAR + n - 1) / n; k++)                                             \
            asm volatile("mbarrier.init.shared.b64 [%0], 1;" ::"r"(sb + SM_BAR + ((w) * ((NBAR + n - 1) / n) + k) * 8)); \
        asm volatile("fence.mbarrier_init.release.cluster;" ::: "memory");                                         \
    }                                                                                                              \
    __syncwarp();

__global__ void __launch_bounds__(NT, 1)
main_kernel(const __grid_constant__ CUtensorMap tmx, const __nv_bfloat16* __restrict__ x, const int* __restrict__ src,
            const int* __restrict__ dst, const __nv_bfloat16* __restrict__ sh, const __nv_bfloat16* __restrict__ ea,
            const __nv_bfloat16* __restrict__ cg, const __nv_bfloat16* __restrict__ wr,
            const __nv_bfloat16* __restrict__ wout, __nv_bfloat16* __restrict__ out, int N, int E, int npb,
            unsigned npb_magic, int chunk, unsigned bkm, int tau, int ramp, int rampn, int tdelay, unsigned polld, int spr, int sprn) {
    extern __shared__ __align__(1024) unsigned char smem[];
    if (s2u(smem) != sb) __trap();
    const int tid = threadIdx.x, lane = tid & 31;
    const int warp = __shfl_sync(0xffffffffu, tid >> 5, 0);
    const int nbins = gridDim.x;
    bool fast = chunk > 0;
    TLSTAMP(0);
    if (fast) {
        const int e0 = blockIdx.x * chunk + tid, left = min(E, (int)(blockIdx.x + 1) * chunk) - e0;
        uint32_t pd[KE], ps[KE];
        {
            const int* dp = dst + e0;
            const int* sp = src + e0;
#pragma unroll
            for (int k = 0; k < KE; k++) {
                pd[k] = nbins * npb, ps[k] = 0;
                asm volatile("{\n.reg .pred p;\nsetp.gt.s32 p, %4, %5;\n@p ld.global.nc.u32 %0, [%2];\n@p ld.global.nc.u32 %1, [%3];\n}"
                             : "+r"(pd[k]), "+r"(ps[k]) : "l"(dp + k * NT), "l"(sp + k * NT), "r"(left), "r"(k * NT));
            }
        }
        uint32_t epoch = 0;
        if (tid == NT - 1) asm volatile("ld.relaxed.gpu.global.u32 %0, [%1];" : "=r"(epoch) : "l"(&g_epoch) : "memory");
        uint4 wv, wo[3];
        const bool wrow = (tid >> 2) == WFT && blockIdx.x < 128;
        {
            const uint4* wp = tid < 256 ? (const uint4*)wr + tid
                              : wrow    ? (const uint4*)(wout + blockIdx.x * 128 + (tid & 3) * 32)
                                        : (const uint4*)cg + (tid & 7);
            if (tid < 264 || wrow) wv = __ldg(wp);
            if (wrow) wo[0] = __ldg(wp + 1), wo[1] = __ldg(wp + 2), wo[2] = __ldg(wp + 3);
        }
        const uint32_t t16 = sb + tid * 16;
        const uint32_t sa = sb + SC_STG + (tid >> 4) * CP + (tid & 15) * 16;
        const uint32_t none = (40u << 23) + (lane << 16);
        const uint32_t pade = min(blockIdx.x * chunk, E - 1) << 13;
        const bool fifth = warp * 2 + 128 < nbins;
#pragma unroll
        for (int k = 0; k < 5; k++)
            if (k < 4 || fifth) sts128(sa + k * 32 * CP, none, 0, none, 0);
        if (tid < 160) sts32(sb + SC_CNT + tid * 4, 8);
#pragma unroll
        for (int k = 0; k < 4; k++) sts128(t16 + SC_TABB + k * NT * 16, 0, 0, 0, 0);
#pragma unroll
        for (int k = 0; k < 3; k++)
            sts128(t16 + SC_TMP + k * NT * 16, (tid + blockIdx.x) & 63, pade, (tid + blockIdx.x + 32) & 63, pade);
        if (tid < RP / 4) {
            uint32_t c[4], d[4];
#pragma unroll
            for (int i = 0; i < 4; i++) {
                const uint32_t k = tid * 4 - 4 + i;
                c[i] = d[i] = 0xc0000000u;
                if (warp == 0 && k < SP) c[i] += sb / 64 + 1 + k * 16;
                if (warp == 0 && k < SP - WSL) d[i] = c[i] + (SP * 1024 + 128) / 64;
            }
            static_assert(SP + 4 <= 128, "first warp");
            sts128(t16 + SM_R, c[0], c[1], c[2], c[3]);
            sts128(t16 + SM_R + 0x2000, d[0], d[1], d[2], d[3]);
        }
        constexpr uint32_t OLEND = (7u << 28) | ((RECN - 4) * 4);
        if (tid < NCW * OLN / 4) sts128(t16 + SM_OL, OLEND, OLEND, OLEND, OLEND);
        if (warp == 12) {
            sts32(sb + SM_CTR + lane * 16 + (lane >> 3) * 4,
                  sb + SM_R + ((lane & 0x19) ? (RP - 1) * 4 : (4 + SP) * 4 + (((lane >> 1) ^ (lane >> 2)) & 1) * 0x2000 + (lane & 4)));
            if (lane < 3) sts32(sb + SM_MISC + (lane ? 16 + lane * 4 : 4), 0);
            if (lane == 8) sts128(sb + SM_REC + (RECN - 4) * 4, pade, pade, pade, pade), sts128(sb + SM_MISC + 64, 0, 0, 0, 0);
            if (lane == 9) asm volatile("prefetch.tensormap [%0];" ::"l"(&tmx) : "memory");
        }
        __syncthreads();
        TLSTAMP(1);

        {
            uint32_t b[KE], r[KE];
#pragma unroll
            for (int k = 0; k < KE; k++) {
                b[k] = __umulhi(pd[k], npb_magic);
                r[k] = atoms_add(sb + SC_CNT + b[k] * 4, 8);
            }
            if (tid == NT - 1) {
                sts32(sb + SM_MISC + 8, (epoch % 2047 + 1) << 2);
                asm volatile("{\n.reg .b64 t;\nmov.u64 t, %%globaltimer;\nred.relaxed.gpu.global.max.u64 [%0], t;\n"
                             "red.relaxed.gpu.global.add.u32 [%0+8], 1;\n}" ::"l"(&g_sync) : "memory");
            }
            __syncwarp();
            const uint32_t et = (e0 << 13) + 1;
#pragma unroll
            for (int k = 0; k < KE; k++) {
                asm volatile(
                    "{\n.reg .pred p;\n.reg .b32 d, t, u;\nmad.lo.u32 d, %1, %3, %0;\nsetp.ge.u32 p, d, 40;\nmul.hi.u32 t, %2, %4;\n"
                    "mad.lo.u32 t, d, 128, t;\nmad.lo.u32 t, t, 65536, %2;\n@p add.u32 t, t, %7;\nmov.b32 u, %5;\n@p add.u32 u, u, 1;\n"
                    "min.u32 d, %6, 376;\nmad.lo.u32 d, %1, %9, d;\nst.shared.v2.b32 [d+%8], {t, u};\n}" ::"r"(pd[k]),
                    "r"(b[k]), "r"(ps[k]), "r"(-npb), "r"(bkm << 7), "r"(et + (k * NT << 13)), "r"(r[k]), "n"(-(40 << 23)), "n"(sb + SC_STG),
                    "n"(CP)
                    : "memory");
            }
        }
        if (tid < 264) sts128(sb + SC_WR + (tid >> 4) * 272 + (tid & 15) * 16, wv.x, wv.y, wv.z, wv.w);
        const uint32_t hm = (tid & 15) ? 0 : 1 << 13;
        uint4* gp = g_cell + ((tid >> 4) * MAXB + blockIdx.x) * 24 + (tid & 15);
        __syncthreads();
        TLSTAMP(6);
        const uint32_t tag = lds32(sb + SM_MISC + 8);
        {
            uint32_t c[5] = {0, 0, 0, 0, 0};
            uint4 v[5];
#pragma unroll
            for (int k = 0; k < 5; k++)
                if (k < 4 || fifth) c[k] = lds32(sb + SC_CNT + (tid >> 4) * 4 + k * 128), v[k] = lds128(sa + k * 32 * CP);
#pragma unroll
            for (int k = 0; k < 5; k++) {
                if (k < 4 || fifth) {
                    v[k].y += c[k] * hm + tag, v[k].w += tag;
                    st_cell(gp + k * 32 * MAXB * 24, v[k]);
                }
            }
            const uint32_t lim = 256 + (tid & 15) * 16;
            if (max(max(c[0], c[1]), max(max(c[2], c[3]), c[4])) > lim && lim < 384) {
#pragma unroll
                for (int k = 0; k < 5; k++) {
                    if (c[k] > lim) {
                        uint4 q = lds128(sa + k * 32 * CP + 256);
                        if (c[k] <= lim + 8) q.z = none, q.w = 0;
                        q.y += tag, q.w += tag;
                        st_cell(gp + k * 32 * MAXB * 24 + 16, q);
                    }
                }
            }
        }
        if (wrow) {
            const int k = blockIdx.x;
            uint4* dp = &g_wf[((tid & 3) * 8 + ((k & 63) >> 3)) * 64 + (k >> 6) * 32 + (k & 7)];
            dp[0] = make_uint4(wv.x, wo[0].x, wo[1].x, wo[2].x);
            dp[8] = make_uint4(wv.y, wo[0].y, wo[1].y, wo[2].y);
            dp[16] = make_uint4(wv.z, wo[0].z, wo[1].z, wo[2].z);
            dp[24] = make_uint4(wv.w, wo[0].w, wo[1].w, wo[2].w);
        }
        if (warp < 15) { BARINIT(warp, 15) }
        __syncwarp();
        if (tid == NT - 1) {
            uint4 q;
            for (int n = 0; n < (1 << 22); n++) {
                q = ld_cell((const uint4*)&g_sync);
                if ((int)(q.z - (epoch + 1) * nbins) >= 0) break;
            }
            sts64(sb + SM_MISC + 32, q.x, q.y), sts32(sb + SM_MISC + 16, (epoch + 1) * 512);
            asm volatile("mbarrier.init.shared.b64 [%0], 1;" ::"r"(sb + SM_MISC + 48) : "memory");
            while ((uint32_t)(gt_lo() - q.x) < polld) {}
        }
        __syncthreads();
        TLSTAMP(14);
        uint4 m[5], mx[5];
        uint32_t rk[10], rx[10];
        bool ext;
        {
            const uint4* hp = g_cell + (blockIdx.x * MAXB + (tid >> 4)) * 24 + (tid & 15);
            m[4] = make_uint4(none, tag, none, tag);
            for (int n = 0; n < (1 << 22); n++) {
#pragma unroll
                for (int k = 0; k < 4; k++) m[k] = ld_cell(hp + k * 32 * 24);
                if ((tid >> 4) + 128 < nbins) m[4] = ld_cell(hp + 4 * 32 * 24);
                uint32_t bad = 0;
#pragma unroll
                for (int k = 0; k < 5; k++) bad |= (m[k].y ^ tag) | (m[k].w ^ tag);
                if (!(bad & 0x1ffc)) break;
            }
            __syncwarp();
            ext = __any_sync(0xffffffffu, hm && max(max(m[0].y, m[1].y), max(max(m[2].y, m[3].y), m[4].y)) >= (257u << 13));
            uint32_t need = 0;
            if (ext) {
#pragma unroll
                for (int k = 0; k < 5; k++) {
                    const uint32_t c = __shfl_sync(0xffffffffu, m[k].y, lane & 16) >> 13;
                    mx[k] = make_uint4(none, tag, none, tag);
                    if (c > 376) sts32(sb + SM_MISC + 4, 1);
                    else if (c > 256 + (tid & 15) * 16) need |= 1 << k, mx[k] = ld_cell(hp + k * 32 * 24 + 16);
                }
            }
            TLSTAMP(8);
#pragma unroll
            for (int k = 0; k < 5; k++)
                if (k < 4 || fifth)
                    rk[2 * k] = atoms_add(sb + SC_TABB + (m[k].x >> 14), 8), rk[2 * k + 1] = atoms_add(sb + SC_TABB + (m[k].z >> 14), 8);
            if (ext) {
#pragma unroll
                for (int k = 0; k < 5; k++) {
                    if (need >> k & 1) {
                        for (int n = 0; n < (1 << 22) && (((mx[k].y ^ tag) | (mx[k].w ^ tag)) & 0x1ffc); n++)
                            mx[k] = ld_cell(hp + k * 32 * 24 + 16);
                        rx[2 * k] = atoms_add(sb + SC_TABB + (mx[k].x >> 14), 8);
                        rx[2 * k + 1] = atoms_add(sb + SC_TABB + (mx[k].z >> 14), 8);
                    }
                }
            }
        }
        __syncthreads();
        TLSTAMP(5);
        if (tid == NT - 1 && blockIdx.x == 0) g_epoch = epoch + 1;
        {
            uint4 c[3];
            uint32_t tt[3];
#pragma unroll
            for (int i = 0; i < 3; i++) {
                c[i] = make_uint4(0, 0, 0, 0);
                if (i < 2 || warp < 8) c[i] = lds128(t16 + SC_TABB + i * 8192);
                tt[i] = c[i].x + c[i].y + c[i].z + c[i].w;
            }
            const uint32_t sum = (tt[0] >> 3) + (tt[1] << 7) + (tt[2] << 17);
            const uint32_t tot = __reduce_add_sync(0xffffffffu, sum);
            const uint32_t q = (tot + 0x300c03) & 0x3fcff3fc, q0 = q & 1023, q1 = q0 + ((q >> 10) & 1023);
            uint32_t base = atoms_add(sb + (lane ? SC_CNT + lane * 4 : SM_MISC + 20), q1 + (q >> 20));
            if (lane < 3) sts32(sb + SC_KEY + (warp + 16 * lane) * 4, ((tot >> (10 * lane)) & 1023) * 64 + 63 - warp - 16 * lane);
            uint32_t inc = sum;
#pragma unroll
            for (int o = 1; o < 32; o <<= 1) inc = scan_step(inc, o);
            base = __shfl_sync(0xffffffffu, base, 0);
            if (max(tt[0], max(tt[1], tt[2])) > 31 * 8) sts32(sb + SM_MISC + 4, 1);
            inc += q - tot - sum;
#pragma unroll
            for (int i = 0; i < 3; i++) {
                const uint32_t e = (((inc >> (10 * i)) & 1023) + base + (i == 0 ? 0 : i == 1 ? q0 : q1)) * 8;
                if (i < 2 || warp < 8) sts128(t16 + SC_TABB + i * 8192, e, e + c[i].x, e + c[i].x + c[i].y, e + tt[i] - c[i].w);
            }
        }
        __syncthreads();
        TLSTAMP(2);
        if (warp >= 11) {
            const uint32_t st = (tid - 352) >> 2, key = lds32(sb + SC_KEY + st * 4);
            uint32_t rank = 0;
#pragma unroll
            for (int i = 0; i < 5; i++) {
                const uint2 q = lds64(sb + SC_KEY + (lane & 3) * 40 + i * 8);
                rank += (q.x > key) + (q.y > key);
            }
            rank += __shfl_xor_sync(0xffffffffu, rank, 1);
            rank += __shfl_xor_sync(0xffffffffu, rank, 2);
            const uint32_t lv = rank >> 2, cw = ((0x969u >> (2 * lv)) & 3) * 4 + ((rank ^ -(lv & 1)) & 3);
            const uint32_t sid = (0xe4a50u >> (2 * lv)) & 3;
            sts32(sb + SC_MAP + st * 4, cw * 512 + (sid << 28));
            asm volatile("st.shared.u8 [%0], %1;" ::"r"(sb + SM_INV + cw * 4 + sid), "r"(st) : "memory");
        }
        const int total = lds32(sb + SM_MISC + 20);
        fast = lds32(sb + SM_MISC + 4) == 0 && total <= RECN - 4;
#pragma unroll
        for (int k = 0; k < 5; k++)
            if (k < 4 || fifth)
            {
                if (m[k].y & 3) rk[2 * k] += lds32(sb + SC_TABB + (m[k].x >> 14));
                if (m[k].w & 3) rk[2 * k + 1] += lds32(sb + SC_TABB + (m[k].z >> 14));
            }
        if (fast) {
#pragma unroll
            for (int k = 0; k < 5; k++) {
                if (k < 4 || fifth) {
                    if (m[k].y & 3) sts64(sb + SC_TMP + rk[2 * k], m[k].x, m[k].y);
                    if (m[k].w & 3) sts64(sb + SC_TMP + rk[2 * k + 1], m[k].z, m[k].w);
                }
            }
            if (ext) {
#pragma unroll
                for (int k = 0; k < 5; k++) {
                    if (mx[k].y & 3) {
                        const uint32_t p0 = lds32(sb + SC_TABB + (mx[k].x >> 14)), p1 = lds32(sb + SC_TABB + (mx[k].z >> 14));
                        sts64(sb + SC_TMP + rx[2 * k] + p0, mx[k].x, mx[k].y);
                        if (mx[k].w & 3) sts64(sb + SC_TMP + rx[2 * k + 1] + p1, mx[k].z, mx[k].w);
                    }
                }
            }
            constexpr int KD = (RECN + NT - 1) / NT;
            const uint32_t P = (lane ^ (lane >> 1)) & 1;
            const uint32_t binc = (P ? 1u << 11 : 1u) + ((lane & 3) == 3 ? 1u << 22 : 0u);
            const bool last = warp * 32 + (KD - 1) * NT < total, q2 = warp * 128 + NT * 4 < total;
            const int rest = total - tid, restq = (total >> 2) - tid;
            uint2 en[KD];
            uint32_t bk[KD], r2[KD], ca[2], ol[2], r3[2];
            __syncthreads();
            TLSTAMP(9);
#pragma unroll
            for (int k = 0; k < KD; k++)
                if (k < KD - 1 || last) en[k] = lds64(sb + SC_TMP + tid * 8 + k * NT * 8);
#pragma unroll
            for (int k = 0; k < 2; k++)
                if (k == 0 || q2) ca[k] = lds32(sb + SC_TMP + (tid + k * NT) * 32 + 24);
#pragma unroll
            for (int k = 0; k < 2; k++)
                if (k == 0 || q2) ol[k] = lds32(sb + SC_MAP + (ca[k] >> 23) * 4);
#pragma unroll
            for (int k = 0; k < KD; k++) {
                if (k < KD - 1 || last) {
                    bk[k] = __umulhi(en[k].x & 0x3fff, bkm << 9) * 4;
                    r2[k] = atoms_add(sb + SC_TABA + bk[k], rest > k * NT ? binc : 0);
                }
            }
#pragma unroll
            for (int k = 0; k < 2; k++) {
                if (k == 0 || q2) {
                    ca[k] = ((ca[k] >> 14) & 0x1fc) | (ol[k] & 0x1e00);
                    ol[k] = (tid + k * NT) * 16 + (ol[k] & 0x30000000);
                    r3[k] = atoms_add(sb + SC_TABC + ca[k], restq > k * NT ? 4 : 0);
                }
            }
            __syncthreads();
            TLSTAMP(12);
            if (warp < NCW) {
                const uint4 c = lds128(t16 + SC_TABC);
                const uint32_t tt = c.x + c.y + c.z + c.w;
                uint32_t inc = tt;
#pragma unroll
                for (int o = 1; o < 32; o <<= 1) inc = scan_step(inc, o);
                if (inc > (OLN - 6) * 4) sts32(sb + SM_MISC + 4, 1);
                inc += warp * (OLN * 4) - tt;
                sts128(t16 + SC_TABC, inc, inc + c.x, inc + c.x + c.y, inc + tt - c.w);
            } else {
                const uint32_t mine = (warp + lane) & 3;
                uint4 c;
                uint32_t cs, inc = 0, e = 4 + (4 << 11);
#pragma unroll
                for (int i = 0; i < 4; i++) {
                    const uint32_t pc = (mine + i) & 3;
                    const uint4 v = lds128(sb + SC_TABA + lane * 64 + (pc << 4));
                    const uint32_t sum = v.x + v.y + v.z + v.w;
                    inc += sum;
                    if (i == 0) c = v, cs = sum;
                    if (pc >= mine) e -= sum;
                }
#pragma unroll
                for (int o = 1; o < 32; o <<= 1) inc = scan_step(inc, o);
                e += inc;
                sts128(sb + SC_TABB + lane * 64 + (mine << 4), e, e + c.x, e + c.x + c.y, e + cs - c.w);
                if ((int)max((e + cs) & 0x7ff, ((e + cs) >> 11) & 0x7ff) - (int)(e >> 22) * 2 > SP) sts32(sb + SM_MISC + 4, 1);
                if (tid == NCW * 32) sts32(sb + SM_MISC + 12, ((total >> 2) + 1) >> 1);
            }
            __syncthreads();
            TLSTAMP(13);
            fast = lds32(sb + SM_MISC + 4) == 0;
#pragma unroll
            for (int k = 0; k < KD; k++)
                if (k < KD - 1 || last) r2[k] += lds32(sb + SC_TABB + bk[k]);
#pragma unroll
            for (int k = 0; k < 2; k++)
                if (k == 0 || q2) r3[k] += lds32(sb + SC_TABC + ca[k]);
            if (fast) {
                const uint32_t rot = P ? 9 : 30;
#pragma unroll
                for (int k = 0; k < KD; k++) {
                    if (k < KD - 1 || last) {
                        const uint32_t k4 = __funnelshift_r(r2[k], r2[k], rot);
                        if (rest > k * NT) {
                            sts16(sb + SM_R + 2 + bitsel(k4, P << 13), en[k].x);
                            sts32(sb + SM_REC + tid * 4 + k * NT * 4, bitsel(k4, en[k].y));
                        }
                    }
                }
#pragma unroll
                for (int k = 0; k < 2; k++)
                    if ((k == 0 || q2) && restq > k * NT) sts32(sb + SM_OL + r3[k], ol[k]);
            }
        }
        asm volatile("fence.proxy.async.shared::cta;" ::: "memory");
        __syncthreads();
        TLSTAMP(3);
        if (!fast && wrow) wf_done();
    }

    if (!fast) {
        float* accs = (float*)smem;
        constexpr int NACC = 96;
        const int node0 = blockIdx.x * npb, nnodes = max(0, min(npb, N - node0));
#pragma unroll 1
        for (int nb = 0; nb < nnodes; nb += NACC) {
            __syncthreads();
            for (int i = tid; i < NACC * 512; i += NT) accs[i] = 0.f;
            __syncthreads();
            const int lim = min(NACC, nnodes - nb);
#pragma unroll 1
            for (int base = warp * 32; base < E; base += NT) {
                const int e = base + lane;
                const int dl = e < E ? dst[e] - node0 - nb : -1;
                unsigned mask = __ballot_sync(0xffffffffu, dl >= 0 && dl < lim);
#pragma unroll 1
                while (mask) {
                    const int l = __ffs(mask) - 1;
                    mask &= mask - 1;
                    const int dd = __shfl_sync(0xffffffffu, dl, l);
                    slow_edge(base + l, src[base + l], accs + dd * 512, x, sh, ea, cg, wr, lane);
                }
            }
            __syncthreads();
#pragma unroll 1
            for (int nl = warp; nl < lim; nl += NT / 32) slow_out(accs + nl * 512, wout, out + (size_t)(node0 + nb + nl) * 512, lane);
        }
    } else if (warp >= NCW) {
        asm volatile("setmaxnreg.dec.sync.aligned.u32 %0;" ::"n"(PREG));
        producer(&tmx, warp - NCW, tau, ramp, rampn, tdelay, spr, sprn);
    } else if (warp >= 4) {
        asm volatile("setmaxnreg.inc.sync.aligned.u32 %0;" ::"n"(R1));
        consumer<3>(sh, ea, out, N, npb);
        TLMAX(4);
    } else {
        asm volatile("setmaxnreg.inc.sync.aligned.u32 %0;" ::"n"(R0));
        consumer<4>(sh, ea, out, N, npb);
        TLMAX(4);
    }
}

typedef CUresult (*EncodeTiledFn)(CUtensorMap*, CUtensorMapDataType, cuuint32_t, void*, const cuuint64_t*,
                                  const cuuint64_t*, const cuuint32_t*, const cuuint32_t*, CUtensorMapInterleave,
                                  CUtensorMapSwizzle, CUtensorMapL2promotion, CUtensorMapFloatOOBfill);

extern "C" void kernel_launch(void* const* d_in, const int* in_sizes, int n_in, void* d_out, int out_size) {
    const __nv_bfloat16* x = (const __nv_bfloat16*)d_in[0];
    const int* src = (const int*)d_in[1];
    const int* dst = (const int*)d_in[2];
    const __nv_bfloat16* sh = (const __nv_bfloat16*)d_in[3];
    const __nv_bfloat16* ea = (const __nv_bfloat16*)d_in[4];
    const __nv_bfloat16* cg = (const __nv_bfloat16*)d_in[5];
    const __nv_bfloat16* wr = (const __nv_bfloat16*)d_in[6];
    const __nv_bfloat16* wout = (const __nv_bfloat16*)d_in[7];
    __nv_bfloat16* out = (__nv_bfloat16*)d_out;
    const int N = in_sizes[0] / 512;
    const int E = in_sizes[1];

    static int num_sms = 0, coresident = 0;
    static EncodeTiledFn encode = nullptr;
    if (num_sms == 0) {
        int dev = 0;
        cudaGetDevice(&dev);
        cudaDeviceGetAttribute(&num_sms, cudaDevAttrMultiProcessorCount, dev);
        cudaFuncSetAttribute(main_kernel, cudaFuncAttributeMaxDynamicSharedMemorySize, SM_TOTAL);
        int occ = 0;
        cudaOccupancyMaxActiveBlocksPerMultiprocessor(&occ, main_kernel, NT, SM_TOTAL);
        coresident = occ * num_sms;
        void* fn = nullptr;
        cudaDriverEntryPointQueryResult qr;
        cudaGetDriverEntryPoint("cuTensorMapEncodeTiled", &fn, cudaEnableDefault, &qr);
        encode = (EncodeTiledFn)fn;
    }
    CUtensorMap tmx;
    const cuuint64_t gd[2] = {64, (cuuint64_t)N * 8}, gs[1] = {128};
    const cuuint32_t bd[2] = {64, 8}, es[2] = {1, 1};
    encode(&tmx, CU_TENSOR_MAP_DATA_TYPE_BFLOAT16, 2, (void*)x, gd, gs, bd, es, CU_TENSOR_MAP_INTERLEAVE_NONE,
           CU_TENSOR_MAP_SWIZZLE_128B, CU_TENSOR_MAP_L2_PROMOTION_NONE, CU_TENSOR_MAP_FLOAT_OOB_FILL_NONE);

    int nbins = num_sms < MAXB ? num_sms : MAXB;
    int npb = (N + nbins - 1) / nbins;
    if (npb < 2) npb = 2;
    nbins = (N + npb - 1) / npb;
    const unsigned npb_magic = (unsigned)((0x100000000ull + npb - 1) / npb);
    int chunk = (E + nbins - 1) / nbins;
    if (nbins > coresident || nbins < 128 || npb > MAXNPB || chunk > KE * NT || N > 16384 || N < 512 || E > (1 << 19)) chunk = 0;
    const unsigned bkm = (unsigned)(0xffffffffull / N);
    double pace = PACE, rampt = RAMP, rampf = RAMPF, sprt = SPRINT, sprf = SPRINTF;
    int tdelay = TDELAY, polld = POLLD;
    const int tau = (int)(1024.0 * pace * ((double)E / nbins) / N);
    const int rampn = (int)(N * rampf), ramp = (int)(1024.0 * rampt / rampn);
    main_kernel<<<nbins, NT, SM_TOTAL, cudaStreamPerThread>>>(tmx, x, src, dst, sh, ea, cg, wr, wout, out, N, E, npb, npb_magic,
                                                              chunk, bkm, tau, ramp, rampn, tdelay, polld, (int)(1024.0 * sprt / (N * sprf)), (int)(N * (1 - sprf)));
}
```

```cpp
#include <cuda_runtime.h>
#include <cuda.h>
#include <cuda_bf16.h>
#include <stdint.h>
#include <stdlib.h>

#define NT 512
#define NCW 12
#define MAXB 144
#define MAXNPB 80
#define KE 5
#define SP 97
#define RECN 2816
#define RP 1512
#define OLN 80
#define NBAR 360
#define R0 168
#define R1 160
#define PREG 24
#define PACE 10.1
#define TDELAY 5200
#define POLLD 1100
#define WFT 80
#define SLIPTH 500
#define SLIPSUB 250
#define SLIPFROM 24
#define AHEAD 96
#define EARLY 32
#define RAMPF 0.1
#define SPRINT 0
#define SPRINTF 0.1
#define SLIPEND 640
#define SPINT 96
#define RAMP 800

__device__ __align__(1024) uint4 g_cell[MAXB * MAXB * 24];
__device__ __align__(1024) uint4 g_wf[2048];
__device__ __align__(256) ulonglong2 g_sync;
__device__ __align__(256) unsigned g_epoch;
__device__ __align__(256) unsigned g_wfcnt;
#define TLSTAMP(i)
#define TLMAX(i)

constexpr uint32_t sb = 1024;
#define PH 128
#define SM_R (2 * SP * 1024 + PH)
#define SM_CTR (SM_R + RP * 4)
#define SM_MISC (SM_CTR + 528)
#define SM_INV (SM_MISC + 80)
#define SM_OFF (SM_INV + 48)
#define SM_REC (SM_R + 0x2000 + RP * 4)
#define SM_OL (SM_REC + RECN * 4)
#define SM_BAR (SM_OL + NCW * OLN * 4)
#define SM_TOTAL (SM_BAR + (NBAR + 16) * 8)
static_assert(SM_TOTAL <= 232448 && SM_OFF + NBAR * 4 <= SM_R + 0x2000, "shared memory");
static_assert(4 + RECN / 2 + SP + 2 <= RP && RECN / 8 + 8 <= NBAR && NBAR % 24 == 0, "tables");
#define SC_STG 0
#define CP 400
#define SC_TMP ((MAXB + 1) * CP)
#define SC_TABB (SC_TMP + 3072 * 8)
#define SC_TABC (SC_TABB + 41 * 512)
#define SC_TABA (SC_TABC + NCW * 512)
#define SC_ZEND (SC_TABB + 4 * NT * 16)
#define SC_CNT SC_ZEND
#define SC_KEY (SC_CNT + 640)
#define SC_MAP (SC_KEY + 192)
#define WSL 5
#define SC_WR ((2 * SP - WSL) * 1024 + PH)
#define SC_CG (SC_WR + 16 * 272)
static_assert(SC_TABA + 2048 <= SC_ZEND && RECN <= 3072, "scratch");

__device__ __forceinline__ uint32_t pack_bf16(float lo, float hi) {
    uint32_t r;
    asm("cvt.rn.bf16x2.f32 %0, %1, %2;" : "=r"(r) : "f"(hi), "f"(lo));
    return r;
}
__device__ __forceinline__ uint32_t s2u(const void* p) { return (uint32_t)__cvta_generic_to_shared(p); }
__device__ __forceinline__ void mbar_wait0(uint32_t a) {
    asm volatile(
        "{\n.reg .pred p, q;\n.reg .u32 n;\nmov.u32 n, 0;\n"
        "LAB_WAIT:\nmbarrier.try_wait.parity.shared.b64 p, [%0], 0;\nadd.u32 n, n, 1;\nsetp.lt.and.u32 q, n, 1000000, !p;\n@q bra LAB_WAIT;\n}" ::"r"(a)
        : "memory");
}
__device__ __forceinline__ uint32_t lds8(uint32_t a) { uint32_t v; asm volatile("ld.shared.u8 %0, [%1];" : "=r"(v) : "r"(a) : "memory"); return v; }
__device__ __forceinline__ uint32_t lds16(uint32_t a) { uint32_t v; asm volatile("ld.shared.u16 %0, [%1];" : "=r"(v) : "r"(a) : "memory"); return v; }
__device__ __forceinline__ uint32_t lds32(uint32_t a) { uint32_t v; asm volatile("ld.shared.u32 %0, [%1];" : "=r"(v) : "r"(a) : "memory"); return v; }
__device__ __forceinline__ uint2 lds64(uint32_t a) {
    uint2 v; asm volatile("ld.shared.v2.u32 {%0,%1}, [%2];" : "=r"(v.x), "=r"(v.y) : "r"(a) : "memory"); return v;
}
__device__ __forceinline__ uint4 lds128(uint32_t a) {
    uint4 v; asm volatile("ld.volatile.shared.v4.u32 {%0,%1,%2,%3}, [%4];" : "=r"(v.x), "=r"(v.y), "=r"(v.z), "=r"(v.w) : "r"(a) : "memory"); return v;
}
__device__ __forceinline__ void sts16(uint32_t a, uint32_t v) { asm volatile("st.shared.u16 [%0], %1;" ::"r"(a), "h"((unsigned short)v) : "memory"); }
__device__ __forceinline__ void sts32(uint32_t a, uint32_t v) { asm volatile("st.shared.u32 [%0], %1;" ::"r"(a), "r"(v) : "memory"); }
__device__ __forceinline__ void sts64(uint32_t a, uint32_t x, uint32_t y) { asm volatile("st.shared.v2.u32 [%0], {%1,%2};" ::"r"(a), "r"(x), "r"(y) : "memory"); }
__device__ __forceinline__ void sts128(uint32_t a, uint32_t x, uint32_t y, uint32_t z, uint32_t w) {
    asm volatile("st.shared.v4.u32 [%0], {%1,%2,%3,%4};" ::"r"(a), "r"(x), "r"(y), "r"(z), "r"(w) : "memory");
}
__device__ __forceinline__ uint32_t atoms_add(uint32_t a, uint32_t v) {
    uint32_t r;
    asm volatile("atom.shared.add.u32 %0, [%1], %2;" : "=r"(r) : "r"(a), "r"(v) : "memory");
    return r;
}
__device__ __forceinline__ uint2 ld_hdr(const uint4* p) {
    uint2 v;
    asm volatile("{\n.reg .b64 a;\nld.relaxed.gpu.global.b64 a, [%2];\nmov.b64 {%0,%1}, a;\n}" : "=r"(v.x), "=r"(v.y) : "l"(p) : "memory");
    return v;
}
__device__ __forceinline__ uint4 ld_cell(const uint4* p) {
    uint4 v;
    asm volatile("{\n.reg .b64 a, b;\nld.relaxed.gpu.global.v2.b64 {a, b}, [%4];\nmov.b64 {%0,%1}, a;\nmov.b64 {%2,%3}, b;\n}"
                 : "=r"(v.x), "=r"(v.y), "=r"(v.z), "=r"(v.w) : "l"(p) : "memory");
    return v;
}
__device__ __forceinline__ void st_cell(uint4* p, const uint4& v) {
    asm volatile("{\n.reg .b64 a, b;\nmov.b64 a, {%1,%2};\nmov.b64 b, {%3,%4};\nst.relaxed.gpu.global.v2.b64 [%0], {a, b};\n}" ::"l"(p),
                 "r"(v.x), "r"(v.y), "r"(v.z), "r"(v.w) : "memory");
}
__device__ __forceinline__ uint32_t scan_step(uint32_t v, int o) {
    asm volatile("{\n.reg .pred p;\n.reg .b32 y;\nshfl.sync.up.b32 y|p, %0, %1, 0, 0xffffffff;\n@p add.u32 %0, %0, y;\n}" : "+r"(v) : "r"(o));
    return v;
}
__device__ __forceinline__ uint32_t bitsel(uint32_t a, uint32_t b) {
    uint32_t r;
    asm("lop3.b32 %0, %1, %2, 0x1ffc, 0xe4;" : "=r"(r) : "r"(a), "r"(b));
    return r;
}
__device__ __forceinline__ uint32_t movm(uint32_t a) {
    uint32_t r;
    asm volatile("movmatrix.sync.aligned.m8n8.trans.b16 %0, %1;" : "=r"(r) : "r"(a));
    return r;
}
__device__ __forceinline__ uint32_t gt_lo() {
    uint32_t t;
    asm volatile("mov.u32 %0, %globaltimer_lo;" : "=r"(t));
    return t;
}
__device__ __forceinline__ bool elect() {
    uint32_t p;
    asm volatile("{\n.reg .pred P;\nelect.sync _|P, 0xffffffff;\nselp.u32 %0, 1, 0, P;\n}" : "=r"(p));
    return p;
}
__device__ __forceinline__ void project4(const uint32_t (&pk)[64], uint32_t ra, uint32_t ba, uint4* const (&p)[4], const uint32_t (&v)[4]) {
    asm volatile(
        "{\n.reg .pred p0, p1, q0, q1, nv, s<4>;\n.reg .b32 t, h, c<16>, a<32>, b<32>, k<16>;\n.reg .b64 d<16>;\n.reg .f32 o<32>;\nsetp.ne.b32 p0, 0, 0;\n"
        "setp.eq.b32 p1, 0, 0;\nmov.b32 h, 8;\nsetp.eq.u32 nv, %64, 0;\nvote.sync.any.pred nv, nv, 0xffffffff;\nsetp.ne.b32 s0, %69, 0;\n"
        "setp.ne.b32 s1, %70, 0;\nsetp.ne.b32 s2, %71, 0;\nsetp.ne.b32 s3, %72, 0;\nmovmatrix.sync.aligned.m8n8.trans.b16 a0, %0;\n"
        "movmatrix.sync.aligned.m8n8.trans.b16 a1, %16;\nmovmatrix.sync.aligned.m8n8.trans.b16 a2, %1;\nmovmatrix.sync.aligned.m8n8.trans.b16 a3, %17;\n"
        "movmatrix.sync.aligned.m8n8.trans.b16 a4, %2;\nmovmatrix.sync.aligned.m8n8.trans.b16 a5, %18;\nmovmatrix.sync.aligned.m8n8.trans.b16 a6, %3;\n"
        "movmatrix.sync.aligned.m8n8.trans.b16 a7, %19;\nmovmatrix.sync.aligned.m8n8.trans.b16 a8, %4;\nmovmatrix.sync.aligned.m8n8.trans.b16 a9, %20;\n"
        "movmatrix.sync.aligned.m8n8.trans.b16 a10, %5;\nmovmatrix.sync.aligned.m8n8.trans.b16 a11, %21;\nmovmatrix.sync.aligned.m8n8.trans.b16 a12, %6;\n"
        "movmatrix.sync.aligned.m8n8.trans.b16 a13, %22;\nmovmatrix.sync.aligned.m8n8.trans.b16 a14, %7;\nmovmatrix.sync.aligned.m8n8.trans.b16 a15, %23;\n"
        "movmatrix.sync.aligned.m8n8.trans.b16 a16, %8;\nmovmatrix.sync.aligned.m8n8.trans.b16 a17, %24;\nmovmatrix.sync.aligned.m8n8.trans.b16 a18, %9;\n"
        "movmatrix.sync.aligned.m8n8.trans.b16 a19, %25;\nmovmatrix.sync.aligned.m8n8.trans.b16 a20, %10;\nmovmatrix.sync.aligned.m8n8.trans.b16 a21, %26;\n"
        "movmatrix.sync.aligned.m8n8.trans.b16 a22, %11;\nmovmatrix.sync.aligned.m8n8.trans.b16 a23, %27;\nmovmatrix.sync.aligned.m8n8.trans.b16 a24, %12;\n"
        "movmatrix.sync.aligned.m8n8.trans.b16 a25, %28;\nmovmatrix.sync.aligned.m8n8.trans.b16 a26, %13;\nmovmatrix.sync.aligned.m8n8.trans.b16 a27, %29;\n"
        "movmatrix.sync.aligned.m8n8.trans.b16 a28, %14;\nmovmatrix.sync.aligned.m8n8.trans.b16 a29, %30;\nmovmatrix.sync.aligned.m8n8.trans.b16 a30, %15;\n"
        "movmatrix.sync.aligned.m8n8.trans.b16 a31, %31;\nmov.b32 t, 0;\n"
        "W0:\nmbarrier.try_wait.parity.shared.b64 q0, [%73+0], 0;\nadd.u32 t, t, 1;\nsetp.lt.and.u32 q1, t, 1000000, !q0;\n@q1 bra.uni W0;\nmov.b32 t, 0;\n"
        "W1:\nmbarrier.try_wait.parity.shared.b64 q0, [%73+8], 0;\nadd.u32 t, t, 1;\nsetp.lt.and.u32 q1, t, 1000000, !q0;\n@q1 bra.uni W1;\nmov.b32 t, 0;\n"
        "W2:\nmbarrier.try_wait.parity.shared.b64 q0, [%73+16], 0;\nadd.u32 t, t, 1;\nsetp.lt.and.u32 q1, t, 1000000, !q0;\n@q1 bra.uni W2;\nmov.b32 t, 0;\n"
        "W3:\nmbarrier.try_wait.parity.shared.b64 q0, [%73+24], 0;\nadd.u32 t, t, 1;\nsetp.lt.and.u32 q1, t, 1000000, !q0;\n@q1 bra.uni W3;\n"
        "ld.volatile.shared.v4.b32 {c0,c1,c2,c3}, [%64+0];\nld.volatile.shared.v4.b32 {c4,c5,c6,c7}, [%64+8192];\n"
        "ld.volatile.shared.v4.b32 {c8,c9,c10,c11}, [%64+16];\nld.volatile.shared.v4.b32 {c12,c13,c14,c15}, [%64+8208];\nand.b32 t, c0, 0xffe;\n"
        "mad.lo.u32 t, t, 4, 0x200000;\nmov.b64 d0, {t, h};\nand.b32 t, c1, 0xffe;\nmad.lo.u32 t, t, 4, 0x200000;\nmov.b64 d1, {t, h};\nand.b32 t, c2, 0xffe;\n"
        "mad.lo.u32 t, t, 4, 0x200000;\nmov.b64 d2, {t, h};\nand.b32 t, c3, 0xffe;\nmad.lo.u32 t, t, 4, 0x200000;\nmov.b64 d3, {t, h};\nand.b32 t, c4, 0xffe;\n"
        "mad.lo.u32 t, t, 4, 0x200000;\nmov.b64 d4, {t, h};\nand.b32 t, c5, 0xffe;\nmad.lo.u32 t, t, 4, 0x200000;\nmov.b64 d5, {t, h};\nand.b32 t, c6, 0xffe;\n"
        "mad.lo.u32 t, t, 4, 0x200000;\nmov.b64 d6, {t, h};\nand.b32 t, c7, 0xffe;\nmad.lo.u32 t, t, 4, 0x200000;\nmov.b64 d7, {t, h};\nand.b32 t, c8, 0xffe;\n"
        "mad.lo.u32 t, t, 4, 0x200000;\nmov.b64 d8, {t, h};\nand.b32 t, c9, 0xffe;\nmad.lo.u32 t, t, 4, 0x200000;\nmov.b64 d9, {t, h};\nand.b32 t, c10, 0xffe;\n"
        "mad.lo.u32 t, t, 4, 0x200000;\nmov.b64 d10, {t, h};\nand.b32 t, c11, 0xffe;\nmad.lo.u32 t, t, 4, 0x200000;\nmov.b64 d11, {t, h};\n"
        "and.b32 t, c12, 0xffe;\nmad.lo.u32 t, t, 4, 0x200000;\nmov.b64 d12, {t, h};\nand.b32 t, c13, 0xffe;\nmad.lo.u32 t, t, 4, 0x200000;\n"
        "mov.b64 d13, {t, h};\nand.b32 t, c14, 0xffe;\nmad.lo.u32 t, t, 4, 0x200000;\nmov.b64 d14, {t, h};\nand.b32 t, c15, 0xffe;\n"
        "mad.lo.u32 t, t, 4, 0x200000;\nmov.b64 d15, {t, h};\nwgmma.fence.sync.aligned;\n"
        "wgmma.mma_async.sync.aligned.m64n32k16.f32.bf16.bf16 {o0,o1,o2,o3,o4,o5,o6,o7,o8,o9,o10,o11,o12,o13,o14,o15}, {a0,a1,a2,a3}, d0, p0, 1, 1, 1;\n"
        "wgmma.mma_async.sync.aligned.m64n32k16.f32.bf16.bf16 {o16,o17,o18,o19,o20,o21,o22,o23,o24,o25,o26,o27,o28,o29,o30,o31}, {a0,a1,a2,a3}, d8, p0, 1, 1, 1;\n"
        "wgmma.mma_async.sync.aligned.m64n32k16.f32.bf16.bf16 {o0,o1,o2,o3,o4,o5,o6,o7,o8,o9,o10,o11,o12,o13,o14,o15}, {a4,a5,a6,a7}, d1, p1, 1, 1, 1;\n"
        "wgmma.mma_async.sync.aligned.m64n32k16.f32.bf16.bf16 {o16,o17,o18,o19,o20,o21,o22,o23,o24,o25,o26,o27,o28,o29,o30,o31}, {a4,a5,a6,a7}, d9, p1, 1, 1, 1;\n"
        "wgmma.mma_async.sync.aligned.m64n32k16.f32.bf16.bf16 {o0,o1,o2,o3,o4,o5,o6,o7,o8,o9,o10,o11,o12,o13,o14,o15}, {a8,a9,a10,a11}, d2, p1, 1, 1, 1;\n"
        "wgmma.mma_async.sync.aligned.m64n32k16.f32.bf16.bf16 {o16,o17,o18,o19,o20,o21,o22,o23,o24,o25,o26,o27,o28,o29,o30,o31}, {a8,a9,a10,a11}, d10, p1, 1, 1, 1;\n"
        "wgmma.mma_async.sync.aligned.m64n32k16.f32.bf16.bf16 {o0,o1,o2,o3,o4,o5,o6,o7,o8,o9,o10,o11,o12,o13,o14,o15}, {a12,a13,a14,a15}, d3, p1, 1, 1, 1;\n"
        "wgmma.mma_async.sync.aligned.m64n32k16.f32.bf16.bf16 {o16,o17,o18,o19,o20,o21,o22,o23,o24,o25,o26,o27,o28,o29,o30,o31}, {a12,a13,a14,a15}, d11, p1, 1, 1, 1;\n"
        "wgmma.mma_async.sync.aligned.m64n32k16.f32.bf16.bf16 {o0,o1,o2,o3,o4,o5,o6,o7,o8,o9,o10,o11,o12,o13,o14,o15}, {a16,a17,a18,a19}, d4, p1, 1, 1, 1;\n"
        "wgmma.mma_async.sync.aligned.m64n32k16.f32.bf16.bf16 {o16,o17,o18,o19,o20,o21,o22,o23,o24,o25,o26,o27,o28,o29,o30,o31}, {a16,a17,a18,a19}, d12, p1, 1, 1, 1;\n"
        "wgmma.mma_async.sync.aligned.m64n32k16.f32.bf16.bf16 {o0,o1,o2,o3,o4,o5,o6,o7,o8,o9,o10,o11,o12,o13,o14,o15}, {a20,a21,a22,a23}, d5, p1, 1, 1, 1;\n"
        "wgmma.mma_async.sync.aligned.m64n32k16.f32.bf16.bf16 {o16,o17,o18,o19,o20,o21,o22,o23,o24,o25,o26,o27,o28,o29,o30,o31}, {a20,a21,a22,a23}, d13, p1, 1, 1, 1;\n"
        "wgmma.mma_async.sync.aligned.m64n32k16.f32.bf16.bf16 {o0,o1,o2,o3,o4,o5,o6,o7,o8,o9,o10,o11,o12,o13,o14,o15}, {a24,a25,a26,a27}, d6, p1, 1, 1, 1;\n"
        "wgmma.mma_async.sync.aligned.m64n32k16.f32.bf16.bf16 {o16,o17,o18,o19,o20,o21,o22,o23,o24,o25,o26,o27,o28,o29,o30,o31}, {a24,a25,a26,a27}, d14, p1, 1, 1, 1;\n"
        "wgmma.mma_async.sync.aligned.m64n32k16.f32.bf16.bf16 {o0,o1,o2,o3,o4,o5,o6,o7,o8,o9,o10,o11,o12,o13,o14,o15}, {a28,a29,a30,a31}, d7, p1, 1, 1, 1;\n"
        "wgmma.mma_async.sync.aligned.m64n32k16.f32.bf16.bf16 {o16,o17,o18,o19,o20,o21,o22,o23,o24,o25,o26,o27,o28,o29,o30,o31}, {a28,a29,a30,a31}, d15, p1, 1, 1, 1;\n"
        "wgmma.commit_group.sync.aligned;\n@nv bra.uni END;\nmovmatrix.sync.aligned.m8n8.trans.b16 b0, %32;\nmovmatrix.sync.aligned.m8n8.trans.b16 b2, %33;\n"
        "movmatrix.sync.aligned.m8n8.trans.b16 b3, %49;\nmovmatrix.sync.aligned.m8n8.trans.b16 b4, %34;\nmovmatrix.sync.aligned.m8n8.trans.b16 b5, %50;\n"
        "movmatrix.sync.aligned.m8n8.trans.b16 b6, %35;\nmovmatrix.sync.aligned.m8n8.trans.b16 b7, %51;\nmovmatrix.sync.aligned.m8n8.trans.b16 b8, %36;\n"
        "movmatrix.sync.aligned.m8n8.trans.b16 b9, %52;\nmovmatrix.sync.aligned.m8n8.trans.b16 b20, %42;\nmovmatrix.sync.aligned.m8n8.trans.b16 b21, %58;\n"
        "movmatrix.sync.aligned.m8n8.trans.b16 b22, %43;\nmovmatrix.sync.aligned.m8n8.trans.b16 b23, %59;\nmovmatrix.sync.aligned.m8n8.trans.b16 b24, %44;\n"
        "movmatrix.sync.aligned.m8n8.trans.b16 b25, %60;\nmovmatrix.sync.aligned.m8n8.trans.b16 b26, %45;\nmovmatrix.sync.aligned.m8n8.trans.b16 b27, %61;\n"
        "movmatrix.sync.aligned.m8n8.trans.b16 b28, %46;\nmovmatrix.sync.aligned.m8n8.trans.b16 b29, %62;\nmovmatrix.sync.aligned.m8n8.trans.b16 b30, %47;\n"
        "movmatrix.sync.aligned.m8n8.trans.b16 b31, %63;\nmovmatrix.sync.aligned.m8n8.trans.b16 b1, %48;\nmovmatrix.sync.aligned.m8n8.trans.b16 b10, %37;\n"
        "movmatrix.sync.aligned.m8n8.trans.b16 b11, %53;\nmovmatrix.sync.aligned.m8n8.trans.b16 b12, %38;\nmovmatrix.sync.aligned.m8n8.trans.b16 b13, %54;\n"
        "movmatrix.sync.aligned.m8n8.trans.b16 b14, %39;\nmovmatrix.sync.aligned.m8n8.trans.b16 b15, %55;\nmovmatrix.sync.aligned.m8n8.trans.b16 b16, %40;\n"
        "movmatrix.sync.aligned.m8n8.trans.b16 b17, %56;\nmovmatrix.sync.aligned.m8n8.trans.b16 b18, %41;\nmovmatrix.sync.aligned.m8n8.trans.b16 b19, %57;\n"
        "@nv bra.uni END;\nwgmma.wait_group.sync.aligned 0;\ncvt.rn.bf16x2.f32 k0, o1, o0;\ncvt.rn.bf16x2.f32 k1, o5, o4;\ncvt.rn.bf16x2.f32 k2, o9, o8;\n"
        "cvt.rn.bf16x2.f32 k3, o13, o12;\ncvt.rn.bf16x2.f32 k4, o3, o2;\ncvt.rn.bf16x2.f32 k5, o7, o6;\ncvt.rn.bf16x2.f32 k6, o11, o10;\n"
        "cvt.rn.bf16x2.f32 k7, o15, o14;\ncvt.rn.bf16x2.f32 k8, o17, o16;\ncvt.rn.bf16x2.f32 k9, o21, o20;\ncvt.rn.bf16x2.f32 k10, o25, o24;\n"
        "cvt.rn.bf16x2.f32 k11, o29, o28;\ncvt.rn.bf16x2.f32 k12, o19, o18;\ncvt.rn.bf16x2.f32 k13, o23, o22;\ncvt.rn.bf16x2.f32 k14, o27, o26;\n"
        "cvt.rn.bf16x2.f32 k15, o31, o30;\nld.volatile.shared.v4.b32 {c0,c1,c2,c3}, [%64+32];\nld.volatile.shared.v4.b32 {c4,c5,c6,c7}, [%64+8224];\n"
        "ld.volatile.shared.v4.b32 {c8,c9,c10,c11}, [%64+48];\nld.volatile.shared.v4.b32 {c12,c13,c14,c15}, [%64+8240];\nand.b32 t, c0, 0xffe;\n"
        "mad.lo.u32 t, t, 4, 0x200000;\nmov.b64 d0, {t, h};\nand.b32 t, c1, 0xffe;\nmad.lo.u32 t, t, 4, 0x200000;\nmov.b64 d1, {t, h};\nand.b32 t, c2, 0xffe;\n"
        "mad.lo.u32 t, t, 4, 0x200000;\nmov.b64 d2, {t, h};\nand.b32 t, c3, 0xffe;\nmad.lo.u32 t, t, 4, 0x200000;\nmov.b64 d3, {t, h};\nand.b32 t, c4, 0xffe;\n"
        "mad.lo.u32 t, t, 4, 0x200000;\nmov.b64 d4, {t, h};\nand.b32 t, c5, 0xffe;\nmad.lo.u32 t, t, 4, 0x200000;\nmov.b64 d5, {t, h};\nand.b32 t, c6, 0xffe;\n"
        "mad.lo.u32 t, t, 4, 0x200000;\nmov.b64 d6, {t, h};\nand.b32 t, c7, 0xffe;\nmad.lo.u32 t, t, 4, 0x200000;\nmov.b64 d7, {t, h};\nand.b32 t, c8, 0xffe;\n"
        "mad.lo.u32 t, t, 4, 0x200000;\nmov.b64 d8, {t, h};\nand.b32 t, c9, 0xffe;\nmad.lo.u32 t, t, 4, 0x200000;\nmov.b64 d9, {t, h};\nand.b32 t, c10, 0xffe;\n"
        "mad.lo.u32 t, t, 4, 0x200000;\nmov.b64 d10, {t, h};\nand.b32 t, c11, 0xffe;\nmad.lo.u32 t, t, 4, 0x200000;\nmov.b64 d11, {t, h};\n"
        "and.b32 t, c12, 0xffe;\nmad.lo.u32 t, t, 4, 0x200000;\nmov.b64 d12, {t, h};\nand.b32 t, c13, 0xffe;\nmad.lo.u32 t, t, 4, 0x200000;\n"
        "mov.b64 d13, {t, h};\nand.b32 t, c14, 0xffe;\nmad.lo.u32 t, t, 4, 0x200000;\nmov.b64 d14, {t, h};\nand.b32 t, c15, 0xffe;\n"
        "mad.lo.u32 t, t, 4, 0x200000;\nmov.b64 d15, {t, h};\nwgmma.fence.sync.aligned;\n"
        "wgmma.mma_async.sync.aligned.m64n32k16.f32.bf16.bf16 {o0,o1,o2,o3,o4,o5,o6,o7,o8,o9,o10,o11,o12,o13,o14,o15}, {a0,a1,a2,a3}, d0, p0, 1, 1, 1;\n"
        "wgmma.mma_async.sync.aligned.m64n32k16.f32.bf16.bf16 {o16,o17,o18,o19,o20,o21,o22,o23,o24,o25,o26,o27,o28,o29,o30,o31}, {a0,a1,a2,a3}, d8, p0, 1, 1, 1;\n"
        "wgmma.mma_async.sync.aligned.m64n32k16.f32.bf16.bf16 {o0,o1,o2,o3,o4,o5,o6,o7,o8,o9,o10,o11,o12,o13,o14,o15}, {a4,a5,a6,a7}, d1, p1, 1, 1, 1;\n"
        "wgmma.mma_async.sync.aligned.m64n32k16.f32.bf16.bf16 {o16,o17,o18,o19,o20,o21,o22,o23,o24,o25,o26,o27,o28,o29,o30,o31}, {a4,a5,a6,a7}, d9, p1, 1, 1, 1;\n"
        "wgmma.mma_async.sync.aligned.m64n32k16.f32.bf16.bf16 {o0,o1,o2,o3,o4,o5,o6,o7,o8,o9,o10,o11,o12,o13,o14,o15}, {a8,a9,a10,a11}, d2, p1, 1, 1, 1;\n"
        "wgmma.mma_async.sync.aligned.m64n32k16.f32.bf16.bf16 {o16,o17,o18,o19,o20,o21,o22,o23,o24,o25,o26,o27,o28,o29,o30,o31}, {a8,a9,a10,a11}, d10, p1, 1, 1, 1;\n"
        "wgmma.mma_async.sync.aligned.m64n32k16.f32.bf16.bf16 {o0,o1,o2,o3,o4,o5,o6,o7,o8,o9,o10,o11,o12,o13,o14,o15}, {a12,a13,a14,a15}, d3, p1, 1, 1, 1;\n"
        "wgmma.mma_async.sync.aligned.m64n32k16.f32.bf16.bf16 {o16,o17,o18,o19,o20,o21,o22,o23,o24,o25,o26,o27,o28,o29,o30,o31}, {a12,a13,a14,a15}, d11, p1, 1, 1, 1;\n"
        "wgmma.mma_async.sync.aligned.m64n32k16.f32.bf16.bf16 {o0,o1,o2,o3,o4,o5,o6,o7,o8,o9,o10,o11,o12,o13,o14,o15}, {a16,a17,a18,a19}, d4, p1, 1, 1, 1;\n"
        "wgmma.mma_async.sync.aligned.m64n32k16.f32.bf16.bf16 {o16,o17,o18,o19,o20,o21,o22,o23,o24,o25,o26,o27,o28,o29,o30,o31}, {a16,a17,a18,a19}, d12, p1, 1, 1, 1;\n"
        "wgmma.mma_async.sync.aligned.m64n32k16.f32.bf16.bf16 {o0,o1,o2,o3,o4,o5,o6,o7,o8,o9,o10,o11,o12,o13,o14,o15}, {a20,a21,a22,a23}, d5, p1, 1, 1, 1;\n"
        "wgmma.mma_async.sync.aligned.m64n32k16.f32.bf16.bf16 {o16,o17,o18,o19,o20,o21,o22,o23,o24,o25,o26,o27,o28,o29,o30,o31}, {a20,a21,a22,a23}, d13, p1, 1, 1, 1;\n"
        "wgmma.mma_async.sync.aligned.m64n32k16.f32.bf16.bf16 {o0,o1,o2,o3,o4,o5,o6,o7,o8,o9,o10,o11,o12,o13,o14,o15}, {a24,a25,a26,a27}, d6, p1, 1, 1, 1;\n"
        "wgmma.mma_async.sync.aligned.m64n32k16.f32.bf16.bf16 {o16,o17,o18,o19,o20,o21,o22,o23,o24,o25,o26,o27,o28,o29,o30,o31}, {a24,a25,a26,a27}, d14, p1, 1, 1, 1;\n"
        "wgmma.mma_async.sync.aligned.m64n32k16.f32.bf16.bf16 {o0,o1,o2,o3,o4,o5,o6,o7,o8,o9,o10,o11,o12,o13,o14,o15}, {a28,a29,a30,a31}, d7, p1, 1, 1, 1;\n"
        "wgmma.mma_async.sync.aligned.m64n32k16.f32.bf16.bf16 {o16,o17,o18,o19,o20,o21,o22,o23,o24,o25,o26,o27,o28,o29,o30,o31}, {a28,a29,a30,a31}, d15, p1, 1, 1, 1;\n"
        "wgmma.commit_group.sync.aligned;\n@nv bra.uni END;\n@s0 st.global.v4.b32 [%65+0], {k0,k1,k2,k3};\n@s1 st.global.v4.b32 [%66+0], {k4,k5,k6,k7};\n"
        "@s0 st.global.v4.b32 [%65+64], {k8,k9,k10,k11};\n@s1 st.global.v4.b32 [%66+64], {k12,k13,k14,k15};\n@nv bra.uni END;\nwgmma.wait_group.sync.aligned 0;\n"
        "cvt.rn.bf16x2.f32 k0, o1, o0;\ncvt.rn.bf16x2.f32 k1, o5, o4;\ncvt.rn.bf16x2.f32 k2, o9, o8;\ncvt.rn.bf16x2.f32 k3, o13, o12;\n"
        "cvt.rn.bf16x2.f32 k4, o3, o2;\ncvt.rn.bf16x2.f32 k5, o7, o6;\ncvt.rn.bf16x2.f32 k6, o11, o10;\ncvt.rn.bf16x2.f32 k7, o15, o14;\n"
        "cvt.rn.bf16x2.f32 k8, o17, o16;\ncvt.rn.bf16x2.f32 k9, o21, o20;\ncvt.rn.bf16x2.f32 k10, o25, o24;\ncvt.rn.bf16x2.f32 k11, o29, o28;\n"
        "cvt.rn.bf16x2.f32 k12, o19, o18;\ncvt.rn.bf16x2.f32 k13, o23, o22;\ncvt.rn.bf16x2.f32 k14, o27, o26;\ncvt.rn.bf16x2.f32 k15, o31, o30;\n"
        "ld.volatile.shared.v4.b32 {c0,c1,c2,c3}, [%64+0];\nld.volatile.shared.v4.b32 {c4,c5,c6,c7}, [%64+8192];\n"
        "ld.volatile.shared.v4.b32 {c8,c9,c10,c11}, [%64+16];\nld.volatile.shared.v4.b32 {c12,c13,c14,c15}, [%64+8208];\nand.b32 t, c0, 0xffe;\n"
        "mad.lo.u32 t, t, 4, 0x200000;\nmov.b64 d0, {t, h};\nand.b32 t, c1, 0xffe;\nmad.lo.u32 t, t, 4, 0x200000;\nmov.b64 d1, {t, h};\nand.b32 t, c2, 0xffe;\n"
        "mad.lo.u32 t, t, 4, 0x200000;\nmov.b64 d2, {t, h};\nand.b32 t, c3, 0xffe;\nmad.lo.u32 t, t, 4, 0x200000;\nmov.b64 d3, {t, h};\nand.b32 t, c4, 0xffe;\n"
        "mad.lo.u32 t, t, 4, 0x200000;\nmov.b64 d4, {t, h};\nand.b32 t, c5, 0xffe;\nmad.lo.u32 t, t, 4, 0x200000;\nmov.b64 d5, {t, h};\nand.b32 t, c6, 0xffe;\n"
        "mad.lo.u32 t, t, 4, 0x200000;\nmov.b64 d6, {t, h};\nand.b32 t, c7, 0xffe;\nmad.lo.u32 t, t, 4, 0x200000;\nmov.b64 d7, {t, h};\nand.b32 t, c8, 0xffe;\n"
        "mad.lo.u32 t, t, 4, 0x200000;\nmov.b64 d8, {t, h};\nand.b32 t, c9, 0xffe;\nmad.lo.u32 t, t, 4, 0x200000;\nmov.b64 d9, {t, h};\nand.b32 t, c10, 0xffe;\n"
        "mad.lo.u32 t, t, 4, 0x200000;\nmov.b64 d10, {t, h};\nand.b32 t, c11, 0xffe;\nmad.lo.u32 t, t, 4, 0x200000;\nmov.b64 d11, {t, h};\n"
        "and.b32 t, c12, 0xffe;\nmad.lo.u32 t, t, 4, 0x200000;\nmov.b64 d12, {t, h};\nand.b32 t, c13, 0xffe;\nmad.lo.u32 t, t, 4, 0x200000;\n"
        "mov.b64 d13, {t, h};\nand.b32 t, c14, 0xffe;\nmad.lo.u32 t, t, 4, 0x200000;\nmov.b64 d14, {t, h};\nand.b32 t, c15, 0xffe;\n"
        "mad.lo.u32 t, t, 4, 0x200000;\nmov.b64 d15, {t, h};\nwgmma.fence.sync.aligned;\n"
        "wgmma.mma_async.sync.aligned.m64n32k16.f32.bf16.bf16 {o0,o1,o2,o3,o4,o5,o6,o7,o8,o9,o10,o11,o12,o13,o14,o15}, {b0,b1,b2,b3}, d0, p0, 1, 1, 1;\n"
        "wgmma.mma_async.sync.aligned.m64n32k16.f32.bf16.bf16 {o16,o17,o18,o19,o20,o21,o22,o23,o24,o25,o26,o27,o28,o29,o30,o31}, {b0,b1,b2,b3}, d8, p0, 1, 1, 1;\n"
        "wgmma.mma_async.sync.aligned.m64n32k16.f32.bf16.bf16 {o0,o1,o2,o3,o4,o5,o6,o7,o8,o9,o10,o11,o12,o13,o14,o15}, {b4,b5,b6,b7}, d1, p1, 1, 1, 1;\n"
        "wgmma.mma_async.sync.aligned.m64n32k16.f32.bf16.bf16 {o16,o17,o18,o19,o20,o21,o22,o23,o24,o25,o26,o27,o28,o29,o30,o31}, {b4,b5,b6,b7}, d9, p1, 1, 1, 1;\n"
        "wgmma.mma_async.sync.aligned.m64n32k16.f32.bf16.bf16 {o0,o1,o2,o3,o4,o5,o6,o7,o8,o9,o10,o11,o12,o13,o14,o15}, {b8,b9,b10,b11}, d2, p1, 1, 1, 1;\n"
        "wgmma.mma_async.sync.aligned.m64n32k16.f32.bf16.bf16 {o16,o17,o18,o19,o20,o21,o22,o23,o24,o25,o26,o27,o28,o29,o30,o31}, {b8,b9,b10,b11}, d10, p1, 1, 1, 1;\n"
        "wgmma.mma_async.sync.aligned.m64n32k16.f32.bf16.bf16 {o0,o1,o2,o3,o4,o5,o6,o7,o8,o9,o10,o11,o12,o13,o14,o15}, {b12,b13,b14,b15}, d3, p1, 1, 1, 1;\n"
        "wgmma.mma_async.sync.aligned.m64n32k16.f32.bf16.bf16 {o16,o17,o18,o19,o20,o21,o22,o23,o24,o25,o26,o27,o28,o29,o30,o31}, {b12,b13,b14,b15}, d11, p1, 1, 1, 1;\n"
        "wgmma.mma_async.sync.aligned.m64n32k16.f32.bf16.bf16 {o0,o1,o2,o3,o4,o5,o6,o7,o8,o9,o10,o11,o12,o13,o14,o15}, {b16,b17,b18,b19}, d4, p1, 1, 1, 1;\n"
        "wgmma.mma_async.sync.aligned.m64n32k16.f32.bf16.bf16 {o16,o17,o18,o19,o20,o21,o22,o23,o24,o25,o26,o27,o28,o29,o30,o31}, {b16,b17,b18,b19}, d12, p1, 1, 1, 1;\n"
        "wgmma.mma_async.sync.aligned.m64n32k16.f32.bf16.bf16 {o0,o1,o2,o3,o4,o5,o6,o7,o8,o9,o10,o11,o12,o13,o14,o15}, {b20,b21,b22,b23}, d5, p1, 1, 1, 1;\n"
        "wgmma.mma_async.sync.aligned.m64n32k16.f32.bf16.bf16 {o16,o17,o18,o19,o20,o21,o22,o23,o24,o25,o26,o27,o28,o29,o30,o31}, {b20,b21,b22,b23}, d13, p1, 1, 1, 1;\n"
        "wgmma.mma_async.sync.aligned.m64n32k16.f32.bf16.bf16 {o0,o1,o2,o3,o4,o5,o6,o7,o8,o9,o10,o11,o12,o13,o14,o15}, {b24,b25,b26,b27}, d6, p1, 1, 1, 1;\n"
        "wgmma.mma_async.sync.aligned.m64n32k16.f32.bf16.bf16 {o16,o17,o18,o19,o20,o21,o22,o23,o24,o25,o26,o27,o28,o29,o30,o31}, {b24,b25,b26,b27}, d14, p1, 1, 1, 1;\n"
        "wgmma.mma_async.sync.aligned.m64n32k16.f32.bf16.bf16 {o0,o1,o2,o3,o4,o5,o6,o7,o8,o9,o10,o11,o12,o13,o14,o15}, {b28,b29,b30,b31}, d7, p1, 1, 1, 1;\n"
        "wgmma.mma_async.sync.aligned.m64n32k16.f32.bf16.bf16 {o16,o17,o18,o19,o20,o21,o22,o23,o24,o25,o26,o27,o28,o29,o30,o31}, {b28,b29,b30,b31}, d15, p1, 1, 1, 1;\n"
        "wgmma.commit_group.sync.aligned;\n@nv bra.uni END;\n@s0 st.global.v4.b32 [%65+128], {k0,k1,k2,k3};\n@s1 st.global.v4.b32 [%66+128], {k4,k5,k6,k7};\n"
        "@s0 st.global.v4.b32 [%65+192], {k8,k9,k10,k11};\n@s1 st.global.v4.b32 [%66+192], {k12,k13,k14,k15};\n@nv bra.uni END;\n"
        "wgmma.wait_group.sync.aligned 0;\ncvt.rn.bf16x2.f32 k0, o1, o0;\ncvt.rn.bf16x2.f32 k1, o5, o4;\ncvt.rn.bf16x2.f32 k2, o9, o8;\n"
        "cvt.rn.bf16x2.f32 k3, o13, o12;\ncvt.rn.bf16x2.f32 k4, o3, o2;\ncvt.rn.bf16x2.f32 k5, o7, o6;\ncvt.rn.bf16x2.f32 k6, o11, o10;\n"
        "cvt.rn.bf16x2.f32 k7, o15, o14;\ncvt.rn.bf16x2.f32 k8, o17, o16;\ncvt.rn.bf16x2.f32 k9, o21, o20;\ncvt.rn.bf16x2.f32 k10, o25, o24;\n"
        "cvt.rn.bf16x2.f32 k11, o29, o28;\ncvt.rn.bf16x2.f32 k12, o19, o18;\ncvt.rn.bf16x2.f32 k13, o23, o22;\ncvt.rn.bf16x2.f32 k14, o27, o26;\n"
        "cvt.rn.bf16x2.f32 k15, o31, o30;\nld.volatile.shared.v4.b32 {c0,c1,c2,c3}, [%64+32];\nld.volatile.shared.v4.b32 {c4,c5,c6,c7}, [%64+8224];\n"
        "ld.volatile.shared.v4.b32 {c8,c9,c10,c11}, [%64+48];\nld.volatile.shared.v4.b32 {c12,c13,c14,c15}, [%64+8240];\nand.b32 t, c0, 0xffe;\n"
        "mad.lo.u32 t, t, 4, 0x200000;\nmov.b64 d0, {t, h};\nand.b32 t, c1, 0xffe;\nmad.lo.u32 t, t, 4, 0x200000;\nmov.b64 d1, {t, h};\nand.b32 t, c2, 0xffe;\n"
        "mad.lo.u32 t, t, 4, 0x200000;\nmov.b64 d2, {t, h};\nand.b32 t, c3, 0xffe;\nmad.lo.u32 t, t, 4, 0x200000;\nmov.b64 d3, {t, h};\nand.b32 t, c4, 0xffe;\n"
        "mad.lo.u32 t, t, 4, 0x200000;\nmov.b64 d4, {t, h};\nand.b32 t, c5, 0xffe;\nmad.lo.u32 t, t, 4, 0x200000;\nmov.b64 d5, {t, h};\nand.b32 t, c6, 0xffe;\n"
        "mad.lo.u32 t, t, 4, 0x200000;\nmov.b64 d6, {t, h};\nand.b32 t, c7, 0xffe;\nmad.lo.u32 t, t, 4, 0x200000;\nmov.b64 d7, {t, h};\nand.b32 t, c8, 0xffe;\n"
        "mad.lo.u32 t, t, 4, 0x200000;\nmov.b64 d8, {t, h};\nand.b32 t, c9, 0xffe;\nmad.lo.u32 t, t, 4, 0x200000;\nmov.b64 d9, {t, h};\nand.b32 t, c10, 0xffe;\n"
        "mad.lo.u32 t, t, 4, 0x200000;\nmov.b64 d10, {t, h};\nand.b32 t, c11, 0xffe;\nmad.lo.u32 t, t, 4, 0x200000;\nmov.b64 d11, {t, h};\n"
        "and.b32 t, c12, 0xffe;\nmad.lo.u32 t, t, 4, 0x200000;\nmov.b64 d12, {t, h};\nand.b32 t, c13, 0xffe;\nmad.lo.u32 t, t, 4, 0x200000;\n"
        "mov.b64 d13, {t, h};\nand.b32 t, c14, 0xffe;\nmad.lo.u32 t, t, 4, 0x200000;\nmov.b64 d14, {t, h};\nand.b32 t, c15, 0xffe;\n"
        "mad.lo.u32 t, t, 4, 0x200000;\nmov.b64 d15, {t, h};\nwgmma.fence.sync.aligned;\n"
        "wgmma.mma_async.sync.aligned.m64n32k16.f32.bf16.bf16 {o0,o1,o2,o3,o4,o5,o6,o7,o8,o9,o10,o11,o12,o13,o14,o15}, {b0,b1,b2,b3}, d0, p0, 1, 1, 1;\n"
        "wgmma.mma_async.sync.aligned.m64n32k16.f32.bf16.bf16 {o16,o17,o18,o19,o20,o21,o22,o23,o24,o25,o26,o27,o28,o29,o30,o31}, {b0,b1,b2,b3}, d8, p0, 1, 1, 1;\n"
        "wgmma.mma_async.sync.aligned.m64n32k16.f32.bf16.bf16 {o0,o1,o2,o3,o4,o5,o6,o7,o8,o9,o10,o11,o12,o13,o14,o15}, {b4,b5,b6,b7}, d1, p1, 1, 1, 1;\n"
        "wgmma.mma_async.sync.aligned.m64n32k16.f32.bf16.bf16 {o16,o17,o18,o19,o20,o21,o22,o23,o24,o25,o26,o27,o28,o29,o30,o31}, {b4,b5,b6,b7}, d9, p1, 1, 1, 1;\n"
        "wgmma.mma_async.sync.aligned.m64n32k16.f32.bf16.bf16 {o0,o1,o2,o3,o4,o5,o6,o7,o8,o9,o10,o11,o12,o13,o14,o15}, {b8,b9,b10,b11}, d2, p1, 1, 1, 1;\n"
        "wgmma.mma_async.sync.aligned.m64n32k16.f32.bf16.bf16 {o16,o17,o18,o19,o20,o21,o22,o23,o24,o25,o26,o27,o28,o29,o30,o31}, {b8,b9,b10,b11}, d10, p1, 1, 1, 1;\n"
        "wgmma.mma_async.sync.aligned.m64n32k16.f32.bf16.bf16 {o0,o1,o2,o3,o4,o5,o6,o7,o8,o9,o10,o11,o12,o13,o14,o15}, {b12,b13,b14,b15}, d3, p1, 1, 1, 1;\n"
        "wgmma.mma_async.sync.aligned.m64n32k16.f32.bf16.bf16 {o16,o17,o18,o19,o20,o21,o22,o23,o24,o25,o26,o27,o28,o29,o30,o31}, {b12,b13,b14,b15}, d11, p1, 1, 1, 1;\n"
        "wgmma.mma_async.sync.aligned.m64n32k16.f32.bf16.bf16 {o0,o1,o2,o3,o4,o5,o6,o7,o8,o9,o10,o11,o12,o13,o14,o15}, {b16,b17,b18,b19}, d4, p1, 1, 1, 1;\n"
        "wgmma.mma_async.sync.aligned.m64n32k16.f32.bf16.bf16 {o16,o17,o18,o19,o20,o21,o22,o23,o24,o25,o26,o27,o28,o29,o30,o31}, {b16,b17,b18,b19}, d12, p1, 1, 1, 1;\n"
        "wgmma.mma_async.sync.aligned.m64n32k16.f32.bf16.bf16 {o0,o1,o2,o3,o4,o5,o6,o7,o8,o9,o10,o11,o12,o13,o14,o15}, {b20,b21,b22,b23}, d5, p1, 1, 1, 1;\n"
        "wgmma.mma_async.sync.aligned.m64n32k16.f32.bf16.bf16 {o16,o17,o18,o19,o20,o21,o22,o23,o24,o25,o26,o27,o28,o29,o30,o31}, {b20,b21,b22,b23}, d13, p1, 1, 1, 1;\n"
        "wgmma.mma_async.sync.aligned.m64n32k16.f32.bf16.bf16 {o0,o1,o2,o3,o4,o5,o6,o7,o8,o9,o10,o11,o12,o13,o14,o15}, {b24,b25,b26,b27}, d6, p1, 1, 1, 1;\n"
        "wgmma.mma_async.sync.aligned.m64n32k16.f32.bf16.bf16 {o16,o17,o18,o19,o20,o21,o22,o23,o24,o25,o26,o27,o28,o29,o30,o31}, {b24,b25,b26,b27}, d14, p1, 1, 1, 1;\n"
        "wgmma.mma_async.sync.aligned.m64n32k16.f32.bf16.bf16 {o0,o1,o2,o3,o4,o5,o6,o7,o8,o9,o10,o11,o12,o13,o14,o15}, {b28,b29,b30,b31}, d7, p1, 1, 1, 1;\n"
        "wgmma.mma_async.sync.aligned.m64n32k16.f32.bf16.bf16 {o16,o17,o18,o19,o20,o21,o22,o23,o24,o25,o26,o27,o28,o29,o30,o31}, {b28,b29,b30,b31}, d15, p1, 1, 1, 1;\n"
        "wgmma.commit_group.sync.aligned;\n@nv bra.uni END;\n@s2 st.global.v4.b32 [%67+0], {k0,k1,k2,k3};\n@s3 st.global.v4.b32 [%68+0], {k4,k5,k6,k7};\n"
        "@s2 st.global.v4.b32 [%67+64], {k8,k9,k10,k11};\n@s3 st.global.v4.b32 [%68+64], {k12,k13,k14,k15};\n@nv bra.uni END;\nwgmma.wait_group.sync.aligned 0;\n"
        "cvt.rn.bf16x2.f32 k0, o1, o0;\ncvt.rn.bf16x2.f32 k1, o5, o4;\ncvt.rn.bf16x2.f32 k2, o9, o8;\ncvt.rn.bf16x2.f32 k3, o13, o12;\n"
        "cvt.rn.bf16x2.f32 k4, o3, o2;\ncvt.rn.bf16x2.f32 k5, o7, o6;\ncvt.rn.bf16x2.f32 k6, o11, o10;\ncvt.rn.bf16x2.f32 k7, o15, o14;\n"
        "cvt.rn.bf16x2.f32 k8, o17, o16;\ncvt.rn.bf16x2.f32 k9, o21, o20;\ncvt.rn.bf16x2.f32 k10, o25, o24;\ncvt.rn.bf16x2.f32 k11, o29, o28;\n"
        "cvt.rn.bf16x2.f32 k12, o19, o18;\ncvt.rn.bf16x2.f32 k13, o23, o22;\ncvt.rn.bf16x2.f32 k14, o27, o26;\ncvt.rn.bf16x2.f32 k15, o31, o30;\n"
        "@s2 st.global.v4.b32 [%67+128], {k0,k1,k2,k3};\n@s3 st.global.v4.b32 [%68+128], {k4,k5,k6,k7};\n@s2 st.global.v4.b32 [%67+192], {k8,k9,k10,k11};\n"
        "@s3 st.global.v4.b32 [%68+192], {k12,k13,k14,k15};\n"
        "END:\n}\n"
        ::"r"(pk[0]), "r"(pk[1]), "r"(pk[2]), "r"(pk[3]), "r"(pk[4]), "r"(pk[5]), "r"(pk[6]), "r"(pk[7]), "r"(pk[8]), "r"(pk[9]), "r"(pk[10]),
          "r"(pk[11]), "r"(pk[12]), "r"(pk[13]), "r"(pk[14]), "r"(pk[15]), "r"(pk[16]), "r"(pk[17]), "r"(pk[18]), "r"(pk[19]), "r"(pk[20]),
          "r"(pk[21]), "r"(pk[22]), "r"(pk[23]), "r"(pk[24]), "r"(pk[25]), "r"(pk[26]), "r"(pk[27]), "r"(pk[28]), "r"(pk[29]), "r"(pk[30]),
          "r"(pk[31]), "r"(pk[32]), "r"(pk[33]), "r"(pk[34]), "r"(pk[35]), "r"(pk[36]), "r"(pk[37]), "r"(pk[38]), "r"(pk[39]), "r"(pk[40]),
          "r"(pk[41]), "r"(pk[42]), "r"(pk[43]), "r"(pk[44]), "r"(pk[45]), "r"(pk[46]), "r"(pk[47]), "r"(pk[48]), "r"(pk[49]), "r"(pk[50]),
          "r"(pk[51]), "r"(pk[52]), "r"(pk[53]), "r"(pk[54]), "r"(pk[55]), "r"(pk[56]), "r"(pk[57]), "r"(pk[58]), "r"(pk[59]), "r"(pk[60]),
          "r"(pk[61]), "r"(pk[62]), "r"(pk[63]), "r"(ra), "l"(p[0]), "l"(p[1]), "l"(p[2]), "l"(p[3]), "r"(v[0]), "r"(v[1]), "r"(v[2]), "r"(v[3]),
          "r"(ba)
        : "memory");
}
__device__ __forceinline__ void project3(const uint32_t (&pk)[48], uint32_t ra, uint32_t ba, uint4* const (&p)[3], const uint32_t (&v)[3]) {
    asm volatile(
        "{\n.reg .pred p0, p1, q0, q1, nv, s<4>;\n.reg .b32 t, h, c<16>, a<32>, b<32>, k<16>;\n.reg .b64 d<16>;\n.reg .f32 o<32>;\nsetp.ne.b32 p0, 0, 0;\n"
        "setp.eq.b32 p1, 0, 0;\nmov.b32 h, 8;\nsetp.eq.u32 nv, %48, 0;\nvote.sync.any.pred nv, nv, 0xffffffff;\nsetp.ne.b32 s0, %52, 0;\n"
        "setp.ne.b32 s1, %53, 0;\nsetp.ne.b32 s2, %54, 0;\nmovmatrix.sync.aligned.m8n8.trans.b16 a0, %0;\nmovmatrix.sync.aligned.m8n8.trans.b16 a1, %16;\n"
        "movmatrix.sync.aligned.m8n8.trans.b16 a2, %1;\nmovmatrix.sync.aligned.m8n8.trans.b16 a3, %17;\nmovmatrix.sync.aligned.m8n8.trans.b16 a4, %2;\n"
        "movmatrix.sync.aligned.m8n8.trans.b16 a5, %18;\nmovmatrix.sync.aligned.m8n8.trans.b16 a6, %3;\nmovmatrix.sync.aligned.m8n8.trans.b16 a7, %19;\n"
        "movmatrix.sync.aligned.m8n8.trans.b16 a8, %4;\nmovmatrix.sync.aligned.m8n8.trans.b16 a9, %20;\nmovmatrix.sync.aligned.m8n8.trans.b16 a10, %5;\n"
        "movmatrix.sync.aligned.m8n8.trans.b16 a11, %21;\nmovmatrix.sync.aligned.m8n8.trans.b16 a12, %6;\nmovmatrix.sync.aligned.m8n8.trans.b16 a13, %22;\n"
        "movmatrix.sync.aligned.m8n8.trans.b16 a14, %7;\nmovmatrix.sync.aligned.m8n8.trans.b16 a15, %23;\nmovmatrix.sync.aligned.m8n8.trans.b16 a16, %8;\n"
        "movmatrix.sync.aligned.m8n8.trans.b16 a17, %24;\nmovmatrix.sync.aligned.m8n8.trans.b16 a18, %9;\nmovmatrix.sync.aligned.m8n8.trans.b16 a19, %25;\n"
        "movmatrix.sync.aligned.m8n8.trans.b16 a20, %10;\nmovmatrix.sync.aligned.m8n8.trans.b16 a21, %26;\nmovmatrix.sync.aligned.m8n8.trans.b16 a22, %11;\n"
        "movmatrix.sync.aligned.m8n8.trans.b16 a23, %27;\nmovmatrix.sync.aligned.m8n8.trans.b16 a24, %12;\nmovmatrix.sync.aligned.m8n8.trans.b16 a25, %28;\n"
        "movmatrix.sync.aligned.m8n8.trans.b16 a26, %13;\nmovmatrix.sync.aligned.m8n8.trans.b16 a27, %29;\nmovmatrix.sync.aligned.m8n8.trans.b16 a28, %14;\n"
        "movmatrix.sync.aligned.m8n8.trans.b16 a29, %30;\nmovmatrix.sync.aligned.m8n8.trans.b16 a30, %15;\nmovmatrix.sync.aligned.m8n8.trans.b16 a31, %31;\n"
        "mov.b32 t, 0;\n"
        "W0:\nmbarrier.try_wait.parity.shared.b64 q0, [%55+0], 0;\nadd.u32 t, t, 1;\nsetp.lt.and.u32 q1, t, 1000000, !q0;\n@q1 bra.uni W0;\nmov.b32 t, 0;\n"
        "W1:\nmbarrier.try_wait.parity.shared.b64 q0, [%55+8], 0;\nadd.u32 t, t, 1;\nsetp.lt.and.u32 q1, t, 1000000, !q0;\n@q1 bra.uni W1;\nmov.b32 t, 0;\n"
        "W2:\nmbarrier.try_wait.parity.shared.b64 q0, [%55+16], 0;\nadd.u32 t, t, 1;\nsetp.lt.and.u32 q1, t, 1000000, !q0;\n@q1 bra.uni W2;\nmov.b32 t, 0;\n"
        "W3:\nmbarrier.try_wait.parity.shared.b64 q0, [%55+24], 0;\nadd.u32 t, t, 1;\nsetp.lt.and.u32 q1, t, 1000000, !q0;\n@q1 bra.uni W3;\n"
        "ld.volatile.shared.v4.b32 {c0,c1,c2,c3}, [%48+0];\nld.volatile.shared.v4.b32 {c4,c5,c6,c7}, [%48+8192];\n"
        "ld.volatile.shared.v4.b32 {c8,c9,c10,c11}, [%48+16];\nld.volatile.shared.v4.b32 {c12,c13,c14,c15}, [%48+8208];\nand.b32 t, c0, 0xffe;\n"
        "mad.lo.u32 t, t, 4, 0x200000;\nmov.b64 d0, {t, h};\nand.b32 t, c1, 0xffe;\nmad.lo.u32 t, t, 4, 0x200000;\nmov.b64 d1, {t, h};\nand.b32 t, c2, 0xffe;\n"
        "mad.lo.u32 t, t, 4, 0x200000;\nmov.b64 d2, {t, h};\nand.b32 t, c3, 0xffe;\nmad.lo.u32 t, t, 4, 0x200000;\nmov.b64 d3, {t, h};\nand.b32 t, c4, 0xffe;\n"
        "mad.lo.u32 t, t, 4, 0x200000;\nmov.b64 d4, {t, h};\nand.b32 t, c5, 0xffe;\nmad.lo.u32 t, t, 4, 0x200000;\nmov.b64 d5, {t, h};\nand.b32 t, c6, 0xffe;\n"
        "mad.lo.u32 t, t, 4, 0x200000;\nmov.b64 d6, {t, h};\nand.b32 t, c7, 0xffe;\nmad.lo.u32 t, t, 4, 0x200000;\nmov.b64 d7, {t, h};\nand.b32 t, c8, 0xffe;\n"
        "mad.lo.u32 t, t, 4, 0x200000;\nmov.b64 d8, {t, h};\nand.b32 t, c9, 0xffe;\nmad.lo.u32 t, t, 4, 0x200000;\nmov.b64 d9, {t, h};\nand.b32 t, c10, 0xffe;\n"
        "mad.lo.u32 t, t, 4, 0x200000;\nmov.b64 d10, {t, h};\nand.b32 t, c11, 0xffe;\nmad.lo.u32 t, t, 4, 0x200000;\nmov.b64 d11, {t, h};\n"
        "and.b32 t, c12, 0xffe;\nmad.lo.u32 t, t, 4, 0x200000;\nmov.b64 d12, {t, h};\nand.b32 t, c13, 0xffe;\nmad.lo.u32 t, t, 4, 0x200000;\n"
        "mov.b64 d13, {t, h};\nand.b32 t, c14, 0xffe;\nmad.lo.u32 t, t, 4, 0x200000;\nmov.b64 d14, {t, h};\nand.b32 t, c15, 0xffe;\n"
        "mad.lo.u32 t, t, 4, 0x200000;\nmov.b64 d15, {t, h};\nwgmma.fence.sync.aligned;\n"
        "wgmma.mma_async.sync.aligned.m64n32k16.f32.bf16.bf16 {o0,o1,o2,o3,o4,o5,o6,o7,o8,o9,o10,o11,o12,o13,o14,o15}, {a0,a1,a2,a3}, d0, p0, 1, 1, 1;\n"
        "wgmma.mma_async.sync.aligned.m64n32k16.f32.bf16.bf16 {o16,o17,o18,o19,o20,o21,o22,o23,o24,o25,o26,o27,o28,o29,o30,o31}, {a0,a1,a2,a3}, d8, p0, 1, 1, 1;\n"
        "wgmma.mma_async.sync.aligned.m64n32k16.f32.bf16.bf16 {o0,o1,o2,o3,o4,o5,o6,o7,o8,o9,o10,o11,o12,o13,o14,o15}, {a4,a5,a6,a7}, d1, p1, 1, 1, 1;\n"
        "wgmma.mma_async.sync.aligned.m64n32k16.f32.bf16.bf16 {o16,o17,o18,o19,o20,o21,o22,o23,o24,o25,o26,o27,o28,o29,o30,o31}, {a4,a5,a6,a7}, d9, p1, 1, 1, 1;\n"
        "wgmma.mma_async.sync.aligned.m64n32k16.f32.bf16.bf16 {o0,o1,o2,o3,o4,o5,o6,o7,o8,o9,o10,o11,o12,o13,o14,o15}, {a8,a9,a10,a11}, d2, p1, 1, 1, 1;\n"
        "wgmma.mma_async.sync.aligned.m64n32k16.f32.bf16.bf16 {o16,o17,o18,o19,o20,o21,o22,o23,o24,o25,o26,o27,o28,o29,o30,o31}, {a8,a9,a10,a11}, d10, p1, 1, 1, 1;\n"
        "wgmma.mma_async.sync.aligned.m64n32k16.f32.bf16.bf16 {o0,o1,o2,o3,o4,o5,o6,o7,o8,o9,o10,o11,o12,o13,o14,o15}, {a12,a13,a14,a15}, d3, p1, 1, 1, 1;\n"
        "wgmma.mma_async.sync.aligned.m64n32k16.f32.bf16.bf16 {o16,o17,o18,o19,o20,o21,o22,o23,o24,o25,o26,o27,o28,o29,o30,o31}, {a12,a13,a14,a15}, d11, p1, 1, 1, 1;\n"
        "wgmma.mma_async.sync.aligned.m64n32k16.f32.bf16.bf16 {o0,o1,o2,o3,o4,o5,o6,o7,o8,o9,o10,o11,o12,o13,o14,o15}, {a16,a17,a18,a19}, d4, p1, 1, 1, 1;\n"
        "wgmma.mma_async.sync.aligned.m64n32k16.f32.bf16.bf16 {o16,o17,o18,o19,o20,o21,o22,o23,o24,o25,o26,o27,o28,o29,o30,o31}, {a16,a17,a18,a19}, d12, p1, 1, 1, 1;\n"
        "wgmma.mma_async.sync.aligned.m64n32k16.f32.bf16.bf16 {o0,o1,o2,o3,o4,o5,o6,o7,o8,o9,o10,o11,o12,o13,o14,o15}, {a20,a21,a22,a23}, d5, p1, 1, 1, 1;\n"
        "wgmma.mma_async.sync.aligned.m64n32k16.f32.bf16.bf16 {o16,o17,o18,o19,o20,o21,o22,o23,o24,o25,o26,o27,o28,o29,o30,o31}, {a20,a21,a22,a23}, d13, p1, 1, 1, 1;\n"
        "wgmma.mma_async.sync.aligned.m64n32k16.f32.bf16.bf16 {o0,o1,o2,o3,o4,o5,o6,o7,o8,o9,o10,o11,o12,o13,o14,o15}, {a24,a25,a26,a27}, d6, p1, 1, 1, 1;\n"
        "wgmma.mma_async.sync.aligned.m64n32k16.f32.bf16.bf16 {o16,o17,o18,o19,o20,o21,o22,o23,o24,o25,o26,o27,o28,o29,o30,o31}, {a24,a25,a26,a27}, d14, p1, 1, 1, 1;\n"
        "wgmma.mma_async.sync.aligned.m64n32k16.f32.bf16.bf16 {o0,o1,o2,o3,o4,o5,o6,o7,o8,o9,o10,o11,o12,o13,o14,o15}, {a28,a29,a30,a31}, d7, p1, 1, 1, 1;\n"
        "wgmma.mma_async.sync.aligned.m64n32k16.f32.bf16.bf16 {o16,o17,o18,o19,o20,o21,o22,o23,o24,o25,o26,o27,o28,o29,o30,o31}, {a28,a29,a30,a31}, d15, p1, 1, 1, 1;\n"
        "wgmma.commit_group.sync.aligned;\n@nv bra.uni END;\nmovmatrix.sync.aligned.m8n8.trans.b16 b0, %32;\nmovmatrix.sync.aligned.m8n8.trans.b16 b2, %33;\n"
        "movmatrix.sync.aligned.m8n8.trans.b16 b3, %33;\nmovmatrix.sync.aligned.m8n8.trans.b16 b4, %34;\nmovmatrix.sync.aligned.m8n8.trans.b16 b5, %34;\n"
        "movmatrix.sync.aligned.m8n8.trans.b16 b6, %35;\nmovmatrix.sync.aligned.m8n8.trans.b16 b7, %35;\nmovmatrix.sync.aligned.m8n8.trans.b16 b8, %36;\n"
        "movmatrix.sync.aligned.m8n8.trans.b16 b9, %36;\nmovmatrix.sync.aligned.m8n8.trans.b16 b20, %42;\nmovmatrix.sync.aligned.m8n8.trans.b16 b21, %42;\n"
        "movmatrix.sync.aligned.m8n8.trans.b16 b22, %43;\nmovmatrix.sync.aligned.m8n8.trans.b16 b23, %43;\nmovmatrix.sync.aligned.m8n8.trans.b16 b24, %44;\n"
        "movmatrix.sync.aligned.m8n8.trans.b16 b25, %44;\nmovmatrix.sync.aligned.m8n8.trans.b16 b26, %45;\nmovmatrix.sync.aligned.m8n8.trans.b16 b27, %45;\n"
        "movmatrix.sync.aligned.m8n8.trans.b16 b28, %46;\nmovmatrix.sync.aligned.m8n8.trans.b16 b29, %46;\nmovmatrix.sync.aligned.m8n8.trans.b16 b30, %47;\n"
        "movmatrix.sync.aligned.m8n8.trans.b16 b31, %47;\nmovmatrix.sync.aligned.m8n8.trans.b16 b1, %32;\nmovmatrix.sync.aligned.m8n8.trans.b16 b10, %37;\n"
        "movmatrix.sync.aligned.m8n8.trans.b16 b11, %37;\nmovmatrix.sync.aligned.m8n8.trans.b16 b12, %38;\nmovmatrix.sync.aligned.m8n8.trans.b16 b13, %38;\n"
        "movmatrix.sync.aligned.m8n8.trans.b16 b14, %39;\nmovmatrix.sync.aligned.m8n8.trans.b16 b15, %39;\nmovmatrix.sync.aligned.m8n8.trans.b16 b16, %40;\n"
        "movmatrix.sync.aligned.m8n8.trans.b16 b17, %40;\nmovmatrix.sync.aligned.m8n8.trans.b16 b18, %41;\nmovmatrix.sync.aligned.m8n8.trans.b16 b19, %41;\n"
        "@nv bra.uni END;\nwgmma.wait_group.sync.aligned 0;\ncvt.rn.bf16x2.f32 k0, o1, o0;\ncvt.rn.bf16x2.f32 k1, o5, o4;\ncvt.rn.bf16x2.f32 k2, o9, o8;\n"
        "cvt.rn.bf16x2.f32 k3, o13, o12;\ncvt.rn.bf16x2.f32 k4, o3, o2;\ncvt.rn.bf16x2.f32 k5, o7, o6;\ncvt.rn.bf16x2.f32 k6, o11, o10;\n"
        "cvt.rn.bf16x2.f32 k7, o15, o14;\ncvt.rn.bf16x2.f32 k8, o17, o16;\ncvt.rn.bf16x2.f32 k9, o21, o20;\ncvt.rn.bf16x2.f32 k10, o25, o24;\n"
        "cvt.rn.bf16x2.f32 k11, o29, o28;\ncvt.rn.bf16x2.f32 k12, o19, o18;\ncvt.rn.bf16x2.f32 k13, o23, o22;\ncvt.rn.bf16x2.f32 k14, o27, o26;\n"
        "cvt.rn.bf16x2.f32 k15, o31, o30;\nld.volatile.shared.v4.b32 {c0,c1,c2,c3}, [%48+32];\nld.volatile.shared.v4.b32 {c4,c5,c6,c7}, [%48+8224];\n"
        "ld.volatile.shared.v4.b32 {c8,c9,c10,c11}, [%48+48];\nld.volatile.shared.v4.b32 {c12,c13,c14,c15}, [%48+8240];\nand.b32 t, c0, 0xffe;\n"
        "mad.lo.u32 t, t, 4, 0x200000;\nmov.b64 d0, {t, h};\nand.b32 t, c1, 0xffe;\nmad.lo.u32 t, t, 4, 0x200000;\nmov.b64 d1, {t, h};\nand.b32 t, c2, 0xffe;\n"
        "mad.lo.u32 t, t, 4, 0x200000;\nmov.b64 d2, {t, h};\nand.b32 t, c3, 0xffe;\nmad.lo.u32 t, t, 4, 0x200000;\nmov.b64 d3, {t, h};\nand.b32 t, c4, 0xffe;\n"
        "mad.lo.u32 t, t, 4, 0x200000;\nmov.b64 d4, {t, h};\nand.b32 t, c5, 0xffe;\nmad.lo.u32 t, t, 4, 0x200000;\nmov.b64 d5, {t, h};\nand.b32 t, c6, 0xffe;\n"
        "mad.lo.u32 t, t, 4, 0x200000;\nmov.b64 d6, {t, h};\nand.b32 t, c7, 0xffe;\nmad.lo.u32 t, t, 4, 0x200000;\nmov.b64 d7, {t, h};\nand.b32 t, c8, 0xffe;\n"
        "mad.lo.u32 t, t, 4, 0x200000;\nmov.b64 d8, {t, h};\nand.b32 t, c9, 0xffe;\nmad.lo.u32 t, t, 4, 0x200000;\nmov.b64 d9, {t, h};\nand.b32 t, c10, 0xffe;\n"
        "mad.lo.u32 t, t, 4, 0x200000;\nmov.b64 d10, {t, h};\nand.b32 t, c11, 0xffe;\nmad.lo.u32 t, t, 4, 0x200000;\nmov.b64 d11, {t, h};\n"
        "and.b32 t, c12, 0xffe;\nmad.lo.u32 t, t, 4, 0x200000;\nmov.b64 d12, {t, h};\nand.b32 t, c13, 0xffe;\nmad.lo.u32 t, t, 4, 0x200000;\n"
        "mov.b64 d13, {t, h};\nand.b32 t, c14, 0xffe;\nmad.lo.u32 t, t, 4, 0x200000;\nmov.b64 d14, {t, h};\nand.b32 t, c15, 0xffe;\n"
        "mad.lo.u32 t, t, 4, 0x200000;\nmov.b64 d15, {t, h};\nwgmma.fence.sync.aligned;\n"
        "wgmma.mma_async.sync.aligned.m64n32k16.f32.bf16.bf16 {o0,o1,o2,o3,o4,o5,o6,o7,o8,o9,o10,o11,o12,o13,o14,o15}, {a0,a1,a2,a3}, d0, p0, 1, 1, 1;\n"
        "wgmma.mma_async.sync.aligned.m64n32k16.f32.bf16.bf16 {o16,o17,o18,o19,o20,o21,o22,o23,o24,o25,o26,o27,o28,o29,o30,o31}, {a0,a1,a2,a3}, d8, p0, 1, 1, 1;\n"
        "wgmma.mma_async.sync.aligned.m64n32k16.f32.bf16.bf16 {o0,o1,o2,o3,o4,o5,o6,o7,o8,o9,o10,o11,o12,o13,o14,o15}, {a4,a5,a6,a7}, d1, p1, 1, 1, 1;\n"
        "wgmma.mma_async.sync.aligned.m64n32k16.f32.bf16.bf16 {o16,o17,o18,o19,o20,o21,o22,o23,o24,o25,o26,o27,o28,o29,o30,o31}, {a4,a5,a6,a7}, d9, p1, 1, 1, 1;\n"
        "wgmma.mma_async.sync.aligned.m64n32k16.f32.bf16.bf16 {o0,o1,o2,o3,o4,o5,o6,o7,o8,o9,o10,o11,o12,o13,o14,o15}, {a8,a9,a10,a11}, d2, p1, 1, 1, 1;\n"
        "wgmma.mma_async.sync.aligned.m64n32k16.f32.bf16.bf16 {o16,o17,o18,o19,o20,o21,o22,o23,o24,o25,o26,o27,o28,o29,o30,o31}, {a8,a9,a10,a11}, d10, p1, 1, 1, 1;\n"
        "wgmma.mma_async.sync.aligned.m64n32k16.f32.bf16.bf16 {o0,o1,o2,o3,o4,o5,o6,o7,o8,o9,o10,o11,o12,o13,o14,o15}, {a12,a13,a14,a15}, d3, p1, 1, 1, 1;\n"
        "wgmma.mma_async.sync.aligned.m64n32k16.f32.bf16.bf16 {o16,o17,o18,o19,o20,o21,o22,o23,o24,o25,o26,o27,o28,o29,o30,o31}, {a12,a13,a14,a15}, d11, p1, 1, 1, 1;\n"
        "wgmma.mma_async.sync.aligned.m64n32k16.f32.bf16.bf16 {o0,o1,o2,o3,o4,o5,o6,o7,o8,o9,o10,o11,o12,o13,o14,o15}, {a16,a17,a18,a19}, d4, p1, 1, 1, 1;\n"
        "wgmma.mma_async.sync.aligned.m64n32k16.f32.bf16.bf16 {o16,o17,o18,o19,o20,o21,o22,o23,o24,o25,o26,o27,o28,o29,o30,o31}, {a16,a17,a18,a19}, d12, p1, 1, 1, 1;\n"
        "wgmma.mma_async.sync.aligned.m64n32k16.f32.bf16.bf16 {o0,o1,o2,o3,o4,o5,o6,o7,o8,o9,o10,o11,o12,o13,o14,o15}, {a20,a21,a22,a23}, d5, p1, 1, 1, 1;\n"
        "wgmma.mma_async.sync.aligned.m64n32k16.f32.bf16.bf16 {o16,o17,o18,o19,o20,o21,o22,o23,o24,o25,o26,o27,o28,o29,o30,o31}, {a20,a21,a22,a23}, d13, p1, 1, 1, 1;\n"
        "wgmma.mma_async.sync.aligned.m64n32k16.f32.bf16.bf16 {o0,o1,o2,o3,o4,o5,o6,o7,o8,o9,o10,o11,o12,o13,o14,o15}, {a24,a25,a26,a27}, d6, p1, 1, 1, 1;\n"
        "wgmma.mma_async.sync.aligned.m64n32k16.f32.bf16.bf16 {o16,o17,o18,o19,o20,o21,o22,o23,o24,o25,o26,o27,o28,o29,o30,o31}, {a24,a25,a26,a27}, d14, p1, 1, 1, 1;\n"
        "wgmma.mma_async.sync.aligned.m64n32k16.f32.bf16.bf16 {o0,o1,o2,o3,o4,o5,o6,o7,o8,o9,o10,o11,o12,o13,o14,o15}, {a28,a29,a30,a31}, d7, p1, 1, 1, 1;\n"
        "wgmma.mma_async.sync.aligned.m64n32k16.f32.bf16.bf16 {o16,o17,o18,o19,o20,o21,o22,o23,o24,o25,o26,o27,o28,o29,o30,o31}, {a28,a29,a30,a31}, d15, p1, 1, 1, 1;\n"
        "wgmma.commit_group.sync.aligned;\n@nv bra.uni END;\n@s0 st.global.v4.b32 [%49+0], {k0,k1,k2,k3};\n@s1 st.global.v4.b32 [%50+0], {k4,k5,k6,k7};\n"
        "@s0 st.global.v4.b32 [%49+64], {k8,k9,k10,k11};\n@s1 st.global.v4.b32 [%50+64], {k12,k13,k14,k15};\n@nv bra.uni END;\nwgmma.wait_group.sync.aligned 0;\n"
        "cvt.rn.bf16x2.f32 k0, o1, o0;\ncvt.rn.bf16x2.f32 k1, o5, o4;\ncvt.rn.bf16x2.f32 k2, o9, o8;\ncvt.rn.bf16x2.f32 k3, o13, o12;\n"
        "cvt.rn.bf16x2.f32 k4, o3, o2;\ncvt.rn.bf16x2.f32 k5, o7, o6;\ncvt.rn.bf16x2.f32 k6, o11, o10;\ncvt.rn.bf16x2.f32 k7, o15, o14;\n"
        "cvt.rn.bf16x2.f32 k8, o17, o16;\ncvt.rn.bf16x2.f32 k9, o21, o20;\ncvt.rn.bf16x2.f32 k10, o25, o24;\ncvt.rn.bf16x2.f32 k11, o29, o28;\n"
        "cvt.rn.bf16x2.f32 k12, o19, o18;\ncvt.rn.bf16x2.f32 k13, o23, o22;\ncvt.rn.bf16x2.f32 k14, o27, o26;\ncvt.rn.bf16x2.f32 k15, o31, o30;\n"
        "ld.volatile.shared.v4.b32 {c0,c1,c2,c3}, [%48+0];\nld.volatile.shared.v4.b32 {c4,c5,c6,c7}, [%48+8192];\n"
        "ld.volatile.shared.v4.b32 {c8,c9,c10,c11}, [%48+16];\nld.volatile.shared.v4.b32 {c12,c13,c14,c15}, [%48+8208];\nand.b32 t, c0, 0xffe;\n"
        "mad.lo.u32 t, t, 4, 0x200000;\nmov.b64 d0, {t, h};\nand.b32 t, c1, 0xffe;\nmad.lo.u32 t, t, 4, 0x200000;\nmov.b64 d1, {t, h};\nand.b32 t, c2, 0xffe;\n"
        "mad.lo.u32 t, t, 4, 0x200000;\nmov.b64 d2, {t, h};\nand.b32 t, c3, 0xffe;\nmad.lo.u32 t, t, 4, 0x200000;\nmov.b64 d3, {t, h};\nand.b32 t, c4, 0xffe;\n"
        "mad.lo.u32 t, t, 4, 0x200000;\nmov.b64 d4, {t, h};\nand.b32 t, c5, 0xffe;\nmad.lo.u32 t, t, 4, 0x200000;\nmov.b64 d5, {t, h};\nand.b32 t, c6, 0xffe;\n"
        "mad.lo.u32 t, t, 4, 0x200000;\nmov.b64 d6, {t, h};\nand.b32 t, c7, 0xffe;\nmad.lo.u32 t, t, 4, 0x200000;\nmov.b64 d7, {t, h};\nand.b32 t, c8, 0xffe;\n"
        "mad.lo.u32 t, t, 4, 0x200000;\nmov.b64 d8, {t, h};\nand.b32 t, c9, 0xffe;\nmad.lo.u32 t, t, 4, 0x200000;\nmov.b64 d9, {t, h};\nand.b32 t, c10, 0xffe;\n"
        "mad.lo.u32 t, t, 4, 0x200000;\nmov.b64 d10, {t, h};\nand.b32 t, c11, 0xffe;\nmad.lo.u32 t, t, 4, 0x200000;\nmov.b64 d11, {t, h};\n"
        "and.b32 t, c12, 0xffe;\nmad.lo.u32 t, t, 4, 0x200000;\nmov.b64 d12, {t, h};\nand.b32 t, c13, 0xffe;\nmad.lo.u32 t, t, 4, 0x200000;\n"
        "mov.b64 d13, {t, h};\nand.b32 t, c14, 0xffe;\nmad.lo.u32 t, t, 4, 0x200000;\nmov.b64 d14, {t, h};\nand.b32 t, c15, 0xffe;\n"
        "mad.lo.u32 t, t, 4, 0x200000;\nmov.b64 d15, {t, h};\nwgmma.fence.sync.aligned;\n"
        "wgmma.mma_async.sync.aligned.m64n32k16.f32.bf16.bf16 {o0,o1,o2,o3,o4,o5,o6,o7,o8,o9,o10,o11,o12,o13,o14,o15}, {b0,b1,b2,b3}, d0, p0, 1, 1, 1;\n"
        "wgmma.mma_async.sync.aligned.m64n32k16.f32.bf16.bf16 {o16,o17,o18,o19,o20,o21,o22,o23,o24,o25,o26,o27,o28,o29,o30,o31}, {b0,b1,b2,b3}, d8, p0, 1, 1, 1;\n"
        "wgmma.mma_async.sync.aligned.m64n32k16.f32.bf16.bf16 {o0,o1,o2,o3,o4,o5,o6,o7,o8,o9,o10,o11,o12,o13,o14,o15}, {b4,b5,b6,b7}, d1, p1, 1, 1, 1;\n"
        "wgmma.mma_async.sync.aligned.m64n32k16.f32.bf16.bf16 {o16,o17,o18,o19,o20,o21,o22,o23,o24,o25,o26,o27,o28,o29,o30,o31}, {b4,b5,b6,b7}, d9, p1, 1, 1, 1;\n"
        "wgmma.mma_async.sync.aligned.m64n32k16.f32.bf16.bf16 {o0,o1,o2,o3,o4,o5,o6,o7,o8,o9,o10,o11,o12,o13,o14,o15}, {b8,b9,b10,b11}, d2, p1, 1, 1, 1;\n"
        "wgmma.mma_async.sync.aligned.m64n32k16.f32.bf16.bf16 {o16,o17,o18,o19,o20,o21,o22,o23,o24,o25,o26,o27,o28,o29,o30,o31}, {b8,b9,b10,b11}, d10, p1, 1, 1, 1;\n"
        "wgmma.mma_async.sync.aligned.m64n32k16.f32.bf16.bf16 {o0,o1,o2,o3,o4,o5,o6,o7,o8,o9,o10,o11,o12,o13,o14,o15}, {b12,b13,b14,b15}, d3, p1, 1, 1, 1;\n"
        "wgmma.mma_async.sync.aligned.m64n32k16.f32.bf16.bf16 {o16,o17,o18,o19,o20,o21,o22,o23,o24,o25,o26,o27,o28,o29,o30,o31}, {b12,b13,b14,b15}, d11, p1, 1, 1, 1;\n"
        "wgmma.mma_async.sync.aligned.m64n32k16.f32.bf16.bf16 {o0,o1,o2,o3,o4,o5,o6,o7,o8,o9,o10,o11,o12,o13,o14,o15}, {b16,b17,b18,b19}, d4, p1, 1, 1, 1;\n"
        "wgmma.mma_async.sync.aligned.m64n32k16.f32.bf16.bf16 {o16,o17,o18,o19,o20,o21,o22,o23,o24,o25,o26,o27,o28,o29,o30,o31}, {b16,b17,b18,b19}, d12, p1, 1, 1, 1;\n"
        "wgmma.mma_async.sync.aligned.m64n32k16.f32.bf16.bf16 {o0,o1,o2,o3,o4,o5,o6,o7,o8,o9,o10,o11,o12,o13,o14,o15}, {b20,b21,b22,b23}, d5, p1, 1, 1, 1;\n"
        "wgmma.mma_async.sync.aligned.m64n32k16.f32.bf16.bf16 {o16,o17,o18,o19,o20,o21,o22,o23,o24,o25,o26,o27,o28,o29,o30,o31}, {b20,b21,b22,b23}, d13, p1, 1, 1, 1;\n"
        "wgmma.mma_async.sync.aligned.m64n32k16.f32.bf16.bf16 {o0,o1,o2,o3,o4,o5,o6,o7,o8,o9,o10,o11,o12,o13,o14,o15}, {b24,b25,b26,b27}, d6, p1, 1, 1, 1;\n"
        "wgmma.mma_async.sync.aligned.m64n32k16.f32.bf16.bf16 {o16,o17,o18,o19,o20,o21,o22,o23,o24,o25,o26,o27,o28,o29,o30,o31}, {b24,b25,b26,b27}, d14, p1, 1, 1, 1;\n"
        "wgmma.mma_async.sync.aligned.m64n32k16.f32.bf16.bf16 {o0,o1,o2,o3,o4,o5,o6,o7,o8,o9,o10,o11,o12,o13,o14,o15}, {b28,b29,b30,b31}, d7, p1, 1, 1, 1;\n"
        "wgmma.mma_async.sync.aligned.m64n32k16.f32.bf16.bf16 {o16,o17,o18,o19,o20,o21,o22,o23,o24,o25,o26,o27,o28,o29,o30,o31}, {b28,b29,b30,b31}, d15, p1, 1, 1, 1;\n"
        "wgmma.commit_group.sync.aligned;\n@nv bra.uni END;\n@s0 st.global.v4.b32 [%49+128], {k0,k1,k2,k3};\n@s1 st.global.v4.b32 [%50+128], {k4,k5,k6,k7};\n"
        "@s0 st.global.v4.b32 [%49+192], {k8,k9,k10,k11};\n@s1 st.global.v4.b32 [%50+192], {k12,k13,k14,k15};\n@nv bra.uni END;\n"
        "wgmma.wait_group.sync.aligned 0;\ncvt.rn.bf16x2.f32 k0, o1, o0;\ncvt.rn.bf16x2.f32 k1, o5, o4;\ncvt.rn.bf16x2.f32 k2, o9, o8;\n"
        "cvt.rn.bf16x2.f32 k3, o13, o12;\ncvt.rn.bf16x2.f32 k8, o17, o16;\ncvt.rn.bf16x2.f32 k9, o21, o20;\ncvt.rn.bf16x2.f32 k10, o25, o24;\n"
        "cvt.rn.bf16x2.f32 k11, o29, o28;\nld.volatile.shared.v4.b32 {c0,c1,c2,c3}, [%48+32];\nld.volatile.shared.v4.b32 {c4,c5,c6,c7}, [%48+8224];\n"
        "ld.volatile.shared.v4.b32 {c8,c9,c10,c11}, [%48+48];\nld.volatile.shared.v4.b32 {c12,c13,c14,c15}, [%48+8240];\nand.b32 t, c0, 0xffe;\n"
        "mad.lo.u32 t, t, 4, 0x200000;\nmov.b64 d0, {t, h};\nand.b32 t, c1, 0xffe;\nmad.lo.u32 t, t, 4, 0x200000;\nmov.b64 d1, {t, h};\nand.b32 t, c2, 0xffe;\n"
        "mad.lo.u32 t, t, 4, 0x200000;\nmov.b64 d2, {t, h};\nand.b32 t, c3, 0xffe;\nmad.lo.u32 t, t, 4, 0x200000;\nmov.b64 d3, {t, h};\nand.b32 t, c4, 0xffe;\n"
        "mad.lo.u32 t, t, 4, 0x200000;\nmov.b64 d4, {t, h};\nand.b32 t, c5, 0xffe;\nmad.lo.u32 t, t, 4, 0x200000;\nmov.b64 d5, {t, h};\nand.b32 t, c6, 0xffe;\n"
        "mad.lo.u32 t, t, 4, 0x200000;\nmov.b64 d6, {t, h};\nand.b32 t, c7, 0xffe;\nmad.lo.u32 t, t, 4, 0x200000;\nmov.b64 d7, {t, h};\nand.b32 t, c8, 0xffe;\n"
        "mad.lo.u32 t, t, 4, 0x200000;\nmov.b64 d8, {t, h};\nand.b32 t, c9, 0xffe;\nmad.lo.u32 t, t, 4, 0x200000;\nmov.b64 d9, {t, h};\nand.b32 t, c10, 0xffe;\n"
        "mad.lo.u32 t, t, 4, 0x200000;\nmov.b64 d10, {t, h};\nand.b32 t, c11, 0xffe;\nmad.lo.u32 t, t, 4, 0x200000;\nmov.b64 d11, {t, h};\n"
        "and.b32 t, c12, 0xffe;\nmad.lo.u32 t, t, 4, 0x200000;\nmov.b64 d12, {t, h};\nand.b32 t, c13, 0xffe;\nmad.lo.u32 t, t, 4, 0x200000;\n"
        "mov.b64 d13, {t, h};\nand.b32 t, c14, 0xffe;\nmad.lo.u32 t, t, 4, 0x200000;\nmov.b64 d14, {t, h};\nand.b32 t, c15, 0xffe;\n"
        "mad.lo.u32 t, t, 4, 0x200000;\nmov.b64 d15, {t, h};\nwgmma.fence.sync.aligned;\n"
        "wgmma.mma_async.sync.aligned.m64n32k16.f32.bf16.bf16 {o0,o1,o2,o3,o4,o5,o6,o7,o8,o9,o10,o11,o12,o13,o14,o15}, {b0,b1,b2,b3}, d0, p0, 1, 1, 1;\n"
        "wgmma.mma_async.sync.aligned.m64n32k16.f32.bf16.bf16 {o16,o17,o18,o19,o20,o21,o22,o23,o24,o25,o26,o27,o28,o29,o30,o31}, {b0,b1,b2,b3}, d8, p0, 1, 1, 1;\n"
        "wgmma.mma_async.sync.aligned.m64n32k16.f32.bf16.bf16 {o0,o1,o2,o3,o4,o5,o6,o7,o8,o9,o10,o11,o12,o13,o14,o15}, {b4,b5,b6,b7}, d1, p1, 1, 1, 1;\n"
        "wgmma.mma_async.sync.aligned.m64n32k16.f32.bf16.bf16 {o16,o17,o18,o19,o20,o21,o22,o23,o24,o25,o26,o27,o28,o29,o30,o31}, {b4,b5,b6,b7}, d9, p1, 1, 1, 1;\n"
        "wgmma.mma_async.sync.aligned.m64n32k16.f32.bf16.bf16 {o0,o1,o2,o3,o4,o5,o6,o7,o8,o9,o10,o11,o12,o13,o14,o15}, {b8,b9,b10,b11}, d2, p1, 1, 1, 1;\n"
        "wgmma.mma_async.sync.aligned.m64n32k16.f32.bf16.bf16 {o16,o17,o18,o19,o20,o21,o22,o23,o24,o25,o26,o27,o28,o29,o30,o31}, {b8,b9,b10,b11}, d10, p1, 1, 1, 1;\n"
        "wgmma.mma_async.sync.aligned.m64n32k16.f32.bf16.bf16 {o0,o1,o2,o3,o4,o5,o6,o7,o8,o9,o10,o11,o12,o13,o14,o15}, {b12,b13,b14,b15}, d3, p1, 1, 1, 1;\n"
        "wgmma.mma_async.sync.aligned.m64n32k16.f32.bf16.bf16 {o16,o17,o18,o19,o20,o21,o22,o23,o24,o25,o26,o27,o28,o29,o30,o31}, {b12,b13,b14,b15}, d11, p1, 1, 1, 1;\n"
        "wgmma.mma_async.sync.aligned.m64n32k16.f32.bf16.bf16 {o0,o1,o2,o3,o4,o5,o6,o7,o8,o9,o10,o11,o12,o13,o14,o15}, {b16,b17,b18,b19}, d4, p1, 1, 1, 1;\n"
        "wgmma.mma_async.sync.aligned.m64n32k16.f32.bf16.bf16 {o16,o17,o18,o19,o20,o21,o22,o23,o24,o25,o26,o27,o28,o29,o30,o31}, {b16,b17,b18,b19}, d12, p1, 1, 1, 1;\n"
        "wgmma.mma_async.sync.aligned.m64n32k16.f32.bf16.bf16 {o0,o1,o2,o3,o4,o5,o6,o7,o8,o9,o10,o11,o12,o13,o14,o15}, {b20,b21,b22,b23}, d5, p1, 1, 1, 1;\n"
        "wgmma.mma_async.sync.aligned.m64n32k16.f32.bf16.bf16 {o16,o17,o18,o19,o20,o21,o22,o23,o24,o25,o26,o27,o28,o29,o30,o31}, {b20,b21,b22,b23}, d13, p1, 1, 1, 1;\n"
        "wgmma.mma_async.sync.aligned.m64n32k16.f32.bf16.bf16 {o0,o1,o2,o3,o4,o5,o6,o7,o8,o9,o10,o11,o12,o13,o14,o15}, {b24,b25,b26,b27}, d6, p1, 1, 1, 1;\n"
        "wgmma.mma_async.sync.aligned.m64n32k16.f32.bf16.bf16 {o16,o17,o18,o19,o20,o21,o22,o23,o24,o25,o26,o27,o28,o29,o30,o31}, {b24,b25,b26,b27}, d14, p1, 1, 1, 1;\n"
        "wgmma.mma_async.sync.aligned.m64n32k16.f32.bf16.bf16 {o0,o1,o2,o3,o4,o5,o6,o7,o8,o9,o10,o11,o12,o13,o14,o15}, {b28,b29,b30,b31}, d7, p1, 1, 1, 1;\n"
        "wgmma.mma_async.sync.aligned.m64n32k16.f32.bf16.bf16 {o16,o17,o18,o19,o20,o21,o22,o23,o24,o25,o26,o27,o28,o29,o30,o31}, {b28,b29,b30,b31}, d15, p1, 1, 1, 1;\n"
        "wgmma.commit_group.sync.aligned;\n@nv bra.uni END;\n@s2 st.global.v4.b32 [%51+0], {k0,k1,k2,k3};\n@s2 st.global.v4.b32 [%51+64], {k8,k9,k10,k11};\n"
        "@nv bra.uni END;\nwgmma.wait_group.sync.aligned 0;\ncvt.rn.bf16x2.f32 k0, o1, o0;\ncvt.rn.bf16x2.f32 k1, o5, o4;\ncvt.rn.bf16x2.f32 k2, o9, o8;\n"
        "cvt.rn.bf16x2.f32 k3, o13, o12;\ncvt.rn.bf16x2.f32 k8, o17, o16;\ncvt.rn.bf16x2.f32 k9, o21, o20;\ncvt.rn.bf16x2.f32 k10, o25, o24;\n"
        "cvt.rn.bf16x2.f32 k11, o29, o28;\n@s2 st.global.v4.b32 [%51+128], {k0,k1,k2,k3};\n@s2 st.global.v4.b32 [%51+192], {k8,k9,k10,k11};\n"
        "END:\n}\n"
        ::"r"(pk[0]), "r"(pk[1]), "r"(pk[2]), "r"(pk[3]), "r"(pk[4]), "r"(pk[5]), "r"(pk[6]), "r"(pk[7]), "r"(pk[8]), "r"(pk[9]), "r"(pk[10]),
          "r"(pk[11]), "r"(pk[12]), "r"(pk[13]), "r"(pk[14]), "r"(pk[15]), "r"(pk[16]), "r"(pk[17]), "r"(pk[18]), "r"(pk[19]), "r"(pk[20]),
          "r"(pk[21]), "r"(pk[22]), "r"(pk[23]), "r"(pk[24]), "r"(pk[25]), "r"(pk[26]), "r"(pk[27]), "r"(pk[28]), "r"(pk[29]), "r"(pk[30]),
          "r"(pk[31]), "r"(pk[32]), "r"(pk[33]), "r"(pk[34]), "r"(pk[35]), "r"(pk[36]), "r"(pk[37]), "r"(pk[38]), "r"(pk[39]), "r"(pk[40]),
          "r"(pk[41]), "r"(pk[42]), "r"(pk[43]), "r"(pk[44]), "r"(pk[45]), "r"(pk[46]), "r"(pk[47]), "r"(ra), "l"(p[0]), "l"(p[1]), "l"(p[2]),
          "r"(v[0]), "r"(v[1]), "r"(v[2]), "r"(ba)
        : "memory");
}
__device__ __forceinline__ int cta_id() {
    int v;
    asm volatile("mov.u32 %0, %ctaid.x;" : "=r"(v));
    return v;
}
__device__ __forceinline__ int thread_id() {
    int v;
    asm volatile("mov.u32 %0, %tid.x;" : "=r"(v));
    return v;
}

__device__ __forceinline__ void slow_edge(int ee, int s, float* accn, const __nv_bfloat16* __restrict__ x,
                                          const __nv_bfloat16* __restrict__ sh, const __nv_bfloat16* __restrict__ ea,
                                          const __nv_bfloat16* __restrict__ cg, const __nv_bfloat16* __restrict__ wr,
                                          int lane) {
    float rwv[4] = {0.f, 0.f, 0.f, 0.f};
#pragma unroll 4
    for (int d = 0; d < 16; d++) {
        const float a = __bfloat162float(ea[(size_t)ee * 16 + d]);
        const uint2 wv = *(const uint2*)(wr + d * 128 + lane * 4);
        rwv[0] += a * __uint_as_float(wv.x << 16);
        rwv[1] += a * __uint_as_float(wv.x & 0xffff0000u);
        rwv[2] += a * __uint_as_float(wv.y << 16);
        rwv[3] += a * __uint_as_float(wv.y & 0xffff0000u);
    }
    float A = 0.f;
#pragma unroll
    for (int v = 0; v < 4; v++)
        A += __bfloat162float(cg[((lane >> 2) & 3) * 16 + v * 4 + (lane & 3)]) * __bfloat162float(sh[(size_t)ee * 4 + v]);
    float m[4][4];
#pragma unroll
    for (int w = 0; w < 4; w++)
#pragma unroll
        for (int j = 0; j < 4; j++) m[w][j] = 0.f;
#pragma unroll
    for (int u = 0; u < 4; u++) {
        const uint2 xv = *(const uint2*)(x + (size_t)s * 512 + u * 128 + lane * 4);
        const float x0 = __uint_as_float(xv.x << 16), x1 = __uint_as_float(xv.x & 0xffff0000u);
        const float x2 = __uint_as_float(xv.y << 16), x3 = __uint_as_float(xv.y & 0xffff0000u);
#pragma unroll
        for (int w = 0; w < 4; w++) {
            const float a = __shfl_sync(0xffffffffu, A, u * 4 + w);
            m[w][0] += a * x0;
            m[w][1] += a * x1;
            m[w][2] += a * x2;
            m[w][3] += a * x3;
        }
    }
#pragma unroll
    for (int w = 0; w < 4; w++)
#pragma unroll
        for (int j = 0; j < 4; j++) atomicAdd(accn + w * 128 + lane * 4 + j, m[w][j] * rwv[j]);
}

__device__ __forceinline__ void slow_out(const float* accn, const __nv_bfloat16* __restrict__ wout,
                                         __nv_bfloat16* __restrict__ outn, int lane) {
    float o[4][4];
#pragma unroll
    for (int w = 0; w < 4; w++)
#pragma unroll
        for (int j = 0; j < 4; j++) o[w][j] = 0.f;
#pragma unroll 2
    for (int c = 0; c < 128; c++) {
        const uint2 wv = *(const uint2*)(wout + c * 128 + lane * 4);
        const float w0 = __uint_as_float(wv.x << 16), w1 = __uint_as_float(wv.x & 0xffff0000u);
        const float w2 = __uint_as_float(wv.y << 16), w3 = __uint_as_float(wv.y & 0xffff0000u);
#pragma unroll
        for (int w = 0; w < 4; w++) {
            const float a = __bfloat162float(__float2bfloat16(accn[w * 128 + c]));
            o[w][0] += a * w0;
            o[w][1] += a * w1;
            o[w][2] += a * w2;
            o[w][3] += a * w3;
        }
    }
#pragma unroll
    for (int w = 0; w < 4; w++)
        *(uint2*)(outn + w * 128 + lane * 4) = make_uint2(pack_bf16(o[w][0], o[w][1]), pack_bf16(o[w][2], o[w][3]));
}

__device__ __forceinline__ void consume4(uint32_t (&pk)[64], const uint32_t (&w)[36], uint32_t olp, uint32_t xa, uint32_t ln,
                                      uint32_t lc, uint32_t linc, uint32_t lt, const __nv_bfloat16* ea, const __nv_bfloat16* sh) {
    ea += lt * 4, sh += lt & 2;
    asm volatile(
        "{\n.reg .pred p, q, psw, prdy, ps1, ps2, ps3, pz;\n.reg .f32 d<32>, fz;\n"
        ".reg .b32 h<64>, x<32>, y<32>, ra<8>, rb<8>, bA0, bA1, bB0, bB1, c0, c1, c2, c3, e0, e1, s0, kept;\n"
        ".reg .b32 olp, v, vB, m, id, ida, bar, xb, pos, t0, t1, t2, t3, n, z<16>;\n.reg .b16 lo, hi, i16;\n.reg .b64 pa, pb;\nmov.f32 fz, 0f00000000;\n"
        "mov.b32 h0, 0;\nmov.b32 h1, 0;\nmov.b32 h2, 0;\nmov.b32 h3, 0;\nmov.b32 h4, 0;\nmov.b32 h5, 0;\nmov.b32 h6, 0;\nmov.b32 h7, 0;\nmov.b32 h8, 0;\n"
        "mov.b32 h9, 0;\nmov.b32 h10, 0;\nmov.b32 h11, 0;\nmov.b32 h12, 0;\nmov.b32 h13, 0;\nmov.b32 h14, 0;\nmov.b32 h15, 0;\nmov.b32 h16, 0;\nmov.b32 h17, 0;\n"
        "mov.b32 h18, 0;\nmov.b32 h19, 0;\nmov.b32 h20, 0;\nmov.b32 h21, 0;\nmov.b32 h22, 0;\nmov.b32 h23, 0;\nmov.b32 h24, 0;\nmov.b32 h25, 0;\n"
        "mov.b32 h26, 0;\nmov.b32 h27, 0;\nmov.b32 h28, 0;\nmov.b32 h29, 0;\nmov.b32 h30, 0;\nmov.b32 h31, 0;\nmov.b32 h32, 0;\nmov.b32 h33, 0;\n"
        "mov.b32 h34, 0;\nmov.b32 h35, 0;\nmov.b32 h36, 0;\nmov.b32 h37, 0;\nmov.b32 h38, 0;\nmov.b32 h39, 0;\nmov.b32 h40, 0;\nmov.b32 h41, 0;\n"
        "mov.b32 h42, 0;\nmov.b32 h43, 0;\nmov.b32 h44, 0;\nmov.b32 h45, 0;\nmov.b32 h46, 0;\nmov.b32 h47, 0;\nmov.b32 h48, 0;\nmov.b32 h49, 0;\n"
        "mov.b32 h50, 0;\nmov.b32 h51, 0;\nmov.b32 h52, 0;\nmov.b32 h53, 0;\nmov.b32 h54, 0;\nmov.b32 h55, 0;\nmov.b32 h56, 0;\nmov.b32 h57, 0;\n"
        "mov.b32 h58, 0;\nmov.b32 h59, 0;\nmov.b32 h60, 0;\nmov.b32 h61, 0;\nmov.b32 h62, 0;\nmov.b32 h63, 0;\nmov.b32 olp, %64;\nand.b32 t0, %66, 32;\n"
        "setp.ne.u32 psw, t0, 0;\nsetp.eq.u32 pz, %64, 0;\nvote.sync.any.pred pz, pz, 0xffffffff;\nld.shared.b32 t0, [olp];\nadd.u32 olp, olp, 8;\n"
        "lop3.b32 t1, t0, %66, 0x3ff0, 0xe4;\nld.shared.b32 t1, [t1+%72];\nlop3.b32 kept, t1, t0, 0x1ffc, 0xe4;\nlop3.b32 t2, t1, %67, 3, 0x80;\n"
        "setp.ne.u32 q, t2, 0;\nshr.u32 t2, t1, 13;\nmad.wide.u32 pa, t2, 32, %70;\nmad.wide.u32 pb, t2, 8, %71;\nmov.b32 s0, 0;\n"
        "ld.global.cg.v2.b32 {e0,e1}, [pa];\n@q ld.global.cg.b32 s0, [pb];\nshfl.sync.idx.b32 v, kept, %67, 0x1f, 0xffffffff;\nor.b32 t3, %67, 4;\n"
        "shfl.sync.idx.b32 vB, kept, t3, 0x1f, 0xffffffff;\nshr.u32 bar, v, 1;\nand.b32 bar, bar, 0xff8;\nmbarrier.test_wait.parity.shared.b64 p, [bar+%74], 0;\n"
        "lop3.b32 ida, v, %67, 0x1fff, 0xe4;\nld.volatile.shared.u16 id, [ida+%73];\nvote.sync.all.pred prdy, p, 0xffffffff;\n"
        "RW:\nmma.sync.aligned.m16n8k8.row.col.f32.bf16.bf16.f32 {d0,d1,d2,d3}, {%108,%109}, {s0}, {fz,fz,fz,fz};\n"
        "mma.sync.aligned.m16n8k8.row.col.f32.bf16.bf16.f32 {d4,d5,d6,d7}, {%110,%111}, {s0}, {fz,fz,fz,fz};\ncvt.rn.bf16x2.f32 c0, d2, d0;\n"
        "cvt.rn.bf16x2.f32 c1, d3, d1;\ncvt.rn.bf16x2.f32 c2, d6, d4;\ncvt.rn.bf16x2.f32 c3, d7, d5;\nselp.b32 bA0, c2, c0, psw;\nselp.b32 bA1, c0, c2, psw;\n"
        "selp.b32 bB0, c3, c1, psw;\nselp.b32 bB1, c1, c3, psw;\n"
        "mma.sync.aligned.m16n8k16.row.col.f32.bf16.bf16.f32 {d0,d1,d2,d3}, {%76,%77,%78,%79}, {e0,e1}, {fz,fz,fz,fz};\ncvt.rn.bf16x2.f32 ra0, d2, d0;\n"
        "cvt.rn.bf16x2.f32 rb0, d3, d1;\nmma.sync.aligned.m16n8k16.row.col.f32.bf16.bf16.f32 {d4,d5,d6,d7}, {%80,%81,%82,%83}, {e0,e1}, {fz,fz,fz,fz};\n"
        "cvt.rn.bf16x2.f32 ra1, d6, d4;\ncvt.rn.bf16x2.f32 rb1, d7, d5;\n"
        "mma.sync.aligned.m16n8k16.row.col.f32.bf16.bf16.f32 {d8,d9,d10,d11}, {%84,%85,%86,%87}, {e0,e1}, {fz,fz,fz,fz};\ncvt.rn.bf16x2.f32 ra2, d10, d8;\n"
        "cvt.rn.bf16x2.f32 rb2, d11, d9;\nmma.sync.aligned.m16n8k16.row.col.f32.bf16.bf16.f32 {d12,d13,d14,d15}, {%88,%89,%90,%91}, {e0,e1}, {fz,fz,fz,fz};\n"
        "cvt.rn.bf16x2.f32 ra3, d14, d12;\ncvt.rn.bf16x2.f32 rb3, d15, d13;\n"
        "mma.sync.aligned.m16n8k16.row.col.f32.bf16.bf16.f32 {d16,d17,d18,d19}, {%92,%93,%94,%95}, {e0,e1}, {fz,fz,fz,fz};\ncvt.rn.bf16x2.f32 ra4, d18, d16;\n"
        "cvt.rn.bf16x2.f32 rb4, d19, d17;\nmma.sync.aligned.m16n8k16.row.col.f32.bf16.bf16.f32 {d20,d21,d22,d23}, {%96,%97,%98,%99}, {e0,e1}, {fz,fz,fz,fz};\n"
        "cvt.rn.bf16x2.f32 ra5, d22, d20;\ncvt.rn.bf16x2.f32 rb5, d23, d21;\n"
        "mma.sync.aligned.m16n8k16.row.col.f32.bf16.bf16.f32 {d24,d25,d26,d27}, {%100,%101,%102,%103}, {e0,e1}, {fz,fz,fz,fz};\n"
        "cvt.rn.bf16x2.f32 ra6, d26, d24;\ncvt.rn.bf16x2.f32 rb6, d27, d25;\n"
        "mma.sync.aligned.m16n8k16.row.col.f32.bf16.bf16.f32 {d28,d29,d30,d31}, {%104,%105,%106,%107}, {e0,e1}, {fz,fz,fz,fz};\n"
        "cvt.rn.bf16x2.f32 ra7, d30, d28;\ncvt.rn.bf16x2.f32 rb7, d31, d29;\nld.shared.b32 t0, [olp];\nadd.u32 olp, olp, 8;\n"
        "lop3.b32 t1, t0, %66, 0x3ff0, 0xe4;\nld.shared.b32 t1, [t1+%72];\nlop3.b32 kept, t1, t0, 0x1ffc, 0xe4;\nlop3.b32 t2, t1, %67, 3, 0x80;\n"
        "setp.ne.u32 q, t2, 0;\nshr.u32 t2, t1, 13;\nmad.wide.u32 pa, t2, 32, %70;\nmad.wide.u32 pb, t2, 8, %71;\nmov.b32 s0, 0;\n"
        "ld.global.cg.v2.b32 {e0,e1}, [pa];\n@q ld.global.cg.b32 s0, [pb];\n@!prdy bra.uni WA;\n"
        "HA:\nmad.lo.u32 xb, id, 64, %65;\ncvt.u16.u32 i16, id;\nldmatrix.sync.aligned.m8n8.x4.trans.shared.b16 {x0,x1,x2,x3}, [xb];\nxor.b32 t1, xb, 16;\n"
        "ldmatrix.sync.aligned.m8n8.x4.trans.shared.b16 {x4,x5,x6,x7}, [t1];\nxor.b32 t1, xb, 32;\n"
        "ldmatrix.sync.aligned.m8n8.x4.trans.shared.b16 {x8,x9,x10,x11}, [t1];\nxor.b32 t1, xb, 48;\n"
        "ldmatrix.sync.aligned.m8n8.x4.trans.shared.b16 {x12,x13,x14,x15}, [t1];\nxor.b32 t1, xb, 64;\n"
        "ldmatrix.sync.aligned.m8n8.x4.trans.shared.b16 {x16,x17,x18,x19}, [t1];\n@pz bra.uni DONE;\natom.shared.add.u32 pos, [%66+%75], %68;\n"
        "xor.b32 t1, xb, 80;\nldmatrix.sync.aligned.m8n8.x4.trans.shared.b16 {x20,x21,x22,x23}, [t1];\nxor.b32 t1, xb, 96;\n"
        "ldmatrix.sync.aligned.m8n8.x4.trans.shared.b16 {x24,x25,x26,x27}, [t1];\nxor.b32 t1, xb, 112;\n"
        "ldmatrix.sync.aligned.m8n8.x4.trans.shared.b16 {x28,x29,x30,x31}, [t1];\nst.volatile.shared.u16 [pos], i16;\nand.b32 t0, v, 268435456;\n"
        "setp.ne.u32 ps1, t0, 0;\nvote.sync.any.pred ps1, ps1, 0xffffffff;\nand.b32 t0, v, 536870912;\nsetp.ne.u32 ps2, t0, 0;\n"
        "vote.sync.any.pred ps2, ps2, 0xffffffff;\nmov.b32 v, vB;\nshr.u32 bar, v, 1;\nand.b32 bar, bar, 0xff8;\n"
        "mbarrier.test_wait.parity.shared.b64 p, [bar+%74], 0;\nlop3.b32 ida, v, %67, 0x1fff, 0xe4;\nld.volatile.shared.u16 id, [ida+%73];\n"
        "vote.sync.all.pred prdy, p, 0xffffffff;\nmov.b32 {lo, hi}, ra0;\nmov.b32 t2, {lo, lo};\nmul.rn.bf16x2 y0, x0, t2;\nmul.rn.bf16x2 y2, x2, t2;\n"
        "mov.b32 t2, {hi, hi};\nmul.rn.bf16x2 y1, x1, t2;\nmul.rn.bf16x2 y3, x3, t2;\n"
        "mma.sync.aligned.m16n8k16.row.col.f32.bf16.bf16.f32 {d0,d1,d2,d3}, {y0,y1,y2,y3}, {bA0,bA1}, {fz,fz,fz,fz};\ncvt.rn.bf16x2.f32 z0, d1, d0;\n"
        "cvt.rn.bf16x2.f32 z1, d3, d2;\nmov.b32 {lo, hi}, ra1;\nmov.b32 t2, {lo, lo};\nmul.rn.bf16x2 y4, x4, t2;\nmul.rn.bf16x2 y6, x6, t2;\n"
        "mov.b32 t2, {hi, hi};\nmul.rn.bf16x2 y5, x5, t2;\nmul.rn.bf16x2 y7, x7, t2;\n"
        "mma.sync.aligned.m16n8k16.row.col.f32.bf16.bf16.f32 {d4,d5,d6,d7}, {y4,y5,y6,y7}, {bA0,bA1}, {fz,fz,fz,fz};\ncvt.rn.bf16x2.f32 z2, d5, d4;\n"
        "cvt.rn.bf16x2.f32 z3, d7, d6;\nmov.b32 {lo, hi}, ra2;\nmov.b32 t2, {lo, lo};\nmul.rn.bf16x2 y8, x8, t2;\nmul.rn.bf16x2 y10, x10, t2;\n"
        "mov.b32 t2, {hi, hi};\nmul.rn.bf16x2 y9, x9, t2;\nmul.rn.bf16x2 y11, x11, t2;\n"
        "mma.sync.aligned.m16n8k16.row.col.f32.bf16.bf16.f32 {d8,d9,d10,d11}, {y8,y9,y10,y11}, {bA0,bA1}, {fz,fz,fz,fz};\ncvt.rn.bf16x2.f32 z4, d9, d8;\n"
        "cvt.rn.bf16x2.f32 z5, d11, d10;\nmov.b32 {lo, hi}, ra3;\nmov.b32 t2, {lo, lo};\nmul.rn.bf16x2 y12, x12, t2;\nmul.rn.bf16x2 y14, x14, t2;\n"
        "mov.b32 t2, {hi, hi};\nmul.rn.bf16x2 y13, x13, t2;\nmul.rn.bf16x2 y15, x15, t2;\n"
        "mma.sync.aligned.m16n8k16.row.col.f32.bf16.bf16.f32 {d12,d13,d14,d15}, {y12,y13,y14,y15}, {bA0,bA1}, {fz,fz,fz,fz};\ncvt.rn.bf16x2.f32 z6, d13, d12;\n"
        "cvt.rn.bf16x2.f32 z7, d15, d14;\nmov.b32 {lo, hi}, ra4;\nmov.b32 t2, {lo, lo};\nmul.rn.bf16x2 y16, x16, t2;\nmul.rn.bf16x2 y18, x18, t2;\n"
        "mov.b32 t2, {hi, hi};\nmul.rn.bf16x2 y17, x17, t2;\nmul.rn.bf16x2 y19, x19, t2;\n"
        "mma.sync.aligned.m16n8k16.row.col.f32.bf16.bf16.f32 {d16,d17,d18,d19}, {y16,y17,y18,y19}, {bA0,bA1}, {fz,fz,fz,fz};\ncvt.rn.bf16x2.f32 z8, d17, d16;\n"
        "cvt.rn.bf16x2.f32 z9, d19, d18;\nmov.b32 {lo, hi}, ra5;\nmov.b32 t2, {lo, lo};\nmul.rn.bf16x2 y20, x20, t2;\nmul.rn.bf16x2 y22, x22, t2;\n"
        "mov.b32 t2, {hi, hi};\nmul.rn.bf16x2 y21, x21, t2;\nmul.rn.bf16x2 y23, x23, t2;\n"
        "mma.sync.aligned.m16n8k16.row.col.f32.bf16.bf16.f32 {d20,d21,d22,d23}, {y20,y21,y22,y23}, {bA0,bA1}, {fz,fz,fz,fz};\ncvt.rn.bf16x2.f32 z10, d21, d20;\n"
        "cvt.rn.bf16x2.f32 z11, d23, d22;\nmov.b32 {lo, hi}, ra6;\nmov.b32 t2, {lo, lo};\nmul.rn.bf16x2 y24, x24, t2;\nmul.rn.bf16x2 y26, x26, t2;\n"
        "mov.b32 t2, {hi, hi};\nmul.rn.bf16x2 y25, x25, t2;\nmul.rn.bf16x2 y27, x27, t2;\n"
        "mma.sync.aligned.m16n8k16.row.col.f32.bf16.bf16.f32 {d24,d25,d26,d27}, {y24,y25,y26,y27}, {bA0,bA1}, {fz,fz,fz,fz};\ncvt.rn.bf16x2.f32 z12, d25, d24;\n"
        "cvt.rn.bf16x2.f32 z13, d27, d26;\nmov.b32 {lo, hi}, ra7;\nmov.b32 t2, {lo, lo};\nmul.rn.bf16x2 y28, x28, t2;\nmul.rn.bf16x2 y30, x30, t2;\n"
        "mov.b32 t2, {hi, hi};\nmul.rn.bf16x2 y29, x29, t2;\nmul.rn.bf16x2 y31, x31, t2;\n"
        "mma.sync.aligned.m16n8k16.row.col.f32.bf16.bf16.f32 {d28,d29,d30,d31}, {y28,y29,y30,y31}, {bA0,bA1}, {fz,fz,fz,fz};\ncvt.rn.bf16x2.f32 z14, d29, d28;\n"
        "cvt.rn.bf16x2.f32 z15, d31, d30;\n@ps2 bra.uni TA2;\n@ps1 bra.uni TA1;\n"
        "TA0:\nadd.rn.bf16x2 h0, h0, z0;\nadd.rn.bf16x2 h1, h1, z1;\nadd.rn.bf16x2 h2, h2, z2;\nadd.rn.bf16x2 h3, h3, z3;\nadd.rn.bf16x2 h4, h4, z4;\n"
        "add.rn.bf16x2 h5, h5, z5;\nadd.rn.bf16x2 h6, h6, z6;\nadd.rn.bf16x2 h7, h7, z7;\nadd.rn.bf16x2 h8, h8, z8;\nadd.rn.bf16x2 h9, h9, z9;\n"
        "add.rn.bf16x2 h10, h10, z10;\nadd.rn.bf16x2 h11, h11, z11;\nadd.rn.bf16x2 h12, h12, z12;\nadd.rn.bf16x2 h13, h13, z13;\nadd.rn.bf16x2 h14, h14, z14;\n"
        "add.rn.bf16x2 h15, h15, z15;\n@prdy bra.uni HB;\nbra.uni WB;\n"
        "TA1:\nadd.rn.bf16x2 h16, h16, z0;\nadd.rn.bf16x2 h17, h17, z1;\nadd.rn.bf16x2 h18, h18, z2;\nadd.rn.bf16x2 h19, h19, z3;\nadd.rn.bf16x2 h20, h20, z4;\n"
        "add.rn.bf16x2 h21, h21, z5;\nadd.rn.bf16x2 h22, h22, z6;\nadd.rn.bf16x2 h23, h23, z7;\nadd.rn.bf16x2 h24, h24, z8;\nadd.rn.bf16x2 h25, h25, z9;\n"
        "add.rn.bf16x2 h26, h26, z10;\nadd.rn.bf16x2 h27, h27, z11;\nadd.rn.bf16x2 h28, h28, z12;\nadd.rn.bf16x2 h29, h29, z13;\nadd.rn.bf16x2 h30, h30, z14;\n"
        "add.rn.bf16x2 h31, h31, z15;\n@prdy bra.uni HB;\nbra.uni WB;\n"
        "TA2:\n@ps1 bra.uni TA3;\nadd.rn.bf16x2 h32, h32, z0;\nadd.rn.bf16x2 h33, h33, z1;\nadd.rn.bf16x2 h34, h34, z2;\nadd.rn.bf16x2 h35, h35, z3;\n"
        "add.rn.bf16x2 h36, h36, z4;\nadd.rn.bf16x2 h37, h37, z5;\nadd.rn.bf16x2 h38, h38, z6;\nadd.rn.bf16x2 h39, h39, z7;\nadd.rn.bf16x2 h40, h40, z8;\n"
        "add.rn.bf16x2 h41, h41, z9;\nadd.rn.bf16x2 h42, h42, z10;\nadd.rn.bf16x2 h43, h43, z11;\nadd.rn.bf16x2 h44, h44, z12;\nadd.rn.bf16x2 h45, h45, z13;\n"
        "add.rn.bf16x2 h46, h46, z14;\nadd.rn.bf16x2 h47, h47, z15;\n@prdy bra.uni HB;\nbra.uni WB;\n"
        "TA3:\nadd.rn.bf16x2 h48, h48, z0;\nadd.rn.bf16x2 h49, h49, z1;\nadd.rn.bf16x2 h50, h50, z2;\nadd.rn.bf16x2 h51, h51, z3;\nadd.rn.bf16x2 h52, h52, z4;\n"
        "add.rn.bf16x2 h53, h53, z5;\nadd.rn.bf16x2 h54, h54, z6;\nadd.rn.bf16x2 h55, h55, z7;\nadd.rn.bf16x2 h56, h56, z8;\nadd.rn.bf16x2 h57, h57, z9;\n"
        "add.rn.bf16x2 h58, h58, z10;\nadd.rn.bf16x2 h59, h59, z11;\nadd.rn.bf16x2 h60, h60, z12;\nadd.rn.bf16x2 h61, h61, z13;\nadd.rn.bf16x2 h62, h62, z14;\n"
        "add.rn.bf16x2 h63, h63, z15;\n@prdy bra.uni HB;\nbra.uni WB;\n"
        "HB:\nmad.lo.u32 xb, id, 64, %65;\ncvt.u16.u32 i16, id;\natom.shared.add.u32 pos, [%66+%75], %68;\n"
        "ldmatrix.sync.aligned.m8n8.x4.trans.shared.b16 {x0,x1,x2,x3}, [xb];\nxor.b32 t1, xb, 16;\n"
        "ldmatrix.sync.aligned.m8n8.x4.trans.shared.b16 {x4,x5,x6,x7}, [t1];\nxor.b32 t1, xb, 32;\n"
        "ldmatrix.sync.aligned.m8n8.x4.trans.shared.b16 {x8,x9,x10,x11}, [t1];\nxor.b32 t1, xb, 48;\n"
        "ldmatrix.sync.aligned.m8n8.x4.trans.shared.b16 {x12,x13,x14,x15}, [t1];\nxor.b32 t1, xb, 64;\n"
        "ldmatrix.sync.aligned.m8n8.x4.trans.shared.b16 {x16,x17,x18,x19}, [t1];\nxor.b32 t1, xb, 80;\n"
        "ldmatrix.sync.aligned.m8n8.x4.trans.shared.b16 {x20,x21,x22,x23}, [t1];\nxor.b32 t1, xb, 96;\n"
        "ldmatrix.sync.aligned.m8n8.x4.trans.shared.b16 {x24,x25,x26,x27}, [t1];\nxor.b32 t1, xb, 112;\n"
        "ldmatrix.sync.aligned.m8n8.x4.trans.shared.b16 {x28,x29,x30,x31}, [t1];\nst.volatile.shared.u16 [pos], i16;\nand.b32 t0, v, 268435456;\n"
        "setp.ne.u32 ps1, t0, 0;\nvote.sync.any.pred ps1, ps1, 0xffffffff;\nand.b32 t0, v, 536870912;\nsetp.ne.u32 ps2, t0, 0;\n"
        "vote.sync.any.pred ps2, ps2, 0xffffffff;\nshfl.sync.idx.b32 v, kept, %67, 0x1f, 0xffffffff;\nor.b32 t3, %67, 4;\n"
        "shfl.sync.idx.b32 vB, kept, t3, 0x1f, 0xffffffff;\nshr.u32 bar, v, 1;\nand.b32 bar, bar, 0xff8;\nmbarrier.test_wait.parity.shared.b64 p, [bar+%74], 0;\n"
        "lop3.b32 ida, v, %67, 0x1fff, 0xe4;\nld.volatile.shared.u16 id, [ida+%73];\nvote.sync.all.pred prdy, p, 0xffffffff;\nmov.b32 {lo, hi}, rb0;\n"
        "mov.b32 t2, {lo, lo};\nmul.rn.bf16x2 y0, x0, t2;\nmul.rn.bf16x2 y2, x2, t2;\nmov.b32 t2, {hi, hi};\nmul.rn.bf16x2 y1, x1, t2;\n"
        "mul.rn.bf16x2 y3, x3, t2;\nmma.sync.aligned.m16n8k16.row.col.f32.bf16.bf16.f32 {d0,d1,d2,d3}, {y0,y1,y2,y3}, {bB0,bB1}, {fz,fz,fz,fz};\n"
        "cvt.rn.bf16x2.f32 z0, d1, d0;\ncvt.rn.bf16x2.f32 z1, d3, d2;\nmov.b32 {lo, hi}, rb1;\nmov.b32 t2, {lo, lo};\nmul.rn.bf16x2 y4, x4, t2;\n"
        "mul.rn.bf16x2 y6, x6, t2;\nmov.b32 t2, {hi, hi};\nmul.rn.bf16x2 y5, x5, t2;\nmul.rn.bf16x2 y7, x7, t2;\n"
        "mma.sync.aligned.m16n8k16.row.col.f32.bf16.bf16.f32 {d4,d5,d6,d7}, {y4,y5,y6,y7}, {bB0,bB1}, {fz,fz,fz,fz};\ncvt.rn.bf16x2.f32 z2, d5, d4;\n"
        "cvt.rn.bf16x2.f32 z3, d7, d6;\nmov.b32 {lo, hi}, rb2;\nmov.b32 t2, {lo, lo};\nmul.rn.bf16x2 y8, x8, t2;\nmul.rn.bf16x2 y10, x10, t2;\n"
        "mov.b32 t2, {hi, hi};\nmul.rn.bf16x2 y9, x9, t2;\nmul.rn.bf16x2 y11, x11, t2;\n"
        "mma.sync.aligned.m16n8k16.row.col.f32.bf16.bf16.f32 {d8,d9,d10,d11}, {y8,y9,y10,y11}, {bB0,bB1}, {fz,fz,fz,fz};\ncvt.rn.bf16x2.f32 z4, d9, d8;\n"
        "cvt.rn.bf16x2.f32 z5, d11, d10;\nmov.b32 {lo, hi}, rb3;\nmov.b32 t2, {lo, lo};\nmul.rn.bf16x2 y12, x12, t2;\nmul.rn.bf16x2 y14, x14, t2;\n"
        "mov.b32 t2, {hi, hi};\nmul.rn.bf16x2 y13, x13, t2;\nmul.rn.bf16x2 y15, x15, t2;\n"
        "mma.sync.aligned.m16n8k16.row.col.f32.bf16.bf16.f32 {d12,d13,d14,d15}, {y12,y13,y14,y15}, {bB0,bB1}, {fz,fz,fz,fz};\ncvt.rn.bf16x2.f32 z6, d13, d12;\n"
        "cvt.rn.bf16x2.f32 z7, d15, d14;\nmov.b32 {lo, hi}, rb4;\nmov.b32 t2, {lo, lo};\nmul.rn.bf16x2 y16, x16, t2;\nmul.rn.bf16x2 y18, x18, t2;\n"
        "mov.b32 t2, {hi, hi};\nmul.rn.bf16x2 y17, x17, t2;\nmul.rn.bf16x2 y19, x19, t2;\n"
        "mma.sync.aligned.m16n8k16.row.col.f32.bf16.bf16.f32 {d16,d17,d18,d19}, {y16,y17,y18,y19}, {bB0,bB1}, {fz,fz,fz,fz};\ncvt.rn.bf16x2.f32 z8, d17, d16;\n"
        "cvt.rn.bf16x2.f32 z9, d19, d18;\nmov.b32 {lo, hi}, rb5;\nmov.b32 t2, {lo, lo};\nmul.rn.bf16x2 y20, x20, t2;\nmul.rn.bf16x2 y22, x22, t2;\n"
        "mov.b32 t2, {hi, hi};\nmul.rn.bf16x2 y21, x21, t2;\nmul.rn.bf16x2 y23, x23, t2;\n"
        "mma.sync.aligned.m16n8k16.row.col.f32.bf16.bf16.f32 {d20,d21,d22,d23}, {y20,y21,y22,y23}, {bB0,bB1}, {fz,fz,fz,fz};\ncvt.rn.bf16x2.f32 z10, d21, d20;\n"
        "cvt.rn.bf16x2.f32 z11, d23, d22;\nmov.b32 {lo, hi}, rb6;\nmov.b32 t2, {lo, lo};\nmul.rn.bf16x2 y24, x24, t2;\nmul.rn.bf16x2 y26, x26, t2;\n"
        "mov.b32 t2, {hi, hi};\nmul.rn.bf16x2 y25, x25, t2;\nmul.rn.bf16x2 y27, x27, t2;\n"
        "mma.sync.aligned.m16n8k16.row.col.f32.bf16.bf16.f32 {d24,d25,d26,d27}, {y24,y25,y26,y27}, {bB0,bB1}, {fz,fz,fz,fz};\ncvt.rn.bf16x2.f32 z12, d25, d24;\n"
        "cvt.rn.bf16x2.f32 z13, d27, d26;\nmov.b32 {lo, hi}, rb7;\nmov.b32 t2, {lo, lo};\nmul.rn.bf16x2 y28, x28, t2;\nmul.rn.bf16x2 y30, x30, t2;\n"
        "mov.b32 t2, {hi, hi};\nmul.rn.bf16x2 y29, x29, t2;\nmul.rn.bf16x2 y31, x31, t2;\n"
        "mma.sync.aligned.m16n8k16.row.col.f32.bf16.bf16.f32 {d28,d29,d30,d31}, {y28,y29,y30,y31}, {bB0,bB1}, {fz,fz,fz,fz};\ncvt.rn.bf16x2.f32 z14, d29, d28;\n"
        "cvt.rn.bf16x2.f32 z15, d31, d30;\n@ps2 bra.uni TB2;\n@ps1 bra.uni TB1;\n"
        "TB0:\nadd.rn.bf16x2 h0, h0, z0;\nadd.rn.bf16x2 h1, h1, z1;\nadd.rn.bf16x2 h2, h2, z2;\nadd.rn.bf16x2 h3, h3, z3;\nadd.rn.bf16x2 h4, h4, z4;\n"
        "add.rn.bf16x2 h5, h5, z5;\nadd.rn.bf16x2 h6, h6, z6;\nadd.rn.bf16x2 h7, h7, z7;\nadd.rn.bf16x2 h8, h8, z8;\nadd.rn.bf16x2 h9, h9, z9;\n"
        "add.rn.bf16x2 h10, h10, z10;\nadd.rn.bf16x2 h11, h11, z11;\nadd.rn.bf16x2 h12, h12, z12;\nadd.rn.bf16x2 h13, h13, z13;\nadd.rn.bf16x2 h14, h14, z14;\n"
        "add.rn.bf16x2 h15, h15, z15;\nbra.uni RW;\n"
        "TB1:\nadd.rn.bf16x2 h16, h16, z0;\nadd.rn.bf16x2 h17, h17, z1;\nadd.rn.bf16x2 h18, h18, z2;\nadd.rn.bf16x2 h19, h19, z3;\nadd.rn.bf16x2 h20, h20, z4;\n"
        "add.rn.bf16x2 h21, h21, z5;\nadd.rn.bf16x2 h22, h22, z6;\nadd.rn.bf16x2 h23, h23, z7;\nadd.rn.bf16x2 h24, h24, z8;\nadd.rn.bf16x2 h25, h25, z9;\n"
        "add.rn.bf16x2 h26, h26, z10;\nadd.rn.bf16x2 h27, h27, z11;\nadd.rn.bf16x2 h28, h28, z12;\nadd.rn.bf16x2 h29, h29, z13;\nadd.rn.bf16x2 h30, h30, z14;\n"
        "add.rn.bf16x2 h31, h31, z15;\nbra.uni RW;\n"
        "TB2:\n@ps1 bra.uni TB3;\nadd.rn.bf16x2 h32, h32, z0;\nadd.rn.bf16x2 h33, h33, z1;\nadd.rn.bf16x2 h34, h34, z2;\nadd.rn.bf16x2 h35, h35, z3;\n"
        "add.rn.bf16x2 h36, h36, z4;\nadd.rn.bf16x2 h37, h37, z5;\nadd.rn.bf16x2 h38, h38, z6;\nadd.rn.bf16x2 h39, h39, z7;\nadd.rn.bf16x2 h40, h40, z8;\n"
        "add.rn.bf16x2 h41, h41, z9;\nadd.rn.bf16x2 h42, h42, z10;\nadd.rn.bf16x2 h43, h43, z11;\nadd.rn.bf16x2 h44, h44, z12;\nadd.rn.bf16x2 h45, h45, z13;\n"
        "add.rn.bf16x2 h46, h46, z14;\nadd.rn.bf16x2 h47, h47, z15;\nbra.uni RW;\n"
        "TB3:\nadd.rn.bf16x2 h48, h48, z0;\nadd.rn.bf16x2 h49, h49, z1;\nadd.rn.bf16x2 h50, h50, z2;\nadd.rn.bf16x2 h51, h51, z3;\nadd.rn.bf16x2 h52, h52, z4;\n"
        "add.rn.bf16x2 h53, h53, z5;\nadd.rn.bf16x2 h54, h54, z6;\nadd.rn.bf16x2 h55, h55, z7;\nadd.rn.bf16x2 h56, h56, z8;\nadd.rn.bf16x2 h57, h57, z9;\n"
        "add.rn.bf16x2 h58, h58, z10;\nadd.rn.bf16x2 h59, h59, z11;\nadd.rn.bf16x2 h60, h60, z12;\nadd.rn.bf16x2 h61, h61, z13;\nadd.rn.bf16x2 h62, h62, z14;\n"
        "add.rn.bf16x2 h63, h63, z15;\nbra.uni RW;\n"
        "WA:\nsetp.ge.u32 p, v, 1073741824;\nvote.sync.all.pred p, p, 0xffffffff;\n@p bra.uni DONE;\nmov.b32 n, 0;\nshr.u32 t2, v, 1;\nand.b32 t2, t2, 0xff8;\n"
        "WA3:\nmbarrier.try_wait.parity.shared.b64 p, [t2+%74], 0;\nvote.sync.all.pred p, p, 0xffffffff;\nadd.u32 n, n, 1;\nsetp.lt.and.u32 q, n, 1000000, !p;\n"
        "@q bra.uni WA3;\nlop3.b32 ida, v, %67, 0x1fff, 0xe4;\nld.volatile.shared.u16 id, [ida+%73];\nbra.uni HA;\n"
        "WB:\nsetp.ge.u32 p, v, 1073741824;\nvote.sync.all.pred p, p, 0xffffffff;\n@p bra.uni DONE;\nmov.b32 n, 0;\nshr.u32 t2, v, 1;\nand.b32 t2, t2, 0xff8;\n"
        "WB3:\nmbarrier.try_wait.parity.shared.b64 p, [t2+%74], 0;\nvote.sync.all.pred p, p, 0xffffffff;\nadd.u32 n, n, 1;\nsetp.lt.and.u32 q, n, 1000000, !p;\n"
        "@q bra.uni WB3;\nlop3.b32 ida, v, %67, 0x1fff, 0xe4;\nld.volatile.shared.u16 id, [ida+%73];\nbra.uni HB;\n"
        "DONE:\nmov.b32 %0, h0;\nmov.b32 %1, h1;\nmov.b32 %2, h2;\nmov.b32 %3, h3;\nmov.b32 %4, h4;\nmov.b32 %5, h5;\nmov.b32 %6, h6;\nmov.b32 %7, h7;\n"
        "mov.b32 %8, h8;\nmov.b32 %9, h9;\nmov.b32 %10, h10;\nmov.b32 %11, h11;\nmov.b32 %12, h12;\nmov.b32 %13, h13;\nmov.b32 %14, h14;\nmov.b32 %15, h15;\n"
        "mov.b32 %16, h16;\nmov.b32 %17, h17;\nmov.b32 %18, h18;\nmov.b32 %19, h19;\nmov.b32 %20, h20;\nmov.b32 %21, h21;\nmov.b32 %22, h22;\nmov.b32 %23, h23;\n"
        "mov.b32 %24, h24;\nmov.b32 %25, h25;\nmov.b32 %26, h26;\nmov.b32 %27, h27;\nmov.b32 %28, h28;\nmov.b32 %29, h29;\nmov.b32 %30, h30;\nmov.b32 %31, h31;\n"
        "mov.b32 %32, h32;\nmov.b32 %33, h33;\nmov.b32 %34, h34;\nmov.b32 %35, h35;\nmov.b32 %36, h36;\nmov.b32 %37, h37;\nmov.b32 %38, h38;\nmov.b32 %39, h39;\n"
        "mov.b32 %40, h40;\nmov.b32 %41, h41;\nmov.b32 %42, h42;\nmov.b32 %43, h43;\nmov.b32 %44, h44;\nmov.b32 %45, h45;\nmov.b32 %46, h46;\nmov.b32 %47, h47;\n"
        "mov.b32 %48, h48;\nmov.b32 %49, h49;\nmov.b32 %50, h50;\nmov.b32 %51, h51;\nmov.b32 %52, h52;\nmov.b32 %53, h53;\nmov.b32 %54, h54;\nmov.b32 %55, h55;\n"
        "mov.b32 %56, h56;\nmov.b32 %57, h57;\nmov.b32 %58, h58;\nmov.b32 %59, h59;\nmov.b32 %60, h60;\nmov.b32 %61, h61;\nmov.b32 %62, h62;\nmov.b32 %63, h63;\n"
        "}\n"
        : "=r"(pk[0]), "=r"(pk[1]), "=r"(pk[2]), "=r"(pk[3]), "=r"(pk[4]), "=r"(pk[5]), "=r"(pk[6]), "=r"(pk[7]), "=r"(pk[8]), "=r"(pk[9]),
          "=r"(pk[10]), "=r"(pk[11]), "=r"(pk[12]), "=r"(pk[13]), "=r"(pk[14]), "=r"(pk[15]), "=r"(pk[16]), "=r"(pk[17]), "=r"(pk[18]), "=r"(pk[19]),
          "=r"(pk[20]), "=r"(pk[21]), "=r"(pk[22]), "=r"(pk[23]), "=r"(pk[24]), "=r"(pk[25]), "=r"(pk[26]), "=r"(pk[27]), "=r"(pk[28]), "=r"(pk[29]),
          "=r"(pk[30]), "=r"(pk[31]), "=r"(pk[32]), "=r"(pk[33]), "=r"(pk[34]), "=r"(pk[35]), "=r"(pk[36]), "=r"(pk[37]), "=r"(pk[38]), "=r"(pk[39]),
          "=r"(pk[40]), "=r"(pk[41]), "=r"(pk[42]), "=r"(pk[43]), "=r"(pk[44]), "=r"(pk[45]), "=r"(pk[46]), "=r"(pk[47]), "=r"(pk[48]), "=r"(pk[49]),
          "=r"(pk[50]), "=r"(pk[51]), "=r"(pk[52]), "=r"(pk[53]), "=r"(pk[54]), "=r"(pk[55]), "=r"(pk[56]), "=r"(pk[57]), "=r"(pk[58]), "=r"(pk[59]),
          "=r"(pk[60]), "=r"(pk[61]), "=r"(pk[62]), "=r"(pk[63])
        : "r"(olp), "r"(xa), "r"(ln), "r"(lc), "r"(linc), "r"(lt), "l"(ea), "l"(sh),
          "n"(sb + SM_REC), "n"(sb + SM_R), "n"(sb + SM_BAR), "n"(sb + SM_CTR),
          "r"(w[0]), "r"(w[1]), "r"(w[2]), "r"(w[3]), "r"(w[4]), "r"(w[5]), "r"(w[6]), "r"(w[7]), "r"(w[8]), "r"(w[9]), "r"(w[10]), "r"(w[11]),
          "r"(w[12]), "r"(w[13]), "r"(w[14]), "r"(w[15]), "r"(w[16]), "r"(w[17]), "r"(w[18]), "r"(w[19]), "r"(w[20]), "r"(w[21]), "r"(w[22]),
          "r"(w[23]), "r"(w[24]), "r"(w[25]), "r"(w[26]), "r"(w[27]), "r"(w[28]), "r"(w[29]), "r"(w[30]), "r"(w[31]), "r"(w[32]), "r"(w[33]),
          "r"(w[34]), "r"(w[35])
        : "memory");
}
__device__ __forceinline__ void consume3(uint32_t (&pk)[48], const uint32_t (&w)[36], uint32_t olp, uint32_t xa, uint32_t ln,
                                      uint32_t lc, uint32_t linc, uint32_t lt, const __nv_bfloat16* ea, const __nv_bfloat16* sh) {
    ea += lt * 4, sh += lt & 2;
    asm volatile(
        "{\n.reg .pred p, q, psw, prdy, ps1, ps2, ps3, pz;\n.reg .f32 d<32>, fz;\n"
        ".reg .b32 h<48>, x<32>, y<32>, ra<8>, rb<8>, bA0, bA1, bB0, bB1, c0, c1, c2, c3, e0, e1, s0, kept;\n"
        ".reg .b32 olp, v, vB, m, id, ida, bar, xb, pos, t0, t1, t2, t3, n, z<16>;\n.reg .b16 lo, hi, i16;\n.reg .b64 pa, pb;\nmov.f32 fz, 0f00000000;\n"
        "mov.b32 h0, 0;\nmov.b32 h1, 0;\nmov.b32 h2, 0;\nmov.b32 h3, 0;\nmov.b32 h4, 0;\nmov.b32 h5, 0;\nmov.b32 h6, 0;\nmov.b32 h7, 0;\nmov.b32 h8, 0;\n"
        "mov.b32 h9, 0;\nmov.b32 h10, 0;\nmov.b32 h11, 0;\nmov.b32 h12, 0;\nmov.b32 h13, 0;\nmov.b32 h14, 0;\nmov.b32 h15, 0;\nmov.b32 h16, 0;\nmov.b32 h17, 0;\n"
        "mov.b32 h18, 0;\nmov.b32 h19, 0;\nmov.b32 h20, 0;\nmov.b32 h21, 0;\nmov.b32 h22, 0;\nmov.b32 h23, 0;\nmov.b32 h24, 0;\nmov.b32 h25, 0;\n"
        "mov.b32 h26, 0;\nmov.b32 h27, 0;\nmov.b32 h28, 0;\nmov.b32 h29, 0;\nmov.b32 h30, 0;\nmov.b32 h31, 0;\nmov.b32 h32, 0;\nmov.b32 h33, 0;\n"
        "mov.b32 h34, 0;\nmov.b32 h35, 0;\nmov.b32 h36, 0;\nmov.b32 h37, 0;\nmov.b32 h38, 0;\nmov.b32 h39, 0;\nmov.b32 h40, 0;\nmov.b32 h41, 0;\n"
        "mov.b32 h42, 0;\nmov.b32 h43, 0;\nmov.b32 h44, 0;\nmov.b32 h45, 0;\nmov.b32 h46, 0;\nmov.b32 h47, 0;\nmov.b32 olp, %48;\nand.b32 t0, %50, 32;\n"
        "setp.ne.u32 psw, t0, 0;\nsetp.eq.u32 pz, %48, 0;\nvote.sync.any.pred pz, pz, 0xffffffff;\nld.shared.b32 t0, [olp];\nadd.u32 olp, olp, 8;\n"
        "lop3.b32 t1, t0, %50, 0x3ff0, 0xe4;\nld.shared.b32 t1, [t1+%56];\nlop3.b32 kept, t1, t0, 0x1ffc, 0xe4;\nlop3.b32 t2, t1, %51, 3, 0x80;\n"
        "setp.ne.u32 q, t2, 0;\nshr.u32 t2, t1, 13;\nmad.wide.u32 pa, t2, 32, %54;\nmad.wide.u32 pb, t2, 8, %55;\nmov.b32 s0, 0;\n"
        "ld.global.cg.v2.b32 {e0,e1}, [pa];\n@q ld.global.cg.b32 s0, [pb];\nshfl.sync.idx.b32 v, kept, %51, 0x1f, 0xffffffff;\nor.b32 t3, %51, 4;\n"
        "shfl.sync.idx.b32 vB, kept, t3, 0x1f, 0xffffffff;\nshr.u32 bar, v, 1;\nand.b32 bar, bar, 0xff8;\nmbarrier.test_wait.parity.shared.b64 p, [bar+%58], 0;\n"
        "lop3.b32 ida, v, %51, 0x1fff, 0xe4;\nld.volatile.shared.u16 id, [ida+%57];\nvote.sync.all.pred prdy, p, 0xffffffff;\n"
        "RW:\nmma.sync.aligned.m16n8k8.row.col.f32.bf16.bf16.f32 {d0,d1,d2,d3}, {%92,%93}, {s0}, {fz,fz,fz,fz};\n"
        "mma.sync.aligned.m16n8k8.row.col.f32.bf16.bf16.f32 {d4,d5,d6,d7}, {%94,%95}, {s0}, {fz,fz,fz,fz};\ncvt.rn.bf16x2.f32 c0, d2, d0;\n"
        "cvt.rn.bf16x2.f32 c1, d3, d1;\ncvt.rn.bf16x2.f32 c2, d6, d4;\ncvt.rn.bf16x2.f32 c3, d7, d5;\nselp.b32 bA0, c2, c0, psw;\nselp.b32 bA1, c0, c2, psw;\n"
        "selp.b32 bB0, c3, c1, psw;\nselp.b32 bB1, c1, c3, psw;\n"
        "mma.sync.aligned.m16n8k16.row.col.f32.bf16.bf16.f32 {d0,d1,d2,d3}, {%60,%61,%62,%63}, {e0,e1}, {fz,fz,fz,fz};\ncvt.rn.bf16x2.f32 ra0, d2, d0;\n"
        "cvt.rn.bf16x2.f32 rb0, d3, d1;\nmma.sync.aligned.m16n8k16.row.col.f32.bf16.bf16.f32 {d4,d5,d6,d7}, {%64,%65,%66,%67}, {e0,e1}, {fz,fz,fz,fz};\n"
        "cvt.rn.bf16x2.f32 ra1, d6, d4;\ncvt.rn.bf16x2.f32 rb1, d7, d5;\n"
        "mma.sync.aligned.m16n8k16.row.col.f32.bf16.bf16.f32 {d8,d9,d10,d11}, {%68,%69,%70,%71}, {e0,e1}, {fz,fz,fz,fz};\ncvt.rn.bf16x2.f32 ra2, d10, d8;\n"
        "cvt.rn.bf16x2.f32 rb2, d11, d9;\nmma.sync.aligned.m16n8k16.row.col.f32.bf16.bf16.f32 {d12,d13,d14,d15}, {%72,%73,%74,%75}, {e0,e1}, {fz,fz,fz,fz};\n"
        "cvt.rn.bf16x2.f32 ra3, d14, d12;\ncvt.rn.bf16x2.f32 rb3, d15, d13;\n"
        "mma.sync.aligned.m16n8k16.row.col.f32.bf16.bf16.f32 {d16,d17,d18,d19}, {%76,%77,%78,%79}, {e0,e1}, {fz,fz,fz,fz};\ncvt.rn.bf16x2.f32 ra4, d18, d16;\n"
        "cvt.rn.bf16x2.f32 rb4, d19, d17;\nmma.sync.aligned.m16n8k16.row.col.f32.bf16.bf16.f32 {d20,d21,d22,d23}, {%80,%81,%82,%83}, {e0,e1}, {fz,fz,fz,fz};\n"
        "cvt.rn.bf16x2.f32 ra5, d22, d20;\ncvt.rn.bf16x2.f32 rb5, d23, d21;\n"
        "mma.sync.aligned.m16n8k16.row.col.f32.bf16.bf16.f32 {d24,d25,d26,d27}, {%84,%85,%86,%87}, {e0,e1}, {fz,fz,fz,fz};\ncvt.rn.bf16x2.f32 ra6, d26, d24;\n"
        "cvt.rn.bf16x2.f32 rb6, d27, d25;\nmma.sync.aligned.m16n8k16.row.col.f32.bf16.bf16.f32 {d28,d29,d30,d31}, {%88,%89,%90,%91}, {e0,e1}, {fz,fz,fz,fz};\n"
        "cvt.rn.bf16x2.f32 ra7, d30, d28;\ncvt.rn.bf16x2.f32 rb7, d31, d29;\nld.shared.b32 t0, [olp];\nadd.u32 olp, olp, 8;\n"
        "lop3.b32 t1, t0, %50, 0x3ff0, 0xe4;\nld.shared.b32 t1, [t1+%56];\nlop3.b32 kept, t1, t0, 0x1ffc, 0xe4;\nlop3.b32 t2, t1, %51, 3, 0x80;\n"
        "setp.ne.u32 q, t2, 0;\nshr.u32 t2, t1, 13;\nmad.wide.u32 pa, t2, 32, %54;\nmad.wide.u32 pb, t2, 8, %55;\nmov.b32 s0, 0;\n"
        "ld.global.cg.v2.b32 {e0,e1}, [pa];\n@q ld.global.cg.b32 s0, [pb];\n@!prdy bra.uni WA;\n"
        "HA:\nmad.lo.u32 xb, id, 64, %49;\ncvt.u16.u32 i16, id;\nldmatrix.sync.aligned.m8n8.x4.trans.shared.b16 {x0,x1,x2,x3}, [xb];\nxor.b32 t1, xb, 16;\n"
        "ldmatrix.sync.aligned.m8n8.x4.trans.shared.b16 {x4,x5,x6,x7}, [t1];\nxor.b32 t1, xb, 32;\n"
        "ldmatrix.sync.aligned.m8n8.x4.trans.shared.b16 {x8,x9,x10,x11}, [t1];\nxor.b32 t1, xb, 48;\n"
        "ldmatrix.sync.aligned.m8n8.x4.trans.shared.b16 {x12,x13,x14,x15}, [t1];\nxor.b32 t1, xb, 64;\n"
        "ldmatrix.sync.aligned.m8n8.x4.trans.shared.b16 {x16,x17,x18,x19}, [t1];\n@pz bra.uni DONE;\natom.shared.add.u32 pos, [%50+%59], %52;\n"
        "xor.b32 t1, xb, 80;\nldmatrix.sync.aligned.m8n8.x4.trans.shared.b16 {x20,x21,x22,x23}, [t1];\nxor.b32 t1, xb, 96;\n"
        "ldmatrix.sync.aligned.m8n8.x4.trans.shared.b16 {x24,x25,x26,x27}, [t1];\nxor.b32 t1, xb, 112;\n"
        "ldmatrix.sync.aligned.m8n8.x4.trans.shared.b16 {x28,x29,x30,x31}, [t1];\nst.volatile.shared.u16 [pos], i16;\nand.b32 t0, v, 268435456;\n"
        "setp.ne.u32 ps1, t0, 0;\nvote.sync.any.pred ps1, ps1, 0xffffffff;\nand.b32 t0, v, 536870912;\nsetp.ne.u32 ps2, t0, 0;\n"
        "vote.sync.any.pred ps2, ps2, 0xffffffff;\nmov.b32 v, vB;\nshr.u32 bar, v, 1;\nand.b32 bar, bar, 0xff8;\n"
        "mbarrier.test_wait.parity.shared.b64 p, [bar+%58], 0;\nlop3.b32 ida, v, %51, 0x1fff, 0xe4;\nld.volatile.shared.u16 id, [ida+%57];\n"
        "vote.sync.all.pred prdy, p, 0xffffffff;\nmov.b32 {lo, hi}, ra0;\nmov.b32 t2, {lo, lo};\nmul.rn.bf16x2 y0, x0, t2;\nmul.rn.bf16x2 y2, x2, t2;\n"
        "mov.b32 t2, {hi, hi};\nmul.rn.bf16x2 y1, x1, t2;\nmul.rn.bf16x2 y3, x3, t2;\n"
        "mma.sync.aligned.m16n8k16.row.col.f32.bf16.bf16.f32 {d0,d1,d2,d3}, {y0,y1,y2,y3}, {bA0,bA1}, {fz,fz,fz,fz};\ncvt.rn.bf16x2.f32 z0, d1, d0;\n"
        "cvt.rn.bf16x2.f32 z1, d3, d2;\nmov.b32 {lo, hi}, ra1;\nmov.b32 t2, {lo, lo};\nmul.rn.bf16x2 y4, x4, t2;\nmul.rn.bf16x2 y6, x6, t2;\n"
        "mov.b32 t2, {hi, hi};\nmul.rn.bf16x2 y5, x5, t2;\nmul.rn.bf16x2 y7, x7, t2;\n"
        "mma.sync.aligned.m16n8k16.row.col.f32.bf16.bf16.f32 {d4,d5,d6,d7}, {y4,y5,y6,y7}, {bA0,bA1}, {fz,fz,fz,fz};\ncvt.rn.bf16x2.f32 z2, d5, d4;\n"
        "cvt.rn.bf16x2.f32 z3, d7, d6;\nmov.b32 {lo, hi}, ra2;\nmov.b32 t2, {lo, lo};\nmul.rn.bf16x2 y8, x8, t2;\nmul.rn.bf16x2 y10, x10, t2;\n"
        "mov.b32 t2, {hi, hi};\nmul.rn.bf16x2 y9, x9, t2;\nmul.rn.bf16x2 y11, x11, t2;\n"
        "mma.sync.aligned.m16n8k16.row.col.f32.bf16.bf16.f32 {d8,d9,d10,d11}, {y8,y9,y10,y11}, {bA0,bA1}, {fz,fz,fz,fz};\ncvt.rn.bf16x2.f32 z4, d9, d8;\n"
        "cvt.rn.bf16x2.f32 z5, d11, d10;\nmov.b32 {lo, hi}, ra3;\nmov.b32 t2, {lo, lo};\nmul.rn.bf16x2 y12, x12, t2;\nmul.rn.bf16x2 y14, x14, t2;\n"
        "mov.b32 t2, {hi, hi};\nmul.rn.bf16x2 y13, x13, t2;\nmul.rn.bf16x2 y15, x15, t2;\n"
        "mma.sync.aligned.m16n8k16.row.col.f32.bf16.bf16.f32 {d12,d13,d14,d15}, {y12,y13,y14,y15}, {bA0,bA1}, {fz,fz,fz,fz};\ncvt.rn.bf16x2.f32 z6, d13, d12;\n"
        "cvt.rn.bf16x2.f32 z7, d15, d14;\nmov.b32 {lo, hi}, ra4;\nmov.b32 t2, {lo, lo};\nmul.rn.bf16x2 y16, x16, t2;\nmul.rn.bf16x2 y18, x18, t2;\n"
        "mov.b32 t2, {hi, hi};\nmul.rn.bf16x2 y17, x17, t2;\nmul.rn.bf16x2 y19, x19, t2;\n"
        "mma.sync.aligned.m16n8k16.row.col.f32.bf16.bf16.f32 {d16,d17,d18,d19}, {y16,y17,y18,y19}, {bA0,bA1}, {fz,fz,fz,fz};\ncvt.rn.bf16x2.f32 z8, d17, d16;\n"
        "cvt.rn.bf16x2.f32 z9, d19, d18;\nmov.b32 {lo, hi}, ra5;\nmov.b32 t2, {lo, lo};\nmul.rn.bf16x2 y20, x20, t2;\nmul.rn.bf16x2 y22, x22, t2;\n"
        "mov.b32 t2, {hi, hi};\nmul.rn.bf16x2 y21, x21, t2;\nmul.rn.bf16x2 y23, x23, t2;\n"
        "mma.sync.aligned.m16n8k16.row.col.f32.bf16.bf16.f32 {d20,d21,d22,d23}, {y20,y21,y22,y23}, {bA0,bA1}, {fz,fz,fz,fz};\ncvt.rn.bf16x2.f32 z10, d21, d20;\n"
        "cvt.rn.bf16x2.f32 z11, d23, d22;\nmov.b32 {lo, hi}, ra6;\nmov.b32 t2, {lo, lo};\nmul.rn.bf16x2 y24, x24, t2;\nmul.rn.bf16x2 y26, x26, t2;\n"
        "mov.b32 t2, {hi, hi};\nmul.rn.bf16x2 y25, x25, t2;\nmul.rn.bf16x2 y27, x27, t2;\n"
        "mma.sync.aligned.m16n8k16.row.col.f32.bf16.bf16.f32 {d24,d25,d26,d27}, {y24,y25,y26,y27}, {bA0,bA1}, {fz,fz,fz,fz};\ncvt.rn.bf16x2.f32 z12, d25, d24;\n"
        "cvt.rn.bf16x2.f32 z13, d27, d26;\nmov.b32 {lo, hi}, ra7;\nmov.b32 t2, {lo, lo};\nmul.rn.bf16x2 y28, x28, t2;\nmul.rn.bf16x2 y30, x30, t2;\n"
        "mov.b32 t2, {hi, hi};\nmul.rn.bf16x2 y29, x29, t2;\nmul.rn.bf16x2 y31, x31, t2;\n"
        "mma.sync.aligned.m16n8k16.row.col.f32.bf16.bf16.f32 {d28,d29,d30,d31}, {y28,y29,y30,y31}, {bA0,bA1}, {fz,fz,fz,fz};\ncvt.rn.bf16x2.f32 z14, d29, d28;\n"
        "cvt.rn.bf16x2.f32 z15, d31, d30;\n@ps2 bra.uni TA2;\n@ps1 bra.uni TA1;\n"
        "TA0:\nadd.rn.bf16x2 h0, h0, z0;\nadd.rn.bf16x2 h1, h1, z1;\nadd.rn.bf16x2 h2, h2, z2;\nadd.rn.bf16x2 h3, h3, z3;\nadd.rn.bf16x2 h4, h4, z4;\n"
        "add.rn.bf16x2 h5, h5, z5;\nadd.rn.bf16x2 h6, h6, z6;\nadd.rn.bf16x2 h7, h7, z7;\nadd.rn.bf16x2 h8, h8, z8;\nadd.rn.bf16x2 h9, h9, z9;\n"
        "add.rn.bf16x2 h10, h10, z10;\nadd.rn.bf16x2 h11, h11, z11;\nadd.rn.bf16x2 h12, h12, z12;\nadd.rn.bf16x2 h13, h13, z13;\nadd.rn.bf16x2 h14, h14, z14;\n"
        "add.rn.bf16x2 h15, h15, z15;\n@prdy bra.uni HB;\nbra.uni WB;\n"
        "TA1:\nadd.rn.bf16x2 h16, h16, z0;\nadd.rn.bf16x2 h17, h17, z1;\nadd.rn.bf16x2 h18, h18, z2;\nadd.rn.bf16x2 h19, h19, z3;\nadd.rn.bf16x2 h20, h20, z4;\n"
        "add.rn.bf16x2 h21, h21, z5;\nadd.rn.bf16x2 h22, h22, z6;\nadd.rn.bf16x2 h23, h23, z7;\nadd.rn.bf16x2 h24, h24, z8;\nadd.rn.bf16x2 h25, h25, z9;\n"
        "add.rn.bf16x2 h26, h26, z10;\nadd.rn.bf16x2 h27, h27, z11;\nadd.rn.bf16x2 h28, h28, z12;\nadd.rn.bf16x2 h29, h29, z13;\nadd.rn.bf16x2 h30, h30, z14;\n"
        "add.rn.bf16x2 h31, h31, z15;\n@prdy bra.uni HB;\nbra.uni WB;\n"
        "TA2:\nadd.rn.bf16x2 h32, h32, z0;\nadd.rn.bf16x2 h33, h33, z1;\nadd.rn.bf16x2 h34, h34, z2;\nadd.rn.bf16x2 h35, h35, z3;\nadd.rn.bf16x2 h36, h36, z4;\n"
        "add.rn.bf16x2 h37, h37, z5;\nadd.rn.bf16x2 h38, h38, z6;\nadd.rn.bf16x2 h39, h39, z7;\nadd.rn.bf16x2 h40, h40, z8;\nadd.rn.bf16x2 h41, h41, z9;\n"
        "add.rn.bf16x2 h42, h42, z10;\nadd.rn.bf16x2 h43, h43, z11;\nadd.rn.bf16x2 h44, h44, z12;\nadd.rn.bf16x2 h45, h45, z13;\nadd.rn.bf16x2 h46, h46, z14;\n"
        "add.rn.bf16x2 h47, h47, z15;\n@prdy bra.uni HB;\nbra.uni WB;\n"
        "HB:\nmad.lo.u32 xb, id, 64, %49;\ncvt.u16.u32 i16, id;\natom.shared.add.u32 pos, [%50+%59], %52;\n"
        "ldmatrix.sync.aligned.m8n8.x4.trans.shared.b16 {x0,x1,x2,x3}, [xb];\nxor.b32 t1, xb, 16;\n"
        "ldmatrix.sync.aligned.m8n8.x4.trans.shared.b16 {x4,x5,x6,x7}, [t1];\nxor.b32 t1, xb, 32;\n"
        "ldmatrix.sync.aligned.m8n8.x4.trans.shared.b16 {x8,x9,x10,x11}, [t1];\nxor.b32 t1, xb, 48;\n"
        "ldmatrix.sync.aligned.m8n8.x4.trans.shared.b16 {x12,x13,x14,x15}, [t1];\nxor.b32 t1, xb, 64;\n"
        "ldmatrix.sync.aligned.m8n8.x4.trans.shared.b16 {x16,x17,x18,x19}, [t1];\nxor.b32 t1, xb, 80;\n"
        "ldmatrix.sync.aligned.m8n8.x4.trans.shared.b16 {x20,x21,x22,x23}, [t1];\nxor.b32 t1, xb, 96;\n"
        "ldmatrix.sync.aligned.m8n8.x4.trans.shared.b16 {x24,x25,x26,x27}, [t1];\nxor.b32 t1, xb, 112;\n"
        "ldmatrix.sync.aligned.m8n8.x4.trans.shared.b16 {x28,x29,x30,x31}, [t1];\nst.volatile.shared.u16 [pos], i16;\nand.b32 t0, v, 268435456;\n"
        "setp.ne.u32 ps1, t0, 0;\nvote.sync.any.pred ps1, ps1, 0xffffffff;\nand.b32 t0, v, 536870912;\nsetp.ne.u32 ps2, t0, 0;\n"
        "vote.sync.any.pred ps2, ps2, 0xffffffff;\nshfl.sync.idx.b32 v, kept, %51, 0x1f, 0xffffffff;\nor.b32 t3, %51, 4;\n"
        "shfl.sync.idx.b32 vB, kept, t3, 0x1f, 0xffffffff;\nshr.u32 bar, v, 1;\nand.b32 bar, bar, 0xff8;\nmbarrier.test_wait.parity.shared.b64 p, [bar+%58], 0;\n"
        "lop3.b32 ida, v, %51, 0x1fff, 0xe4;\nld.volatile.shared.u16 id, [ida+%57];\nvote.sync.all.pred prdy, p, 0xffffffff;\nmov.b32 {lo, hi}, rb0;\n"
        "mov.b32 t2, {lo, lo};\nmul.rn.bf16x2 y0, x0, t2;\nmul.rn.bf16x2 y2, x2, t2;\nmov.b32 t2, {hi, hi};\nmul.rn.bf16x2 y1, x1, t2;\n"
        "mul.rn.bf16x2 y3, x3, t2;\nmma.sync.aligned.m16n8k16.row.col.f32.bf16.bf16.f32 {d0,d1,d2,d3}, {y0,y1,y2,y3}, {bB0,bB1}, {fz,fz,fz,fz};\n"
        "cvt.rn.bf16x2.f32 z0, d1, d0;\ncvt.rn.bf16x2.f32 z1, d3, d2;\nmov.b32 {lo, hi}, rb1;\nmov.b32 t2, {lo, lo};\nmul.rn.bf16x2 y4, x4, t2;\n"
        "mul.rn.bf16x2 y6, x6, t2;\nmov.b32 t2, {hi, hi};\nmul.rn.bf16x2 y5, x5, t2;\nmul.rn.bf16x2 y7, x7, t2;\n"
        "mma.sync.aligned.m16n8k16.row.col.f32.bf16.bf16.f32 {d4,d5,d6,d7}, {y4,y5,y6,y7}, {bB0,bB1}, {fz,fz,fz,fz};\ncvt.rn.bf16x2.f32 z2, d5, d4;\n"
        "cvt.rn.bf16x2.f32 z3, d7, d6;\nmov.b32 {lo, hi}, rb2;\nmov.b32 t2, {lo, lo};\nmul.rn.bf16x2 y8, x8, t2;\nmul.rn.bf16x2 y10, x10, t2;\n"
        "mov.b32 t2, {hi, hi};\nmul.rn.bf16x2 y9, x9, t2;\nmul.rn.bf16x2 y11, x11, t2;\n"
        "mma.sync.aligned.m16n8k16.row.col.f32.bf16.bf16.f32 {d8,d9,d10,d11}, {y8,y9,y10,y11}, {bB0,bB1}, {fz,fz,fz,fz};\ncvt.rn.bf16x2.f32 z4, d9, d8;\n"
        "cvt.rn.bf16x2.f32 z5, d11, d10;\nmov.b32 {lo, hi}, rb3;\nmov.b32 t2, {lo, lo};\nmul.rn.bf16x2 y12, x12, t2;\nmul.rn.bf16x2 y14, x14, t2;\n"
        "mov.b32 t2, {hi, hi};\nmul.rn.bf16x2 y13, x13, t2;\nmul.rn.bf16x2 y15, x15, t2;\n"
        "mma.sync.aligned.m16n8k16.row.col.f32.bf16.bf16.f32 {d12,d13,d14,d15}, {y12,y13,y14,y15}, {bB0,bB1}, {fz,fz,fz,fz};\ncvt.rn.bf16x2.f32 z6, d13, d12;\n"
        "cvt.rn.bf16x2.f32 z7, d15, d14;\nmov.b32 {lo, hi}, rb4;\nmov.b32 t2, {lo, lo};\nmul.rn.bf16x2 y16, x16, t2;\nmul.rn.bf16x2 y18, x18, t2;\n"
        "mov.b32 t2, {hi, hi};\nmul.rn.bf16x2 y17, x17, t2;\nmul.rn.bf16x2 y19, x19, t2;\n"
        "mma.sync.aligned.m16n8k16.row.col.f32.bf16.bf16.f32 {d16,d17,d18,d19}, {y16,y17,y18,y19}, {bB0,bB1}, {fz,fz,fz,fz};\ncvt.rn.bf16x2.f32 z8, d17, d16;\n"
        "cvt.rn.bf16x2.f32 z9, d19, d18;\nmov.b32 {lo, hi}, rb5;\nmov.b32 t2, {lo, lo};\nmul.rn.bf16x2 y20, x20, t2;\nmul.rn.bf16x2 y22, x22, t2;\n"
        "mov.b32 t2, {hi, hi};\nmul.rn.bf16x2 y21, x21, t2;\nmul.rn.bf16x2 y23, x23, t2;\n"
        "mma.sync.aligned.m16n8k16.row.col.f32.bf16.bf16.f32 {d20,d21,d22,d23}, {y20,y21,y22,y23}, {bB0,bB1}, {fz,fz,fz,fz};\ncvt.rn.bf16x2.f32 z10, d21, d20;\n"
        "cvt.rn.bf16x2.f32 z11, d23, d22;\nmov.b32 {lo, hi}, rb6;\nmov.b32 t2, {lo, lo};\nmul.rn.bf16x2 y24, x24, t2;\nmul.rn.bf16x2 y26, x26, t2;\n"
        "mov.b32 t2, {hi, hi};\nmul.rn.bf16x2 y25, x25, t2;\nmul.rn.bf16x2 y27, x27, t2;\n"
        "mma.sync.aligned.m16n8k16.row.col.f32.bf16.bf16.f32 {d24,d25,d26,d27}, {y24,y25,y26,y27}, {bB0,bB1}, {fz,fz,fz,fz};\ncvt.rn.bf16x2.f32 z12, d25, d24;\n"
        "cvt.rn.bf16x2.f32 z13, d27, d26;\nmov.b32 {lo, hi}, rb7;\nmov.b32 t2, {lo, lo};\nmul.rn.bf16x2 y28, x28, t2;\nmul.rn.bf16x2 y30, x30, t2;\n"
        "mov.b32 t2, {hi, hi};\nmul.rn.bf16x2 y29, x29, t2;\nmul.rn.bf16x2 y31, x31, t2;\n"
        "mma.sync.aligned.m16n8k16.row.col.f32.bf16.bf16.f32 {d28,d29,d30,d31}, {y28,y29,y30,y31}, {bB0,bB1}, {fz,fz,fz,fz};\ncvt.rn.bf16x2.f32 z14, d29, d28;\n"
        "cvt.rn.bf16x2.f32 z15, d31, d30;\n@ps2 bra.uni TB2;\n@ps1 bra.uni TB1;\n"
        "TB0:\nadd.rn.bf16x2 h0, h0, z0;\nadd.rn.bf16x2 h1, h1, z1;\nadd.rn.bf16x2 h2, h2, z2;\nadd.rn.bf16x2 h3, h3, z3;\nadd.rn.bf16x2 h4, h4, z4;\n"
        "add.rn.bf16x2 h5, h5, z5;\nadd.rn.bf16x2 h6, h6, z6;\nadd.rn.bf16x2 h7, h7, z7;\nadd.rn.bf16x2 h8, h8, z8;\nadd.rn.bf16x2 h9, h9, z9;\n"
        "add.rn.bf16x2 h10, h10, z10;\nadd.rn.bf16x2 h11, h11, z11;\nadd.rn.bf16x2 h12, h12, z12;\nadd.rn.bf16x2 h13, h13, z13;\nadd.rn.bf16x2 h14, h14, z14;\n"
        "add.rn.bf16x2 h15, h15, z15;\nbra.uni RW;\n"
        "TB1:\nadd.rn.bf16x2 h16, h16, z0;\nadd.rn.bf16x2 h17, h17, z1;\nadd.rn.bf16x2 h18, h18, z2;\nadd.rn.bf16x2 h19, h19, z3;\nadd.rn.bf16x2 h20, h20, z4;\n"
        "add.rn.bf16x2 h21, h21, z5;\nadd.rn.bf16x2 h22, h22, z6;\nadd.rn.bf16x2 h23, h23, z7;\nadd.rn.bf16x2 h24, h24, z8;\nadd.rn.bf16x2 h25, h25, z9;\n"
        "add.rn.bf16x2 h26, h26, z10;\nadd.rn.bf16x2 h27, h27, z11;\nadd.rn.bf16x2 h28, h28, z12;\nadd.rn.bf16x2 h29, h29, z13;\nadd.rn.bf16x2 h30, h30, z14;\n"
        "add.rn.bf16x2 h31, h31, z15;\nbra.uni RW;\n"
        "TB2:\nadd.rn.bf16x2 h32, h32, z0;\nadd.rn.bf16x2 h33, h33, z1;\nadd.rn.bf16x2 h34, h34, z2;\nadd.rn.bf16x2 h35, h35, z3;\nadd.rn.bf16x2 h36, h36, z4;\n"
        "add.rn.bf16x2 h37, h37, z5;\nadd.rn.bf16x2 h38, h38, z6;\nadd.rn.bf16x2 h39, h39, z7;\nadd.rn.bf16x2 h40, h40, z8;\nadd.rn.bf16x2 h41, h41, z9;\n"
        "add.rn.bf16x2 h42, h42, z10;\nadd.rn.bf16x2 h43, h43, z11;\nadd.rn.bf16x2 h44, h44, z12;\nadd.rn.bf16x2 h45, h45, z13;\nadd.rn.bf16x2 h46, h46, z14;\n"
        "add.rn.bf16x2 h47, h47, z15;\nbra.uni RW;\n"
        "WA:\nsetp.ge.u32 p, v, 805306368;\nvote.sync.all.pred p, p, 0xffffffff;\n@p bra.uni DONE;\nmov.b32 n, 0;\nshr.u32 t2, v, 1;\nand.b32 t2, t2, 0xff8;\n"
        "WA3:\nmbarrier.try_wait.parity.shared.b64 p, [t2+%58], 0;\nvote.sync.all.pred p, p, 0xffffffff;\nadd.u32 n, n, 1;\nsetp.lt.and.u32 q, n, 1000000, !p;\n"
        "@q bra.uni WA3;\nlop3.b32 ida, v, %51, 0x1fff, 0xe4;\nld.volatile.shared.u16 id, [ida+%57];\nbra.uni HA;\n"
        "WB:\nsetp.ge.u32 p, v, 805306368;\nvote.sync.all.pred p, p, 0xffffffff;\n@p bra.uni DONE;\nmov.b32 n, 0;\nshr.u32 t2, v, 1;\nand.b32 t2, t2, 0xff8;\n"
        "WB3:\nmbarrier.try_wait.parity.shared.b64 p, [t2+%58], 0;\nvote.sync.all.pred p, p, 0xffffffff;\nadd.u32 n, n, 1;\nsetp.lt.and.u32 q, n, 1000000, !p;\n"
        "@q bra.uni WB3;\nlop3.b32 ida, v, %51, 0x1fff, 0xe4;\nld.volatile.shared.u16 id, [ida+%57];\nbra.uni HB;\n"
        "DONE:\nmov.b32 %0, h0;\nmov.b32 %1, h1;\nmov.b32 %2, h2;\nmov.b32 %3, h3;\nmov.b32 %4, h4;\nmov.b32 %5, h5;\nmov.b32 %6, h6;\nmov.b32 %7, h7;\n"
        "mov.b32 %8, h8;\nmov.b32 %9, h9;\nmov.b32 %10, h10;\nmov.b32 %11, h11;\nmov.b32 %12, h12;\nmov.b32 %13, h13;\nmov.b32 %14, h14;\nmov.b32 %15, h15;\n"
        "mov.b32 %16, h16;\nmov.b32 %17, h17;\nmov.b32 %18, h18;\nmov.b32 %19, h19;\nmov.b32 %20, h20;\nmov.b32 %21, h21;\nmov.b32 %22, h22;\nmov.b32 %23, h23;\n"
        "mov.b32 %24, h24;\nmov.b32 %25, h25;\nmov.b32 %26, h26;\nmov.b32 %27, h27;\nmov.b32 %28, h28;\nmov.b32 %29, h29;\nmov.b32 %30, h30;\nmov.b32 %31, h31;\n"
        "mov.b32 %32, h32;\nmov.b32 %33, h33;\nmov.b32 %34, h34;\nmov.b32 %35, h35;\nmov.b32 %36, h36;\nmov.b32 %37, h37;\nmov.b32 %38, h38;\nmov.b32 %39, h39;\n"
        "mov.b32 %40, h40;\nmov.b32 %41, h41;\nmov.b32 %42, h42;\nmov.b32 %43, h43;\nmov.b32 %44, h44;\nmov.b32 %45, h45;\nmov.b32 %46, h46;\nmov.b32 %47, h47;\n"
        "}\n"
        : "=r"(pk[0]), "=r"(pk[1]), "=r"(pk[2]), "=r"(pk[3]), "=r"(pk[4]), "=r"(pk[5]), "=r"(pk[6]), "=r"(pk[7]), "=r"(pk[8]), "=r"(pk[9]),
          "=r"(pk[10]), "=r"(pk[11]), "=r"(pk[12]), "=r"(pk[13]), "=r"(pk[14]), "=r"(pk[15]), "=r"(pk[16]), "=r"(pk[17]), "=r"(pk[18]), "=r"(pk[19]),
          "=r"(pk[20]), "=r"(pk[21]), "=r"(pk[22]), "=r"(pk[23]), "=r"(pk[24]), "=r"(pk[25]), "=r"(pk[26]), "=r"(pk[27]), "=r"(pk[28]), "=r"(pk[29]),
          "=r"(pk[30]), "=r"(pk[31]), "=r"(pk[32]), "=r"(pk[33]), "=r"(pk[34]), "=r"(pk[35]), "=r"(pk[36]), "=r"(pk[37]), "=r"(pk[38]), "=r"(pk[39]),
          "=r"(pk[40]), "=r"(pk[41]), "=r"(pk[42]), "=r"(pk[43]), "=r"(pk[44]), "=r"(pk[45]), "=r"(pk[46]), "=r"(pk[47])
        : "r"(olp), "r"(xa), "r"(ln), "r"(lc), "r"(linc), "r"(lt), "l"(ea), "l"(sh),
          "n"(sb + SM_REC), "n"(sb + SM_R), "n"(sb + SM_BAR), "n"(sb + SM_CTR),
          "r"(w[0]), "r"(w[1]), "r"(w[2]), "r"(w[3]), "r"(w[4]), "r"(w[5]), "r"(w[6]), "r"(w[7]), "r"(w[8]), "r"(w[9]), "r"(w[10]), "r"(w[11]),
          "r"(w[12]), "r"(w[13]), "r"(w[14]), "r"(w[15]), "r"(w[16]), "r"(w[17]), "r"(w[18]), "r"(w[19]), "r"(w[20]), "r"(w[21]), "r"(w[22]),
          "r"(w[23]), "r"(w[24]), "r"(w[25]), "r"(w[26]), "r"(w[27]), "r"(w[28]), "r"(w[29]), "r"(w[30]), "r"(w[31]), "r"(w[32]), "r"(w[33]),
          "r"(w[34]), "r"(w[35])
        : "memory");
}

__device__ __forceinline__ void wf_done() {
    asm volatile("fence.proxy.async.global;\nred.release.gpu.global.add.u32 [%0], 1;" ::"l"(&g_wfcnt) : "memory");
}

template <int NS>
__device__ __forceinline__ void consumer(const __nv_bfloat16* __restrict__ sh,
                                         const __nv_bfloat16* __restrict__ ea, __nv_bfloat16* __restrict__ out, int N, int npb) {
    uint32_t pk[NS * 16];
    {
        const int lane = threadIdx.x & 31, warp = threadIdx.x >> 5;
        const int mi = lane >> 3, r = lane & 7, j = r >> 1;
        const int u = 2 * ((mi >> 1) ^ (j >> 1)) + (r & 1), ph = (j ^ (j >> 1)) & 1;
        uint32_t w[36];
        {
            const uint32_t a = sb + SC_WR + (4 * j + (r & 1) + (mi & 2)) * 272 + (mi & 1) * 128;
#pragma unroll
            for (int c = 0; c < 8; c++)
                asm volatile("ldmatrix.sync.aligned.m8n8.x4.trans.shared.b16 {%0,%1,%2,%3}, [%4];"
                             : "=r"(w[4 * c]), "=r"(w[4 * c + 1]), "=r"(w[4 * c + 2]), "=r"(w[4 * c + 3]) : "r"(a + c * 16) : "memory");
            const uint32_t ca = sb + SC_CG + (lane & 2) * 8 + ((lane >> 2) & 3) * 2;
#pragma unroll
            for (int k = 0; k < 4; k++) {
                const uint32_t f = lds16(ca + 32 * k) | (lds16(ca + 32 * k + 8) << 16);
                w[32 + k] = (lane & 1) == (lane >> 4) ? f : 0;
            }
            asm volatile("fence.proxy.async.shared::cta;\nbar.sync 2, %0;" ::"n"(NCW * 32) : "memory");
            if (threadIdx.x < WSL) sts16(sb + SM_R + 0x2000 + (4 + SP - WSL + lane) * 4, (sb + SC_WR) / 64 + 1 + lane * 16);
        }
        if ((threadIdx.x >> 2) == WFT && blockIdx.x < 128) wf_done();
        if (threadIdx.x == NCW * 32 - 1) {
            const uint32_t target = lds32(sb + SM_MISC + 16);
            for (int n = 0; n < 1000000; n++) {
                uint32_t c;
                asm volatile("ld.acquire.gpu.global.u32 %0, [%1];" : "=r"(c) : "l"(&g_wfcnt) : "memory");
                if ((int)(c - target) >= 0) break;
            }
            asm volatile("st.release.cta.shared.u32 [%0], 1;" ::"r"(sb + SM_MISC + 24) : "memory");
        }
        __syncwarp();
        const int L = 2 * u + (mi & 1);
        const uint32_t xa = __shfl_sync(0xffffffffu, L * 128 + (((L + ph) & 7) << 4) - 64, lane);
        const uint32_t ln = __shfl_sync(0xffffffffu, lane * 16 + (lane >> 3) * 4, lane);
        const uint32_t lc = __shfl_sync(0xffffffffu, j * 8 + (1 << (lane & 1)) + (ph << 13), lane);
        const uint32_t linc = __shfl_sync(0xffffffffu, (lane & 0x19) ? 0 : 8, lane);
        const uint32_t lt = __shfl_sync(0xffffffffu, lane & 3, lane);
        const uint32_t olp = sb + SM_OL + warp * (OLN * 4) + (lane & 4);
        if constexpr (NS == 4) consume4(pk, w, olp, xa, ln, lc, linc, lt, ea, sh);
        else consume3(pk, w, olp, xa, ln, lc, linc, lt, ea, sh);
    }
    TLMAX(10);
    const int tid = thread_id(), lane = tid & 31, warp = tid >> 5, g = lane >> 2, t = lane & 3;
    const uint32_t wc = lds32(sb + SM_MISC + 12) + 1;
    const uint32_t inv = lds32(sb + SM_INV + warp * 4);
    const int node0 = cta_id() * npb, nnodes = min(npb, N - node0);
    uint4* op[NS];
    uint32_t on[NS];
#pragma unroll
    for (int s = 0; s < NS; s++) {
        const int nl = ((inv >> (8 * s)) & 255) + (g >> 2) * 40;
        op[s] = (uint4*)(out + ((size_t)(node0 + nl) * 4 + (g & 3)) * 128 + 8 * t);
        on[s] = nl < nnodes;
    }
    if constexpr (NS == 4) project4(pk, sb + SM_R + wc * 16, sb + SM_BAR + wc * 8, op, on);
    else project3(pk, sb + SM_R + wc * 16, sb + SM_BAR + wc * 8, op, on);
}

#define TLHI "shl.b32 d, tb, 16;\n"
#define RAOFF ((threadIdx.x & 96) >> 1)
#define UNPACK(v) "shl.b32 d, " #v ", 6;\nand.b32 d, d, 0x3ff80;\nshr.s32 r, " #v ", 13;\n"
#define XSTR(x) XSTR2(x)
#define XSTR2(x) #x
__device__ __forceinline__ void producer(const CUtensorMap* tmx, int pw) {
    const uint32_t nch = lds32(sb + SM_MISC + 12);
    if (elect()) {
        asm volatile(
            "{\n.reg .pred p, q, lead;\n.reg .b32 ra, oa, off, poff, due, now, a<4>, b<4>, d, r, z<8>, bar<4>, t, n, tb, ta, prev;\n"
            ".reg .b64 lg, t64;\n"
            "mov.b32 ta, %5;\nld.volatile.shared.v4.b32 {z0,z1,z2,z3}, [ta+32];\nld.volatile.shared.v4.b32 {z4,z5,z6,z7}, [ta+32];\n"
            "mov.b32 ra, %9;\nmad.lo.u32 t, %0, 8, %10;\n"
            "add.u32 bar0, t, z0;\n"
            "mov.b32 n, 0;\nld.volatile.shared.b32 prev, [ta];\nmov.b32 poff, 1000000;\nsetp.eq.u32 lead, %0, 0;\n"
            "mov.u32 due, %%globaltimer_lo;\n"
            "setp.gt.u32 p, ra, %1;\n@p bra.uni END;\n"
            "GO:\n"
            "ld.volatile.shared.v4.b32 {a0,a1,a2,a3}, [ra];\nld.volatile.shared.v4.b32 {b0,b1,b2,b3}, [ra+0x2000];\n"
            "shr.u32 oa, ra, 2;\nld.volatile.shared.b32 off, [oa+%11];\nld.volatile.shared.b32 tb, [ta];\n"
            "mov.u32 now, %%globaltimer_lo;\n"
            "lop3.b32 t, a0, a1, a2, 0x80;\nlop3.b32 d, a3, b0, b1, 0x80;\nlop3.b32 t, t, d, b2, 0x80;\nand.b32 t, t, b3;\nand.b32 t, t, 1;\n"
            "setp.eq.u32 p, t, 0;\n"
            "@p bra.uni BACK;\n"
            "add.u32 bar0, bar0, 32;\nmbarrier.arrive.expect_tx.shared.b64 _, [bar0], 8192;\n"
            "add.u32 ra, ra, 64;\nadd.u32 due, off, tb;\nsub.u32 t, due, now;\nsetp.le.and.u32 q, ra, %1, !lead;\nsetp.le.and.s32 q, t, %2, q;\n"
            UNPACK(a0)
            "cp.async.bulk.tensor.2d.shared::cluster.global.mbarrier::complete_tx::bytes [d], [%3, {z0, r}], [bar0];\n"
            UNPACK(b0)
            "cp.async.bulk.tensor.2d.shared::cluster.global.mbarrier::complete_tx::bytes [d], [%3, {z1, r}], [bar0];\n"
            UNPACK(a1)
            "cp.async.bulk.tensor.2d.shared::cluster.global.mbarrier::complete_tx::bytes [d], [%3, {z2, r}], [bar0];\n"
            UNPACK(b1)
            "cp.async.bulk.tensor.2d.shared::cluster.global.mbarrier::complete_tx::bytes [d], [%3, {z3, r}], [bar0];\n"
            UNPACK(a2)
            "cp.async.bulk.tensor.2d.shared::cluster.global.mbarrier::complete_tx::bytes [d], [%3, {z4, r}], [bar0];\n"
            UNPACK(b2)
            "cp.async.bulk.tensor.2d.shared::cluster.global.mbarrier::complete_tx::bytes [d], [%3, {z5, r}], [bar0];\n"
            UNPACK(a3)
            "cp.async.bulk.tensor.2d.shared::cluster.global.mbarrier::complete_tx::bytes [d], [%3, {z6, r}], [bar0];\n"
            UNPACK(b3)
            "cp.async.bulk.tensor.2d.shared::cluster.global.mbarrier::complete_tx::bytes [d], [%3, {z7, r}], [bar0];\n"
            "@q bra.uni GO;\n"
            "setp.gt.u32 p, ra, %1;\n@p bra.uni END;\n@!lead bra.uni WAIT0;\n"
            "add.u32 d, ta, 16;\ncp.async.bulk.shared::cluster.global.mbarrier::complete_tx::bytes [ta], [%4], 16, [d];\n"
            "sub.u32 r, now, poff;\nmov.b32 poff, off;\nsub.u32 d, prev, tb;\nmov.b32 prev, r;\nsub.u32 r, r, tb;\nmin.s32 d, d, r;\n"
            "setp.le.s32 p, d, %6;\n@p bra.uni NOSLIP;\n"
            "setp.lt.u32 p, ra, %8;\n@p bra.uni NOSLIP;\nadd.u32 r, ra, " XSTR(SLIPEND) ";\nsetp.gt.u32 p, r, %1;\n@p bra.uni NOSLIP;\n"
            "ld.volatile.shared.b64 t64, [ta];\ncvt.u32.u64 r, t64;\nsub.u32 r, tb, r;\nsub.u32 d, d, %7;\nadd.s32 d, d, r;\n"
            "cvt.s64.s32 lg, d;\nadd.u64 t64, t64, lg;\n"
            "red.relaxed.gpu.global.max.u64 [%4], t64;\n"
            "NOSLIP:\n"
            "setp.le.s32 p, t, %2;\n@p bra.uni GO;\n"
            "WAIT0:\n"
            "ld.volatile.shared.b32 tb, [ta];\nld.volatile.shared.b32 off, [oa+%11];\nmov.u32 now, %%globaltimer_lo;\nadd.u32 due, tb, off;\nsub.u32 t, due, now;\n"
            "setp.le.s32 p, t, %12;\n@p bra.uni GO;\n"
            "setp.gt.s32 p, t, " XSTR(SPINT) ";\n@p nanosleep.u32 32;\nbra.uni WAIT0;\n"
            "BACK:\n"
            "nanosleep.u32 32;\nadd.u32 n, n, 1;\nsetp.lt.u32 p, n, 1000000;\n@p bra.uni GO;\n"
            "END:\n}" ::"r"(pw),
            "r"(sb + SM_R + nch * 16), "n"(AHEAD + EARLY), "l"(tmx), "l"(&g_sync), "n"(sb + SM_MISC + 32), "n"(SLIPTH), "n"(SLIPSUB),
            "n"(sb + SM_R + SLIPFROM * 16), "r"(sb + SM_R + 16 + RAOFF), "n"(sb + SM_BAR + 8 - 32),
            "n"(sb + SM_OFF + 16 - (sb + SM_R) / 4), "n"(EARLY)
            : "memory");
        const uint32_t ra = sb + SM_R + (nch + 1 + pw) * 16, bar = sb + SM_BAR + (nch + 1 + pw) * 8;
        uint4 a, b;
        for (int n = 0; n < 1000000; n++) {
            uint32_t c;
            asm volatile("ld.acquire.cta.shared.u32 %0, [%1];" : "=r"(c) : "r"(sb + SM_MISC + 24) : "memory");
            a = lds128(ra), b = lds128(ra + 0x2000);
            if (a.x & a.y & a.z & a.w & b.x & b.y & b.z & b.w & c) break;
        }
        asm volatile("fence.proxy.async.global;" ::: "memory");
        asm volatile("mbarrier.arrive.expect_tx.shared.b64 _, [%0], 8192;" ::"r"(bar) : "memory");
        const uint32_t c[8] = {a.x, a.y, a.z, a.w, b.x, b.y, b.z, b.w};
#pragma unroll
        for (int i = 0; i < 8; i++)
            asm volatile("cp.async.bulk.shared::cluster.global.mbarrier::complete_tx::bytes [%0], [%1], 1024, [%2];" ::"r"(
                             (c[i] & 0xffe) << 6),
                         "l"(g_wf + (pw * 8 + i) * 64), "r"(bar)
                         : "memory");
    }
}

#define BARINIT(w, n)                                                                                              \
    if (elect()) {                                                                                                 \
        _Pragma("unroll") for (int k = 0; k < (NBAR + n - 1) / n; k++)                                             \
            asm volatile("mbarrier.init.shared.b64 [%0], 1;" ::"r"(sb + SM_BAR + ((w) * ((NBAR + n - 1) / n) + k) * 8)); \
        asm volatile("fence.mbarrier_init.release.cluster;" ::: "memory");                                         \
    }                                                                                                              \
    __syncwarp();

__global__ void __launch_bounds__(NT, 1)
main_kernel(const __grid_constant__ CUtensorMap tmx, const __nv_bfloat16* __restrict__ x, const int* __restrict__ src,
            const int* __restrict__ dst, const __nv_bfloat16* __restrict__ sh, const __nv_bfloat16* __restrict__ ea,
            const __nv_bfloat16* __restrict__ cg, const __nv_bfloat16* __restrict__ wr,
            const __nv_bfloat16* __restrict__ wout, __nv_bfloat16* __restrict__ out, int N, int E, int npb,
            unsigned npb_magic, int chunk, unsigned bkm, int tau, int ramp, int rampn, int tdelay, unsigned polld, int spr, int sprn) {
    extern __shared__ __align__(1024) unsigned char smem[];
    if (s2u(smem) != sb) __trap();
    const int tid = threadIdx.x, lane = tid & 31;
    const int warp = __shfl_sync(0xffffffffu, tid >> 5, 0);
    const int nbins = gridDim.x;
    bool fast = chunk > 0;
    TLSTAMP(0);
    if (fast) {
        const int e0 = blockIdx.x * chunk + tid, left = min(E, (int)(blockIdx.x + 1) * chunk) - e0;
        uint32_t pd[KE], ps[KE];
        {
            const int* dp = dst + e0;
            const int* sp = src + e0;
#pragma unroll
            for (int k = 0; k < KE; k++) {
                pd[k] = nbins * npb, ps[k] = 0;
                asm volatile("{\n.reg .pred p;\nsetp.gt.s32 p, %4, %5;\n@p ld.global.nc.u32 %0, [%2];\n@p ld.global.nc.u32 %1, [%3];\n}"
                             : "+r"(pd[k]), "+r"(ps[k]) : "l"(dp + k * NT), "l"(sp + k * NT), "r"(left), "r"(k * NT));
            }
        }
        uint32_t epoch = 0;
        if (tid == NT - 1) asm volatile("ld.relaxed.gpu.global.u32 %0, [%1];" : "=r"(epoch) : "l"(&g_epoch) : "memory");
        uint4 wv, wo[3];
        const bool wrow = (tid >> 2) == WFT && blockIdx.x < 128;
        {
            const uint4* wp = tid < 256 ? (const uint4*)wr + tid
                              : wrow    ? (const uint4*)(wout + blockIdx.x * 128 + (tid & 3) * 32)
                                        : (const uint4*)cg + (tid & 7);
            if (tid < 264 || wrow) wv = __ldg(wp);
            if (wrow) wo[0] = __ldg(wp + 1), wo[1] = __ldg(wp + 2), wo[2] = __ldg(wp + 3);
        }
        const uint32_t t16 = sb + tid * 16;
        const uint32_t sa = sb + SC_STG + (tid >> 4) * CP + (tid & 15) * 16;
        const uint32_t none = (40u << 23) + (lane << 16);
        const uint32_t pade = min(blockIdx.x * chunk, E - 1) << 13;
        const bool fifth = warp * 2 + 128 < nbins;
#pragma unroll
        for (int k = 0; k < 5; k++)
            if (k < 4 || fifth) sts128(sa + k * 32 * CP, none, 0, none, 0);
        if (tid < 160) sts32(sb + SC_CNT + tid * 4, 8);
        if (tid < NBAR) sts32(sb + SM_OFF + tid * 4, 1000000);
#pragma unroll
        for (int k = 0; k < 4; k++) sts128(t16 + SC_TABB + k * NT * 16, 0, 0, 0, 0);
#pragma unroll
        for (int k = 0; k < 3; k++)
            sts128(t16 + SC_TMP + k * NT * 16, (tid + blockIdx.x) & 63, pade, (tid + blockIdx.x + 32) & 63, pade);
        if (tid < RP / 4) {
            uint32_t c[4], d[4];
#pragma unroll
            for (int i = 0; i < 4; i++) {
                const uint32_t k = tid * 4 - 4 + i;
                c[i] = d[i] = 0xc0000000u;
                if (warp == 0 && k < SP) c[i] += sb / 64 + 1 + k * 16;
                if (warp == 0 && k < SP - WSL) d[i] = c[i] + (SP * 1024 + PH) / 64;
            }
            static_assert(SP + 4 <= 128, "first warp");
            sts128(t16 + SM_R, c[0], c[1], c[2], c[3]);
            sts128(t16 + SM_R + 0x2000, d[0], d[1], d[2], d[3]);
        }
        constexpr uint32_t OLEND = (7u << 28) | ((RECN - 4) * 4);
        if (tid < NCW * OLN / 4) sts128(t16 + SM_OL, OLEND, OLEND, OLEND, OLEND);
        if (warp == 12) {
            sts32(sb + SM_CTR + lane * 16 + (lane >> 3) * 4,
                  sb + SM_R + ((lane & 0x19) ? (RP - 1) * 4 : (4 + SP) * 4 + (((lane >> 1) ^ (lane >> 2)) & 1) * 0x2000 + (lane & 4)));
            if (lane < 3) sts32(sb + SM_MISC + (lane ? 16 + lane * 4 : 4), 0);
            if (lane == 8) sts128(sb + SM_REC + (RECN - 4) * 4, pade, pade, pade, pade), sts128(sb + SM_MISC + 64, 0, 0, 0, 0);
            if (lane == 9) asm volatile("prefetch.tensormap [%0];" ::"l"(&tmx) : "memory");
        }
        __syncthreads();
        TLSTAMP(1);

        {
            uint32_t b[KE], r[KE];
#pragma unroll
            for (int k = 0; k < KE; k++) {
                b[k] = __umulhi(pd[k], npb_magic);
                r[k] = atoms_add(sb + SC_CNT + b[k] * 4, 8);
            }
            if (tid == NT - 1) {
                sts32(sb + SM_MISC + 8, (epoch % 2047 + 1) << 2);
                asm volatile("{\n.reg .b64 t;\nmov.u64 t, %%globaltimer;\nred.relaxed.gpu.global.max.u64 [%0], t;\n"
                             "red.relaxed.gpu.global.add.u32 [%0+8], 1;\n}" ::"l"(&g_sync) : "memory");
            }
            __syncwarp();
            const uint32_t et = (e0 << 13) + 1;
#pragma unroll
            for (int k = 0; k < KE; k++) {
                asm volatile(
                    "{\n.reg .pred p;\n.reg .b32 d, t, u;\nmad.lo.u32 d, %1, %3, %0;\nsetp.ge.u32 p, d, 40;\nmul.hi.u32 t, %2, %4;\n"
                    "mad.lo.u32 t, d, 128, t;\nmad.lo.u32 t, t, 65536, %2;\n@p add.u32 t, t, %7;\nmov.b32 u, %5;\n@p add.u32 u, u, 1;\n"
                    "min.u32 d, %6, 376;\nmad.lo.u32 d, %1, %9, d;\nst.shared.v2.b32 [d+%8], {t, u};\n}" ::"r"(pd[k]),
                    "r"(b[k]), "r"(ps[k]), "r"(-npb), "r"(bkm << 7), "r"(et + (k * NT << 13)), "r"(r[k]), "n"(-(40 << 23)), "n"(sb + SC_STG),
                    "n"(CP)
                    : "memory");
            }
        }
        if (tid < 264) sts128(sb + SC_WR + (tid >> 4) * 272 + (tid & 15) * 16, wv.x, wv.y, wv.z, wv.w);
        const uint32_t hm = (tid & 15) ? 0 : 1 << 13;
        uint4* gp = g_cell + ((tid >> 4) * MAXB + blockIdx.x) * 24 + (tid & 15);
        __syncthreads();
        TLSTAMP(6);
        const uint32_t tag = lds32(sb + SM_MISC + 8);
        {
            uint32_t c[5] = {0, 0, 0, 0, 0};
            uint4 v[5];
#pragma unroll
            for (int k = 0; k < 5; k++)
                if (k < 4 || fifth) c[k] = lds32(sb + SC_CNT + (tid >> 4) * 4 + k * 128), v[k] = lds128(sa + k * 32 * CP);
#pragma unroll
            for (int k = 0; k < 5; k++) {
                if (k < 4 || fifth) {
                    v[k].y += c[k] * hm + tag, v[k].w += tag;
                    st_cell(gp + k * 32 * MAXB * 24, v[k]);
                }
            }
            const uint32_t lim = 256 + (tid & 15) * 16;
            if (max(max(c[0], c[1]), max(max(c[2], c[3]), c[4])) > lim && lim < 384) {
#pragma unroll
                for (int k = 0; k < 5; k++) {
                    if (c[k] > lim) {
                        uint4 q = lds128(sa + k * 32 * CP + 256);
                        if (c[k] <= lim + 8) q.z = none, q.w = 0;
                        q.y += tag, q.w += tag;
                        st_cell(gp + k * 32 * MAXB * 24 + 16, q);
                    }
                }
            }
        }
        if (wrow) {
            const int k = blockIdx.x;
            uint4* dp = &g_wf[((tid & 3) * 8 + ((k & 63) >> 3)) * 64 + (k >> 6) * 32 + (k & 7)];
            dp[0] = make_uint4(wv.x, wo[0].x, wo[1].x, wo[2].x);
            dp[8] = make_uint4(wv.y, wo[0].y, wo[1].y, wo[2].y);
            dp[16] = make_uint4(wv.z, wo[0].z, wo[1].z, wo[2].z);
            dp[24] = make_uint4(wv.w, wo[0].w, wo[1].w, wo[2].w);
        }
        if (warp < 15) { BARINIT(warp, 15) }
        __syncwarp();
        if (tid == NT - 1) {
            uint4 q;
            for (int n = 0; n < (1 << 22); n++) {
                q = ld_cell((const uint4*)&g_sync);
                if ((int)(q.z - (epoch + 1) * nbins) >= 0) break;
            }
            sts64(sb + SM_MISC + 32, q.x, q.y), sts32(sb + SM_MISC + 16, (epoch + 1) * 512);
            asm volatile("mbarrier.init.shared.b64 [%0], 1;" ::"r"(sb + SM_MISC + 48) : "memory");
            while ((uint32_t)(gt_lo() - q.x) < polld) {}
        }
        __syncthreads();
        TLSTAMP(14);
        uint4 m[5], mx[5];
        uint32_t rk[10], rx[10];
        bool ext;
        {
            const uint4* hp = g_cell + (blockIdx.x * MAXB + (tid >> 4)) * 24 + (tid & 15);
            m[4] = make_uint4(none, tag, none, tag);
            for (int n = 0; n < (1 << 22); n++) {
#pragma unroll
                for (int k = 0; k < 4; k++) m[k] = ld_cell(hp + k * 32 * 24);
                if ((tid >> 4) + 128 < nbins) m[4] = ld_cell(hp + 4 * 32 * 24);
                uint32_t bad = 0;
#pragma unroll
                for (int k = 0; k < 5; k++) bad |= (m[k].y ^ tag) | (m[k].w ^ tag);
                if (!(bad & 0x1ffc)) break;
            }
            __syncwarp();
            ext = __any_sync(0xffffffffu, hm && max(max(m[0].y, m[1].y), max(max(m[2].y, m[3].y), m[4].y)) >= (257u << 13));
            uint32_t need = 0;
            if (ext) {
#pragma unroll
                for (int k = 0; k < 5; k++) {
                    const uint32_t c = __shfl_sync(0xffffffffu, m[k].y, lane & 16) >> 13;
                    mx[k] = make_uint4(none, tag, none, tag);
                    if (c > 376) sts32(sb + SM_MISC + 4, 1);
                    else if (c > 256 + (tid & 15) * 16) need |= 1 << k, mx[k] = ld_cell(hp + k * 32 * 24 + 16);
                }
            }
            TLSTAMP(8);
#pragma unroll
            for (int k = 0; k < 5; k++)
                if (k < 4 || fifth)
                    rk[2 * k] = atoms_add(sb + SC_TABB + (m[k].x >> 14), 8), rk[2 * k + 1] = atoms_add(sb + SC_TABB + (m[k].z >> 14), 8);
            if (ext) {
#pragma unroll
                for (int k = 0; k < 5; k++) {
                    if (need >> k & 1) {
                        for (int n = 0; n < (1 << 22) && (((mx[k].y ^ tag) | (mx[k].w ^ tag)) & 0x1ffc); n++)
                            mx[k] = ld_cell(hp + k * 32 * 24 + 16);
                        rx[2 * k] = atoms_add(sb + SC_TABB + (mx[k].x >> 14), 8);
                        rx[2 * k + 1] = atoms_add(sb + SC_TABB + (mx[k].z >> 14), 8);
                    }
                }
            }
        }
        __syncthreads();
        TLSTAMP(5);
        if (tid == NT - 1 && blockIdx.x == 0) g_epoch = epoch + 1;
        {
            uint4 c[3];
            uint32_t tt[3];
#pragma unroll
            for (int i = 0; i < 3; i++) {
                c[i] = make_uint4(0, 0, 0, 0);
                if (i < 2 || warp < 8) c[i] = lds128(t16 + SC_TABB + i * 8192);
                tt[i] = c[i].x + c[i].y + c[i].z + c[i].w;
            }
            const uint32_t sum = (tt[0] >> 3) + (tt[1] << 7) + (tt[2] << 17);
            const uint32_t tot = __reduce_add_sync(0xffffffffu, sum);
            const uint32_t q = (tot + 0x300c03) & 0x3fcff3fc, q0 = q & 1023, q1 = q0 + ((q >> 10) & 1023);
            uint32_t base = atoms_add(sb + (lane ? SC_CNT + lane * 4 : SM_MISC + 20), q1 + (q >> 20));
            if (lane < 3) sts32(sb + SC_KEY + (warp + 16 * lane) * 4, ((tot >> (10 * lane)) & 1023) * 64 + 63 - warp - 16 * lane);
            uint32_t inc = sum;
#pragma unroll
            for (int o = 1; o < 32; o <<= 1) inc = scan_step(inc, o);
            base = __shfl_sync(0xffffffffu, base, 0);
            if (max(tt[0], max(tt[1], tt[2])) > 31 * 8) sts32(sb + SM_MISC + 4, 1);
            inc += q - tot - sum;
#pragma unroll
            for (int i = 0; i < 3; i++) {
                const uint32_t e = (((inc >> (10 * i)) & 1023) + base + (i == 0 ? 0 : i == 1 ? q0 : q1)) * 8;
                if (i < 2 || warp < 8) sts128(t16 + SC_TABB + i * 8192, e, e + c[i].x, e + c[i].x + c[i].y, e + tt[i] - c[i].w);
            }
        }
        __syncthreads();
        TLSTAMP(2);
        if (warp >= 11) {
            const uint32_t st = (tid - 352) >> 2, key = lds32(sb + SC_KEY + st * 4);
            uint32_t rank = 0;
#pragma unroll
            for (int i = 0; i < 5; i++) {
                const uint2 q = lds64(sb + SC_KEY + (lane & 3) * 40 + i * 8);
                rank += (q.x > key) + (q.y > key);
            }
            rank += __shfl_xor_sync(0xffffffffu, rank, 1);
            rank += __shfl_xor_sync(0xffffffffu, rank, 2);
            const uint32_t lv = rank >> 2, cw = ((0x969u >> (2 * lv)) & 3) * 4 + ((rank ^ -(lv & 1)) & 3);
            const uint32_t sid = (0xe4a50u >> (2 * lv)) & 3;
            sts32(sb + SC_MAP + st * 4, cw * 512 + (sid << 28));
            asm volatile("st.shared.u8 [%0], %1;" ::"r"(sb + SM_INV + cw * 4 + sid), "r"(st) : "memory");
        }
        const int total = lds32(sb + SM_MISC + 20);
        fast = lds32(sb + SM_MISC + 4) == 0 && total <= RECN - 4;
#pragma unroll
        for (int k = 0; k < 5; k++)
            if (k < 4 || fifth)
            {
                if (m[k].y & 3) rk[2 * k] += lds32(sb + SC_TABB + (m[k].x >> 14));
                if (m[k].w & 3) rk[2 * k + 1] += lds32(sb + SC_TABB + (m[k].z >> 14));
            }
        if (fast) {
#pragma unroll
            for (int k = 0; k < 5; k++) {
                if (k < 4 || fifth) {
                    if (m[k].y & 3) sts64(sb + SC_TMP + rk[2 * k], m[k].x, m[k].y);
                    if (m[k].w & 3) sts64(sb + SC_TMP + rk[2 * k + 1], m[k].z, m[k].w);
                }
            }
            if (ext) {
#pragma unroll
                for (int k = 0; k < 5; k++) {
                    if (mx[k].y & 3) {
                        const uint32_t p0 = lds32(sb + SC_TABB + (mx[k].x >> 14)), p1 = lds32(sb + SC_TABB + (mx[k].z >> 14));
                        sts64(sb + SC_TMP + rx[2 * k] + p0, mx[k].x, mx[k].y);
                        if (mx[k].w & 3) sts64(sb + SC_TMP + rx[2 * k + 1] + p1, mx[k].z, mx[k].w);
                    }
                }
            }
            constexpr int KD = (RECN + NT - 1) / NT;
            const uint32_t P = (lane ^ (lane >> 1)) & 1;
            const uint32_t binc = (P ? 1u << 11 : 1u) + ((lane & 3) == 3 ? 1u << 22 : 0u);
            const bool last = warp * 32 + (KD - 1) * NT < total, q2 = warp * 128 + NT * 4 < total;
            const int rest = total - tid, restq = (total >> 2) - tid;
            uint2 en[KD];
            uint32_t bk[KD], r2[KD], ca[2], ol[2], r3[2];
            __syncthreads();
            TLSTAMP(9);
#pragma unroll
            for (int k = 0; k < KD; k++)
                if (k < KD - 1 || last) en[k] = lds64(sb + SC_TMP + tid * 8 + k * NT * 8);
#pragma unroll
            for (int k = 0; k < 2; k++)
                if (k == 0 || q2) ca[k] = lds32(sb + SC_TMP + (tid + k * NT) * 32 + 24);
#pragma unroll
            for (int k = 0; k < 2; k++)
                if (k == 0 || q2) ol[k] = lds32(sb + SC_MAP + (ca[k] >> 23) * 4);
#pragma unroll
            for (int k = 0; k < KD; k++) {
                if (k < KD - 1 || last) {
                    bk[k] = __umulhi(en[k].x & 0x3fff, bkm << 9) * 4;
                    r2[k] = atoms_add(sb + SC_TABA + bk[k], rest > k * NT ? binc : 0);
                }
            }
#pragma unroll
            for (int k = 0; k < 2; k++) {
                if (k == 0 || q2) {
                    ca[k] = ((ca[k] >> 14) & 0x1fc) | (ol[k] & 0x1e00);
                    ol[k] = (tid + k * NT) * 16 + (ol[k] & 0x30000000);
                    r3[k] = atoms_add(sb + SC_TABC + ca[k], restq > k * NT ? 4 : 0);
                }
            }
            __syncthreads();
            TLSTAMP(12);
            if (warp < NCW) {
                const uint4 c = lds128(t16 + SC_TABC);
                const uint32_t tt = c.x + c.y + c.z + c.w;
                uint32_t inc = tt;
#pragma unroll
                for (int o = 1; o < 32; o <<= 1) inc = scan_step(inc, o);
                if (inc > (OLN - 6) * 4) sts32(sb + SM_MISC + 4, 1);
                inc += warp * (OLN * 4) - tt;
                sts128(t16 + SC_TABC, inc, inc + c.x, inc + c.x + c.y, inc + tt - c.w);
            } else {
                const uint32_t mine = (warp + lane) & 3;
                uint4 c;
                uint32_t cs, inc = 0, e = 4 + (4 << 11);
#pragma unroll
                for (int i = 0; i < 4; i++) {
                    const uint32_t pc = (mine + i) & 3;
                    const uint4 v = lds128(sb + SC_TABA + lane * 64 + (pc << 4));
                    const uint32_t sum = v.x + v.y + v.z + v.w;
                    inc += sum;
                    if (i == 0) c = v, cs = sum;
                    if (pc >= mine) e -= sum;
                }
#pragma unroll
                for (int o = 1; o < 32; o <<= 1) inc = scan_step(inc, o);
                e += inc;
                sts128(sb + SC_TABB + lane * 64 + (mine << 4), e, e + c.x, e + c.x + c.y, e + cs - c.w);
                if ((int)max((e + cs) & 0x7ff, ((e + cs) >> 11) & 0x7ff) - (int)(e >> 22) * 2 > SP) sts32(sb + SM_MISC + 4, 1);
                if (tid == NCW * 32) sts32(sb + SM_MISC + 12, ((total >> 2) + 1) >> 1);
            }
            __syncthreads();
            TLSTAMP(13);
            fast = lds32(sb + SM_MISC + 4) == 0;
#pragma unroll
            for (int k = 0; k < KD; k++)
                if (k < KD - 1 || last) r2[k] += lds32(sb + SC_TABB + bk[k]);
#pragma unroll
            for (int k = 0; k < 2; k++)
                if (k == 0 || q2) r3[k] += lds32(sb + SC_TABC + ca[k]);
            if (fast) {
                const uint32_t rot = P ? 9 : 30;
#pragma unroll
                for (int k = 0; k < KD; k++) {
                    if (k < KD - 1 || last) {
                        const uint32_t k4 = __funnelshift_r(r2[k], r2[k], rot);
                        if (rest > k * NT) {
                            sts16(sb + SM_R + 2 + bitsel(k4, P << 13), en[k].x);
                            sts32(sb + SM_REC + tid * 4 + k * NT * 4, bitsel(k4, en[k].y));
                        }
                    }
                }
#pragma unroll
                for (int k = 0; k < 2; k++)
                    if ((k == 0 || q2) && restq > k * NT) sts32(sb + SM_OL + r3[k], ol[k]);
            }
        }
        asm volatile("fence.proxy.async.shared::cta;" ::: "memory");
        __syncthreads();
        TLSTAMP(3);
        if (!fast && wrow) wf_done();
        if (fast && tid < NBAR) {
            const uint4 a = lds128(t16 + SM_R), b = lds128(t16 + SM_R + 0x2000);
            const int s = (((int)a.x >> 3) + ((int)a.y >> 3) + ((int)a.z >> 3) + ((int)a.w >> 3) + ((int)b.x >> 3) + ((int)b.y >> 3) +
                           ((int)b.z >> 3) + ((int)b.w >> 3)) >> 16;
            sts32(sb + SM_OFF + tid * 4, tdelay + ((s * tau + min(s, rampn) * ramp - max(s - sprn, 0) * spr) >> 10));
        }
        __syncwarp();
    }

    if (!fast) {
        float* accs = (float*)smem;
        constexpr int NACC = 96;
        const int node0 = blockIdx.x * npb, nnodes = max(0, min(npb, N - node0));
#pragma unroll 1
        for (int nb = 0; nb < nnodes; nb += NACC) {
            __syncthreads();
            for (int i = tid; i < NACC * 512; i += NT) accs[i] = 0.f;
            __syncthreads();
            const int lim = min(NACC, nnodes - nb);
#pragma unroll 1
            for (int base = warp * 32; base < E; base += NT) {
                const int e = base + lane;
                const int dl = e < E ? dst[e] - node0 - nb : -1;
                unsigned mask = __ballot_sync(0xffffffffu, dl >= 0 && dl < lim);
#pragma unroll 1
                while (mask) {
                    const int l = __ffs(mask) - 1;
                    mask &= mask - 1;
                    const int dd = __shfl_sync(0xffffffffu, dl, l);
                    slow_edge(base + l, src[base + l], accs + dd * 512, x, sh, ea, cg, wr, lane);
                }
            }
            __syncthreads();
#pragma unroll 1
            for (int nl = warp; nl < lim; nl += NT / 32) slow_out(accs + nl * 512, wout, out + (size_t)(node0 + nb + nl) * 512, lane);
        }
    } else if (warp >= NCW) {
        asm volatile("setmaxnreg.dec.sync.aligned.u32 %0;" ::"n"(PREG));
        producer(&tmx, warp - NCW);
    } else if (warp >= 4) {
        asm volatile("setmaxnreg.inc.sync.aligned.u32 %0;" ::"n"(R1));
        consumer<3>(sh, ea, out, N, npb);
        TLMAX(4);
    } else {
        asm volatile("setmaxnreg.inc.sync.aligned.u32 %0;" ::"n"(R0));
        consumer<4>(sh, ea, out, N, npb);
        TLMAX(4);
    }
}

typedef CUresult (*EncodeTiledFn)(CUtensorMap*, CUtensorMapDataType, cuuint32_t, void*, const cuuint64_t*,
                                  const cuuint64_t*, const cuuint32_t*, const cuuint32_t*, CUtensorMapInterleave,
                                  CUtensorMapSwizzle, CUtensorMapL2promotion, CUtensorMapFloatOOBfill);

extern "C" void kernel_launch(void* const* d_in, const int* in_sizes, int n_in, void* d_out, int out_size) {
    const __nv_bfloat16* x = (const __nv_bfloat16*)d_in[0];
    const int* src = (const int*)d_in[1];
    const int* dst = (const int*)d_in[2];
    const __nv_bfloat16* sh = (const __nv_bfloat16*)d_in[3];
    const __nv_bfloat16* ea = (const __nv_bfloat16*)d_in[4];
    const __nv_bfloat16* cg = (const __nv_bfloat16*)d_in[5];
    const __nv_bfloat16* wr = (const __nv_bfloat16*)d_in[6];
    const __nv_bfloat16* wout = (const __nv_bfloat16*)d_in[7];
    __nv_bfloat16* out = (__nv_bfloat16*)d_out;
    const int N = in_sizes[0] / 512;
    const int E = in_sizes[1];

    static int num_sms = 0, coresident = 0;
    static EncodeTiledFn encode = nullptr;
    if (num_sms == 0) {
        int dev = 0;
        cudaGetDevice(&dev);
        cudaDeviceGetAttribute(&num_sms, cudaDevAttrMultiProcessorCount, dev);
        cudaFuncSetAttribute(main_kernel, cudaFuncAttributeMaxDynamicSharedMemorySize, SM_TOTAL);
        int occ = 0;
        cudaOccupancyMaxActiveBlocksPerMultiprocessor(&occ, main_kernel, NT, SM_TOTAL);
        coresident = occ * num_sms;
        void* fn = nullptr;
        cudaDriverEntryPointQueryResult qr;
        cudaGetDriverEntryPoint("cuTensorMapEncodeTiled", &fn, cudaEnableDefault, &qr);
        encode = (EncodeTiledFn)fn;
    }
    CUtensorMap tmx;
    const int rank = 2;
    const cuuint64_t gd[2] = {64, (cuuint64_t)N * 8}, gs[1] = {128};
    const cuuint32_t bd[2] = {64, 8}, es[2] = {1, 1};
    encode(&tmx, CU_TENSOR_MAP_DATA_TYPE_BFLOAT16, rank, (void*)x, gd, gs, bd, es, CU_TENSOR_MAP_INTERLEAVE_NONE,
           CU_TENSOR_MAP_SWIZZLE_128B, CU_TENSOR_MAP_L2_PROMOTION_NONE, CU_TENSOR_MAP_FLOAT_OOB_FILL_NONE);

    int nbins = num_sms < MAXB ? num_sms : MAXB;
    int npb = (N + nbins - 1) / nbins;
    if (npb < 2) npb = 2;
    nbins = (N + npb - 1) / npb;
    const unsigned npb_magic = (unsigned)((0x100000000ull + npb - 1) / npb);
    int chunk = (E + nbins - 1) / nbins;
    if (nbins > coresident || nbins < 128 || npb > MAXNPB || chunk > KE * NT || N > 16384 || N < 512 || E > (1 << 19)) chunk = 0;
    const unsigned bkm = (unsigned)(0xffffffffull / N);
    double pace = PACE, rampt = RAMP, rampf = RAMPF, sprt = SPRINT, sprf = SPRINTF;
    int tdelay = TDELAY, polld = POLLD;
    const int tau = (int)(1024.0 * pace * ((double)E / nbins) / N);
    const int rampn = (int)(N * rampf), ramp = (int)(1024.0 * rampt / rampn);
    main_kernel<<<nbins, NT, SM_TOTAL, cudaStreamPerThread>>>(tmx, x, src, dst, sh, ea, cg, wr, wout, out, N, E, npb, npb_magic,
                                                              chunk, bkm, tau, ramp, rampn, tdelay, polld, (int)(1024.0 * sprt / (N * sprf)), (int)(N * (1 - sprf)));
}
```

```cpp
#include <cuda_runtime.h>
#include <cuda.h>
#include <cuda_bf16.h>
#include <stdint.h>
#include <stdlib.h>

#define NT 512
#define NCW 12
#define MAXB 144
#define MAXNPB 80
#define KE 5
#define SP 97
#define RECN 2816
#define RP 1512
#define OLN 80
#define NBAR 360
#define R0 168
#define R1 160
#define PREG 24
#define PACE 10.3
#define TDELAY 4550
#define POLLD 1000
#define WFT 80
#define SLIPTH 500
#define SLIPSUB 250
#define SLIPFROM 36
#define AHEAD 96
#define EARLY 32
#define RAMPF 0.1
#define SPRINT 500
#define SPRINTF 0.5
#define SLIPEND 640
#define SPINT 96
#define BP 0
#define RAMP 600

__device__ __align__(1024) uint4 g_cell[MAXB * MAXB * 8];
__device__ __align__(1024) uint4 g_more[MAXB * MAXB * 4];
__device__ __align__(1024) uint4 g_wf[2048];
__device__ __align__(256) ulonglong2 g_sync[16];
__device__ __align__(256) unsigned g_epoch;
#define TLSTAMP(i)
#define TLMAX(i)

constexpr uint32_t sb = 1024;
#define PH 128
#define SHR "13"
#define SM_R (2 * SP * 1024 + PH)
#define SM_CTR (SM_R + RP * 4)
#define SM_MISC (SM_CTR + 528)
#define SM_INV (SM_MISC + 80)
#define SM_OFF (SM_INV + 48)
#define SM_REC (SM_R + 0x2000 + RP * 4)
#define SM_OL (SM_REC + RECN * 4)
#define SM_BAR (SM_OL + NCW * OLN * 4)
#define SM_TOTAL (SM_BAR + (NBAR + 16) * 8)
static_assert(SM_TOTAL <= 232448 && SM_OFF + NBAR * 4 <= SM_R + 0x2000, "shared memory");
static_assert(4 + RECN / 2 + SP + 2 <= RP && RECN / 8 + 8 <= NBAR && NBAR % 24 == 0, "tables");
#define ZSL 32
#define NWIN 96
#define CH 2432
#define CP 208
#define SC_STG ((SP + ZSL) * 1024 + PH)
#define SC_TMP (ZSL * 1024)
#define SC_TABB (SC_TMP + 3072 * 8)
#define SC_TABC (SC_TABB + 41 * NWIN * 4)
#define SC_TABA (SC_TABC + NCW * NWIN * 4)
#define SC_ZEND (SC_TABB + 3 * NT * 16)
#define SC_CNT SC_ZEND
#define SC_KEY (SC_CNT + (MAXB + 32) * 4)
#define SC_MAP (SC_KEY + 192)
#define WSL 5
#define SC_WR ((2 * SP - WSL) * 1024 + PH)
#define SC_CG (SC_WR + 16 * 272)
static_assert(SC_TABA + 2048 + 128 <= SC_ZEND && RECN <= 3072 && SC_MAP + 192 <= SP * 1024 && SC_STG + (MAXB + 1) * CP <= SC_WR, "scratch");

__device__ __forceinline__ uint32_t pack_bf16(float lo, float hi) {
    uint32_t r;
    asm("cvt.rn.bf16x2.f32 %0, %1, %2;" : "=r"(r) : "f"(hi), "f"(lo));
    return r;
}
__device__ __forceinline__ uint32_t s2u(const void* p) { return (uint32_t)__cvta_generic_to_shared(p); }
__device__ __forceinline__ void mbar_wait0(uint32_t a) {
    asm volatile(
        "{\n.reg .pred p, q;\n.reg .u32 n;\nmov.u32 n, 0;\n"
        "LAB_WAIT:\nmbarrier.try_wait.parity.shared.b64 p, [%0], 0;\nadd.u32 n, n, 1;\nsetp.lt.and.u32 q, n, 1000000, !p;\n@q bra LAB_WAIT;\n}" ::"r"(a)
        : "memory");
}
__device__ __forceinline__ uint32_t lds8(uint32_t a) { uint32_t v; asm volatile("ld.shared.u8 %0, [%1];" : "=r"(v) : "r"(a) : "memory"); return v; }
__device__ __forceinline__ uint32_t lds16(uint32_t a) { uint32_t v; asm volatile("ld.shared.u16 %0, [%1];" : "=r"(v) : "r"(a) : "memory"); return v; }
__device__ __forceinline__ uint32_t lds32(uint32_t a) { uint32_t v; asm volatile("ld.shared.u32 %0, [%1];" : "=r"(v) : "r"(a) : "memory"); return v; }
__device__ __forceinline__ uint2 lds64(uint32_t a) {
    uint2 v; asm volatile("ld.shared.v2.u32 {%0,%1}, [%2];" : "=r"(v.x), "=r"(v.y) : "r"(a) : "memory"); return v;
}
__device__ __forceinline__ uint4 lds128(uint32_t a) {
    uint4 v; asm volatile("ld.volatile.shared.v4.u32 {%0,%1,%2,%3}, [%4];" : "=r"(v.x), "=r"(v.y), "=r"(v.z), "=r"(v.w) : "r"(a) : "memory"); return v;
}
__device__ __forceinline__ void sts16(uint32_t a, uint32_t v) { asm volatile("st.shared.u16 [%0], %1;" ::"r"(a), "h"((unsigned short)v) : "memory"); }
__device__ __forceinline__ void sts32(uint32_t a, uint32_t v) { asm volatile("st.shared.u32 [%0], %1;" ::"r"(a), "r"(v) : "memory"); }
__device__ __forceinline__ void sts64(uint32_t a, uint32_t x, uint32_t y) { asm volatile("st.shared.v2.u32 [%0], {%1,%2};" ::"r"(a), "r"(x), "r"(y) : "memory"); }
__device__ __forceinline__ void sts128(uint32_t a, uint32_t x, uint32_t y, uint32_t z, uint32_t w) {
    asm volatile("st.shared.v4.u32 [%0], {%1,%2,%3,%4};" ::"r"(a), "r"(x), "r"(y), "r"(z), "r"(w) : "memory");
}
__device__ __forceinline__ uint32_t atoms_add(uint32_t a, uint32_t v) {
    uint32_t r;
    asm volatile("atom.shared.add.u32 %0, [%1], %2;" : "=r"(r) : "r"(a), "r"(v) : "memory");
    return r;
}
__device__ __forceinline__ uint4 ld_cell(const uint4* p) {
    uint4 v;
    asm volatile("{\n.reg .b64 a, b;\nld.relaxed.gpu.global.v2.b64 {a, b}, [%4];\nmov.b64 {%0,%1}, a;\nmov.b64 {%2,%3}, b;\n}"
                 : "=r"(v.x), "=r"(v.y), "=r"(v.z), "=r"(v.w) : "l"(p) : "memory");
    return v;
}
__device__ __forceinline__ void st_cell(uint4* p, uint32_t x, uint32_t y, uint32_t z, uint32_t w) {
    asm volatile("st.relaxed.gpu.global.v2.b64 [%0], {%1, %2};" ::"l"(p), "l"(x | (uint64_t)y << 32), "l"(z | (uint64_t)w << 32) : "memory");
}
__device__ __forceinline__ uint32_t scan_step(uint32_t v, int o) {
    asm volatile("{\n.reg .pred p;\n.reg .b32 y;\nshfl.sync.up.b32 y|p, %0, %1, 0, 0xffffffff;\n@p add.u32 %0, %0, y;\n}" : "+r"(v) : "r"(o));
    return v;
}
__device__ __forceinline__ uint32_t bitsel(uint32_t a, uint32_t b) {
    uint32_t r;
    asm("lop3.b32 %0, %1, %2, 0x1ffc, 0xe4;" : "=r"(r) : "r"(a), "r"(b));
    return r;
}
__device__ __forceinline__ uint32_t movm(uint32_t a) {
    uint32_t r;
    asm volatile("movmatrix.sync.aligned.m8n8.trans.b16 %0, %1;" : "=r"(r) : "r"(a));
    return r;
}
__device__ __forceinline__ uint32_t gt_lo() {
    uint32_t t;
    asm volatile("mov.u32 %0, %globaltimer_lo;" : "=r"(t));
    return t;
}
__device__ __forceinline__ bool elect() {
    uint32_t p;
    asm volatile("{\n.reg .pred P;\nelect.sync _|P, 0xffffffff;\nselp.u32 %0, 1, 0, P;\n}" : "=r"(p));
    return p;
}
__device__ __forceinline__ void project4(const uint32_t (&pk)[64], uint32_t ra, uint32_t ba, uint4* const (&p)[4], const uint32_t (&v)[4]) {
    asm volatile(
        "{\n.reg .pred p0, p1, q0, q1, nv, s<4>;\n.reg .b32 t, h, c<16>, a<32>, b<32>, k<16>;\n.reg .b64 d<16>;\n.reg .f32 o<32>;\nsetp.ne.b32 p0, 0, 0;\n"
        "setp.eq.b32 p1, 0, 0;\nmov.b32 h, 8;\nsetp.eq.u32 nv, %64, 0;\nvote.sync.any.pred nv, nv, 0xffffffff;\nsetp.ne.b32 s0, %69, 0;\n"
        "setp.ne.b32 s1, %70, 0;\nsetp.ne.b32 s2, %71, 0;\nsetp.ne.b32 s3, %72, 0;\nmovmatrix.sync.aligned.m8n8.trans.b16 a0, %0;\n"
        "movmatrix.sync.aligned.m8n8.trans.b16 a1, %16;\nmovmatrix.sync.aligned.m8n8.trans.b16 a2, %1;\nmovmatrix.sync.aligned.m8n8.trans.b16 a3, %17;\n"
        "movmatrix.sync.aligned.m8n8.trans.b16 a4, %2;\nmovmatrix.sync.aligned.m8n8.trans.b16 a5, %18;\nmovmatrix.sync.aligned.m8n8.trans.b16 a6, %3;\n"
        "movmatrix.sync.aligned.m8n8.trans.b16 a7, %19;\nmovmatrix.sync.aligned.m8n8.trans.b16 a8, %4;\nmovmatrix.sync.aligned.m8n8.trans.b16 a9, %20;\n"
        "movmatrix.sync.aligned.m8n8.trans.b16 a10, %5;\nmovmatrix.sync.aligned.m8n8.trans.b16 a11, %21;\nmovmatrix.sync.aligned.m8n8.trans.b16 a12, %6;\n"
        "movmatrix.sync.aligned.m8n8.trans.b16 a13, %22;\nmovmatrix.sync.aligned.m8n8.trans.b16 a14, %7;\nmovmatrix.sync.aligned.m8n8.trans.b16 a15, %23;\n"
        "movmatrix.sync.aligned.m8n8.trans.b16 a16, %8;\nmovmatrix.sync.aligned.m8n8.trans.b16 a17, %24;\nmovmatrix.sync.aligned.m8n8.trans.b16 a18, %9;\n"
        "movmatrix.sync.aligned.m8n8.trans.b16 a19, %25;\nmovmatrix.sync.aligned.m8n8.trans.b16 a20, %10;\nmovmatrix.sync.aligned.m8n8.trans.b16 a21, %26;\n"
        "movmatrix.sync.aligned.m8n8.trans.b16 a22, %11;\nmovmatrix.sync.aligned.m8n8.trans.b16 a23, %27;\nmovmatrix.sync.aligned.m8n8.trans.b16 a24, %12;\n"
        "movmatrix.sync.aligned.m8n8.trans.b16 a25, %28;\nmovmatrix.sync.aligned.m8n8.trans.b16 a26, %13;\nmovmatrix.sync.aligned.m8n8.trans.b16 a27, %29;\n"
        "movmatrix.sync.aligned.m8n8.trans.b16 a28, %14;\nmovmatrix.sync.aligned.m8n8.trans.b16 a29, %30;\nmovmatrix.sync.aligned.m8n8.trans.b16 a30, %15;\n"
        "movmatrix.sync.aligned.m8n8.trans.b16 a31, %31;\nmov.b32 t, 0;\n"
        "W0:\nmbarrier.try_wait.parity.shared.b64 q0, [%73+0], 0;\nadd.u32 t, t, 1;\nsetp.lt.and.u32 q1, t, 1000000, !q0;\n@q1 bra.uni W0;\nmov.b32 t, 0;\n"
        "W1:\nmbarrier.try_wait.parity.shared.b64 q0, [%73+8], 0;\nadd.u32 t, t, 1;\nsetp.lt.and.u32 q1, t, 1000000, !q0;\n@q1 bra.uni W1;\nmov.b32 t, 0;\n"
        "W2:\nmbarrier.try_wait.parity.shared.b64 q0, [%73+16], 0;\nadd.u32 t, t, 1;\nsetp.lt.and.u32 q1, t, 1000000, !q0;\n@q1 bra.uni W2;\nmov.b32 t, 0;\n"
        "W3:\nmbarrier.try_wait.parity.shared.b64 q0, [%73+24], 0;\nadd.u32 t, t, 1;\nsetp.lt.and.u32 q1, t, 1000000, !q0;\n@q1 bra.uni W3;\n"
        "ld.volatile.shared.v4.b32 {c0,c1,c2,c3}, [%64+0];\nld.volatile.shared.v4.b32 {c4,c5,c6,c7}, [%64+8192];\n"
        "ld.volatile.shared.v4.b32 {c8,c9,c10,c11}, [%64+16];\nld.volatile.shared.v4.b32 {c12,c13,c14,c15}, [%64+8208];\nand.b32 t, c0, 0xffe;\n"
        "mad.lo.u32 t, t, 4, 0x200000;\nmov.b64 d0, {t, h};\nand.b32 t, c1, 0xffe;\nmad.lo.u32 t, t, 4, 0x200000;\nmov.b64 d1, {t, h};\nand.b32 t, c2, 0xffe;\n"
        "mad.lo.u32 t, t, 4, 0x200000;\nmov.b64 d2, {t, h};\nand.b32 t, c3, 0xffe;\nmad.lo.u32 t, t, 4, 0x200000;\nmov.b64 d3, {t, h};\nand.b32 t, c4, 0xffe;\n"
        "mad.lo.u32 t, t, 4, 0x200000;\nmov.b64 d4, {t, h};\nand.b32 t, c5, 0xffe;\nmad.lo.u32 t, t, 4, 0x200000;\nmov.b64 d5, {t, h};\nand.b32 t, c6, 0xffe;\n"
        "mad.lo.u32 t, t, 4, 0x200000;\nmov.b64 d6, {t, h};\nand.b32 t, c7, 0xffe;\nmad.lo.u32 t, t, 4, 0x200000;\nmov.b64 d7, {t, h};\nand.b32 t, c8, 0xffe;\n"
        "mad.lo.u32 t, t, 4, 0x200000;\nmov.b64 d8, {t, h};\nand.b32 t, c9, 0xffe;\nmad.lo.u32 t, t, 4, 0x200000;\nmov.b64 d9, {t, h};\nand.b32 t, c10, 0xffe;\n"
        "mad.lo.u32 t, t, 4, 0x200000;\nmov.b64 d10, {t, h};\nand.b32 t, c11, 0xffe;\nmad.lo.u32 t, t, 4, 0x200000;\nmov.b64 d11, {t, h};\n"
        "and.b32 t, c12, 0xffe;\nmad.lo.u32 t, t, 4, 0x200000;\nmov.b64 d12, {t, h};\nand.b32 t, c13, 0xffe;\nmad.lo.u32 t, t, 4, 0x200000;\n"
        "mov.b64 d13, {t, h};\nand.b32 t, c14, 0xffe;\nmad.lo.u32 t, t, 4, 0x200000;\nmov.b64 d14, {t, h};\nand.b32 t, c15, 0xffe;\n"
        "mad.lo.u32 t, t, 4, 0x200000;\nmov.b64 d15, {t, h};\nwgmma.fence.sync.aligned;\n"
        "wgmma.mma_async.sync.aligned.m64n32k16.f32.bf16.bf16 {o0,o1,o2,o3,o4,o5,o6,o7,o8,o9,o10,o11,o12,o13,o14,o15}, {a0,a1,a2,a3}, d0, p0, 1, 1, 1;\n"
        "wgmma.mma_async.sync.aligned.m64n32k16.f32.bf16.bf16 {o16,o17,o18,o19,o20,o21,o22,o23,o24,o25,o26,o27,o28,o29,o30,o31}, {a0,a1,a2,a3}, d8, p0, 1, 1, 1;\n"
        "wgmma.mma_async.sync.aligned.m64n32k16.f32.bf16.bf16 {o0,o1,o2,o3,o4,o5,o6,o7,o8,o9,o10,o11,o12,o13,o14,o15}, {a4,a5,a6,a7}, d1, p1, 1, 1, 1;\n"
        "wgmma.mma_async.sync.aligned.m64n32k16.f32.bf16.bf16 {o16,o17,o18,o19,o20,o21,o22,o23,o24,o25,o26,o27,o28,o29,o30,o31}, {a4,a5,a6,a7}, d9, p1, 1, 1, 1;\n"
        "wgmma.mma_async.sync.aligned.m64n32k16.f32.bf16.bf16 {o0,o1,o2,o3,o4,o5,o6,o7,o8,o9,o10,o11,o12,o13,o14,o15}, {a8,a9,a10,a11}, d2, p1, 1, 1, 1;\n"
        "wgmma.mma_async.sync.aligned.m64n32k16.f32.bf16.bf16 {o16,o17,o18,o19,o20,o21,o22,o23,o24,o25,o26,o27,o28,o29,o30,o31}, {a8,a9,a10,a11}, d10, p1, 1, 1, 1;\n"
        "wgmma.mma_async.sync.aligned.m64n32k16.f32.bf16.bf16 {o0,o1,o2,o3,o4,o5,o6,o7,o8,o9,o10,o11,o12,o13,o14,o15}, {a12,a13,a14,a15}, d3, p1, 1, 1, 1;\n"
        "wgmma.mma_async.sync.aligned.m64n32k16.f32.bf16.bf16 {o16,o17,o18,o19,o20,o21,o22,o23,o24,o25,o26,o27,o28,o29,o30,o31}, {a12,a13,a14,a15}, d11, p1, 1, 1, 1;\n"
        "wgmma.mma_async.sync.aligned.m64n32k16.f32.bf16.bf16 {o0,o1,o2,o3,o4,o5,o6,o7,o8,o9,o10,o11,o12,o13,o14,o15}, {a16,a17,a18,a19}, d4, p1, 1, 1, 1;\n"
        "wgmma.mma_async.sync.aligned.m64n32k16.f32.bf16.bf16 {o16,o17,o18,o19,o20,o21,o22,o23,o24,o25,o26,o27,o28,o29,o30,o31}, {a16,a17,a18,a19}, d12, p1, 1, 1, 1;\n"
        "wgmma.mma_async.sync.aligned.m64n32k16.f32.bf16.bf16 {o0,o1,o2,o3,o4,o5,o6,o7,o8,o9,o10,o11,o12,o13,o14,o15}, {a20,a21,a22,a23}, d5, p1, 1, 1, 1;\n"
        "wgmma.mma_async.sync.aligned.m64n32k16.f32.bf16.bf16 {o16,o17,o18,o19,o20,o21,o22,o23,o24,o25,o26,o27,o28,o29,o30,o31}, {a20,a21,a22,a23}, d13, p1, 1, 1, 1;\n"
        "wgmma.mma_async.sync.aligned.m64n32k16.f32.bf16.bf16 {o0,o1,o2,o3,o4,o5,o6,o7,o8,o9,o10,o11,o12,o13,o14,o15}, {a24,a25,a26,a27}, d6, p1, 1, 1, 1;\n"
        "wgmma.mma_async.sync.aligned.m64n32k16.f32.bf16.bf16 {o16,o17,o18,o19,o20,o21,o22,o23,o24,o25,o26,o27,o28,o29,o30,o31}, {a24,a25,a26,a27}, d14, p1, 1, 1, 1;\n"
        "wgmma.mma_async.sync.aligned.m64n32k16.f32.bf16.bf16 {o0,o1,o2,o3,o4,o5,o6,o7,o8,o9,o10,o11,o12,o13,o14,o15}, {a28,a29,a30,a31}, d7, p1, 1, 1, 1;\n"
        "wgmma.mma_async.sync.aligned.m64n32k16.f32.bf16.bf16 {o16,o17,o18,o19,o20,o21,o22,o23,o24,o25,o26,o27,o28,o29,o30,o31}, {a28,a29,a30,a31}, d15, p1, 1, 1, 1;\n"
        "wgmma.commit_group.sync.aligned;\n@nv bra.uni END;\nmovmatrix.sync.aligned.m8n8.trans.b16 b0, %32;\nmovmatrix.sync.aligned.m8n8.trans.b16 b2, %33;\n"
        "movmatrix.sync.aligned.m8n8.trans.b16 b3, %49;\nmovmatrix.sync.aligned.m8n8.trans.b16 b4, %34;\nmovmatrix.sync.aligned.m8n8.trans.b16 b5, %50;\n"
        "movmatrix.sync.aligned.m8n8.trans.b16 b6, %35;\nmovmatrix.sync.aligned.m8n8.trans.b16 b7, %51;\nmovmatrix.sync.aligned.m8n8.trans.b16 b8, %36;\n"
        "movmatrix.sync.aligned.m8n8.trans.b16 b9, %52;\nmovmatrix.sync.aligned.m8n8.trans.b16 b20, %42;\nmovmatrix.sync.aligned.m8n8.trans.b16 b21, %58;\n"
        "movmatrix.sync.aligned.m8n8.trans.b16 b22, %43;\nmovmatrix.sync.aligned.m8n8.trans.b16 b23, %59;\nmovmatrix.sync.aligned.m8n8.trans.b16 b24, %44;\n"
        "movmatrix.sync.aligned.m8n8.trans.b16 b25, %60;\nmovmatrix.sync.aligned.m8n8.trans.b16 b26, %45;\nmovmatrix.sync.aligned.m8n8.trans.b16 b27, %61;\n"
        "movmatrix.sync.aligned.m8n8.trans.b16 b28, %46;\nmovmatrix.sync.aligned.m8n8.trans.b16 b29, %62;\nmovmatrix.sync.aligned.m8n8.trans.b16 b30, %47;\n"
        "movmatrix.sync.aligned.m8n8.trans.b16 b31, %63;\nmovmatrix.sync.aligned.m8n8.trans.b16 b1, %48;\nmovmatrix.sync.aligned.m8n8.trans.b16 b10, %37;\n"
        "movmatrix.sync.aligned.m8n8.trans.b16 b11, %53;\nmovmatrix.sync.aligned.m8n8.trans.b16 b12, %38;\nmovmatrix.sync.aligned.m8n8.trans.b16 b13, %54;\n"
        "movmatrix.sync.aligned.m8n8.trans.b16 b14, %39;\nmovmatrix.sync.aligned.m8n8.trans.b16 b15, %55;\nmovmatrix.sync.aligned.m8n8.trans.b16 b16, %40;\n"
        "movmatrix.sync.aligned.m8n8.trans.b16 b17, %56;\nmovmatrix.sync.aligned.m8n8.trans.b16 b18, %41;\nmovmatrix.sync.aligned.m8n8.trans.b16 b19, %57;\n"
        "@nv bra.uni END;\nwgmma.wait_group.sync.aligned 0;\ncvt.rn.bf16x2.f32 k0, o1, o0;\ncvt.rn.bf16x2.f32 k1, o5, o4;\ncvt.rn.bf16x2.f32 k2, o9, o8;\n"
        "cvt.rn.bf16x2.f32 k3, o13, o12;\ncvt.rn.bf16x2.f32 k4, o3, o2;\ncvt.rn.bf16x2.f32 k5, o7, o6;\ncvt.rn.bf16x2.f32 k6, o11, o10;\n"
        "cvt.rn.bf16x2.f32 k7, o15, o14;\ncvt.rn.bf16x2.f32 k8, o17, o16;\ncvt.rn.bf16x2.f32 k9, o21, o20;\ncvt.rn.bf16x2.f32 k10, o25, o24;\n"
        "cvt.rn.bf16x2.f32 k11, o29, o28;\ncvt.rn.bf16x2.f32 k12, o19, o18;\ncvt.rn.bf16x2.f32 k13, o23, o22;\ncvt.rn.bf16x2.f32 k14, o27, o26;\n"
        "cvt.rn.bf16x2.f32 k15, o31, o30;\nld.volatile.shared.v4.b32 {c0,c1,c2,c3}, [%64+32];\nld.volatile.shared.v4.b32 {c4,c5,c6,c7}, [%64+8224];\n"
        "ld.volatile.shared.v4.b32 {c8,c9,c10,c11}, [%64+48];\nld.volatile.shared.v4.b32 {c12,c13,c14,c15}, [%64+8240];\nand.b32 t, c0, 0xffe;\n"
        "mad.lo.u32 t, t, 4, 0x200000;\nmov.b64 d0, {t, h};\nand.b32 t, c1, 0xffe;\nmad.lo.u32 t, t, 4, 0x200000;\nmov.b64 d1, {t, h};\nand.b32 t, c2, 0xffe;\n"
        "mad.lo.u32 t, t, 4, 0x200000;\nmov.b64 d2, {t, h};\nand.b32 t, c3, 0xffe;\nmad.lo.u32 t, t, 4, 0x200000;\nmov.b64 d3, {t, h};\nand.b32 t, c4, 0xffe;\n"
        "mad.lo.u32 t, t, 4, 0x200000;\nmov.b64 d4, {t, h};\nand.b32 t, c5, 0xffe;\nmad.lo.u32 t, t, 4, 0x200000;\nmov.b64 d5, {t, h};\nand.b32 t, c6, 0xffe;\n"
        "mad.lo.u32 t, t, 4, 0x200000;\nmov.b64 d6, {t, h};\nand.b32 t, c7, 0xffe;\nmad.lo.u32 t, t, 4, 0x200000;\nmov.b64 d7, {t, h};\nand.b32 t, c8, 0xffe;\n"
        "mad.lo.u32 t, t, 4, 0x200000;\nmov.b64 d8, {t, h};\nand.b32 t, c9, 0xffe;\nmad.lo.u32 t, t, 4, 0x200000;\nmov.b64 d9, {t, h};\nand.b32 t, c10, 0xffe;\n"
        "mad.lo.u32 t, t, 4, 0x200000;\nmov.b64 d10, {t, h};\nand.b32 t, c11, 0xffe;\nmad.lo.u32 t, t, 4, 0x200000;\nmov.b64 d11, {t, h};\n"
        "and.b32 t, c12, 0xffe;\nmad.lo.u32 t, t, 4, 0x200000;\nmov.b64 d12, {t, h};\nand.b32 t, c13, 0xffe;\nmad.lo.u32 t, t, 4, 0x200000;\n"
        "mov.b64 d13, {t, h};\nand.b32 t, c14, 0xffe;\nmad.lo.u32 t, t, 4, 0x200000;\nmov.b64 d14, {t, h};\nand.b32 t, c15, 0xffe;\n"
        "mad.lo.u32 t, t, 4, 0x200000;\nmov.b64 d15, {t, h};\nwgmma.fence.sync.aligned;\n"
        "wgmma.mma_async.sync.aligned.m64n32k16.f32.bf16.bf16 {o0,o1,o2,o3,o4,o5,o6,o7,o8,o9,o10,o11,o12,o13,o14,o15}, {a0,a1,a2,a3}, d0, p0, 1, 1, 1;\n"
        "wgmma.mma_async.sync.aligned.m64n32k16.f32.bf16.bf16 {o16,o17,o18,o19,o20,o21,o22,o23,o24,o25,o26,o27,o28,o29,o30,o31}, {a0,a1,a2,a3}, d8, p0, 1, 1, 1;\n"
        "wgmma.mma_async.sync.aligned.m64n32k16.f32.bf16.bf16 {o0,o1,o2,o3,o4,o5,o6,o7,o8,o9,o10,o11,o12,o13,o14,o15}, {a4,a5,a6,a7}, d1, p1, 1, 1, 1;\n"
        "wgmma.mma_async.sync.aligned.m64n32k16.f32.bf16.bf16 {o16,o17,o18,o19,o20,o21,o22,o23,o24,o25,o26,o27,o28,o29,o30,o31}, {a4,a5,a6,a7}, d9, p1, 1, 1, 1;\n"
        "wgmma.mma_async.sync.aligned.m64n32k16.f32.bf16.bf16 {o0,o1,o2,o3,o4,o5,o6,o7,o8,o9,o10,o11,o12,o13,o14,o15}, {a8,a9,a10,a11}, d2, p1, 1, 1, 1;\n"
        "wgmma.mma_async.sync.aligned.m64n32k16.f32.bf16.bf16 {o16,o17,o18,o19,o20,o21,o22,o23,o24,o25,o26,o27,o28,o29,o30,o31}, {a8,a9,a10,a11}, d10, p1, 1, 1, 1;\n"
        "wgmma.mma_async.sync.aligned.m64n32k16.f32.bf16.bf16 {o0,o1,o2,o3,o4,o5,o6,o7,o8,o9,o10,o11,o12,o13,o14,o15}, {a12,a13,a14,a15}, d3, p1, 1, 1, 1;\n"
        "wgmma.mma_async.sync.aligned.m64n32k16.f32.bf16.bf16 {o16,o17,o18,o19,o20,o21,o22,o23,o24,o25,o26,o27,o28,o29,o30,o31}, {a12,a13,a14,a15}, d11, p1, 1, 1, 1;\n"
        "wgmma.mma_async.sync.aligned.m64n32k16.f32.bf16.bf16 {o0,o1,o2,o3,o4,o5,o6,o7,o8,o9,o10,o11,o12,o13,o14,o15}, {a16,a17,a18,a19}, d4, p1, 1, 1, 1;\n"
        "wgmma.mma_async.sync.aligned.m64n32k16.f32.bf16.bf16 {o16,o17,o18,o19,o20,o21,o22,o23,o24,o25,o26,o27,o28,o29,o30,o31}, {a16,a17,a18,a19}, d12, p1, 1, 1, 1;\n"
        "wgmma.mma_async.sync.aligned.m64n32k16.f32.bf16.bf16 {o0,o1,o2,o3,o4,o5,o6,o7,o8,o9,o10,o11,o12,o13,o14,o15}, {a20,a21,a22,a23}, d5, p1, 1, 1, 1;\n"
        "wgmma.mma_async.sync.aligned.m64n32k16.f32.bf16.bf16 {o16,o17,o18,o19,o20,o21,o22,o23,o24,o25,o26,o27,o28,o29,o30,o31}, {a20,a21,a22,a23}, d13, p1, 1, 1, 1;\n"
        "wgmma.mma_async.sync.aligned.m64n32k16.f32.bf16.bf16 {o0,o1,o2,o3,o4,o5,o6,o7,o8,o9,o10,o11,o12,o13,o14,o15}, {a24,a25,a26,a27}, d6, p1, 1, 1, 1;\n"
        "wgmma.mma_async.sync.aligned.m64n32k16.f32.bf16.bf16 {o16,o17,o18,o19,o20,o21,o22,o23,o24,o25,o26,o27,o28,o29,o30,o31}, {a24,a25,a26,a27}, d14, p1, 1, 1, 1;\n"
        "wgmma.mma_async.sync.aligned.m64n32k16.f32.bf16.bf16 {o0,o1,o2,o3,o4,o5,o6,o7,o8,o9,o10,o11,o12,o13,o14,o15}, {a28,a29,a30,a31}, d7, p1, 1, 1, 1;\n"
        "wgmma.mma_async.sync.aligned.m64n32k16.f32.bf16.bf16 {o16,o17,o18,o19,o20,o21,o22,o23,o24,o25,o26,o27,o28,o29,o30,o31}, {a28,a29,a30,a31}, d15, p1, 1, 1, 1;\n"
        "wgmma.commit_group.sync.aligned;\n@nv bra.uni END;\n@s0 st.global.v4.b32 [%65+0], {k0,k1,k2,k3};\n@s1 st.global.v4.b32 [%66+0], {k4,k5,k6,k7};\n"
        "@s0 st.global.v4.b32 [%65+64], {k8,k9,k10,k11};\n@s1 st.global.v4.b32 [%66+64], {k12,k13,k14,k15};\n@nv bra.uni END;\nwgmma.wait_group.sync.aligned 0;\n"
        "cvt.rn.bf16x2.f32 k0, o1, o0;\ncvt.rn.bf16x2.f32 k1, o5, o4;\ncvt.rn.bf16x2.f32 k2, o9, o8;\ncvt.rn.bf16x2.f32 k3, o13, o12;\n"
        "cvt.rn.bf16x2.f32 k4, o3, o2;\ncvt.rn.bf16x2.f32 k5, o7, o6;\ncvt.rn.bf16x2.f32 k6, o11, o10;\ncvt.rn.bf16x2.f32 k7, o15, o14;\n"
        "cvt.rn.bf16x2.f32 k8, o17, o16;\ncvt.rn.bf16x2.f32 k9, o21, o20;\ncvt.rn.bf16x2.f32 k10, o25, o24;\ncvt.rn.bf16x2.f32 k11, o29, o28;\n"
        "cvt.rn.bf16x2.f32 k12, o19, o18;\ncvt.rn.bf16x2.f32 k13, o23, o22;\ncvt.rn.bf16x2.f32 k14, o27, o26;\ncvt.rn.bf16x2.f32 k15, o31, o30;\n"
        "ld.volatile.shared.v4.b32 {c0,c1,c2,c3}, [%64+0];\nld.volatile.shared.v4.b32 {c4,c5,c6,c7}, [%64+8192];\n"
        "ld.volatile.shared.v4.b32 {c8,c9,c10,c11}, [%64+16];\nld.volatile.shared.v4.b32 {c12,c13,c14,c15}, [%64+8208];\nand.b32 t, c0, 0xffe;\n"
        "mad.lo.u32 t, t, 4, 0x200000;\nmov.b64 d0, {t, h};\nand.b32 t, c1, 0xffe;\nmad.lo.u32 t, t, 4, 0x200000;\nmov.b64 d1, {t, h};\nand.b32 t, c2, 0xffe;\n"
        "mad.lo.u32 t, t, 4, 0x200000;\nmov.b64 d2, {t, h};\nand.b32 t, c3, 0xffe;\nmad.lo.u32 t, t, 4, 0x200000;\nmov.b64 d3, {t, h};\nand.b32 t, c4, 0xffe;\n"
        "mad.lo.u32 t, t, 4, 0x200000;\nmov.b64 d4, {t, h};\nand.b32 t, c5, 0xffe;\nmad.lo.u32 t, t, 4, 0x200000;\nmov.b64 d5, {t, h};\nand.b32 t, c6, 0xffe;\n"
        "mad.lo.u32 t, t, 4, 0x200000;\nmov.b64 d6, {t, h};\nand.b32 t, c7, 0xffe;\nmad.lo.u32 t, t, 4, 0x200000;\nmov.b64 d7, {t, h};\nand.b32 t, c8, 0xffe;\n"
        "mad.lo.u32 t, t, 4, 0x200000;\nmov.b64 d8, {t, h};\nand.b32 t, c9, 0xffe;\nmad.lo.u32 t, t, 4, 0x200000;\nmov.b64 d9, {t, h};\nand.b32 t, c10, 0xffe;\n"
        "mad.lo.u32 t, t, 4, 0x200000;\nmov.b64 d10, {t, h};\nand.b32 t, c11, 0xffe;\nmad.lo.u32 t, t, 4, 0x200000;\nmov.b64 d11, {t, h};\n"
        "and.b32 t, c12, 0xffe;\nmad.lo.u32 t, t, 4, 0x200000;\nmov.b64 d12, {t, h};\nand.b32 t, c13, 0xffe;\nmad.lo.u32 t, t, 4, 0x200000;\n"
        "mov.b64 d13, {t, h};\nand.b32 t, c14, 0xffe;\nmad.lo.u32 t, t, 4, 0x200000;\nmov.b64 d14, {t, h};\nand.b32 t, c15, 0xffe;\n"
        "mad.lo.u32 t, t, 4, 0x200000;\nmov.b64 d15, {t, h};\nwgmma.fence.sync.aligned;\n"
        "wgmma.mma_async.sync.aligned.m64n32k16.f32.bf16.bf16 {o0,o1,o2,o3,o4,o5,o6,o7,o8,o9,o10,o11,o12,o13,o14,o15}, {b0,b1,b2,b3}, d0, p0, 1, 1, 1;\n"
        "wgmma.mma_async.sync.aligned.m64n32k16.f32.bf16.bf16 {o16,o17,o18,o19,o20,o21,o22,o23,o24,o25,o26,o27,o28,o29,o30,o31}, {b0,b1,b2,b3}, d8, p0, 1, 1, 1;\n"
        "wgmma.mma_async.sync.aligned.m64n32k16.f32.bf16.bf16 {o0,o1,o2,o3,o4,o5,o6,o7,o8,o9,o10,o11,o12,o13,o14,o15}, {b4,b5,b6,b7}, d1, p1, 1, 1, 1;\n"
        "wgmma.mma_async.sync.aligned.m64n32k16.f32.bf16.bf16 {o16,o17,o18,o19,o20,o21,o22,o23,o24,o25,o26,o27,o28,o29,o30,o31}, {b4,b5,b6,b7}, d9, p1, 1, 1, 1;\n"
        "wgmma.mma_async.sync.aligned.m64n32k16.f32.bf16.bf16 {o0,o1,o2,o3,o4,o5,o6,o7,o8,o9,o10,o11,o12,o13,o14,o15}, {b8,b9,b10,b11}, d2, p1, 1, 1, 1;\n"
        "wgmma.mma_async.sync.aligned.m64n32k16.f32.bf16.bf16 {o16,o17,o18,o19,o20,o21,o22,o23,o24,o25,o26,o27,o28,o29,o30,o31}, {b8,b9,b10,b11}, d10, p1, 1, 1, 1;\n"
        "wgmma.mma_async.sync.aligned.m64n32k16.f32.bf16.bf16 {o0,o1,o2,o3,o4,o5,o6,o7,o8,o9,o10,o11,o12,o13,o14,o15}, {b12,b13,b14,b15}, d3, p1, 1, 1, 1;\n"
        "wgmma.mma_async.sync.aligned.m64n32k16.f32.bf16.bf16 {o16,o17,o18,o19,o20,o21,o22,o23,o24,o25,o26,o27,o28,o29,o30,o31}, {b12,b13,b14,b15}, d11, p1, 1, 1, 1;\n"
        "wgmma.mma_async.sync.aligned.m64n32k16.f32.bf16.bf16 {o0,o1,o2,o3,o4,o5,o6,o7,o8,o9,o10,o11,o12,o13,o14,o15}, {b16,b17,b18,b19}, d4, p1, 1, 1, 1;\n"
        "wgmma.mma_async.sync.aligned.m64n32k16.f32.bf16.bf16 {o16,o17,o18,o19,o20,o21,o22,o23,o24,o25,o26,o27,o28,o29,o30,o31}, {b16,b17,b18,b19}, d12, p1, 1, 1, 1;\n"
        "wgmma.mma_async.sync.aligned.m64n32k16.f32.bf16.bf16 {o0,o1,o2,o3,o4,o5,o6,o7,o8,o9,o10,o11,o12,o13,o14,o15}, {b20,b21,b22,b23}, d5, p1, 1, 1, 1;\n"
        "wgmma.mma_async.sync.aligned.m64n32k16.f32.bf16.bf16 {o16,o17,o18,o19,o20,o21,o22,o23,o24,o25,o26,o27,o28,o29,o30,o31}, {b20,b21,b22,b23}, d13, p1, 1, 1, 1;\n"
        "wgmma.mma_async.sync.aligned.m64n32k16.f32.bf16.bf16 {o0,o1,o2,o3,o4,o5,o6,o7,o8,o9,o10,o11,o12,o13,o14,o15}, {b24,b25,b26,b27}, d6, p1, 1, 1, 1;\n"
        "wgmma.mma_async.sync.aligned.m64n32k16.f32.bf16.bf16 {o16,o17,o18,o19,o20,o21,o22,o23,o24,o25,o26,o27,o28,o29,o30,o31}, {b24,b25,b26,b27}, d14, p1, 1, 1, 1;\n"
        "wgmma.mma_async.sync.aligned.m64n32k16.f32.bf16.bf16 {o0,o1,o2,o3,o4,o5,o6,o7,o8,o9,o10,o11,o12,o13,o14,o15}, {b28,b29,b30,b31}, d7, p1, 1, 1, 1;\n"
        "wgmma.mma_async.sync.aligned.m64n32k16.f32.bf16.bf16 {o16,o17,o18,o19,o20,o21,o22,o23,o24,o25,o26,o27,o28,o29,o30,o31}, {b28,b29,b30,b31}, d15, p1, 1, 1, 1;\n"
        "wgmma.commit_group.sync.aligned;\n@nv bra.uni END;\n@s0 st.global.v4.b32 [%65+128], {k0,k1,k2,k3};\n@s1 st.global.v4.b32 [%66+128], {k4,k5,k6,k7};\n"
        "@s0 st.global.v4.b32 [%65+192], {k8,k9,k10,k11};\n@s1 st.global.v4.b32 [%66+192], {k12,k13,k14,k15};\n@nv bra.uni END;\n"
        "wgmma.wait_group.sync.aligned 0;\ncvt.rn.bf16x2.f32 k0, o1, o0;\ncvt.rn.bf16x2.f32 k1, o5, o4;\ncvt.rn.bf16x2.f32 k2, o9, o8;\n"
        "cvt.rn.bf16x2.f32 k3, o13, o12;\ncvt.rn.bf16x2.f32 k4, o3, o2;\ncvt.rn.bf16x2.f32 k5, o7, o6;\ncvt.rn.bf16x2.f32 k6, o11, o10;\n"
        "cvt.rn.bf16x2.f32 k7, o15, o14;\ncvt.rn.bf16x2.f32 k8, o17, o16;\ncvt.rn.bf16x2.f32 k9, o21, o20;\ncvt.rn.bf16x2.f32 k10, o25, o24;\n"
        "cvt.rn.bf16x2.f32 k11, o29, o28;\ncvt.rn.bf16x2.f32 k12, o19, o18;\ncvt.rn.bf16x2.f32 k13, o23, o22;\ncvt.rn.bf16x2.f32 k14, o27, o26;\n"
        "cvt.rn.bf16x2.f32 k15, o31, o30;\nld.volatile.shared.v4.b32 {c0,c1,c2,c3}, [%64+32];\nld.volatile.shared.v4.b32 {c4,c5,c6,c7}, [%64+8224];\n"
        "ld.volatile.shared.v4.b32 {c8,c9,c10,c11}, [%64+48];\nld.volatile.shared.v4.b32 {c12,c13,c14,c15}, [%64+8240];\nand.b32 t, c0, 0xffe;\n"
        "mad.lo.u32 t, t, 4, 0x200000;\nmov.b64 d0, {t, h};\nand.b32 t, c1, 0xffe;\nmad.lo.u32 t, t, 4, 0x200000;\nmov.b64 d1, {t, h};\nand.b32 t, c2, 0xffe;\n"
        "mad.lo.u32 t, t, 4, 0x200000;\nmov.b64 d2, {t, h};\nand.b32 t, c3, 0xffe;\nmad.lo.u32 t, t, 4, 0x200000;\nmov.b64 d3, {t, h};\nand.b32 t, c4, 0xffe;\n"
        "mad.lo.u32 t, t, 4, 0x200000;\nmov.b64 d4, {t, h};\nand.b32 t, c5, 0xffe;\nmad.lo.u32 t, t, 4, 0x200000;\nmov.b64 d5, {t, h};\nand.b32 t, c6, 0xffe;\n"
        "mad.lo.u32 t, t, 4, 0x200000;\nmov.b64 d6, {t, h};\nand.b32 t, c7, 0xffe;\nmad.lo.u32 t, t, 4, 0x200000;\nmov.b64 d7, {t, h};\nand.b32 t, c8, 0xffe;\n"
        "mad.lo.u32 t, t, 4, 0x200000;\nmov.b64 d8, {t, h};\nand.b32 t, c9, 0xffe;\nmad.lo.u32 t, t, 4, 0x200000;\nmov.b64 d9, {t, h};\nand.b32 t, c10, 0xffe;\n"
        "mad.lo.u32 t, t, 4, 0x200000;\nmov.b64 d10, {t, h};\nand.b32 t, c11, 0xffe;\nmad.lo.u32 t, t, 4, 0x200000;\nmov.b64 d11, {t, h};\n"
        "and.b32 t, c12, 0xffe;\nmad.lo.u32 t, t, 4, 0x200000;\nmov.b64 d12, {t, h};\nand.b32 t, c13, 0xffe;\nmad.lo.u32 t, t, 4, 0x200000;\n"
        "mov.b64 d13, {t, h};\nand.b32 t, c14, 0xffe;\nmad.lo.u32 t, t, 4, 0x200000;\nmov.b64 d14, {t, h};\nand.b32 t, c15, 0xffe;\n"
        "mad.lo.u32 t, t, 4, 0x200000;\nmov.b64 d15, {t, h};\nwgmma.fence.sync.aligned;\n"
        "wgmma.mma_async.sync.aligned.m64n32k16.f32.bf16.bf16 {o0,o1,o2,o3,o4,o5,o6,o7,o8,o9,o10,o11,o12,o13,o14,o15}, {b0,b1,b2,b3}, d0, p0, 1, 1, 1;\n"
        "wgmma.mma_async.sync.aligned.m64n32k16.f32.bf16.bf16 {o16,o17,o18,o19,o20,o21,o22,o23,o24,o25,o26,o27,o28,o29,o30,o31}, {b0,b1,b2,b3}, d8, p0, 1, 1, 1;\n"
        "wgmma.mma_async.sync.aligned.m64n32k16.f32.bf16.bf16 {o0,o1,o2,o3,o4,o5,o6,o7,o8,o9,o10,o11,o12,o13,o14,o15}, {b4,b5,b6,b7}, d1, p1, 1, 1, 1;\n"
        "wgmma.mma_async.sync.aligned.m64n32k16.f32.bf16.bf16 {o16,o17,o18,o19,o20,o21,o22,o23,o24,o25,o26,o27,o28,o29,o30,o31}, {b4,b5,b6,b7}, d9, p1, 1, 1, 1;\n"
        "wgmma.mma_async.sync.aligned.m64n32k16.f32.bf16.bf16 {o0,o1,o2,o3,o4,o5,o6,o7,o8,o9,o10,o11,o12,o13,o14,o15}, {b8,b9,b10,b11}, d2, p1, 1, 1, 1;\n"
        "wgmma.mma_async.sync.aligned.m64n32k16.f32.bf16.bf16 {o16,o17,o18,o19,o20,o21,o22,o23,o24,o25,o26,o27,o28,o29,o30,o31}, {b8,b9,b10,b11}, d10, p1, 1, 1, 1;\n"
        "wgmma.mma_async.sync.aligned.m64n32k16.f32.bf16.bf16 {o0,o1,o2,o3,o4,o5,o6,o7,o8,o9,o10,o11,o12,o13,o14,o15}, {b12,b13,b14,b15}, d3, p1, 1, 1, 1;\n"
        "wgmma.mma_async.sync.aligned.m64n32k16.f32.bf16.bf16 {o16,o17,o18,o19,o20,o21,o22,o23,o24,o25,o26,o27,o28,o29,o30,o31}, {b12,b13,b14,b15}, d11, p1, 1, 1, 1;\n"
        "wgmma.mma_async.sync.aligned.m64n32k16.f32.bf16.bf16 {o0,o1,o2,o3,o4,o5,o6,o7,o8,o9,o10,o11,o12,o13,o14,o15}, {b16,b17,b18,b19}, d4, p1, 1, 1, 1;\n"
        "wgmma.mma_async.sync.aligned.m64n32k16.f32.bf16.bf16 {o16,o17,o18,o19,o20,o21,o22,o23,o24,o25,o26,o27,o28,o29,o30,o31}, {b16,b17,b18,b19}, d12, p1, 1, 1, 1;\n"
        "wgmma.mma_async.sync.aligned.m64n32k16.f32.bf16.bf16 {o0,o1,o2,o3,o4,o5,o6,o7,o8,o9,o10,o11,o12,o13,o14,o15}, {b20,b21,b22,b23}, d5, p1, 1, 1, 1;\n"
        "wgmma.mma_async.sync.aligned.m64n32k16.f32.bf16.bf16 {o16,o17,o18,o19,o20,o21,o22,o23,o24,o25,o26,o27,o28,o29,o30,o31}, {b20,b21,b22,b23}, d13, p1, 1, 1, 1;\n"
        "wgmma.mma_async.sync.aligned.m64n32k16.f32.bf16.bf16 {o0,o1,o2,o3,o4,o5,o6,o7,o8,o9,o10,o11,o12,o13,o14,o15}, {b24,b25,b26,b27}, d6, p1, 1, 1, 1;\n"
        "wgmma.mma_async.sync.aligned.m64n32k16.f32.bf16.bf16 {o16,o17,o18,o19,o20,o21,o22,o23,o24,o25,o26,o27,o28,o29,o30,o31}, {b24,b25,b26,b27}, d14, p1, 1, 1, 1;\n"
        "wgmma.mma_async.sync.aligned.m64n32k16.f32.bf16.bf16 {o0,o1,o2,o3,o4,o5,o6,o7,o8,o9,o10,o11,o12,o13,o14,o15}, {b28,b29,b30,b31}, d7, p1, 1, 1, 1;\n"
        "wgmma.mma_async.sync.aligned.m64n32k16.f32.bf16.bf16 {o16,o17,o18,o19,o20,o21,o22,o23,o24,o25,o26,o27,o28,o29,o30,o31}, {b28,b29,b30,b31}, d15, p1, 1, 1, 1;\n"
        "wgmma.commit_group.sync.aligned;\n@nv bra.uni END;\n@s2 st.global.v4.b32 [%67+0], {k0,k1,k2,k3};\n@s3 st.global.v4.b32 [%68+0], {k4,k5,k6,k7};\n"
        "@s2 st.global.v4.b32 [%67+64], {k8,k9,k10,k11};\n@s3 st.global.v4.b32 [%68+64], {k12,k13,k14,k15};\n@nv bra.uni END;\nwgmma.wait_group.sync.aligned 0;\n"
        "cvt.rn.bf16x2.f32 k0, o1, o0;\ncvt.rn.bf16x2.f32 k1, o5, o4;\ncvt.rn.bf16x2.f32 k2, o9, o8;\ncvt.rn.bf16x2.f32 k3, o13, o12;\n"
        "cvt.rn.bf16x2.f32 k4, o3, o2;\ncvt.rn.bf16x2.f32 k5, o7, o6;\ncvt.rn.bf16x2.f32 k6, o11, o10;\ncvt.rn.bf16x2.f32 k7, o15, o14;\n"
        "cvt.rn.bf16x2.f32 k8, o17, o16;\ncvt.rn.bf16x2.f32 k9, o21, o20;\ncvt.rn.bf16x2.f32 k10, o25, o24;\ncvt.rn.bf16x2.f32 k11, o29, o28;\n"
        "cvt.rn.bf16x2.f32 k12, o19, o18;\ncvt.rn.bf16x2.f32 k13, o23, o22;\ncvt.rn.bf16x2.f32 k14, o27, o26;\ncvt.rn.bf16x2.f32 k15, o31, o30;\n"
        "@s2 st.global.v4.b32 [%67+128], {k0,k1,k2,k3};\n@s3 st.global.v4.b32 [%68+128], {k4,k5,k6,k7};\n@s2 st.global.v4.b32 [%67+192], {k8,k9,k10,k11};\n"
        "@s3 st.global.v4.b32 [%68+192], {k12,k13,k14,k15};\n"
        "END:\n}\n"
        ::"r"(pk[0]), "r"(pk[1]), "r"(pk[2]), "r"(pk[3]), "r"(pk[4]), "r"(pk[5]), "r"(pk[6]), "r"(pk[7]), "r"(pk[8]), "r"(pk[9]), "r"(pk[10]),
          "r"(pk[11]), "r"(pk[12]), "r"(pk[13]), "r"(pk[14]), "r"(pk[15]), "r"(pk[16]), "r"(pk[17]), "r"(pk[18]), "r"(pk[19]), "r"(pk[20]),
          "r"(pk[21]), "r"(pk[22]), "r"(pk[23]), "r"(pk[24]), "r"(pk[25]), "r"(pk[26]), "r"(pk[27]), "r"(pk[28]), "r"(pk[29]), "r"(pk[30]),
          "r"(pk[31]), "r"(pk[32]), "r"(pk[33]), "r"(pk[34]), "r"(pk[35]), "r"(pk[36]), "r"(pk[37]), "r"(pk[38]), "r"(pk[39]), "r"(pk[40]),
          "r"(pk[41]), "r"(pk[42]), "r"(pk[43]), "r"(pk[44]), "r"(pk[45]), "r"(pk[46]), "r"(pk[47]), "r"(pk[48]), "r"(pk[49]), "r"(pk[50]),
          "r"(pk[51]), "r"(pk[52]), "r"(pk[53]), "r"(pk[54]), "r"(pk[55]), "r"(pk[56]), "r"(pk[57]), "r"(pk[58]), "r"(pk[59]), "r"(pk[60]),
          "r"(pk[61]), "r"(pk[62]), "r"(pk[63]), "r"(ra), "l"(p[0]), "l"(p[1]), "l"(p[2]), "l"(p[3]), "r"(v[0]), "r"(v[1]), "r"(v[2]), "r"(v[3]),
          "r"(ba)
        : "memory");
}
__device__ __forceinline__ void project3(const uint32_t (&pk)[48], uint32_t ra, uint32_t ba, uint4* const (&p)[3], const uint32_t (&v)[3]) {
    asm volatile(
        "{\n.reg .pred p0, p1, q0, q1, nv, s<4>;\n.reg .b32 t, h, c<16>, a<32>, b<32>, k<16>;\n.reg .b64 d<16>;\n.reg .f32 o<32>;\nsetp.ne.b32 p0, 0, 0;\n"
        "setp.eq.b32 p1, 0, 0;\nmov.b32 h, 8;\nsetp.eq.u32 nv, %48, 0;\nvote.sync.any.pred nv, nv, 0xffffffff;\nsetp.ne.b32 s0, %52, 0;\n"
        "setp.ne.b32 s1, %53, 0;\nsetp.ne.b32 s2, %54, 0;\nmovmatrix.sync.aligned.m8n8.trans.b16 a0, %0;\nmovmatrix.sync.aligned.m8n8.trans.b16 a1, %16;\n"
        "movmatrix.sync.aligned.m8n8.trans.b16 a2, %1;\nmovmatrix.sync.aligned.m8n8.trans.b16 a3, %17;\nmovmatrix.sync.aligned.m8n8.trans.b16 a4, %2;\n"
        "movmatrix.sync.aligned.m8n8.trans.b16 a5, %18;\nmovmatrix.sync.aligned.m8n8.trans.b16 a6, %3;\nmovmatrix.sync.aligned.m8n8.trans.b16 a7, %19;\n"
        "movmatrix.sync.aligned.m8n8.trans.b16 a8, %4;\nmovmatrix.sync.aligned.m8n8.trans.b16 a9, %20;\nmovmatrix.sync.aligned.m8n8.trans.b16 a10, %5;\n"
        "movmatrix.sync.aligned.m8n8.trans.b16 a11, %21;\nmovmatrix.sync.aligned.m8n8.trans.b16 a12, %6;\nmovmatrix.sync.aligned.m8n8.trans.b16 a13, %22;\n"
        "movmatrix.sync.aligned.m8n8.trans.b16 a14, %7;\nmovmatrix.sync.aligned.m8n8.trans.b16 a15, %23;\nmovmatrix.sync.aligned.m8n8.trans.b16 a16, %8;\n"
        "movmatrix.sync.aligned.m8n8.trans.b16 a17, %24;\nmovmatrix.sync.aligned.m8n8.trans.b16 a18, %9;\nmovmatrix.sync.aligned.m8n8.trans.b16 a19, %25;\n"
        "movmatrix.sync.aligned.m8n8.trans.b16 a20, %10;\nmovmatrix.sync.aligned.m8n8.trans.b16 a21, %26;\nmovmatrix.sync.aligned.m8n8.trans.b16 a22, %11;\n"
        "movmatrix.sync.aligned.m8n8.trans.b16 a23, %27;\nmovmatrix.sync.aligned.m8n8.trans.b16 a24, %12;\nmovmatrix.sync.aligned.m8n8.trans.b16 a25, %28;\n"
        "movmatrix.sync.aligned.m8n8.trans.b16 a26, %13;\nmovmatrix.sync.aligned.m8n8.trans.b16 a27, %29;\nmovmatrix.sync.aligned.m8n8.trans.b16 a28, %14;\n"
        "movmatrix.sync.aligned.m8n8.trans.b16 a29, %30;\nmovmatrix.sync.aligned.m8n8.trans.b16 a30, %15;\nmovmatrix.sync.aligned.m8n8.trans.b16 a31, %31;\n"
        "mov.b32 t, 0;\n"
        "W0:\nmbarrier.try_wait.parity.shared.b64 q0, [%55+0], 0;\nadd.u32 t, t, 1;\nsetp.lt.and.u32 q1, t, 1000000, !q0;\n@q1 bra.uni W0;\nmov.b32 t, 0;\n"
        "W1:\nmbarrier.try_wait.parity.shared.b64 q0, [%55+8], 0;\nadd.u32 t, t, 1;\nsetp.lt.and.u32 q1, t, 1000000, !q0;\n@q1 bra.uni W1;\nmov.b32 t, 0;\n"
        "W2:\nmbarrier.try_wait.parity.shared.b64 q0, [%55+16], 0;\nadd.u32 t, t, 1;\nsetp.lt.and.u32 q1, t, 1000000, !q0;\n@q1 bra.uni W2;\nmov.b32 t, 0;\n"
        "W3:\nmbarrier.try_wait.parity.shared.b64 q0, [%55+24], 0;\nadd.u32 t, t, 1;\nsetp.lt.and.u32 q1, t, 1000000, !q0;\n@q1 bra.uni W3;\n"
        "ld.volatile.shared.v4.b32 {c0,c1,c2,c3}, [%48+0];\nld.volatile.shared.v4.b32 {c4,c5,c6,c7}, [%48+8192];\n"
        "ld.volatile.shared.v4.b32 {c8,c9,c10,c11}, [%48+16];\nld.volatile.shared.v4.b32 {c12,c13,c14,c15}, [%48+8208];\nand.b32 t, c0, 0xffe;\n"
        "mad.lo.u32 t, t, 4, 0x200000;\nmov.b64 d0, {t, h};\nand.b32 t, c1, 0xffe;\nmad.lo.u32 t, t, 4, 0x200000;\nmov.b64 d1, {t, h};\nand.b32 t, c2, 0xffe;\n"
        "mad.lo.u32 t, t, 4, 0x200000;\nmov.b64 d2, {t, h};\nand.b32 t, c3, 0xffe;\nmad.lo.u32 t, t, 4, 0x200000;\nmov.b64 d3, {t, h};\nand.b32 t, c4, 0xffe;\n"
        "mad.lo.u32 t, t, 4, 0x200000;\nmov.b64 d4, {t, h};\nand.b32 t, c5, 0xffe;\nmad.lo.u32 t, t, 4, 0x200000;\nmov.b64 d5, {t, h};\nand.b32 t, c6, 0xffe;\n"
        "mad.lo.u32 t, t, 4, 0x200000;\nmov.b64 d6, {t, h};\nand.b32 t, c7, 0xffe;\nmad.lo.u32 t, t, 4, 0x200000;\nmov.b64 d7, {t, h};\nand.b32 t, c8, 0xffe;\n"
        "mad.lo.u32 t, t, 4, 0x200000;\nmov.b64 d8, {t, h};\nand.b32 t, c9, 0xffe;\nmad.lo.u32 t, t, 4, 0x200000;\nmov.b64 d9, {t, h};\nand.b32 t, c10, 0xffe;\n"
        "mad.lo.u32 t, t, 4, 0x200000;\nmov.b64 d10, {t, h};\nand.b32 t, c11, 0xffe;\nmad.lo.u32 t, t, 4, 0x200000;\nmov.b64 d11, {t, h};\n"
        "and.b32 t, c12, 0xffe;\nmad.lo.u32 t, t, 4, 0x200000;\nmov.b64 d12, {t, h};\nand.b32 t, c13, 0xffe;\nmad.lo.u32 t, t, 4, 0x200000;\n"
        "mov.b64 d13, {t, h};\nand.b32 t, c14, 0xffe;\nmad.lo.u32 t, t, 4, 0x200000;\nmov.b64 d14, {t, h};\nand.b32 t, c15, 0xffe;\n"
        "mad.lo.u32 t, t, 4, 0x200000;\nmov.b64 d15, {t, h};\nwgmma.fence.sync.aligned;\n"
        "wgmma.mma_async.sync.aligned.m64n32k16.f32.bf16.bf16 {o0,o1,o2,o3,o4,o5,o6,o7,o8,o9,o10,o11,o12,o13,o14,o15}, {a0,a1,a2,a3}, d0, p0, 1, 1, 1;\n"
        "wgmma.mma_async.sync.aligned.m64n32k16.f32.bf16.bf16 {o16,o17,o18,o19,o20,o21,o22,o23,o24,o25,o26,o27,o28,o29,o30,o31}, {a0,a1,a2,a3}, d8, p0, 1, 1, 1;\n"
        "wgmma.mma_async.sync.aligned.m64n32k16.f32.bf16.bf16 {o0,o1,o2,o3,o4,o5,o6,o7,o8,o9,o10,o11,o12,o13,o14,o15}, {a4,a5,a6,a7}, d1, p1, 1, 1, 1;\n"
        "wgmma.mma_async.sync.aligned.m64n32k16.f32.bf16.bf16 {o16,o17,o18,o19,o20,o21,o22,o23,o24,o25,o26,o27,o28,o29,o30,o31}, {a4,a5,a6,a7}, d9, p1, 1, 1, 1;\n"
        "wgmma.mma_async.sync.aligned.m64n32k16.f32.bf16.bf16 {o0,o1,o2,o3,o4,o5,o6,o7,o8,o9,o10,o11,o12,o13,o14,o15}, {a8,a9,a10,a11}, d2, p1, 1, 1, 1;\n"
        "wgmma.mma_async.sync.aligned.m64n32k16.f32.bf16.bf16 {o16,o17,o18,o19,o20,o21,o22,o23,o24,o25,o26,o27,o28,o29,o30,o31}, {a8,a9,a10,a11}, d10, p1, 1, 1, 1;\n"
        "wgmma.mma_async.sync.aligned.m64n32k16.f32.bf16.bf16 {o0,o1,o2,o3,o4,o5,o6,o7,o8,o9,o10,o11,o12,o13,o14,o15}, {a12,a13,a14,a15}, d3, p1, 1, 1, 1;\n"
        "wgmma.mma_async.sync.aligned.m64n32k16.f32.bf16.bf16 {o16,o17,o18,o19,o20,o21,o22,o23,o24,o25,o26,o27,o28,o29,o30,o31}, {a12,a13,a14,a15}, d11, p1, 1, 1, 1;\n"
        "wgmma.mma_async.sync.aligned.m64n32k16.f32.bf16.bf16 {o0,o1,o2,o3,o4,o5,o6,o7,o8,o9,o10,o11,o12,o13,o14,o15}, {a16,a17,a18,a19}, d4, p1, 1, 1, 1;\n"
        "wgmma.mma_async.sync.aligned.m64n32k16.f32.bf16.bf16 {o16,o17,o18,o19,o20,o21,o22,o23,o24,o25,o26,o27,o28,o29,o30,o31}, {a16,a17,a18,a19}, d12, p1, 1, 1, 1;\n"
        "wgmma.mma_async.sync.aligned.m64n32k16.f32.bf16.bf16 {o0,o1,o2,o3,o4,o5,o6,o7,o8,o9,o10,o11,o12,o13,o14,o15}, {a20,a21,a22,a23}, d5, p1, 1, 1, 1;\n"
        "wgmma.mma_async.sync.aligned.m64n32k16.f32.bf16.bf16 {o16,o17,o18,o19,o20,o21,o22,o23,o24,o25,o26,o27,o28,o29,o30,o31}, {a20,a21,a22,a23}, d13, p1, 1, 1, 1;\n"
        "wgmma.mma_async.sync.aligned.m64n32k16.f32.bf16.bf16 {o0,o1,o2,o3,o4,o5,o6,o7,o8,o9,o10,o11,o12,o13,o14,o15}, {a24,a25,a26,a27}, d6, p1, 1, 1, 1;\n"
        "wgmma.mma_async.sync.aligned.m64n32k16.f32.bf16.bf16 {o16,o17,o18,o19,o20,o21,o22,o23,o24,o25,o26,o27,o28,o29,o30,o31}, {a24,a25,a26,a27}, d14, p1, 1, 1, 1;\n"
        "wgmma.mma_async.sync.aligned.m64n32k16.f32.bf16.bf16 {o0,o1,o2,o3,o4,o5,o6,o7,o8,o9,o10,o11,o12,o13,o14,o15}, {a28,a29,a30,a31}, d7, p1, 1, 1, 1;\n"
        "wgmma.mma_async.sync.aligned.m64n32k16.f32.bf16.bf16 {o16,o17,o18,o19,o20,o21,o22,o23,o24,o25,o26,o27,o28,o29,o30,o31}, {a28,a29,a30,a31}, d15, p1, 1, 1, 1;\n"
        "wgmma.commit_group.sync.aligned;\n@nv bra.uni END;\nmovmatrix.sync.aligned.m8n8.trans.b16 b0, %32;\nmovmatrix.sync.aligned.m8n8.trans.b16 b2, %33;\n"
        "movmatrix.sync.aligned.m8n8.trans.b16 b3, %33;\nmovmatrix.sync.aligned.m8n8.trans.b16 b4, %34;\nmovmatrix.sync.aligned.m8n8.trans.b16 b5, %34;\n"
        "movmatrix.sync.aligned.m8n8.trans.b16 b6, %35;\nmovmatrix.sync.aligned.m8n8.trans.b16 b7, %35;\nmovmatrix.sync.aligned.m8n8.trans.b16 b8, %36;\n"
        "movmatrix.sync.aligned.m8n8.trans.b16 b9, %36;\nmovmatrix.sync.aligned.m8n8.trans.b16 b20, %42;\nmovmatrix.sync.aligned.m8n8.trans.b16 b21, %42;\n"
        "movmatrix.sync.aligned.m8n8.trans.b16 b22, %43;\nmovmatrix.sync.aligned.m8n8.trans.b16 b23, %43;\nmovmatrix.sync.aligned.m8n8.trans.b16 b24, %44;\n"
        "movmatrix.sync.aligned.m8n8.trans.b16 b25, %44;\nmovmatrix.sync.aligned.m8n8.trans.b16 b26, %45;\nmovmatrix.sync.aligned.m8n8.trans.b16 b27, %45;\n"
        "movmatrix.sync.aligned.m8n8.trans.b16 b28, %46;\nmovmatrix.sync.aligned.m8n8.trans.b16 b29, %46;\nmovmatrix.sync.aligned.m8n8.trans.b16 b30, %47;\n"
        "movmatrix.sync.aligned.m8n8.trans.b16 b31, %47;\nmovmatrix.sync.aligned.m8n8.trans.b16 b1, %32;\nmovmatrix.sync.aligned.m8n8.trans.b16 b10, %37;\n"
        "movmatrix.sync.aligned.m8n8.trans.b16 b11, %37;\nmovmatrix.sync.aligned.m8n8.trans.b16 b12, %38;\nmovmatrix.sync.aligned.m8n8.trans.b16 b13, %38;\n"
        "movmatrix.sync.aligned.m8n8.trans.b16 b14, %39;\nmovmatrix.sync.aligned.m8n8.trans.b16 b15, %39;\nmovmatrix.sync.aligned.m8n8.trans.b16 b16, %40;\n"
        "movmatrix.sync.aligned.m8n8.trans.b16 b17, %40;\nmovmatrix.sync.aligned.m8n8.trans.b16 b18, %41;\nmovmatrix.sync.aligned.m8n8.trans.b16 b19, %41;\n"
        "@nv bra.uni END;\nwgmma.wait_group.sync.aligned 0;\ncvt.rn.bf16x2.f32 k0, o1, o0;\ncvt.rn.bf16x2.f32 k1, o5, o4;\ncvt.rn.bf16x2.f32 k2, o9, o8;\n"
        "cvt.rn.bf16x2.f32 k3, o13, o12;\ncvt.rn.bf16x2.f32 k4, o3, o2;\ncvt.rn.bf16x2.f32 k5, o7, o6;\ncvt.rn.bf16x2.f32 k6, o11, o10;\n"
        "cvt.rn.bf16x2.f32 k7, o15, o14;\ncvt.rn.bf16x2.f32 k8, o17, o16;\ncvt.rn.bf16x2.f32 k9, o21, o20;\ncvt.rn.bf16x2.f32 k10, o25, o24;\n"
        "cvt.rn.bf16x2.f32 k11, o29, o28;\ncvt.rn.bf16x2.f32 k12, o19, o18;\ncvt.rn.bf16x2.f32 k13, o23, o22;\ncvt.rn.bf16x2.f32 k14, o27, o26;\n"
        "cvt.rn.bf16x2.f32 k15, o31, o30;\nld.volatile.shared.v4.b32 {c0,c1,c2,c3}, [%48+32];\nld.volatile.shared.v4.b32 {c4,c5,c6,c7}, [%48+8224];\n"
        "ld.volatile.shared.v4.b32 {c8,c9,c10,c11}, [%48+48];\nld.volatile.shared.v4.b32 {c12,c13,c14,c15}, [%48+8240];\nand.b32 t, c0, 0xffe;\n"
        "mad.lo.u32 t, t, 4, 0x200000;\nmov.b64 d0, {t, h};\nand.b32 t, c1, 0xffe;\nmad.lo.u32 t, t, 4, 0x200000;\nmov.b64 d1, {t, h};\nand.b32 t, c2, 0xffe;\n"
        "mad.lo.u32 t, t, 4, 0x200000;\nmov.b64 d2, {t, h};\nand.b32 t, c3, 0xffe;\nmad.lo.u32 t, t, 4, 0x200000;\nmov.b64 d3, {t, h};\nand.b32 t, c4, 0xffe;\n"
        "mad.lo.u32 t, t, 4, 0x200000;\nmov.b64 d4, {t, h};\nand.b32 t, c5, 0xffe;\nmad.lo.u32 t, t, 4, 0x200000;\nmov.b64 d5, {t, h};\nand.b32 t, c6, 0xffe;\n"
        "mad.lo.u32 t, t, 4, 0x200000;\nmov.b64 d6, {t, h};\nand.b32 t, c7, 0xffe;\nmad.lo.u32 t, t, 4, 0x200000;\nmov.b64 d7, {t, h};\nand.b32 t, c8, 0xffe;\n"
        "mad.lo.u32 t, t, 4, 0x200000;\nmov.b64 d8, {t, h};\nand.b32 t, c9, 0xffe;\nmad.lo.u32 t, t, 4, 0x200000;\nmov.b64 d9, {t, h};\nand.b32 t, c10, 0xffe;\n"
        "mad.lo.u32 t, t, 4, 0x200000;\nmov.b64 d10, {t, h};\nand.b32 t, c11, 0xffe;\nmad.lo.u32 t, t, 4, 0x200000;\nmov.b64 d11, {t, h};\n"
        "and.b32 t, c12, 0xffe;\nmad.lo.u32 t, t, 4, 0x200000;\nmov.b64 d12, {t, h};\nand.b32 t, c13, 0xffe;\nmad.lo.u32 t, t, 4, 0x200000;\n"
        "mov.b64 d13, {t, h};\nand.b32 t, c14, 0xffe;\nmad.lo.u32 t, t, 4, 0x200000;\nmov.b64 d14, {t, h};\nand.b32 t, c15, 0xffe;\n"
        "mad.lo.u32 t, t, 4, 0x200000;\nmov.b64 d15, {t, h};\nwgmma.fence.sync.aligned;\n"
        "wgmma.mma_async.sync.aligned.m64n32k16.f32.bf16.bf16 {o0,o1,o2,o3,o4,o5,o6,o7,o8,o9,o10,o11,o12,o13,o14,o15}, {a0,a1,a2,a3}, d0, p0, 1, 1, 1;\n"
        "wgmma.mma_async.sync.aligned.m64n32k16.f32.bf16.bf16 {o16,o17,o18,o19,o20,o21,o22,o23,o24,o25,o26,o27,o28,o29,o30,o31}, {a0,a1,a2,a3}, d8, p0, 1, 1, 1;\n"
        "wgmma.mma_async.sync.aligned.m64n32k16.f32.bf16.bf16 {o0,o1,o2,o3,o4,o5,o6,o7,o8,o9,o10,o11,o12,o13,o14,o15}, {a4,a5,a6,a7}, d1, p1, 1, 1, 1;\n"
        "wgmma.mma_async.sync.aligned.m64n32k16.f32.bf16.bf16 {o16,o17,o18,o19,o20,o21,o22,o23,o24,o25,o26,o27,o28,o29,o30,o31}, {a4,a5,a6,a7}, d9, p1, 1, 1, 1;\n"
        "wgmma.mma_async.sync.aligned.m64n32k16.f32.bf16.bf16 {o0,o1,o2,o3,o4,o5,o6,o7,o8,o9,o10,o11,o12,o13,o14,o15}, {a8,a9,a10,a11}, d2, p1, 1, 1, 1;\n"
        "wgmma.mma_async.sync.aligned.m64n32k16.f32.bf16.bf16 {o16,o17,o18,o19,o20,o21,o22,o23,o24,o25,o26,o27,o28,o29,o30,o31}, {a8,a9,a10,a11}, d10, p1, 1, 1, 1;\n"
        "wgmma.mma_async.sync.aligned.m64n32k16.f32.bf16.bf16 {o0,o1,o2,o3,o4,o5,o6,o7,o8,o9,o10,o11,o12,o13,o14,o15}, {a12,a13,a14,a15}, d3, p1, 1, 1, 1;\n"
        "wgmma.mma_async.sync.aligned.m64n32k16.f32.bf16.bf16 {o16,o17,o18,o19,o20,o21,o22,o23,o24,o25,o26,o27,o28,o29,o30,o31}, {a12,a13,a14,a15}, d11, p1, 1, 1, 1;\n"
        "wgmma.mma_async.sync.aligned.m64n32k16.f32.bf16.bf16 {o0,o1,o2,o3,o4,o5,o6,o7,o8,o9,o10,o11,o12,o13,o14,o15}, {a16,a17,a18,a19}, d4, p1, 1, 1, 1;\n"
        "wgmma.mma_async.sync.aligned.m64n32k16.f32.bf16.bf16 {o16,o17,o18,o19,o20,o21,o22,o23,o24,o25,o26,o27,o28,o29,o30,o31}, {a16,a17,a18,a19}, d12, p1, 1, 1, 1;\n"
        "wgmma.mma_async.sync.aligned.m64n32k16.f32.bf16.bf16 {o0,o1,o2,o3,o4,o5,o6,o7,o8,o9,o10,o11,o12,o13,o14,o15}, {a20,a21,a22,a23}, d5, p1, 1, 1, 1;\n"
        "wgmma.mma_async.sync.aligned.m64n32k16.f32.bf16.bf16 {o16,o17,o18,o19,o20,o21,o22,o23,o24,o25,o26,o27,o28,o29,o30,o31}, {a20,a21,a22,a23}, d13, p1, 1, 1, 1;\n"
        "wgmma.mma_async.sync.aligned.m64n32k16.f32.bf16.bf16 {o0,o1,o2,o3,o4,o5,o6,o7,o8,o9,o10,o11,o12,o13,o14,o15}, {a24,a25,a26,a27}, d6, p1, 1, 1, 1;\n"
        "wgmma.mma_async.sync.aligned.m64n32k16.f32.bf16.bf16 {o16,o17,o18,o19,o20,o21,o22,o23,o24,o25,o26,o27,o28,o29,o30,o31}, {a24,a25,a26,a27}, d14, p1, 1, 1, 1;\n"
        "wgmma.mma_async.sync.aligned.m64n32k16.f32.bf16.bf16 {o0,o1,o2,o3,o4,o5,o6,o7,o8,o9,o10,o11,o12,o13,o14,o15}, {a28,a29,a30,a31}, d7, p1, 1, 1, 1;\n"
        "wgmma.mma_async.sync.aligned.m64n32k16.f32.bf16.bf16 {o16,o17,o18,o19,o20,o21,o22,o23,o24,o25,o26,o27,o28,o29,o30,o31}, {a28,a29,a30,a31}, d15, p1, 1, 1, 1;\n"
        "wgmma.commit_group.sync.aligned;\n@nv bra.uni END;\n@s0 st.global.v4.b32 [%49+0], {k0,k1,k2,k3};\n@s1 st.global.v4.b32 [%50+0], {k4,k5,k6,k7};\n"
        "@s0 st.global.v4.b32 [%49+64], {k8,k9,k10,k11};\n@s1 st.global.v4.b32 [%50+64], {k12,k13,k14,k15};\n@nv bra.uni END;\nwgmma.wait_group.sync.aligned 0;\n"
        "cvt.rn.bf16x2.f32 k0, o1, o0;\ncvt.rn.bf16x2.f32 k1, o5, o4;\ncvt.rn.bf16x2.f32 k2, o9, o8;\ncvt.rn.bf16x2.f32 k3, o13, o12;\n"
        "cvt.rn.bf16x2.f32 k4, o3, o2;\ncvt.rn.bf16x2.f32 k5, o7, o6;\ncvt.rn.bf16x2.f32 k6, o11, o10;\ncvt.rn.bf16x2.f32 k7, o15, o14;\n"
        "cvt.rn.bf16x2.f32 k8, o17, o16;\ncvt.rn.bf16x2.f32 k9, o21, o20;\ncvt.rn.bf16x2.f32 k10, o25, o24;\ncvt.rn.bf16x2.f32 k11, o29, o28;\n"
        "cvt.rn.bf16x2.f32 k12, o19, o18;\ncvt.rn.bf16x2.f32 k13, o23, o22;\ncvt.rn.bf16x2.f32 k14, o27, o26;\ncvt.rn.bf16x2.f32 k15, o31, o30;\n"
        "ld.volatile.shared.v4.b32 {c0,c1,c2,c3}, [%48+0];\nld.volatile.shared.v4.b32 {c4,c5,c6,c7}, [%48+8192];\n"
        "ld.volatile.shared.v4.b32 {c8,c9,c10,c11}, [%48+16];\nld.volatile.shared.v4.b32 {c12,c13,c14,c15}, [%48+8208];\nand.b32 t, c0, 0xffe;\n"
        "mad.lo.u32 t, t, 4, 0x200000;\nmov.b64 d0, {t, h};\nand.b32 t, c1, 0xffe;\nmad.lo.u32 t, t, 4, 0x200000;\nmov.b64 d1, {t, h};\nand.b32 t, c2, 0xffe;\n"
        "mad.lo.u32 t, t, 4, 0x200000;\nmov.b64 d2, {t, h};\nand.b32 t, c3, 0xffe;\nmad.lo.u32 t, t, 4, 0x200000;\nmov.b64 d3, {t, h};\nand.b32 t, c4, 0xffe;\n"
        "mad.lo.u32 t, t, 4, 0x200000;\nmov.b64 d4, {t, h};\nand.b32 t, c5, 0xffe;\nmad.lo.u32 t, t, 4, 0x200000;\nmov.b64 d5, {t, h};\nand.b32 t, c6, 0xffe;\n"
        "mad.lo.u32 t, t, 4, 0x200000;\nmov.b64 d6, {t, h};\nand.b32 t, c7, 0xffe;\nmad.lo.u32 t, t, 4, 0x200000;\nmov.b64 d7, {t, h};\nand.b32 t, c8, 0xffe;\n"
        "mad.lo.u32 t, t, 4, 0x200000;\nmov.b64 d8, {t, h};\nand.b32 t, c9, 0xffe;\nmad.lo.u32 t, t, 4, 0x200000;\nmov.b64 d9, {t, h};\nand.b32 t, c10, 0xffe;\n"
        "mad.lo.u32 t, t, 4, 0x200000;\nmov.b64 d10, {t, h};\nand.b32 t, c11, 0xffe;\nmad.lo.u32 t, t, 4, 0x200000;\nmov.b64 d11, {t, h};\n"
        "and.b32 t, c12, 0xffe;\nmad.lo.u32 t, t, 4, 0x200000;\nmov.b64 d12, {t, h};\nand.b32 t, c13, 0xffe;\nmad.lo.u32 t, t, 4, 0x200000;\n"
        "mov.b64 d13, {t, h};\nand.b32 t, c14, 0xffe;\nmad.lo.u32 t, t, 4, 0x200000;\nmov.b64 d14, {t, h};\nand.b32 t, c15, 0xffe;\n"
        "mad.lo.u32 t, t, 4, 0x200000;\nmov.b64 d15, {t, h};\nwgmma.fence.sync.aligned;\n"
        "wgmma.mma_async.sync.aligned.m64n32k16.f32.bf16.bf16 {o0,o1,o2,o3,o4,o5,o6,o7,o8,o9,o10,o11,o12,o13,o14,o15}, {b0,b1,b2,b3}, d0, p0, 1, 1, 1;\n"
        "wgmma.mma_async.sync.aligned.m64n32k16.f32.bf16.bf16 {o16,o17,o18,o19,o20,o21,o22,o23,o24,o25,o26,o27,o28,o29,o30,o31}, {b0,b1,b2,b3}, d8, p0, 1, 1, 1;\n"
        "wgmma.mma_async.sync.aligned.m64n32k16.f32.bf16.bf16 {o0,o1,o2,o3,o4,o5,o6,o7,o8,o9,o10,o11,o12,o13,o14,o15}, {b4,b5,b6,b7}, d1, p1, 1, 1, 1;\n"
        "wgmma.mma_async.sync.aligned.m64n32k16.f32.bf16.bf16 {o16,o17,o18,o19,o20,o21,o22,o23,o24,o25,o26,o27,o28,o29,o30,o31}, {b4,b5,b6,b7}, d9, p1, 1, 1, 1;\n"
        "wgmma.mma_async.sync.aligned.m64n32k16.f32.bf16.bf16 {o0,o1,o2,o3,o4,o5,o6,o7,o8,o9,o10,o11,o12,o13,o14,o15}, {b8,b9,b10,b11}, d2, p1, 1, 1, 1;\n"
        "wgmma.mma_async.sync.aligned.m64n32k16.f32.bf16.bf16 {o16,o17,o18,o19,o20,o21,o22,o23,o24,o25,o26,o27,o28,o29,o30,o31}, {b8,b9,b10,b11}, d10, p1, 1, 1, 1;\n"
        "wgmma.mma_async.sync.aligned.m64n32k16.f32.bf16.bf16 {o0,o1,o2,o3,o4,o5,o6,o7,o8,o9,o10,o11,o12,o13,o14,o15}, {b12,b13,b14,b15}, d3, p1, 1, 1, 1;\n"
        "wgmma.mma_async.sync.aligned.m64n32k16.f32.bf16.bf16 {o16,o17,o18,o19,o20,o21,o22,o23,o24,o25,o26,o27,o28,o29,o30,o31}, {b12,b13,b14,b15}, d11, p1, 1, 1, 1;\n"
        "wgmma.mma_async.sync.aligned.m64n32k16.f32.bf16.bf16 {o0,o1,o2,o3,o4,o5,o6,o7,o8,o9,o10,o11,o12,o13,o14,o15}, {b16,b17,b18,b19}, d4, p1, 1, 1, 1;\n"
        "wgmma.mma_async.sync.aligned.m64n32k16.f32.bf16.bf16 {o16,o17,o18,o19,o20,o21,o22,o23,o24,o25,o26,o27,o28,o29,o30,o31}, {b16,b17,b18,b19}, d12, p1, 1, 1, 1;\n"
        "wgmma.mma_async.sync.aligned.m64n32k16.f32.bf16.bf16 {o0,o1,o2,o3,o4,o5,o6,o7,o8,o9,o10,o11,o12,o13,o14,o15}, {b20,b21,b22,b23}, d5, p1, 1, 1, 1;\n"
        "wgmma.mma_async.sync.aligned.m64n32k16.f32.bf16.bf16 {o16,o17,o18,o19,o20,o21,o22,o23,o24,o25,o26,o27,o28,o29,o30,o31}, {b20,b21,b22,b23}, d13, p1, 1, 1, 1;\n"
        "wgmma.mma_async.sync.aligned.m64n32k16.f32.bf16.bf16 {o0,o1,o2,o3,o4,o5,o6,o7,o8,o9,o10,o11,o12,o13,o14,o15}, {b24,b25,b26,b27}, d6, p1, 1, 1, 1;\n"
        "wgmma.mma_async.sync.aligned.m64n32k16.f32.bf16.bf16 {o16,o17,o18,o19,o20,o21,o22,o23,o24,o25,o26,o27,o28,o29,o30,o31}, {b24,b25,b26,b27}, d14, p1, 1, 1, 1;\n"
        "wgmma.mma_async.sync.aligned.m64n32k16.f32.bf16.bf16 {o0,o1,o2,o3,o4,o5,o6,o7,o8,o9,o10,o11,o12,o13,o14,o15}, {b28,b29,b30,b31}, d7, p1, 1, 1, 1;\n"
        "wgmma.mma_async.sync.aligned.m64n32k16.f32.bf16.bf16 {o16,o17,o18,o19,o20,o21,o22,o23,o24,o25,o26,o27,o28,o29,o30,o31}, {b28,b29,b30,b31}, d15, p1, 1, 1, 1;\n"
        "wgmma.commit_group.sync.aligned;\n@nv bra.uni END;\n@s0 st.global.v4.b32 [%49+128], {k0,k1,k2,k3};\n@s1 st.global.v4.b32 [%50+128], {k4,k5,k6,k7};\n"
        "@s0 st.global.v4.b32 [%49+192], {k8,k9,k10,k11};\n@s1 st.global.v4.b32 [%50+192], {k12,k13,k14,k15};\n@nv bra.uni END;\n"
        "wgmma.wait_group.sync.aligned 0;\ncvt.rn.bf16x2.f32 k0, o1, o0;\ncvt.rn.bf16x2.f32 k1, o5, o4;\ncvt.rn.bf16x2.f32 k2, o9, o8;\n"
        "cvt.rn.bf16x2.f32 k3, o13, o12;\ncvt.rn.bf16x2.f32 k8, o17, o16;\ncvt.rn.bf16x2.f32 k9, o21, o20;\ncvt.rn.bf16x2.f32 k10, o25, o24;\n"
        "cvt.rn.bf16x2.f32 k11, o29, o28;\nld.volatile.shared.v4.b32 {c0,c1,c2,c3}, [%48+32];\nld.volatile.shared.v4.b32 {c4,c5,c6,c7}, [%48+8224];\n"
        "ld.volatile.shared.v4.b32 {c8,c9,c10,c11}, [%48+48];\nld.volatile.shared.v4.b32 {c12,c13,c14,c15}, [%48+8240];\nand.b32 t, c0, 0xffe;\n"
        "mad.lo.u32 t, t, 4, 0x200000;\nmov.b64 d0, {t, h};\nand.b32 t, c1, 0xffe;\nmad.lo.u32 t, t, 4, 0x200000;\nmov.b64 d1, {t, h};\nand.b32 t, c2, 0xffe;\n"
        "mad.lo.u32 t, t, 4, 0x200000;\nmov.b64 d2, {t, h};\nand.b32 t, c3, 0xffe;\nmad.lo.u32 t, t, 4, 0x200000;\nmov.b64 d3, {t, h};\nand.b32 t, c4, 0xffe;\n"
        "mad.lo.u32 t, t, 4, 0x200000;\nmov.b64 d4, {t, h};\nand.b32 t, c5, 0xffe;\nmad.lo.u32 t, t, 4, 0x200000;\nmov.b64 d5, {t, h};\nand.b32 t, c6, 0xffe;\n"
        "mad.lo.u32 t, t, 4, 0x200000;\nmov.b64 d6, {t, h};\nand.b32 t, c7, 0xffe;\nmad.lo.u32 t, t, 4, 0x200000;\nmov.b64 d7, {t, h};\nand.b32 t, c8, 0xffe;\n"
        "mad.lo.u32 t, t, 4, 0x200000;\nmov.b64 d8, {t, h};\nand.b32 t, c9, 0xffe;\nmad.lo.u32 t, t, 4, 0x200000;\nmov.b64 d9, {t, h};\nand.b32 t, c10, 0xffe;\n"
        "mad.lo.u32 t, t, 4, 0x200000;\nmov.b64 d10, {t, h};\nand.b32 t, c11, 0xffe;\nmad.lo.u32 t, t, 4, 0x200000;\nmov.b64 d11, {t, h};\n"
        "and.b32 t, c12, 0xffe;\nmad.lo.u32 t, t, 4, 0x200000;\nmov.b64 d12, {t, h};\nand.b32 t, c13, 0xffe;\nmad.lo.u32 t, t, 4, 0x200000;\n"
        "mov.b64 d13, {t, h};\nand.b32 t, c14, 0xffe;\nmad.lo.u32 t, t, 4, 0x200000;\nmov.b64 d14, {t, h};\nand.b32 t, c15, 0xffe;\n"
        "mad.lo.u32 t, t, 4, 0x200000;\nmov.b64 d15, {t, h};\nwgmma.fence.sync.aligned;\n"
        "wgmma.mma_async.sync.aligned.m64n32k16.f32.bf16.bf16 {o0,o1,o2,o3,o4,o5,o6,o7,o8,o9,o10,o11,o12,o13,o14,o15}, {b0,b1,b2,b3}, d0, p0, 1, 1, 1;\n"
        "wgmma.mma_async.sync.aligned.m64n32k16.f32.bf16.bf16 {o16,o17,o18,o19,o20,o21,o22,o23,o24,o25,o26,o27,o28,o29,o30,o31}, {b0,b1,b2,b3}, d8, p0, 1, 1, 1;\n"
        "wgmma.mma_async.sync.aligned.m64n32k16.f32.bf16.bf16 {o0,o1,o2,o3,o4,o5,o6,o7,o8,o9,o10,o11,o12,o13,o14,o15}, {b4,b5,b6,b7}, d1, p1, 1, 1, 1;\n"
        "wgmma.mma_async.sync.aligned.m64n32k16.f32.bf16.bf16 {o16,o17,o18,o19,o20,o21,o22,o23,o24,o25,o26,o27,o28,o29,o30,o31}, {b4,b5,b6,b7}, d9, p1, 1, 1, 1;\n"
        "wgmma.mma_async.sync.aligned.m64n32k16.f32.bf16.bf16 {o0,o1,o2,o3,o4,o5,o6,o7,o8,o9,o10,o11,o12,o13,o14,o15}, {b8,b9,b10,b11}, d2, p1, 1, 1, 1;\n"
        "wgmma.mma_async.sync.aligned.m64n32k16.f32.bf16.bf16 {o16,o17,o18,o19,o20,o21,o22,o23,o24,o25,o26,o27,o28,o29,o30,o31}, {b8,b9,b10,b11}, d10, p1, 1, 1, 1;\n"
        "wgmma.mma_async.sync.aligned.m64n32k16.f32.bf16.bf16 {o0,o1,o2,o3,o4,o5,o6,o7,o8,o9,o10,o11,o12,o13,o14,o15}, {b12,b13,b14,b15}, d3, p1, 1, 1, 1;\n"
        "wgmma.mma_async.sync.aligned.m64n32k16.f32.bf16.bf16 {o16,o17,o18,o19,o20,o21,o22,o23,o24,o25,o26,o27,o28,o29,o30,o31}, {b12,b13,b14,b15}, d11, p1, 1, 1, 1;\n"
        "wgmma.mma_async.sync.aligned.m64n32k16.f32.bf16.bf16 {o0,o1,o2,o3,o4,o5,o6,o7,o8,o9,o10,o11,o12,o13,o14,o15}, {b16,b17,b18,b19}, d4, p1, 1, 1, 1;\n"
        "wgmma.mma_async.sync.aligned.m64n32k16.f32.bf16.bf16 {o16,o17,o18,o19,o20,o21,o22,o23,o24,o25,o26,o27,o28,o29,o30,o31}, {b16,b17,b18,b19}, d12, p1, 1, 1, 1;\n"
        "wgmma.mma_async.sync.aligned.m64n32k16.f32.bf16.bf16 {o0,o1,o2,o3,o4,o5,o6,o7,o8,o9,o10,o11,o12,o13,o14,o15}, {b20,b21,b22,b23}, d5, p1, 1, 1, 1;\n"
        "wgmma.mma_async.sync.aligned.m64n32k16.f32.bf16.bf16 {o16,o17,o18,o19,o20,o21,o22,o23,o24,o25,o26,o27,o28,o29,o30,o31}, {b20,b21,b22,b23}, d13, p1, 1, 1, 1;\n"
        "wgmma.mma_async.sync.aligned.m64n32k16.f32.bf16.bf16 {o0,o1,o2,o3,o4,o5,o6,o7,o8,o9,o10,o11,o12,o13,o14,o15}, {b24,b25,b26,b27}, d6, p1, 1, 1, 1;\n"
        "wgmma.mma_async.sync.aligned.m64n32k16.f32.bf16.bf16 {o16,o17,o18,o19,o20,o21,o22,o23,o24,o25,o26,o27,o28,o29,o30,o31}, {b24,b25,b26,b27}, d14, p1, 1, 1, 1;\n"
        "wgmma.mma_async.sync.aligned.m64n32k16.f32.bf16.bf16 {o0,o1,o2,o3,o4,o5,o6,o7,o8,o9,o10,o11,o12,o13,o14,o15}, {b28,b29,b30,b31}, d7, p1, 1, 1, 1;\n"
        "wgmma.mma_async.sync.aligned.m64n32k16.f32.bf16.bf16 {o16,o17,o18,o19,o20,o21,o22,o23,o24,o25,o26,o27,o28,o29,o30,o31}, {b28,b29,b30,b31}, d15, p1, 1, 1, 1;\n"
        "wgmma.commit_group.sync.aligned;\n@nv bra.uni END;\n@s2 st.global.v4.b32 [%51+0], {k0,k1,k2,k3};\n@s2 st.global.v4.b32 [%51+64], {k8,k9,k10,k11};\n"
        "@nv bra.uni END;\nwgmma.wait_group.sync.aligned 0;\ncvt.rn.bf16x2.f32 k0, o1, o0;\ncvt.rn.bf16x2.f32 k1, o5, o4;\ncvt.rn.bf16x2.f32 k2, o9, o8;\n"
        "cvt.rn.bf16x2.f32 k3, o13, o12;\ncvt.rn.bf16x2.f32 k8, o17, o16;\ncvt.rn.bf16x2.f32 k9, o21, o20;\ncvt.rn.bf16x2.f32 k10, o25, o24;\n"
        "cvt.rn.bf16x2.f32 k11, o29, o28;\n@s2 st.global.v4.b32 [%51+128], {k0,k1,k2,k3};\n@s2 st.global.v4.b32 [%51+192], {k8,k9,k10,k11};\n"
        "END:\n}\n"
        ::"r"(pk[0]), "r"(pk[1]), "r"(pk[2]), "r"(pk[3]), "r"(pk[4]), "r"(pk[5]), "r"(pk[6]), "r"(pk[7]), "r"(pk[8]), "r"(pk[9]), "r"(pk[10]),
          "r"(pk[11]), "r"(pk[12]), "r"(pk[13]), "r"(pk[14]), "r"(pk[15]), "r"(pk[16]), "r"(pk[17]), "r"(pk[18]), "r"(pk[19]), "r"(pk[20]),
          "r"(pk[21]), "r"(pk[22]), "r"(pk[23]), "r"(pk[24]), "r"(pk[25]), "r"(pk[26]), "r"(pk[27]), "r"(pk[28]), "r"(pk[29]), "r"(pk[30]),
          "r"(pk[31]), "r"(pk[32]), "r"(pk[33]), "r"(pk[34]), "r"(pk[35]), "r"(pk[36]), "r"(pk[37]), "r"(pk[38]), "r"(pk[39]), "r"(pk[40]),
          "r"(pk[41]), "r"(pk[42]), "r"(pk[43]), "r"(pk[44]), "r"(pk[45]), "r"(pk[46]), "r"(pk[47]), "r"(ra), "l"(p[0]), "l"(p[1]), "l"(p[2]),
          "r"(v[0]), "r"(v[1]), "r"(v[2]), "r"(ba)
        : "memory");
}
__device__ __forceinline__ int cta_id() {
    int v;
    asm volatile("mov.u32 %0, %ctaid.x;" : "=r"(v));
    return v;
}
__device__ __forceinline__ int thread_id() {
    int v;
    asm volatile("mov.u32 %0, %tid.x;" : "=r"(v));
    return v;
}

__device__ __forceinline__ void slow_edge(int ee, int s, float* accn, const __nv_bfloat16* __restrict__ x,
                                          const __nv_bfloat16* __restrict__ sh, const __nv_bfloat16* __restrict__ ea,
                                          const __nv_bfloat16* __restrict__ cg, const __nv_bfloat16* __restrict__ wr,
                                          int lane) {
    float rwv[4] = {0.f, 0.f, 0.f, 0.f};
#pragma unroll 4
    for (int d = 0; d < 16; d++) {
        const float a = __bfloat162float(ea[(size_t)ee * 16 + d]);
        const uint2 wv = *(const uint2*)(wr + d * 128 + lane * 4);
        rwv[0] += a * __uint_as_float(wv.x << 16);
        rwv[1] += a * __uint_as_float(wv.x & 0xffff0000u);
        rwv[2] += a * __uint_as_float(wv.y << 16);
        rwv[3] += a * __uint_as_float(wv.y & 0xffff0000u);
    }
    float A = 0.f;
#pragma unroll
    for (int v = 0; v < 4; v++)
        A += __bfloat162float(cg[((lane >> 2) & 3) * 16 + v * 4 + (lane & 3)]) * __bfloat162float(sh[(size_t)ee * 4 + v]);
    float m[4][4];
#pragma unroll
    for (int w = 0; w < 4; w++)
#pragma unroll
        for (int j = 0; j < 4; j++) m[w][j] = 0.f;
#pragma unroll
    for (int u = 0; u < 4; u++) {
        const uint2 xv = *(const uint2*)(x + (size_t)s * 512 + u * 128 + lane * 4);
        const float x0 = __uint_as_float(xv.x << 16), x1 = __uint_as_float(xv.x & 0xffff0000u);
        const float x2 = __uint_as_float(xv.y << 16), x3 = __uint_as_float(xv.y & 0xffff0000u);
#pragma unroll
        for (int w = 0; w < 4; w++) {
            const float a = __shfl_sync(0xffffffffu, A, u * 4 + w);
            m[w][0] += a * x0;
            m[w][1] += a * x1;
            m[w][2] += a * x2;
            m[w][3] += a * x3;
        }
    }
#pragma unroll
    for (int w = 0; w < 4; w++)
#pragma unroll
        for (int j = 0; j < 4; j++) atomicAdd(accn + w * 128 + lane * 4 + j, m[w][j] * rwv[j]);
}

__device__ __forceinline__ void slow_out(const float* accn, const __nv_bfloat16* __restrict__ wout,
                                         __nv_bfloat16* __restrict__ outn, int lane) {
    float o[4][4];
#pragma unroll
    for (int w = 0; w < 4; w++)
#pragma unroll
        for (int j = 0; j < 4; j++) o[w][j] = 0.f;
#pragma unroll 2
    for (int c = 0; c < 128; c++) {
        const uint2 wv = *(const uint2*)(wout + c * 128 + lane * 4);
        const float w0 = __uint_as_float(wv.x << 16), w1 = __uint_as_float(wv.x & 0xffff0000u);
        const float w2 = __uint_as_float(wv.y << 16), w3 = __uint_as_float(wv.y & 0xffff0000u);
#pragma unroll
        for (int w = 0; w < 4; w++) {
            const float a = __bfloat162float(__float2bfloat16(accn[w * 128 + c]));
            o[w][0] += a * w0;
            o[w][1] += a * w1;
            o[w][2] += a * w2;
            o[w][3] += a * w3;
        }
    }
#pragma unroll
    for (int w = 0; w < 4; w++)
        *(uint2*)(outn + w * 128 + lane * 4) = make_uint2(pack_bf16(o[w][0], o[w][1]), pack_bf16(o[w][2], o[w][3]));
}

__device__ __forceinline__ void consume4(uint32_t (&pk)[64], const uint32_t (&w)[36], uint32_t olp, uint32_t xa, uint32_t ln,
                                      uint32_t lc, uint32_t linc, uint32_t lt, const __nv_bfloat16* ea, const __nv_bfloat16* sh, const void* wf) {
    ea += lt * 4, sh += lt & 2;
    asm volatile(
        "{\n.reg .pred p, q, psw, prdy, ps1, ps2, ps3, pz;\n.reg .f32 d<32>, fz;\n"
        ".reg .b32 h<64>, x<32>, y<32>, ra<8>, rb<8>, bA0, bA1, bB0, bB1, c0, c1, c2, c3, e0, e1, s0, kept;\n"
        ".reg .b32 olp, v, vB, m, id, ida, bar, xb, pos, t0, t1, t2, t3, n, z<16>;\n.reg .b16 lo, hi, i16;\n.reg .b64 pa, pb;\nmov.f32 fz, 0f00000000;\n"
        "mov.b32 h0, 0;\nmov.b32 h1, 0;\nmov.b32 h2, 0;\nmov.b32 h3, 0;\nmov.b32 h4, 0;\nmov.b32 h5, 0;\nmov.b32 h6, 0;\nmov.b32 h7, 0;\nmov.b32 h8, 0;\n"
        "mov.b32 h9, 0;\nmov.b32 h10, 0;\nmov.b32 h11, 0;\nmov.b32 h12, 0;\nmov.b32 h13, 0;\nmov.b32 h14, 0;\nmov.b32 h15, 0;\nmov.b32 h16, 0;\nmov.b32 h17, 0;\n"
        "mov.b32 h18, 0;\nmov.b32 h19, 0;\nmov.b32 h20, 0;\nmov.b32 h21, 0;\nmov.b32 h22, 0;\nmov.b32 h23, 0;\nmov.b32 h24, 0;\nmov.b32 h25, 0;\n"
        "mov.b32 h26, 0;\nmov.b32 h27, 0;\nmov.b32 h28, 0;\nmov.b32 h29, 0;\nmov.b32 h30, 0;\nmov.b32 h31, 0;\nmov.b32 h32, 0;\nmov.b32 h33, 0;\n"
        "mov.b32 h34, 0;\nmov.b32 h35, 0;\nmov.b32 h36, 0;\nmov.b32 h37, 0;\nmov.b32 h38, 0;\nmov.b32 h39, 0;\nmov.b32 h40, 0;\nmov.b32 h41, 0;\n"
        "mov.b32 h42, 0;\nmov.b32 h43, 0;\nmov.b32 h44, 0;\nmov.b32 h45, 0;\nmov.b32 h46, 0;\nmov.b32 h47, 0;\nmov.b32 h48, 0;\nmov.b32 h49, 0;\n"
        "mov.b32 h50, 0;\nmov.b32 h51, 0;\nmov.b32 h52, 0;\nmov.b32 h53, 0;\nmov.b32 h54, 0;\nmov.b32 h55, 0;\nmov.b32 h56, 0;\nmov.b32 h57, 0;\n"
        "mov.b32 h58, 0;\nmov.b32 h59, 0;\nmov.b32 h60, 0;\nmov.b32 h61, 0;\nmov.b32 h62, 0;\nmov.b32 h63, 0;\nmov.b32 olp, %64;\nand.b32 t0, %66, 32;\n"
        "setp.ne.u32 psw, t0, 0;\nsetp.eq.u32 pz, %64, 0;\nvote.sync.any.pred pz, pz, 0xffffffff;\nld.shared.b32 t0, [olp];\nadd.u32 olp, olp, 8;\n"
        "lop3.b32 t1, t0, %66, 0x3ff0, 0xe4;\nld.shared.b32 t1, [t1+%73];\nlop3.b32 kept, t1, t0, 0x1ffc, 0xe4;\nlop3.b32 t2, t1, %67, 3, 0x80;\n"
        "setp.ne.u32 q, t2, 0;\nshr.u32 t2, t1, 13;\nmad.wide.u32 pa, t2, 32, %70;\nmad.wide.u32 pb, t2, 8, %71;\nmov.b32 s0, 0;\n"
        "ld.global.cg.v2.b32 {e0,e1}, [pa];\n@q ld.global.cg.b32 s0, [pb];\nsetp.ne.u64 p, %72, 0;\n@p fence.proxy.async.global;\n"
        "@p red.release.gpu.global.add.u32 [%72+12], 1;\nbar.warp.sync 0xffffffff;\nshfl.sync.idx.b32 v, kept, %67, 0x1f, 0xffffffff;\nor.b32 t3, %67, 4;\n"
        "shfl.sync.idx.b32 vB, kept, t3, 0x1f, 0xffffffff;\nshr.u32 bar, v, 1;\nand.b32 bar, bar, 0xff8;\nmbarrier.test_wait.parity.shared.b64 p, [bar+%75], 0;\n"
        "lop3.b32 ida, v, %67, 0x1fff, 0xe4;\nld.volatile.shared.u16 id, [ida+%74];\nvote.sync.all.pred prdy, p, 0xffffffff;\n"
        "RW:\nmma.sync.aligned.m16n8k8.row.col.f32.bf16.bf16.f32 {d0,d1,d2,d3}, {%109,%110}, {s0}, {fz,fz,fz,fz};\n"
        "mma.sync.aligned.m16n8k8.row.col.f32.bf16.bf16.f32 {d4,d5,d6,d7}, {%111,%112}, {s0}, {fz,fz,fz,fz};\ncvt.rn.bf16x2.f32 c0, d2, d0;\n"
        "cvt.rn.bf16x2.f32 c1, d3, d1;\ncvt.rn.bf16x2.f32 c2, d6, d4;\ncvt.rn.bf16x2.f32 c3, d7, d5;\nselp.b32 bA0, c2, c0, psw;\nselp.b32 bA1, c0, c2, psw;\n"
        "selp.b32 bB0, c3, c1, psw;\nselp.b32 bB1, c1, c3, psw;\n"
        "mma.sync.aligned.m16n8k16.row.col.f32.bf16.bf16.f32 {d0,d1,d2,d3}, {%77,%78,%79,%80}, {e0,e1}, {fz,fz,fz,fz};\ncvt.rn.bf16x2.f32 ra0, d2, d0;\n"
        "cvt.rn.bf16x2.f32 rb0, d3, d1;\nmma.sync.aligned.m16n8k16.row.col.f32.bf16.bf16.f32 {d4,d5,d6,d7}, {%81,%82,%83,%84}, {e0,e1}, {fz,fz,fz,fz};\n"
        "cvt.rn.bf16x2.f32 ra1, d6, d4;\ncvt.rn.bf16x2.f32 rb1, d7, d5;\n"
        "mma.sync.aligned.m16n8k16.row.col.f32.bf16.bf16.f32 {d8,d9,d10,d11}, {%85,%86,%87,%88}, {e0,e1}, {fz,fz,fz,fz};\ncvt.rn.bf16x2.f32 ra2, d10, d8;\n"
        "cvt.rn.bf16x2.f32 rb2, d11, d9;\nmma.sync.aligned.m16n8k16.row.col.f32.bf16.bf16.f32 {d12,d13,d14,d15}, {%89,%90,%91,%92}, {e0,e1}, {fz,fz,fz,fz};\n"
        "cvt.rn.bf16x2.f32 ra3, d14, d12;\ncvt.rn.bf16x2.f32 rb3, d15, d13;\n"
        "mma.sync.aligned.m16n8k16.row.col.f32.bf16.bf16.f32 {d16,d17,d18,d19}, {%93,%94,%95,%96}, {e0,e1}, {fz,fz,fz,fz};\ncvt.rn.bf16x2.f32 ra4, d18, d16;\n"
        "cvt.rn.bf16x2.f32 rb4, d19, d17;\nmma.sync.aligned.m16n8k16.row.col.f32.bf16.bf16.f32 {d20,d21,d22,d23}, {%97,%98,%99,%100}, {e0,e1}, {fz,fz,fz,fz};\n"
        "cvt.rn.bf16x2.f32 ra5, d22, d20;\ncvt.rn.bf16x2.f32 rb5, d23, d21;\n"
        "mma.sync.aligned.m16n8k16.row.col.f32.bf16.bf16.f32 {d24,d25,d26,d27}, {%101,%102,%103,%104}, {e0,e1}, {fz,fz,fz,fz};\n"
        "cvt.rn.bf16x2.f32 ra6, d26, d24;\ncvt.rn.bf16x2.f32 rb6, d27, d25;\n"
        "mma.sync.aligned.m16n8k16.row.col.f32.bf16.bf16.f32 {d28,d29,d30,d31}, {%105,%106,%107,%108}, {e0,e1}, {fz,fz,fz,fz};\n"
        "cvt.rn.bf16x2.f32 ra7, d30, d28;\ncvt.rn.bf16x2.f32 rb7, d31, d29;\nld.shared.b32 t0, [olp];\nadd.u32 olp, olp, 8;\n"
        "lop3.b32 t1, t0, %66, 0x3ff0, 0xe4;\nld.shared.b32 t1, [t1+%73];\nlop3.b32 kept, t1, t0, 0x1ffc, 0xe4;\nlop3.b32 t2, t1, %67, 3, 0x80;\n"
        "setp.ne.u32 q, t2, 0;\nshr.u32 t2, t1, 13;\nmad.wide.u32 pa, t2, 32, %70;\nmad.wide.u32 pb, t2, 8, %71;\nmov.b32 s0, 0;\n"
        "ld.global.cg.v2.b32 {e0,e1}, [pa];\n@q ld.global.cg.b32 s0, [pb];\n@!prdy bra.uni WA;\n"
        "HA:\nmad.lo.u32 xb, id, 64, %65;\ncvt.u16.u32 i16, id;\nldmatrix.sync.aligned.m8n8.x4.trans.shared.b16 {x0,x1,x2,x3}, [xb];\nxor.b32 t1, xb, 16;\n"
        "ldmatrix.sync.aligned.m8n8.x4.trans.shared.b16 {x4,x5,x6,x7}, [t1];\nxor.b32 t1, xb, 32;\n"
        "ldmatrix.sync.aligned.m8n8.x4.trans.shared.b16 {x8,x9,x10,x11}, [t1];\nxor.b32 t1, xb, 48;\n"
        "ldmatrix.sync.aligned.m8n8.x4.trans.shared.b16 {x12,x13,x14,x15}, [t1];\nxor.b32 t1, xb, 64;\n"
        "ldmatrix.sync.aligned.m8n8.x4.trans.shared.b16 {x16,x17,x18,x19}, [t1];\n@pz bra.uni DONE;\natom.shared.add.u32 pos, [%66+%76], %68;\n"
        "xor.b32 t1, xb, 80;\nldmatrix.sync.aligned.m8n8.x4.trans.shared.b16 {x20,x21,x22,x23}, [t1];\nxor.b32 t1, xb, 96;\n"
        "ldmatrix.sync.aligned.m8n8.x4.trans.shared.b16 {x24,x25,x26,x27}, [t1];\nxor.b32 t1, xb, 112;\n"
        "ldmatrix.sync.aligned.m8n8.x4.trans.shared.b16 {x28,x29,x30,x31}, [t1];\nst.volatile.shared.u16 [pos], i16;\nand.b32 t0, v, 268435456;\n"
        "setp.ne.u32 ps1, t0, 0;\nvote.sync.any.pred ps1, ps1, 0xffffffff;\nand.b32 t0, v, 536870912;\nsetp.ne.u32 ps2, t0, 0;\n"
        "vote.sync.any.pred ps2, ps2, 0xffffffff;\nmov.b32 v, vB;\nshr.u32 bar, v, 1;\nand.b32 bar, bar, 0xff8;\n"
        "mbarrier.test_wait.parity.shared.b64 p, [bar+%75], 0;\nlop3.b32 ida, v, %67, 0x1fff, 0xe4;\nld.volatile.shared.u16 id, [ida+%74];\n"
        "vote.sync.all.pred prdy, p, 0xffffffff;\nmov.b32 {lo, hi}, ra0;\nmov.b32 t2, {lo, lo};\nmul.rn.bf16x2 y0, x0, t2;\nmul.rn.bf16x2 y2, x2, t2;\n"
        "mov.b32 t2, {hi, hi};\nmul.rn.bf16x2 y1, x1, t2;\nmul.rn.bf16x2 y3, x3, t2;\n"
        "mma.sync.aligned.m16n8k16.row.col.f32.bf16.bf16.f32 {d0,d1,d2,d3}, {y0,y1,y2,y3}, {bA0,bA1}, {fz,fz,fz,fz};\ncvt.rn.bf16x2.f32 z0, d1, d0;\n"
        "cvt.rn.bf16x2.f32 z1, d3, d2;\nmov.b32 {lo, hi}, ra1;\nmov.b32 t2, {lo, lo};\nmul.rn.bf16x2 y4, x4, t2;\nmul.rn.bf16x2 y6, x6, t2;\n"
        "mov.b32 t2, {hi, hi};\nmul.rn.bf16x2 y5, x5, t2;\nmul.rn.bf16x2 y7, x7, t2;\n"
        "mma.sync.aligned.m16n8k16.row.col.f32.bf16.bf16.f32 {d4,d5,d6,d7}, {y4,y5,y6,y7}, {bA0,bA1}, {fz,fz,fz,fz};\ncvt.rn.bf16x2.f32 z2, d5, d4;\n"
        "cvt.rn.bf16x2.f32 z3, d7, d6;\nmov.b32 {lo, hi}, ra2;\nmov.b32 t2, {lo, lo};\nmul.rn.bf16x2 y8, x8, t2;\nmul.rn.bf16x2 y10, x10, t2;\n"
        "mov.b32 t2, {hi, hi};\nmul.rn.bf16x2 y9, x9, t2;\nmul.rn.bf16x2 y11, x11, t2;\n"
        "mma.sync.aligned.m16n8k16.row.col.f32.bf16.bf16.f32 {d8,d9,d10,d11}, {y8,y9,y10,y11}, {bA0,bA1}, {fz,fz,fz,fz};\ncvt.rn.bf16x2.f32 z4, d9, d8;\n"
        "cvt.rn.bf16x2.f32 z5, d11, d10;\nmov.b32 {lo, hi}, ra3;\nmov.b32 t2, {lo, lo};\nmul.rn.bf16x2 y12, x12, t2;\nmul.rn.bf16x2 y14, x14, t2;\n"
        "mov.b32 t2, {hi, hi};\nmul.rn.bf16x2 y13, x13, t2;\nmul.rn.bf16x2 y15, x15, t2;\n"
        "mma.sync.aligned.m16n8k16.row.col.f32.bf16.bf16.f32 {d12,d13,d14,d15}, {y12,y13,y14,y15}, {bA0,bA1}, {fz,fz,fz,fz};\ncvt.rn.bf16x2.f32 z6, d13, d12;\n"
        "cvt.rn.bf16x2.f32 z7, d15, d14;\nmov.b32 {lo, hi}, ra4;\nmov.b32 t2, {lo, lo};\nmul.rn.bf16x2 y16, x16, t2;\nmul.rn.bf16x2 y18, x18, t2;\n"
        "mov.b32 t2, {hi, hi};\nmul.rn.bf16x2 y17, x17, t2;\nmul.rn.bf16x2 y19, x19, t2;\n"
        "mma.sync.aligned.m16n8k16.row.col.f32.bf16.bf16.f32 {d16,d17,d18,d19}, {y16,y17,y18,y19}, {bA0,bA1}, {fz,fz,fz,fz};\ncvt.rn.bf16x2.f32 z8, d17, d16;\n"
        "cvt.rn.bf16x2.f32 z9, d19, d18;\nmov.b32 {lo, hi}, ra5;\nmov.b32 t2, {lo, lo};\nmul.rn.bf16x2 y20, x20, t2;\nmul.rn.bf16x2 y22, x22, t2;\n"
        "mov.b32 t2, {hi, hi};\nmul.rn.bf16x2 y21, x21, t2;\nmul.rn.bf16x2 y23, x23, t2;\n"
        "mma.sync.aligned.m16n8k16.row.col.f32.bf16.bf16.f32 {d20,d21,d22,d23}, {y20,y21,y22,y23}, {bA0,bA1}, {fz,fz,fz,fz};\ncvt.rn.bf16x2.f32 z10, d21, d20;\n"
        "cvt.rn.bf16x2.f32 z11, d23, d22;\nmov.b32 {lo, hi}, ra6;\nmov.b32 t2, {lo, lo};\nmul.rn.bf16x2 y24, x24, t2;\nmul.rn.bf16x2 y26, x26, t2;\n"
        "mov.b32 t2, {hi, hi};\nmul.rn.bf16x2 y25, x25, t2;\nmul.rn.bf16x2 y27, x27, t2;\n"
        "mma.sync.aligned.m16n8k16.row.col.f32.bf16.bf16.f32 {d24,d25,d26,d27}, {y24,y25,y26,y27}, {bA0,bA1}, {fz,fz,fz,fz};\ncvt.rn.bf16x2.f32 z12, d25, d24;\n"
        "cvt.rn.bf16x2.f32 z13, d27, d26;\nmov.b32 {lo, hi}, ra7;\nmov.b32 t2, {lo, lo};\nmul.rn.bf16x2 y28, x28, t2;\nmul.rn.bf16x2 y30, x30, t2;\n"
        "mov.b32 t2, {hi, hi};\nmul.rn.bf16x2 y29, x29, t2;\nmul.rn.bf16x2 y31, x31, t2;\n"
        "mma.sync.aligned.m16n8k16.row.col.f32.bf16.bf16.f32 {d28,d29,d30,d31}, {y28,y29,y30,y31}, {bA0,bA1}, {fz,fz,fz,fz};\ncvt.rn.bf16x2.f32 z14, d29, d28;\n"
        "cvt.rn.bf16x2.f32 z15, d31, d30;\n@ps2 bra.uni TA2;\n@ps1 bra.uni TA1;\n"
        "TA0:\nadd.rn.bf16x2 h0, h0, z0;\nadd.rn.bf16x2 h1, h1, z1;\nadd.rn.bf16x2 h2, h2, z2;\nadd.rn.bf16x2 h3, h3, z3;\nadd.rn.bf16x2 h4, h4, z4;\n"
        "add.rn.bf16x2 h5, h5, z5;\nadd.rn.bf16x2 h6, h6, z6;\nadd.rn.bf16x2 h7, h7, z7;\nadd.rn.bf16x2 h8, h8, z8;\nadd.rn.bf16x2 h9, h9, z9;\n"
        "add.rn.bf16x2 h10, h10, z10;\nadd.rn.bf16x2 h11, h11, z11;\nadd.rn.bf16x2 h12, h12, z12;\nadd.rn.bf16x2 h13, h13, z13;\nadd.rn.bf16x2 h14, h14, z14;\n"
        "add.rn.bf16x2 h15, h15, z15;\n@prdy bra.uni HB;\nbra.uni WB;\n"
        "TA1:\nadd.rn.bf16x2 h16, h16, z0;\nadd.rn.bf16x2 h17, h17, z1;\nadd.rn.bf16x2 h18, h18, z2;\nadd.rn.bf16x2 h19, h19, z3;\nadd.rn.bf16x2 h20, h20, z4;\n"
        "add.rn.bf16x2 h21, h21, z5;\nadd.rn.bf16x2 h22, h22, z6;\nadd.rn.bf16x2 h23, h23, z7;\nadd.rn.bf16x2 h24, h24, z8;\nadd.rn.bf16x2 h25, h25, z9;\n"
        "add.rn.bf16x2 h26, h26, z10;\nadd.rn.bf16x2 h27, h27, z11;\nadd.rn.bf16x2 h28, h28, z12;\nadd.rn.bf16x2 h29, h29, z13;\nadd.rn.bf16x2 h30, h30, z14;\n"
        "add.rn.bf16x2 h31, h31, z15;\n@prdy bra.uni HB;\nbra.uni WB;\n"
        "TA2:\n@ps1 bra.uni TA3;\nadd.rn.bf16x2 h32, h32, z0;\nadd.rn.bf16x2 h33, h33, z1;\nadd.rn.bf16x2 h34, h34, z2;\nadd.rn.bf16x2 h35, h35, z3;\n"
        "add.rn.bf16x2 h36, h36, z4;\nadd.rn.bf16x2 h37, h37, z5;\nadd.rn.bf16x2 h38, h38, z6;\nadd.rn.bf16x2 h39, h39, z7;\nadd.rn.bf16x2 h40, h40, z8;\n"
        "add.rn.bf16x2 h41, h41, z9;\nadd.rn.bf16x2 h42, h42, z10;\nadd.rn.bf16x2 h43, h43, z11;\nadd.rn.bf16x2 h44, h44, z12;\nadd.rn.bf16x2 h45, h45, z13;\n"
        "add.rn.bf16x2 h46, h46, z14;\nadd.rn.bf16x2 h47, h47, z15;\n@prdy bra.uni HB;\nbra.uni WB;\n"
        "TA3:\nadd.rn.bf16x2 h48, h48, z0;\nadd.rn.bf16x2 h49, h49, z1;\nadd.rn.bf16x2 h50, h50, z2;\nadd.rn.bf16x2 h51, h51, z3;\nadd.rn.bf16x2 h52, h52, z4;\n"
        "add.rn.bf16x2 h53, h53, z5;\nadd.rn.bf16x2 h54, h54, z6;\nadd.rn.bf16x2 h55, h55, z7;\nadd.rn.bf16x2 h56, h56, z8;\nadd.rn.bf16x2 h57, h57, z9;\n"
        "add.rn.bf16x2 h58, h58, z10;\nadd.rn.bf16x2 h59, h59, z11;\nadd.rn.bf16x2 h60, h60, z12;\nadd.rn.bf16x2 h61, h61, z13;\nadd.rn.bf16x2 h62, h62, z14;\n"
        "add.rn.bf16x2 h63, h63, z15;\n@prdy bra.uni HB;\nbra.uni WB;\n"
        "HB:\nmad.lo.u32 xb, id, 64, %65;\ncvt.u16.u32 i16, id;\natom.shared.add.u32 pos, [%66+%76], %68;\n"
        "ldmatrix.sync.aligned.m8n8.x4.trans.shared.b16 {x0,x1,x2,x3}, [xb];\nxor.b32 t1, xb, 16;\n"
        "ldmatrix.sync.aligned.m8n8.x4.trans.shared.b16 {x4,x5,x6,x7}, [t1];\nxor.b32 t1, xb, 32;\n"
        "ldmatrix.sync.aligned.m8n8.x4.trans.shared.b16 {x8,x9,x10,x11}, [t1];\nxor.b32 t1, xb, 48;\n"
        "ldmatrix.sync.aligned.m8n8.x4.trans.shared.b16 {x12,x13,x14,x15}, [t1];\nxor.b32 t1, xb, 64;\n"
        "ldmatrix.sync.aligned.m8n8.x4.trans.shared.b16 {x16,x17,x18,x19}, [t1];\nxor.b32 t1, xb, 80;\n"
        "ldmatrix.sync.aligned.m8n8.x4.trans.shared.b16 {x20,x21,x22,x23}, [t1];\nxor.b32 t1, xb, 96;\n"
        "ldmatrix.sync.aligned.m8n8.x4.trans.shared.b16 {x24,x25,x26,x27}, [t1];\nxor.b32 t1, xb, 112;\n"
        "ldmatrix.sync.aligned.m8n8.x4.trans.shared.b16 {x28,x29,x30,x31}, [t1];\nst.volatile.shared.u16 [pos], i16;\nand.b32 t0, v, 268435456;\n"
        "setp.ne.u32 ps1, t0, 0;\nvote.sync.any.pred ps1, ps1, 0xffffffff;\nand.b32 t0, v, 536870912;\nsetp.ne.u32 ps2, t0, 0;\n"
        "vote.sync.any.pred ps2, ps2, 0xffffffff;\nshfl.sync.idx.b32 v, kept, %67, 0x1f, 0xffffffff;\nor.b32 t3, %67, 4;\n"
        "shfl.sync.idx.b32 vB, kept, t3, 0x1f, 0xffffffff;\nshr.u32 bar, v, 1;\nand.b32 bar, bar, 0xff8;\nmbarrier.test_wait.parity.shared.b64 p, [bar+%75], 0;\n"
        "lop3.b32 ida, v, %67, 0x1fff, 0xe4;\nld.volatile.shared.u16 id, [ida+%74];\nvote.sync.all.pred prdy, p, 0xffffffff;\nmov.b32 {lo, hi}, rb0;\n"
        "mov.b32 t2, {lo, lo};\nmul.rn.bf16x2 y0, x0, t2;\nmul.rn.bf16x2 y2, x2, t2;\nmov.b32 t2, {hi, hi};\nmul.rn.bf16x2 y1, x1, t2;\n"
        "mul.rn.bf16x2 y3, x3, t2;\nmma.sync.aligned.m16n8k16.row.col.f32.bf16.bf16.f32 {d0,d1,d2,d3}, {y0,y1,y2,y3}, {bB0,bB1}, {fz,fz,fz,fz};\n"
        "cvt.rn.bf16x2.f32 z0, d1, d0;\ncvt.rn.bf16x2.f32 z1, d3, d2;\nmov.b32 {lo, hi}, rb1;\nmov.b32 t2, {lo, lo};\nmul.rn.bf16x2 y4, x4, t2;\n"
        "mul.rn.bf16x2 y6, x6, t2;\nmov.b32 t2, {hi, hi};\nmul.rn.bf16x2 y5, x5, t2;\nmul.rn.bf16x2 y7, x7, t2;\n"
        "mma.sync.aligned.m16n8k16.row.col.f32.bf16.bf16.f32 {d4,d5,d6,d7}, {y4,y5,y6,y7}, {bB0,bB1}, {fz,fz,fz,fz};\ncvt.rn.bf16x2.f32 z2, d5, d4;\n"
        "cvt.rn.bf16x2.f32 z3, d7, d6;\nmov.b32 {lo, hi}, rb2;\nmov.b32 t2, {lo, lo};\nmul.rn.bf16x2 y8, x8, t2;\nmul.rn.bf16x2 y10, x10, t2;\n"
        "mov.b32 t2, {hi, hi};\nmul.rn.bf16x2 y9, x9, t2;\nmul.rn.bf16x2 y11, x11, t2;\n"
        "mma.sync.aligned.m16n8k16.row.col.f32.bf16.bf16.f32 {d8,d9,d10,d11}, {y8,y9,y10,y11}, {bB0,bB1}, {fz,fz,fz,fz};\ncvt.rn.bf16x2.f32 z4, d9, d8;\n"
        "cvt.rn.bf16x2.f32 z5, d11, d10;\nmov.b32 {lo, hi}, rb3;\nmov.b32 t2, {lo, lo};\nmul.rn.bf16x2 y12, x12, t2;\nmul.rn.bf16x2 y14, x14, t2;\n"
        "mov.b32 t2, {hi, hi};\nmul.rn.bf16x2 y13, x13, t2;\nmul.rn.bf16x2 y15, x15, t2;\n"
        "mma.sync.aligned.m16n8k16.row.col.f32.bf16.bf16.f32 {d12,d13,d14,d15}, {y12,y13,y14,y15}, {bB0,bB1}, {fz,fz,fz,fz};\ncvt.rn.bf16x2.f32 z6, d13, d12;\n"
        "cvt.rn.bf16x2.f32 z7, d15, d14;\nmov.b32 {lo, hi}, rb4;\nmov.b32 t2, {lo, lo};\nmul.rn.bf16x2 y16, x16, t2;\nmul.rn.bf16x2 y18, x18, t2;\n"
        "mov.b32 t2, {hi, hi};\nmul.rn.bf16x2 y17, x17, t2;\nmul.rn.bf16x2 y19, x19, t2;\n"
        "mma.sync.aligned.m16n8k16.row.col.f32.bf16.bf16.f32 {d16,d17,d18,d19}, {y16,y17,y18,y19}, {bB0,bB1}, {fz,fz,fz,fz};\ncvt.rn.bf16x2.f32 z8, d17, d16;\n"
        "cvt.rn.bf16x2.f32 z9, d19, d18;\nmov.b32 {lo, hi}, rb5;\nmov.b32 t2, {lo, lo};\nmul.rn.bf16x2 y20, x20, t2;\nmul.rn.bf16x2 y22, x22, t2;\n"
        "mov.b32 t2, {hi, hi};\nmul.rn.bf16x2 y21, x21, t2;\nmul.rn.bf16x2 y23, x23, t2;\n"
        "mma.sync.aligned.m16n8k16.row.col.f32.bf16.bf16.f32 {d20,d21,d22,d23}, {y20,y21,y22,y23}, {bB0,bB1}, {fz,fz,fz,fz};\ncvt.rn.bf16x2.f32 z10, d21, d20;\n"
        "cvt.rn.bf16x2.f32 z11, d23, d22;\nmov.b32 {lo, hi}, rb6;\nmov.b32 t2, {lo, lo};\nmul.rn.bf16x2 y24, x24, t2;\nmul.rn.bf16x2 y26, x26, t2;\n"
        "mov.b32 t2, {hi, hi};\nmul.rn.bf16x2 y25, x25, t2;\nmul.rn.bf16x2 y27, x27, t2;\n"
        "mma.sync.aligned.m16n8k16.row.col.f32.bf16.bf16.f32 {d24,d25,d26,d27}, {y24,y25,y26,y27}, {bB0,bB1}, {fz,fz,fz,fz};\ncvt.rn.bf16x2.f32 z12, d25, d24;\n"
        "cvt.rn.bf16x2.f32 z13, d27, d26;\nmov.b32 {lo, hi}, rb7;\nmov.b32 t2, {lo, lo};\nmul.rn.bf16x2 y28, x28, t2;\nmul.rn.bf16x2 y30, x30, t2;\n"
        "mov.b32 t2, {hi, hi};\nmul.rn.bf16x2 y29, x29, t2;\nmul.rn.bf16x2 y31, x31, t2;\n"
        "mma.sync.aligned.m16n8k16.row.col.f32.bf16.bf16.f32 {d28,d29,d30,d31}, {y28,y29,y30,y31}, {bB0,bB1}, {fz,fz,fz,fz};\ncvt.rn.bf16x2.f32 z14, d29, d28;\n"
        "cvt.rn.bf16x2.f32 z15, d31, d30;\n@ps2 bra.uni TB2;\n@ps1 bra.uni TB1;\n"
        "TB0:\nadd.rn.bf16x2 h0, h0, z0;\nadd.rn.bf16x2 h1, h1, z1;\nadd.rn.bf16x2 h2, h2, z2;\nadd.rn.bf16x2 h3, h3, z3;\nadd.rn.bf16x2 h4, h4, z4;\n"
        "add.rn.bf16x2 h5, h5, z5;\nadd.rn.bf16x2 h6, h6, z6;\nadd.rn.bf16x2 h7, h7, z7;\nadd.rn.bf16x2 h8, h8, z8;\nadd.rn.bf16x2 h9, h9, z9;\n"
        "add.rn.bf16x2 h10, h10, z10;\nadd.rn.bf16x2 h11, h11, z11;\nadd.rn.bf16x2 h12, h12, z12;\nadd.rn.bf16x2 h13, h13, z13;\nadd.rn.bf16x2 h14, h14, z14;\n"
        "add.rn.bf16x2 h15, h15, z15;\nbra.uni RW;\n"
        "TB1:\nadd.rn.bf16x2 h16, h16, z0;\nadd.rn.bf16x2 h17, h17, z1;\nadd.rn.bf16x2 h18, h18, z2;\nadd.rn.bf16x2 h19, h19, z3;\nadd.rn.bf16x2 h20, h20, z4;\n"
        "add.rn.bf16x2 h21, h21, z5;\nadd.rn.bf16x2 h22, h22, z6;\nadd.rn.bf16x2 h23, h23, z7;\nadd.rn.bf16x2 h24, h24, z8;\nadd.rn.bf16x2 h25, h25, z9;\n"
        "add.rn.bf16x2 h26, h26, z10;\nadd.rn.bf16x2 h27, h27, z11;\nadd.rn.bf16x2 h28, h28, z12;\nadd.rn.bf16x2 h29, h29, z13;\nadd.rn.bf16x2 h30, h30, z14;\n"
        "add.rn.bf16x2 h31, h31, z15;\nbra.uni RW;\n"
        "TB2:\n@ps1 bra.uni TB3;\nadd.rn.bf16x2 h32, h32, z0;\nadd.rn.bf16x2 h33, h33, z1;\nadd.rn.bf16x2 h34, h34, z2;\nadd.rn.bf16x2 h35, h35, z3;\n"
        "add.rn.bf16x2 h36, h36, z4;\nadd.rn.bf16x2 h37, h37, z5;\nadd.rn.bf16x2 h38, h38, z6;\nadd.rn.bf16x2 h39, h39, z7;\nadd.rn.bf16x2 h40, h40, z8;\n"
        "add.rn.bf16x2 h41, h41, z9;\nadd.rn.bf16x2 h42, h42, z10;\nadd.rn.bf16x2 h43, h43, z11;\nadd.rn.bf16x2 h44, h44, z12;\nadd.rn.bf16x2 h45, h45, z13;\n"
        "add.rn.bf16x2 h46, h46, z14;\nadd.rn.bf16x2 h47, h47, z15;\nbra.uni RW;\n"
        "TB3:\nadd.rn.bf16x2 h48, h48, z0;\nadd.rn.bf16x2 h49, h49, z1;\nadd.rn.bf16x2 h50, h50, z2;\nadd.rn.bf16x2 h51, h51, z3;\nadd.rn.bf16x2 h52, h52, z4;\n"
        "add.rn.bf16x2 h53, h53, z5;\nadd.rn.bf16x2 h54, h54, z6;\nadd.rn.bf16x2 h55, h55, z7;\nadd.rn.bf16x2 h56, h56, z8;\nadd.rn.bf16x2 h57, h57, z9;\n"
        "add.rn.bf16x2 h58, h58, z10;\nadd.rn.bf16x2 h59, h59, z11;\nadd.rn.bf16x2 h60, h60, z12;\nadd.rn.bf16x2 h61, h61, z13;\nadd.rn.bf16x2 h62, h62, z14;\n"
        "add.rn.bf16x2 h63, h63, z15;\nbra.uni RW;\n"
        "WA:\nshr.u32 t2, v, 1;\nand.b32 t2, t2, 0xff8;\nsetp.ge.u32 p, v, 1073741824;\nvote.sync.all.pred p, p, 0xffffffff;\n@p bra.uni DONE;\nmov.b32 n, 0;\n"
        "WA3:\nmbarrier.try_wait.parity.shared.b64 p, [t2+%75], 0;\nvote.sync.all.pred p, p, 0xffffffff;\nadd.u32 n, n, 1;\nsetp.lt.and.u32 q, n, 1000000, !p;\n"
        "@q bra.uni WA3;\nlop3.b32 ida, v, %67, 0x1fff, 0xe4;\nld.volatile.shared.u16 id, [ida+%74];\nbra.uni HA;\n"
        "WB:\nshr.u32 t2, v, 1;\nand.b32 t2, t2, 0xff8;\nsetp.ge.u32 p, v, 1073741824;\nvote.sync.all.pred p, p, 0xffffffff;\n@p bra.uni DONE;\nmov.b32 n, 0;\n"
        "WB3:\nmbarrier.try_wait.parity.shared.b64 p, [t2+%75], 0;\nvote.sync.all.pred p, p, 0xffffffff;\nadd.u32 n, n, 1;\nsetp.lt.and.u32 q, n, 1000000, !p;\n"
        "@q bra.uni WB3;\nlop3.b32 ida, v, %67, 0x1fff, 0xe4;\nld.volatile.shared.u16 id, [ida+%74];\nbra.uni HB;\n"
        "DONE:\nmov.b32 %0, h0;\nmov.b32 %1, h1;\nmov.b32 %2, h2;\nmov.b32 %3, h3;\nmov.b32 %4, h4;\nmov.b32 %5, h5;\nmov.b32 %6, h6;\nmov.b32 %7, h7;\n"
        "mov.b32 %8, h8;\nmov.b32 %9, h9;\nmov.b32 %10, h10;\nmov.b32 %11, h11;\nmov.b32 %12, h12;\nmov.b32 %13, h13;\nmov.b32 %14, h14;\nmov.b32 %15, h15;\n"
        "mov.b32 %16, h16;\nmov.b32 %17, h17;\nmov.b32 %18, h18;\nmov.b32 %19, h19;\nmov.b32 %20, h20;\nmov.b32 %21, h21;\nmov.b32 %22, h22;\nmov.b32 %23, h23;\n"
        "mov.b32 %24, h24;\nmov.b32 %25, h25;\nmov.b32 %26, h26;\nmov.b32 %27, h27;\nmov.b32 %28, h28;\nmov.b32 %29, h29;\nmov.b32 %30, h30;\nmov.b32 %31, h31;\n"
        "mov.b32 %32, h32;\nmov.b32 %33, h33;\nmov.b32 %34, h34;\nmov.b32 %35, h35;\nmov.b32 %36, h36;\nmov.b32 %37, h37;\nmov.b32 %38, h38;\nmov.b32 %39, h39;\n"
        "mov.b32 %40, h40;\nmov.b32 %41, h41;\nmov.b32 %42, h42;\nmov.b32 %43, h43;\nmov.b32 %44, h44;\nmov.b32 %45, h45;\nmov.b32 %46, h46;\nmov.b32 %47, h47;\n"
        "mov.b32 %48, h48;\nmov.b32 %49, h49;\nmov.b32 %50, h50;\nmov.b32 %51, h51;\nmov.b32 %52, h52;\nmov.b32 %53, h53;\nmov.b32 %54, h54;\nmov.b32 %55, h55;\n"
        "mov.b32 %56, h56;\nmov.b32 %57, h57;\nmov.b32 %58, h58;\nmov.b32 %59, h59;\nmov.b32 %60, h60;\nmov.b32 %61, h61;\nmov.b32 %62, h62;\nmov.b32 %63, h63;\n"
        "}\n"
        : "=r"(pk[0]), "=r"(pk[1]), "=r"(pk[2]), "=r"(pk[3]), "=r"(pk[4]), "=r"(pk[5]), "=r"(pk[6]), "=r"(pk[7]), "=r"(pk[8]), "=r"(pk[9]),
          "=r"(pk[10]), "=r"(pk[11]), "=r"(pk[12]), "=r"(pk[13]), "=r"(pk[14]), "=r"(pk[15]), "=r"(pk[16]), "=r"(pk[17]), "=r"(pk[18]), "=r"(pk[19]),
          "=r"(pk[20]), "=r"(pk[21]), "=r"(pk[22]), "=r"(pk[23]), "=r"(pk[24]), "=r"(pk[25]), "=r"(pk[26]), "=r"(pk[27]), "=r"(pk[28]), "=r"(pk[29]),
          "=r"(pk[30]), "=r"(pk[31]), "=r"(pk[32]), "=r"(pk[33]), "=r"(pk[34]), "=r"(pk[35]), "=r"(pk[36]), "=r"(pk[37]), "=r"(pk[38]), "=r"(pk[39]),
          "=r"(pk[40]), "=r"(pk[41]), "=r"(pk[42]), "=r"(pk[43]), "=r"(pk[44]), "=r"(pk[45]), "=r"(pk[46]), "=r"(pk[47]), "=r"(pk[48]), "=r"(pk[49]),
          "=r"(pk[50]), "=r"(pk[51]), "=r"(pk[52]), "=r"(pk[53]), "=r"(pk[54]), "=r"(pk[55]), "=r"(pk[56]), "=r"(pk[57]), "=r"(pk[58]), "=r"(pk[59]),
          "=r"(pk[60]), "=r"(pk[61]), "=r"(pk[62]), "=r"(pk[63])
        : "r"(olp), "r"(xa), "r"(ln), "r"(lc), "r"(linc), "r"(lt), "l"(ea), "l"(sh), "l"(wf),
          "n"(sb + SM_REC), "n"(sb + SM_R), "n"(sb + SM_BAR), "n"(sb + SM_CTR),
          "r"(w[0]), "r"(w[1]), "r"(w[2]), "r"(w[3]), "r"(w[4]), "r"(w[5]), "r"(w[6]), "r"(w[7]), "r"(w[8]), "r"(w[9]), "r"(w[10]), "r"(w[11]),
          "r"(w[12]), "r"(w[13]), "r"(w[14]), "r"(w[15]), "r"(w[16]), "r"(w[17]), "r"(w[18]), "r"(w[19]), "r"(w[20]), "r"(w[21]), "r"(w[22]),
          "r"(w[23]), "r"(w[24]), "r"(w[25]), "r"(w[26]), "r"(w[27]), "r"(w[28]), "r"(w[29]), "r"(w[30]), "r"(w[31]), "r"(w[32]), "r"(w[33]),
          "r"(w[34]), "r"(w[35])
        : "memory");
}
__device__ __forceinline__ void consume3(uint32_t (&pk)[48], const uint32_t (&w)[36], uint32_t olp, uint32_t xa, uint32_t ln,
                                      uint32_t lc, uint32_t linc, uint32_t lt, const __nv_bfloat16* ea, const __nv_bfloat16* sh, const void* wf) {
    ea += lt * 4, sh += lt & 2;
    asm volatile(
        "{\n.reg .pred p, q, psw, prdy, ps1, ps2, ps3, pz;\n.reg .f32 d<32>, fz;\n"
        ".reg .b32 h<48>, x<32>, y<32>, ra<8>, rb<8>, bA0, bA1, bB0, bB1, c0, c1, c2, c3, e0, e1, s0, kept;\n"
        ".reg .b32 olp, v, vB, m, id, ida, bar, xb, pos, t0, t1, t2, t3, n, z<16>;\n.reg .b16 lo, hi, i16;\n.reg .b64 pa, pb;\nmov.f32 fz, 0f00000000;\n"
        "mov.b32 h0, 0;\nmov.b32 h1, 0;\nmov.b32 h2, 0;\nmov.b32 h3, 0;\nmov.b32 h4, 0;\nmov.b32 h5, 0;\nmov.b32 h6, 0;\nmov.b32 h7, 0;\nmov.b32 h8, 0;\n"
        "mov.b32 h9, 0;\nmov.b32 h10, 0;\nmov.b32 h11, 0;\nmov.b32 h12, 0;\nmov.b32 h13, 0;\nmov.b32 h14, 0;\nmov.b32 h15, 0;\nmov.b32 h16, 0;\nmov.b32 h17, 0;\n"
        "mov.b32 h18, 0;\nmov.b32 h19, 0;\nmov.b32 h20, 0;\nmov.b32 h21, 0;\nmov.b32 h22, 0;\nmov.b32 h23, 0;\nmov.b32 h24, 0;\nmov.b32 h25, 0;\n"
        "mov.b32 h26, 0;\nmov.b32 h27, 0;\nmov.b32 h28, 0;\nmov.b32 h29, 0;\nmov.b32 h30, 0;\nmov.b32 h31, 0;\nmov.b32 h32, 0;\nmov.b32 h33, 0;\n"
        "mov.b32 h34, 0;\nmov.b32 h35, 0;\nmov.b32 h36, 0;\nmov.b32 h37, 0;\nmov.b32 h38, 0;\nmov.b32 h39, 0;\nmov.b32 h40, 0;\nmov.b32 h41, 0;\n"
        "mov.b32 h42, 0;\nmov.b32 h43, 0;\nmov.b32 h44, 0;\nmov.b32 h45, 0;\nmov.b32 h46, 0;\nmov.b32 h47, 0;\nmov.b32 olp, %48;\nand.b32 t0, %50, 32;\n"
        "setp.ne.u32 psw, t0, 0;\nsetp.eq.u32 pz, %48, 0;\nvote.sync.any.pred pz, pz, 0xffffffff;\nld.shared.b32 t0, [olp];\nadd.u32 olp, olp, 8;\n"
        "lop3.b32 t1, t0, %50, 0x3ff0, 0xe4;\nld.shared.b32 t1, [t1+%57];\nlop3.b32 kept, t1, t0, 0x1ffc, 0xe4;\nlop3.b32 t2, t1, %51, 3, 0x80;\n"
        "setp.ne.u32 q, t2, 0;\nshr.u32 t2, t1, 13;\nmad.wide.u32 pa, t2, 32, %54;\nmad.wide.u32 pb, t2, 8, %55;\nmov.b32 s0, 0;\n"
        "ld.global.cg.v2.b32 {e0,e1}, [pa];\n@q ld.global.cg.b32 s0, [pb];\nsetp.ne.u64 p, %56, 0;\n@p fence.proxy.async.global;\n"
        "@p red.release.gpu.global.add.u32 [%56+12], 1;\nbar.warp.sync 0xffffffff;\nshfl.sync.idx.b32 v, kept, %51, 0x1f, 0xffffffff;\nor.b32 t3, %51, 4;\n"
        "shfl.sync.idx.b32 vB, kept, t3, 0x1f, 0xffffffff;\nshr.u32 bar, v, 1;\nand.b32 bar, bar, 0xff8;\nmbarrier.test_wait.parity.shared.b64 p, [bar+%59], 0;\n"
        "lop3.b32 ida, v, %51, 0x1fff, 0xe4;\nld.volatile.shared.u16 id, [ida+%58];\nvote.sync.all.pred prdy, p, 0xffffffff;\n"
        "RW:\nmma.sync.aligned.m16n8k8.row.col.f32.bf16.bf16.f32 {d0,d1,d2,d3}, {%93,%94}, {s0}, {fz,fz,fz,fz};\n"
        "mma.sync.aligned.m16n8k8.row.col.f32.bf16.bf16.f32 {d4,d5,d6,d7}, {%95,%96}, {s0}, {fz,fz,fz,fz};\ncvt.rn.bf16x2.f32 c0, d2, d0;\n"
        "cvt.rn.bf16x2.f32 c1, d3, d1;\ncvt.rn.bf16x2.f32 c2, d6, d4;\ncvt.rn.bf16x2.f32 c3, d7, d5;\nselp.b32 bA0, c2, c0, psw;\nselp.b32 bA1, c0, c2, psw;\n"
        "selp.b32 bB0, c3, c1, psw;\nselp.b32 bB1, c1, c3, psw;\n"
        "mma.sync.aligned.m16n8k16.row.col.f32.bf16.bf16.f32 {d0,d1,d2,d3}, {%61,%62,%63,%64}, {e0,e1}, {fz,fz,fz,fz};\ncvt.rn.bf16x2.f32 ra0, d2, d0;\n"
        "cvt.rn.bf16x2.f32 rb0, d3, d1;\nmma.sync.aligned.m16n8k16.row.col.f32.bf16.bf16.f32 {d4,d5,d6,d7}, {%65,%66,%67,%68}, {e0,e1}, {fz,fz,fz,fz};\n"
        "cvt.rn.bf16x2.f32 ra1, d6, d4;\ncvt.rn.bf16x2.f32 rb1, d7, d5;\n"
        "mma.sync.aligned.m16n8k16.row.col.f32.bf16.bf16.f32 {d8,d9,d10,d11}, {%69,%70,%71,%72}, {e0,e1}, {fz,fz,fz,fz};\ncvt.rn.bf16x2.f32 ra2, d10, d8;\n"
        "cvt.rn.bf16x2.f32 rb2, d11, d9;\nmma.sync.aligned.m16n8k16.row.col.f32.bf16.bf16.f32 {d12,d13,d14,d15}, {%73,%74,%75,%76}, {e0,e1}, {fz,fz,fz,fz};\n"
        "cvt.rn.bf16x2.f32 ra3, d14, d12;\ncvt.rn.bf16x2.f32 rb3, d15, d13;\n"
        "mma.sync.aligned.m16n8k16.row.col.f32.bf16.bf16.f32 {d16,d17,d18,d19}, {%77,%78,%79,%80}, {e0,e1}, {fz,fz,fz,fz};\ncvt.rn.bf16x2.f32 ra4, d18, d16;\n"
        "cvt.rn.bf16x2.f32 rb4, d19, d17;\nmma.sync.aligned.m16n8k16.row.col.f32.bf16.bf16.f32 {d20,d21,d22,d23}, {%81,%82,%83,%84}, {e0,e1}, {fz,fz,fz,fz};\n"
        "cvt.rn.bf16x2.f32 ra5, d22, d20;\ncvt.rn.bf16x2.f32 rb5, d23, d21;\n"
        "mma.sync.aligned.m16n8k16.row.col.f32.bf16.bf16.f32 {d24,d25,d26,d27}, {%85,%86,%87,%88}, {e0,e1}, {fz,fz,fz,fz};\ncvt.rn.bf16x2.f32 ra6, d26, d24;\n"
        "cvt.rn.bf16x2.f32 rb6, d27, d25;\nmma.sync.aligned.m16n8k16.row.col.f32.bf16.bf16.f32 {d28,d29,d30,d31}, {%89,%90,%91,%92}, {e0,e1}, {fz,fz,fz,fz};\n"
        "cvt.rn.bf16x2.f32 ra7, d30, d28;\ncvt.rn.bf16x2.f32 rb7, d31, d29;\nld.shared.b32 t0, [olp];\nadd.u32 olp, olp, 8;\n"
        "lop3.b32 t1, t0, %50, 0x3ff0, 0xe4;\nld.shared.b32 t1, [t1+%57];\nlop3.b32 kept, t1, t0, 0x1ffc, 0xe4;\nlop3.b32 t2, t1, %51, 3, 0x80;\n"
        "setp.ne.u32 q, t2, 0;\nshr.u32 t2, t1, 13;\nmad.wide.u32 pa, t2, 32, %54;\nmad.wide.u32 pb, t2, 8, %55;\nmov.b32 s0, 0;\n"
        "ld.global.cg.v2.b32 {e0,e1}, [pa];\n@q ld.global.cg.b32 s0, [pb];\n@!prdy bra.uni WA;\n"
        "HA:\nmad.lo.u32 xb, id, 64, %49;\ncvt.u16.u32 i16, id;\nldmatrix.sync.aligned.m8n8.x4.trans.shared.b16 {x0,x1,x2,x3}, [xb];\nxor.b32 t1, xb, 16;\n"
        "ldmatrix.sync.aligned.m8n8.x4.trans.shared.b16 {x4,x5,x6,x7}, [t1];\nxor.b32 t1, xb, 32;\n"
        "ldmatrix.sync.aligned.m8n8.x4.trans.shared.b16 {x8,x9,x10,x11}, [t1];\nxor.b32 t1, xb, 48;\n"
        "ldmatrix.sync.aligned.m8n8.x4.trans.shared.b16 {x12,x13,x14,x15}, [t1];\nxor.b32 t1, xb, 64;\n"
        "ldmatrix.sync.aligned.m8n8.x4.trans.shared.b16 {x16,x17,x18,x19}, [t1];\n@pz bra.uni DONE;\natom.shared.add.u32 pos, [%50+%60], %52;\n"
        "xor.b32 t1, xb, 80;\nldmatrix.sync.aligned.m8n8.x4.trans.shared.b16 {x20,x21,x22,x23}, [t1];\nxor.b32 t1, xb, 96;\n"
        "ldmatrix.sync.aligned.m8n8.x4.trans.shared.b16 {x24,x25,x26,x27}, [t1];\nxor.b32 t1, xb, 112;\n"
        "ldmatrix.sync.aligned.m8n8.x4.trans.shared.b16 {x28,x29,x30,x31}, [t1];\nst.volatile.shared.u16 [pos], i16;\nand.b32 t0, v, 268435456;\n"
        "setp.ne.u32 ps1, t0, 0;\nvote.sync.any.pred ps1, ps1, 0xffffffff;\nand.b32 t0, v, 536870912;\nsetp.ne.u32 ps2, t0, 0;\n"
        "vote.sync.any.pred ps2, ps2, 0xffffffff;\nmov.b32 v, vB;\nshr.u32 bar, v, 1;\nand.b32 bar, bar, 0xff8;\n"
        "mbarrier.test_wait.parity.shared.b64 p, [bar+%59], 0;\nlop3.b32 ida, v, %51, 0x1fff, 0xe4;\nld.volatile.shared.u16 id, [ida+%58];\n"
        "vote.sync.all.pred prdy, p, 0xffffffff;\nmov.b32 {lo, hi}, ra0;\nmov.b32 t2, {lo, lo};\nmul.rn.bf16x2 y0, x0, t2;\nmul.rn.bf16x2 y2, x2, t2;\n"
        "mov.b32 t2, {hi, hi};\nmul.rn.bf16x2 y1, x1, t2;\nmul.rn.bf16x2 y3, x3, t2;\n"
        "mma.sync.aligned.m16n8k16.row.col.f32.bf16.bf16.f32 {d0,d1,d2,d3}, {y0,y1,y2,y3}, {bA0,bA1}, {fz,fz,fz,fz};\ncvt.rn.bf16x2.f32 z0, d1, d0;\n"
        "cvt.rn.bf16x2.f32 z1, d3, d2;\nmov.b32 {lo, hi}, ra1;\nmov.b32 t2, {lo, lo};\nmul.rn.bf16x2 y4, x4, t2;\nmul.rn.bf16x2 y6, x6, t2;\n"
        "mov.b32 t2, {hi, hi};\nmul.rn.bf16x2 y5, x5, t2;\nmul.rn.bf16x2 y7, x7, t2;\n"
        "mma.sync.aligned.m16n8k16.row.col.f32.bf16.bf16.f32 {d4,d5,d6,d7}, {y4,y5,y6,y7}, {bA0,bA1}, {fz,fz,fz,fz};\ncvt.rn.bf16x2.f32 z2, d5, d4;\n"
        "cvt.rn.bf16x2.f32 z3, d7, d6;\nmov.b32 {lo, hi}, ra2;\nmov.b32 t2, {lo, lo};\nmul.rn.bf16x2 y8, x8, t2;\nmul.rn.bf16x2 y10, x10, t2;\n"
        "mov.b32 t2, {hi, hi};\nmul.rn.bf16x2 y9, x9, t2;\nmul.rn.bf16x2 y11, x11, t2;\n"
        "mma.sync.aligned.m16n8k16.row.col.f32.bf16.bf16.f32 {d8,d9,d10,d11}, {y8,y9,y10,y11}, {bA0,bA1}, {fz,fz,fz,fz};\ncvt.rn.bf16x2.f32 z4, d9, d8;\n"
        "cvt.rn.bf16x2.f32 z5, d11, d10;\nmov.b32 {lo, hi}, ra3;\nmov.b32 t2, {lo, lo};\nmul.rn.bf16x2 y12, x12, t2;\nmul.rn.bf16x2 y14, x14, t2;\n"
        "mov.b32 t2, {hi, hi};\nmul.rn.bf16x2 y13, x13, t2;\nmul.rn.bf16x2 y15, x15, t2;\n"
        "mma.sync.aligned.m16n8k16.row.col.f32.bf16.bf16.f32 {d12,d13,d14,d15}, {y12,y13,y14,y15}, {bA0,bA1}, {fz,fz,fz,fz};\ncvt.rn.bf16x2.f32 z6, d13, d12;\n"
        "cvt.rn.bf16x2.f32 z7, d15, d14;\nmov.b32 {lo, hi}, ra4;\nmov.b32 t2, {lo, lo};\nmul.rn.bf16x2 y16, x16, t2;\nmul.rn.bf16x2 y18, x18, t2;\n"
        "mov.b32 t2, {hi, hi};\nmul.rn.bf16x2 y17, x17, t2;\nmul.rn.bf16x2 y19, x19, t2;\n"
        "mma.sync.aligned.m16n8k16.row.col.f32.bf16.bf16.f32 {d16,d17,d18,d19}, {y16,y17,y18,y19}, {bA0,bA1}, {fz,fz,fz,fz};\ncvt.rn.bf16x2.f32 z8, d17, d16;\n"
        "cvt.rn.bf16x2.f32 z9, d19, d18;\nmov.b32 {lo, hi}, ra5;\nmov.b32 t2, {lo, lo};\nmul.rn.bf16x2 y20, x20, t2;\nmul.rn.bf16x2 y22, x22, t2;\n"
        "mov.b32 t2, {hi, hi};\nmul.rn.bf16x2 y21, x21, t2;\nmul.rn.bf16x2 y23, x23, t2;\n"
        "mma.sync.aligned.m16n8k16.row.col.f32.bf16.bf16.f32 {d20,d21,d22,d23}, {y20,y21,y22,y23}, {bA0,bA1}, {fz,fz,fz,fz};\ncvt.rn.bf16x2.f32 z10, d21, d20;\n"
        "cvt.rn.bf16x2.f32 z11, d23, d22;\nmov.b32 {lo, hi}, ra6;\nmov.b32 t2, {lo, lo};\nmul.rn.bf16x2 y24, x24, t2;\nmul.rn.bf16x2 y26, x26, t2;\n"
        "mov.b32 t2, {hi, hi};\nmul.rn.bf16x2 y25, x25, t2;\nmul.rn.bf16x2 y27, x27, t2;\n"
        "mma.sync.aligned.m16n8k16.row.col.f32.bf16.bf16.f32 {d24,d25,d26,d27}, {y24,y25,y26,y27}, {bA0,bA1}, {fz,fz,fz,fz};\ncvt.rn.bf16x2.f32 z12, d25, d24;\n"
        "cvt.rn.bf16x2.f32 z13, d27, d26;\nmov.b32 {lo, hi}, ra7;\nmov.b32 t2, {lo, lo};\nmul.rn.bf16x2 y28, x28, t2;\nmul.rn.bf16x2 y30, x30, t2;\n"
        "mov.b32 t2, {hi, hi};\nmul.rn.bf16x2 y29, x29, t2;\nmul.rn.bf16x2 y31, x31, t2;\n"
        "mma.sync.aligned.m16n8k16.row.col.f32.bf16.bf16.f32 {d28,d29,d30,d31}, {y28,y29,y30,y31}, {bA0,bA1}, {fz,fz,fz,fz};\ncvt.rn.bf16x2.f32 z14, d29, d28;\n"
        "cvt.rn.bf16x2.f32 z15, d31, d30;\n@ps2 bra.uni TA2;\n@ps1 bra.uni TA1;\n"
        "TA0:\nadd.rn.bf16x2 h0, h0, z0;\nadd.rn.bf16x2 h1, h1, z1;\nadd.rn.bf16x2 h2, h2, z2;\nadd.rn.bf16x2 h3, h3, z3;\nadd.rn.bf16x2 h4, h4, z4;\n"
        "add.rn.bf16x2 h5, h5, z5;\nadd.rn.bf16x2 h6, h6, z6;\nadd.rn.bf16x2 h7, h7, z7;\nadd.rn.bf16x2 h8, h8, z8;\nadd.rn.bf16x2 h9, h9, z9;\n"
        "add.rn.bf16x2 h10, h10, z10;\nadd.rn.bf16x2 h11, h11, z11;\nadd.rn.bf16x2 h12, h12, z12;\nadd.rn.bf16x2 h13, h13, z13;\nadd.rn.bf16x2 h14, h14, z14;\n"
        "add.rn.bf16x2 h15, h15, z15;\n@prdy bra.uni HB;\nbra.uni WB;\n"
        "TA1:\nadd.rn.bf16x2 h16, h16, z0;\nadd.rn.bf16x2 h17, h17, z1;\nadd.rn.bf16x2 h18, h18, z2;\nadd.rn.bf16x2 h19, h19, z3;\nadd.rn.bf16x2 h20, h20, z4;\n"
        "add.rn.bf16x2 h21, h21, z5;\nadd.rn.bf16x2 h22, h22, z6;\nadd.rn.bf16x2 h23, h23, z7;\nadd.rn.bf16x2 h24, h24, z8;\nadd.rn.bf16x2 h25, h25, z9;\n"
        "add.rn.bf16x2 h26, h26, z10;\nadd.rn.bf16x2 h27, h27, z11;\nadd.rn.bf16x2 h28, h28, z12;\nadd.rn.bf16x2 h29, h29, z13;\nadd.rn.bf16x2 h30, h30, z14;\n"
        "add.rn.bf16x2 h31, h31, z15;\n@prdy bra.uni HB;\nbra.uni WB;\n"
        "TA2:\nadd.rn.bf16x2 h32, h32, z0;\nadd.rn.bf16x2 h33, h33, z1;\nadd.rn.bf16x2 h34, h34, z2;\nadd.rn.bf16x2 h35, h35, z3;\nadd.rn.bf16x2 h36, h36, z4;\n"
        "add.rn.bf16x2 h37, h37, z5;\nadd.rn.bf16x2 h38, h38, z6;\nadd.rn.bf16x2 h39, h39, z7;\nadd.rn.bf16x2 h40, h40, z8;\nadd.rn.bf16x2 h41, h41, z9;\n"
        "add.rn.bf16x2 h42, h42, z10;\nadd.rn.bf16x2 h43, h43, z11;\nadd.rn.bf16x2 h44, h44, z12;\nadd.rn.bf16x2 h45, h45, z13;\nadd.rn.bf16x2 h46, h46, z14;\n"
        "add.rn.bf16x2 h47, h47, z15;\n@prdy bra.uni HB;\nbra.uni WB;\n"
        "HB:\nmad.lo.u32 xb, id, 64, %49;\ncvt.u16.u32 i16, id;\natom.shared.add.u32 pos, [%50+%60], %52;\n"
        "ldmatrix.sync.aligned.m8n8.x4.trans.shared.b16 {x0,x1,x2,x3}, [xb];\nxor.b32 t1, xb, 16;\n"
        "ldmatrix.sync.aligned.m8n8.x4.trans.shared.b16 {x4,x5,x6,x7}, [t1];\nxor.b32 t1, xb, 32;\n"
        "ldmatrix.sync.aligned.m8n8.x4.trans.shared.b16 {x8,x9,x10,x11}, [t1];\nxor.b32 t1, xb, 48;\n"
        "ldmatrix.sync.aligned.m8n8.x4.trans.shared.b16 {x12,x13,x14,x15}, [t1];\nxor.b32 t1, xb, 64;\n"
        "ldmatrix.sync.aligned.m8n8.x4.trans.shared.b16 {x16,x17,x18,x19}, [t1];\nxor.b32 t1, xb, 80;\n"
        "ldmatrix.sync.aligned.m8n8.x4.trans.shared.b16 {x20,x21,x22,x23}, [t1];\nxor.b32 t1, xb, 96;\n"
        "ldmatrix.sync.aligned.m8n8.x4.trans.shared.b16 {x24,x25,x26,x27}, [t1];\nxor.b32 t1, xb, 112;\n"
        "ldmatrix.sync.aligned.m8n8.x4.trans.shared.b16 {x28,x29,x30,x31}, [t1];\nst.volatile.shared.u16 [pos], i16;\nand.b32 t0, v, 268435456;\n"
        "setp.ne.u32 ps1, t0, 0;\nvote.sync.any.pred ps1, ps1, 0xffffffff;\nand.b32 t0, v, 536870912;\nsetp.ne.u32 ps2, t0, 0;\n"
        "vote.sync.any.pred ps2, ps2, 0xffffffff;\nshfl.sync.idx.b32 v, kept, %51, 0x1f, 0xffffffff;\nor.b32 t3, %51, 4;\n"
        "shfl.sync.idx.b32 vB, kept, t3, 0x1f, 0xffffffff;\nshr.u32 bar, v, 1;\nand.b32 bar, bar, 0xff8;\nmbarrier.test_wait.parity.shared.b64 p, [bar+%59], 0;\n"
        "lop3.b32 ida, v, %51, 0x1fff, 0xe4;\nld.volatile.shared.u16 id, [ida+%58];\nvote.sync.all.pred prdy, p, 0xffffffff;\nmov.b32 {lo, hi}, rb0;\n"
        "mov.b32 t2, {lo, lo};\nmul.rn.bf16x2 y0, x0, t2;\nmul.rn.bf16x2 y2, x2, t2;\nmov.b32 t2, {hi, hi};\nmul.rn.bf16x2 y1, x1, t2;\n"
        "mul.rn.bf16x2 y3, x3, t2;\nmma.sync.aligned.m16n8k16.row.col.f32.bf16.bf16.f32 {d0,d1,d2,d3}, {y0,y1,y2,y3}, {bB0,bB1}, {fz,fz,fz,fz};\n"
        "cvt.rn.bf16x2.f32 z0, d1, d0;\ncvt.rn.bf16x2.f32 z1, d3, d2;\nmov.b32 {lo, hi}, rb1;\nmov.b32 t2, {lo, lo};\nmul.rn.bf16x2 y4, x4, t2;\n"
        "mul.rn.bf16x2 y6, x6, t2;\nmov.b32 t2, {hi, hi};\nmul.rn.bf16x2 y5, x5, t2;\nmul.rn.bf16x2 y7, x7, t2;\n"
        "mma.sync.aligned.m16n8k16.row.col.f32.bf16.bf16.f32 {d4,d5,d6,d7}, {y4,y5,y6,y7}, {bB0,bB1}, {fz,fz,fz,fz};\ncvt.rn.bf16x2.f32 z2, d5, d4;\n"
        "cvt.rn.bf16x2.f32 z3, d7, d6;\nmov.b32 {lo, hi}, rb2;\nmov.b32 t2, {lo, lo};\nmul.rn.bf16x2 y8, x8, t2;\nmul.rn.bf16x2 y10, x10, t2;\n"
        "mov.b32 t2, {hi, hi};\nmul.rn.bf16x2 y9, x9, t2;\nmul.rn.bf16x2 y11, x11, t2;\n"
        "mma.sync.aligned.m16n8k16.row.col.f32.bf16.bf16.f32 {d8,d9,d10,d11}, {y8,y9,y10,y11}, {bB0,bB1}, {fz,fz,fz,fz};\ncvt.rn.bf16x2.f32 z4, d9, d8;\n"
        "cvt.rn.bf16x2.f32 z5, d11, d10;\nmov.b32 {lo, hi}, rb3;\nmov.b32 t2, {lo, lo};\nmul.rn.bf16x2 y12, x12, t2;\nmul.rn.bf16x2 y14, x14, t2;\n"
        "mov.b32 t2, {hi, hi};\nmul.rn.bf16x2 y13, x13, t2;\nmul.rn.bf16x2 y15, x15, t2;\n"
        "mma.sync.aligned.m16n8k16.row.col.f32.bf16.bf16.f32 {d12,d13,d14,d15}, {y12,y13,y14,y15}, {bB0,bB1}, {fz,fz,fz,fz};\ncvt.rn.bf16x2.f32 z6, d13, d12;\n"
        "cvt.rn.bf16x2.f32 z7, d15, d14;\nmov.b32 {lo, hi}, rb4;\nmov.b32 t2, {lo, lo};\nmul.rn.bf16x2 y16, x16, t2;\nmul.rn.bf16x2 y18, x18, t2;\n"
        "mov.b32 t2, {hi, hi};\nmul.rn.bf16x2 y17, x17, t2;\nmul.rn.bf16x2 y19, x19, t2;\n"
        "mma.sync.aligned.m16n8k16.row.col.f32.bf16.bf16.f32 {d16,d17,d18,d19}, {y16,y17,y18,y19}, {bB0,bB1}, {fz,fz,fz,fz};\ncvt.rn.bf16x2.f32 z8, d17, d16;\n"
        "cvt.rn.bf16x2.f32 z9, d19, d18;\nmov.b32 {lo, hi}, rb5;\nmov.b32 t2, {lo, lo};\nmul.rn.bf16x2 y20, x20, t2;\nmul.rn.bf16x2 y22, x22, t2;\n"
        "mov.b32 t2, {hi, hi};\nmul.rn.bf16x2 y21, x21, t2;\nmul.rn.bf16x2 y23, x23, t2;\n"
        "mma.sync.aligned.m16n8k16.row.col.f32.bf16.bf16.f32 {d20,d21,d22,d23}, {y20,y21,y22,y23}, {bB0,bB1}, {fz,fz,fz,fz};\ncvt.rn.bf16x2.f32 z10, d21, d20;\n"
        "cvt.rn.bf16x2.f32 z11, d23, d22;\nmov.b32 {lo, hi}, rb6;\nmov.b32 t2, {lo, lo};\nmul.rn.bf16x2 y24, x24, t2;\nmul.rn.bf16x2 y26, x26, t2;\n"
        "mov.b32 t2, {hi, hi};\nmul.rn.bf16x2 y25, x25, t2;\nmul.rn.bf16x2 y27, x27, t2;\n"
        "mma.sync.aligned.m16n8k16.row.col.f32.bf16.bf16.f32 {d24,d25,d26,d27}, {y24,y25,y26,y27}, {bB0,bB1}, {fz,fz,fz,fz};\ncvt.rn.bf16x2.f32 z12, d25, d24;\n"
        "cvt.rn.bf16x2.f32 z13, d27, d26;\nmov.b32 {lo, hi}, rb7;\nmov.b32 t2, {lo, lo};\nmul.rn.bf16x2 y28, x28, t2;\nmul.rn.bf16x2 y30, x30, t2;\n"
        "mov.b32 t2, {hi, hi};\nmul.rn.bf16x2 y29, x29, t2;\nmul.rn.bf16x2 y31, x31, t2;\n"
        "mma.sync.aligned.m16n8k16.row.col.f32.bf16.bf16.f32 {d28,d29,d30,d31}, {y28,y29,y30,y31}, {bB0,bB1}, {fz,fz,fz,fz};\ncvt.rn.bf16x2.f32 z14, d29, d28;\n"
        "cvt.rn.bf16x2.f32 z15, d31, d30;\n@ps2 bra.uni TB2;\n@ps1 bra.uni TB1;\n"
        "TB0:\nadd.rn.bf16x2 h0, h0, z0;\nadd.rn.bf16x2 h1, h1, z1;\nadd.rn.bf16x2 h2, h2, z2;\nadd.rn.bf16x2 h3, h3, z3;\nadd.rn.bf16x2 h4, h4, z4;\n"
        "add.rn.bf16x2 h5, h5, z5;\nadd.rn.bf16x2 h6, h6, z6;\nadd.rn.bf16x2 h7, h7, z7;\nadd.rn.bf16x2 h8, h8, z8;\nadd.rn.bf16x2 h9, h9, z9;\n"
        "add.rn.bf16x2 h10, h10, z10;\nadd.rn.bf16x2 h11, h11, z11;\nadd.rn.bf16x2 h12, h12, z12;\nadd.rn.bf16x2 h13, h13, z13;\nadd.rn.bf16x2 h14, h14, z14;\n"
        "add.rn.bf16x2 h15, h15, z15;\nbra.uni RW;\n"
        "TB1:\nadd.rn.bf16x2 h16, h16, z0;\nadd.rn.bf16x2 h17, h17, z1;\nadd.rn.bf16x2 h18, h18, z2;\nadd.rn.bf16x2 h19, h19, z3;\nadd.rn.bf16x2 h20, h20, z4;\n"
        "add.rn.bf16x2 h21, h21, z5;\nadd.rn.bf16x2 h22, h22, z6;\nadd.rn.bf16x2 h23, h23, z7;\nadd.rn.bf16x2 h24, h24, z8;\nadd.rn.bf16x2 h25, h25, z9;\n"
        "add.rn.bf16x2 h26, h26, z10;\nadd.rn.bf16x2 h27, h27, z11;\nadd.rn.bf16x2 h28, h28, z12;\nadd.rn.bf16x2 h29, h29, z13;\nadd.rn.bf16x2 h30, h30, z14;\n"
        "add.rn.bf16x2 h31, h31, z15;\nbra.uni RW;\n"
        "TB2:\nadd.rn.bf16x2 h32, h32, z0;\nadd.rn.bf16x2 h33, h33, z1;\nadd.rn.bf16x2 h34, h34, z2;\nadd.rn.bf16x2 h35, h35, z3;\nadd.rn.bf16x2 h36, h36, z4;\n"
        "add.rn.bf16x2 h37, h37, z5;\nadd.rn.bf16x2 h38, h38, z6;\nadd.rn.bf16x2 h39, h39, z7;\nadd.rn.bf16x2 h40, h40, z8;\nadd.rn.bf16x2 h41, h41, z9;\n"
        "add.rn.bf16x2 h42, h42, z10;\nadd.rn.bf16x2 h43, h43, z11;\nadd.rn.bf16x2 h44, h44, z12;\nadd.rn.bf16x2 h45, h45, z13;\nadd.rn.bf16x2 h46, h46, z14;\n"
        "add.rn.bf16x2 h47, h47, z15;\nbra.uni RW;\n"
        "WA:\nshr.u32 t2, v, 1;\nand.b32 t2, t2, 0xff8;\nsetp.ge.u32 p, v, 805306368;\nvote.sync.all.pred p, p, 0xffffffff;\n@p bra.uni DONE;\nmov.b32 n, 0;\n"
        "WA3:\nmbarrier.try_wait.parity.shared.b64 p, [t2+%59], 0;\nvote.sync.all.pred p, p, 0xffffffff;\nadd.u32 n, n, 1;\nsetp.lt.and.u32 q, n, 1000000, !p;\n"
        "@q bra.uni WA3;\nlop3.b32 ida, v, %51, 0x1fff, 0xe4;\nld.volatile.shared.u16 id, [ida+%58];\nbra.uni HA;\n"
        "WB:\nshr.u32 t2, v, 1;\nand.b32 t2, t2, 0xff8;\nsetp.ge.u32 p, v, 805306368;\nvote.sync.all.pred p, p, 0xffffffff;\n@p bra.uni DONE;\nmov.b32 n, 0;\n"
        "WB3:\nmbarrier.try_wait.parity.shared.b64 p, [t2+%59], 0;\nvote.sync.all.pred p, p, 0xffffffff;\nadd.u32 n, n, 1;\nsetp.lt.and.u32 q, n, 1000000, !p;\n"
        "@q bra.uni WB3;\nlop3.b32 ida, v, %51, 0x1fff, 0xe4;\nld.volatile.shared.u16 id, [ida+%58];\nbra.uni HB;\n"
        "DONE:\nmov.b32 %0, h0;\nmov.b32 %1, h1;\nmov.b32 %2, h2;\nmov.b32 %3, h3;\nmov.b32 %4, h4;\nmov.b32 %5, h5;\nmov.b32 %6, h6;\nmov.b32 %7, h7;\n"
        "mov.b32 %8, h8;\nmov.b32 %9, h9;\nmov.b32 %10, h10;\nmov.b32 %11, h11;\nmov.b32 %12, h12;\nmov.b32 %13, h13;\nmov.b32 %14, h14;\nmov.b32 %15, h15;\n"
        "mov.b32 %16, h16;\nmov.b32 %17, h17;\nmov.b32 %18, h18;\nmov.b32 %19, h19;\nmov.b32 %20, h20;\nmov.b32 %21, h21;\nmov.b32 %22, h22;\nmov.b32 %23, h23;\n"
        "mov.b32 %24, h24;\nmov.b32 %25, h25;\nmov.b32 %26, h26;\nmov.b32 %27, h27;\nmov.b32 %28, h28;\nmov.b32 %29, h29;\nmov.b32 %30, h30;\nmov.b32 %31, h31;\n"
        "mov.b32 %32, h32;\nmov.b32 %33, h33;\nmov.b32 %34, h34;\nmov.b32 %35, h35;\nmov.b32 %36, h36;\nmov.b32 %37, h37;\nmov.b32 %38, h38;\nmov.b32 %39, h39;\n"
        "mov.b32 %40, h40;\nmov.b32 %41, h41;\nmov.b32 %42, h42;\nmov.b32 %43, h43;\nmov.b32 %44, h44;\nmov.b32 %45, h45;\nmov.b32 %46, h46;\nmov.b32 %47, h47;\n"
        "}\n"
        : "=r"(pk[0]), "=r"(pk[1]), "=r"(pk[2]), "=r"(pk[3]), "=r"(pk[4]), "=r"(pk[5]), "=r"(pk[6]), "=r"(pk[7]), "=r"(pk[8]), "=r"(pk[9]),
          "=r"(pk[10]), "=r"(pk[11]), "=r"(pk[12]), "=r"(pk[13]), "=r"(pk[14]), "=r"(pk[15]), "=r"(pk[16]), "=r"(pk[17]), "=r"(pk[18]), "=r"(pk[19]),
          "=r"(pk[20]), "=r"(pk[21]), "=r"(pk[22]), "=r"(pk[23]), "=r"(pk[24]), "=r"(pk[25]), "=r"(pk[26]), "=r"(pk[27]), "=r"(pk[28]), "=r"(pk[29]),
          "=r"(pk[30]), "=r"(pk[31]), "=r"(pk[32]), "=r"(pk[33]), "=r"(pk[34]), "=r"(pk[35]), "=r"(pk[36]), "=r"(pk[37]), "=r"(pk[38]), "=r"(pk[39]),
          "=r"(pk[40]), "=r"(pk[41]), "=r"(pk[42]), "=r"(pk[43]), "=r"(pk[44]), "=r"(pk[45]), "=r"(pk[46]), "=r"(pk[47])
        : "r"(olp), "r"(xa), "r"(ln), "r"(lc), "r"(linc), "r"(lt), "l"(ea), "l"(sh), "l"(wf),
          "n"(sb + SM_REC), "n"(sb + SM_R), "n"(sb + SM_BAR), "n"(sb + SM_CTR),
          "r"(w[0]), "r"(w[1]), "r"(w[2]), "r"(w[3]), "r"(w[4]), "r"(w[5]), "r"(w[6]), "r"(w[7]), "r"(w[8]), "r"(w[9]), "r"(w[10]), "r"(w[11]),
          "r"(w[12]), "r"(w[13]), "r"(w[14]), "r"(w[15]), "r"(w[16]), "r"(w[17]), "r"(w[18]), "r"(w[19]), "r"(w[20]), "r"(w[21]), "r"(w[22]),
          "r"(w[23]), "r"(w[24]), "r"(w[25]), "r"(w[26]), "r"(w[27]), "r"(w[28]), "r"(w[29]), "r"(w[30]), "r"(w[31]), "r"(w[32]), "r"(w[33]),
          "r"(w[34]), "r"(w[35])
        : "memory");
}

__device__ __forceinline__ void wf_done() {
    asm volatile("fence.proxy.async.global;\nred.release.gpu.global.add.u32 [%0+12], 1;" ::"l"(g_sync) : "memory");
}

template <int NS>
__device__ __forceinline__ void consumer(const __nv_bfloat16* __restrict__ sh,
                                         const __nv_bfloat16* __restrict__ ea, __nv_bfloat16* __restrict__ out, int N, int npb) {
    uint32_t pk[NS * 16];
    {
        const int lane = threadIdx.x & 31, warp = threadIdx.x >> 5;
        const int mi = lane >> 3, r = lane & 7, j = r >> 1;
        const int u = 2 * ((mi >> 1) ^ (j >> 1)) + (r & 1), ph = (j ^ (j >> 1)) & 1;
        uint32_t w[36];
        {
            const uint32_t a = sb + SC_WR + (4 * j + (r & 1) + (mi & 2)) * 272 + (mi & 1) * (PH == 128 ? 128 : 16);
#pragma unroll
            for (int c = 0; c < 8; c++)
                asm volatile("ldmatrix.sync.aligned.m8n8.x4.trans.shared.b16 {%0,%1,%2,%3}, [%4];"
                             : "=r"(w[4 * c]), "=r"(w[4 * c + 1]), "=r"(w[4 * c + 2]), "=r"(w[4 * c + 3]) : "r"(a + c * (PH == 128 ? 16 : 32)) : "memory");
            const uint32_t ca = sb + SC_CG + (lane & 2) * 8 + ((lane >> 2) & 3) * 2;
#pragma unroll
            for (int k = 0; k < 4; k++) {
                const uint32_t f = lds16(ca + 32 * k) | (lds16(ca + 32 * k + 8) << 16);
                w[32 + k] = (lane & 1) == (lane >> 4) ? f : 0;
            }
            asm volatile("fence.proxy.async.shared::cta;\nbar.sync 2, %0;" ::"n"(NCW * 32) : "memory");
            if (threadIdx.x < WSL) sts16(sb + SM_R + 0x2000 + (4 + SP - WSL + lane) * 4, (sb + SC_WR) / 64 + lane * 16);
        }
        const int L = 2 * u + (mi & 1);
        const uint32_t xa = __shfl_sync(0xffffffffu, PH == 128 ? L * 128 + (((L + ph) & 7) << 4) : u * 128 + (((u + 4 * ph) ^ (mi & 1)) << 4), lane);
        const uint32_t ln = __shfl_sync(0xffffffffu, lane * 16 + (lane >> 3) * 4, lane);
        const uint32_t lc = __shfl_sync(0xffffffffu, j * 8 + (1 << (lane & 1)) + (ph << 13), lane);
        const uint32_t linc = __shfl_sync(0xffffffffu, (lane & 0x19) ? 0 : 8, lane);
        const uint32_t lt = __shfl_sync(0xffffffffu, lane & 3, lane);
        const void* wfp = (threadIdx.x >> 2) == WFT && blockIdx.x < 128 ? g_sync : nullptr;
        const uint32_t olp = sb + SM_OL + warp * (OLN * 4) + (lane & 4);
        if constexpr (NS == 4) consume4(pk, w, olp, xa, ln, lc, linc, lt, ea, sh, wfp);
        else consume3(pk, w, olp, xa, ln, lc, linc, lt, ea, sh, wfp);
    }
    TLMAX(10);
    const int tid = thread_id(), lane = tid & 31, warp = tid >> 5, g = lane >> 2, t = lane & 3;
    const uint32_t wc = lds32(sb + SM_MISC + 12) + 1;
    const uint32_t inv = lds32(sb + SM_INV + warp * 4);
    const int node0 = cta_id() * npb, nnodes = min(npb, N - node0);
    uint4* op[NS];
    uint32_t on[NS];
#pragma unroll
    for (int s = 0; s < NS; s++) {
        const int nl = ((inv >> (8 * s)) & 255) + (g >> 2) * 40;
        op[s] = (uint4*)(out + ((size_t)(node0 + nl) * 4 + (g & 3)) * 128 + 8 * t);
        on[s] = nl < nnodes;
    }
    if constexpr (NS == 4) project4(pk, sb + SM_R + wc * 16, sb + SM_BAR + wc * 8, op, on);
    else project3(pk, sb + SM_R + wc * 16, sb + SM_BAR + wc * 8, op, on);
}

#define TLHI "shl.b32 d, tb, 16;\n"
#define RAOFF ((threadIdx.x & 96) >> 1)
#define UNPACK(v) "dp2a.lo.u32.u32 d, " #v ", 64, 0;\nshr.s32 r, " #v ", " SHR ";\n"
#define XSTR(x) XSTR2(x)
#define XSTR2(x) #x
__device__ __forceinline__ void producer(const CUtensorMap* tmx, int pw) {
    const uint32_t nch = lds32(sb + SM_MISC + 12), c0 = lds32(sb + SM_MISC + 24);
    if (elect()) {
        asm volatile(
            "{\n.reg .pred p, q, lead, never;\n.reg .b32 ra, oa, off, poff, due, now, a<4>, b<4>, d, r, z<8>, bar<4>, t, n, tb, ta, prev;\n"
            ".reg .b64 lg, t64;\n"
            "mov.b32 ta, %5;\nld.volatile.shared.v4.b32 {z0,z1,z2,z3}, [ta+32];\nld.volatile.shared.v4.b32 {z4,z5,z6,z7}, [ta+32];\n"
            "mov.b32 ra, %9;\nmad.lo.u32 t, %0, 8, %10;\n"
            "add.u32 bar0, t, z0;\nadd.u32 bar1, t, z1;\nadd.u32 bar2, t, z2;\nadd.u32 bar3, t, z3;\nsetp.ne.u32 never, z0, 0;\n"
            "mov.b32 n, 0;\nld.volatile.shared.b32 prev, [ta];\nmov.b32 poff, 1000000;\nsetp.eq.u32 lead, %0, 0;\n"
            "mov.u32 due, %%globaltimer_lo;\n"
            "setp.gt.u32 p, ra, %1;\n@p bra.uni END;\nshr.u32 oa, ra, 2;\n"
            "FIRST:\n"
            "ld.volatile.shared.b32 off, [oa+%11-16];\nmov.u32 now, %%globaltimer_lo;\nadd.u32 due, prev, off;\nsub.u32 t, due, now;\n"
            "setp.gt.s32 p, t, %12;\n@p bra.uni FIRST;\n"
            "GO:\n"
            "ld.volatile.shared.v4.b32 {a0,a1,a2,a3}, [ra];\nld.volatile.shared.v4.b32 {b0,b1,b2,b3}, [ra+0x2000];\n"
            "shr.u32 oa, ra, 2;\nld.volatile.shared.b32 off, [oa+%11];\nld.volatile.shared.b32 tb, [ta];\n"
            "mov.u32 now, %%globaltimer_lo;\n"
            "lop3.b32 t, a0, a1, a2, 0xfe;\nlop3.b32 d, a3, b0, b1, 0xfe;\nlop3.b32 t, t, d, b2, 0xfe;\nor.b32 t, t, b3;\nand.b32 t, t, 1;\n"
            "setp.ne.u32 p, t, 0;\n"
            "@p bra.uni BACK;\n"
            "add.u32 bar0, bar0, 32;\nmbarrier.arrive.expect_tx.shared.b64 _, [bar0], 8192;\n"
            "add.u32 ra, ra, 64;\nadd.u32 due, off, tb;\nsub.u32 t, due, now;\nsetp.le.and.u32 q, ra, %1, !lead;\nsetp.le.and.s32 q, t, %2, q;\n"
            UNPACK(a0)
            "cp.async.bulk.tensor.2d.shared::cluster.global.mbarrier::complete_tx::bytes [d], [%3, {z0, r}], [bar0];\n"
            UNPACK(b0)
            "cp.async.bulk.tensor.2d.shared::cluster.global.mbarrier::complete_tx::bytes [d], [%3, {z1, r}], [bar0];\n"
            UNPACK(a1)
            "cp.async.bulk.tensor.2d.shared::cluster.global.mbarrier::complete_tx::bytes [d], [%3, {z2, r}], [bar0];\n"
            UNPACK(b1)
            "cp.async.bulk.tensor.2d.shared::cluster.global.mbarrier::complete_tx::bytes [d], [%3, {z3, r}], [bar0];\n"
            UNPACK(a2)
            "cp.async.bulk.tensor.2d.shared::cluster.global.mbarrier::complete_tx::bytes [d], [%3, {z4, r}], [bar0];\n"
            UNPACK(b2)
            "cp.async.bulk.tensor.2d.shared::cluster.global.mbarrier::complete_tx::bytes [d], [%3, {z5, r}], [bar0];\n"
            UNPACK(a3)
            "cp.async.bulk.tensor.2d.shared::cluster.global.mbarrier::complete_tx::bytes [d], [%3, {z6, r}], [bar0];\n"
            UNPACK(b3)
            "cp.async.bulk.tensor.2d.shared::cluster.global.mbarrier::complete_tx::bytes [d], [%3, {z7, r}], [bar0];\n"
            "@q bra.uni GO;\n"
            "setp.gt.u32 p, ra, %1;\n@p bra.uni END;\n@!lead bra.uni WAIT0;\n"
            "add.u32 d, ta, 16;\ncp.async.bulk.shared::cluster.global.mbarrier::complete_tx::bytes [ta], [%4], 16, [d];\n"
            "sub.u32 r, now, poff;\nmov.b32 poff, off;\nsub.u32 d, prev, tb;\nmov.b32 prev, r;\nsub.u32 r, r, tb;\nmin.s32 d, d, r;\n"
            "setp.le.s32 p, d, %6;\n@p bra.uni NOSLIP;\n"
            "setp.lt.u32 p, ra, %8;\n@p bra.uni NOSLIP;\nadd.u32 r, ra, " XSTR(SLIPEND) ";\nsetp.gt.u32 p, r, %1;\n@p bra.uni NOSLIP;\n"
            "ld.volatile.shared.b64 t64, [ta];\ncvt.u32.u64 r, t64;\nsub.u32 r, tb, r;\nsub.u32 d, d, %7;\nadd.s32 d, d, r;\n"
            "cvt.s64.s32 lg, d;\nadd.u64 t64, t64, lg;\n"
            "red.relaxed.gpu.global.max.u64 [%4], t64;\n"
            "NOSLIP:\n"
            "setp.le.s32 p, t, %2;\n@p bra.uni GO;\n"
            "WAIT0:\n"
            "ld.volatile.shared.b32 tb, [ta];\nld.volatile.shared.b32 off, [oa+%11];\nmov.u32 now, %%globaltimer_lo;\nadd.u32 due, tb, off;\nsub.u32 t, due, now;\n"
            "setp.le.s32 p, t, %12;\n@p bra.uni GO;\n"
            "setp.gt.s32 p, t, " XSTR(SPINT) ";\n@p nanosleep.u32 32;\nbra.uni WAIT0;\n"
            "BACK:\n"
            "nanosleep.u32 32;\nsub.u32 t, now, tb;\nsetp.lt.s32 p, t, 200000000;\n@p bra.uni GO;\n"
            "END:\n}" ::"r"(pw),
            "r"(sb + SM_R + nch * 16), "n"(AHEAD + EARLY), "l"(tmx), "l"(g_sync), "n"(sb + SM_MISC + 32), "n"(SLIPTH), "n"(SLIPSUB),
            "n"(sb + SM_R + SLIPFROM * 16), "r"(sb + SM_R + 16 + c0 * 16 + RAOFF), "r"(sb + SM_BAR + 8 - 32 + c0 * 8),
            "n"(sb + SM_OFF + 16 - (sb + SM_R) / 4), "n"(EARLY)
            : "memory");
        const uint32_t wch = lds32(sb + SM_MISC + 12) + 1 + pw;
        const uint32_t ra = sb + SM_R + wch * 16, bar = sb + SM_BAR + wch * 8;
        const uint32_t target = lds32(sb + SM_MISC + 16);
        uint32_t cnt = lds128(sb + SM_MISC + 32).w;
        for (int n = 0; n < 1000000 && (int)(cnt - target) < 0; n++)
            asm volatile("ld.acquire.gpu.global.u32 %0, [%1+12];" : "=r"(cnt) : "l"(g_sync) : "memory");
        uint4 a, b;
        for (int n = 0; n < 1000000; n++) {
            a = lds128(ra), b = lds128(ra + 0x2000);
            if (!((a.x | a.y | a.z | a.w | b.x | b.y | b.z | b.w) & 1)) break;
        }
        asm volatile("fence.proxy.async.global;" ::: "memory");
        asm volatile("mbarrier.arrive.expect_tx.shared.b64 _, [%0], 8192;" ::"r"(bar) : "memory");
        const uint32_t c[8] = {a.x, a.y, a.z, a.w, b.x, b.y, b.z, b.w};
#pragma unroll
        for (int i = 0; i < 8; i++)
            asm volatile("cp.async.bulk.shared::cluster.global.mbarrier::complete_tx::bytes [%0], [%1], 1024, [%2];" ::"r"(
                             (c[i] & 0xffe) << 6),
                         "l"(g_wf + (pw * 8 + i) * 64), "r"(bar)
                         : "memory");
    }
}

#define BARINIT(w, n)                                                                                              \
    if (elect()) {                                                                                                 \
        _Pragma("unroll") for (int k = 0; k < (NBAR + n - 1) / n; k++)                                             \
            asm volatile("mbarrier.init.shared.b64 [%0], 1;" ::"r"(sb + SM_BAR + ((w) * ((NBAR + n - 1) / n) + k) * 8)); \
        asm volatile("fence.mbarrier_init.release.cluster;" ::: "memory");                                         \
    }                                                                                                              \
    __syncwarp();

#define BARINIT2(from, n)                                                                                          \
    _Pragma("unroll") for (int k = 0; k < n; k++)                                                                  \
        asm volatile("mbarrier.init.shared.b64 [%0], 1;" ::"r"(sb + SM_BAR + (from + warp * n + k) * 8));

__global__ void __launch_bounds__(NT, 1)
main_kernel(const __grid_constant__ CUtensorMap tmx, const __nv_bfloat16* __restrict__ x, const int* __restrict__ src,
            const int* __restrict__ dst, const __nv_bfloat16* __restrict__ sh, const __nv_bfloat16* __restrict__ ea,
            const __nv_bfloat16* __restrict__ cg, const __nv_bfloat16* __restrict__ wr,
            const __nv_bfloat16* __restrict__ wout, __nv_bfloat16* __restrict__ out, int N, int E, int npb,
            unsigned npb_magic, int chunk, unsigned wsz, unsigned wmagic, unsigned bkm, int tau, int ramp, int rampn, int tdelay, unsigned polld, int spr, int sprn) {
    extern __shared__ __align__(1024) unsigned char smem[];
    if (s2u(smem) != sb) __trap();
    const int tid = threadIdx.x, lane = tid & 31;
    const int warp = __shfl_sync(0xffffffffu, tid >> 5, 0);
    const int nbins = gridDim.x;
    bool fast = chunk > 0;
    TLSTAMP(0);
    if (fast) {
        const int e0 = blockIdx.x * chunk + tid, left = min(E, (int)(blockIdx.x + 1) * chunk) - e0;
        uint32_t pd[KE], ps[KE];
        {
            const int* dp = dst + e0;
            const int* sp = src + e0;
#pragma unroll
            for (int k = 0; k < KE; k++) {
                pd[k] = (nbins + (k == KE - 1 ? lane : 0)) * npb, ps[k] = 0;
                asm volatile("{\n.reg .pred p;\nsetp.gt.s32 p, %4, %5;\n@p ld.global.nc.u32 %0, [%2];\n@p ld.global.nc.u32 %1, [%3];\n}"
                             : "+r"(pd[k]), "+r"(ps[k]) : "l"(dp + k * NT), "l"(sp + k * NT), "r"(left), "r"(k * NT));
            }
        }
        uint32_t epoch = 0;
        if (tid == NT - 1) asm volatile("ld.relaxed.gpu.global.u32 %0, [%1];" : "=r"(epoch) : "l"(&g_epoch) : "memory");
        uint4 wv, wo[3];
        const bool wrow = (tid >> 2) == WFT && blockIdx.x < 128;
        {
            const uint4* wp = tid < 256 ? (const uint4*)wr + tid
                              : wrow    ? (const uint4*)(wout + blockIdx.x * 128 + (tid & 3) * 32)
                                        : (const uint4*)cg + (tid & 7);
            if (tid < 264 || wrow) wv = __ldg(wp);
            if (wrow) wo[0] = __ldg(wp + 1), wo[1] = __ldg(wp + 2), wo[2] = __ldg(wp + 3);
        }
        const uint32_t t16 = sb + tid * 16;
        const uint32_t sa = sb + SC_STG + (tid >> 3) * CP + (tid & 7) * 16;
        const uint32_t sm = sb + SC_STG + (tid >> 2) * CP + (tid & 3) * 16 + 128;
        const uint32_t none = (40 * NWIN + (lane & 7) + (blockIdx.x & 3) * 8) << 2;
        const uint32_t pade = min(blockIdx.x * chunk, E - 1) << 13;
        const bool third = warp * 4 + 128 < nbins, second = warp * 8 + 128 < nbins;
#pragma unroll
        for (int k = 0; k < 3; k++)
            if (k < 2 || third) sts128(sa + k * 64 * CP, none, none, none, none);
#pragma unroll
        for (int k = 0; k < 2; k++)
            if (k < 1 || second) sts128(sm + k * 128 * CP, none, none, none, none);
        if (tid < MAXB + 32) sts32(sb + SC_CNT + tid * 4, 0);
        if (tid < NBAR) sts32(sb + SM_OFF + tid * 4, 1000000);
#pragma unroll
        for (int k = 0; k < 3; k++) sts128(t16 + SC_TABB + k * NT * 16, 0, 0, 0, 0);
        const uint32_t ecomp = -(wsz * (CH << 13));
#pragma unroll
        for (int k = 0; k < 3; k++)
            sts128(t16 + SC_TMP + k * NT * 16, 0, pade + ecomp, 0, pade + ecomp);
#pragma unroll
        for (int k = 0; k < ZSL / 8; k++) sts128(t16 + k * NT * 16, 0, 0, 0, 0), sts128(t16 + SP * 1024 + PH + k * NT * 16, 0, 0, 0, 0);
        if (tid < RP / 4) {
            uint32_t c[4], d[4];
#pragma unroll
            for (int i = 0; i < 4; i++) {
                const uint32_t k = tid * 4 - 4 + i;
                c[i] = d[i] = 0xc0000001u;
                if (warp == 0 && k < SP) c[i] += sb / 64 - 1 + k * 16;
                if (warp == 0 && k < SP - WSL) d[i] = c[i] + (SP * 1024 + PH) / 64;
            }
            static_assert(SP + 4 <= 128, "first warp");
            sts128(t16 + SM_R, c[0], c[1], c[2], c[3]);
            sts128(t16 + SM_R + 0x2000, d[0], d[1], d[2], d[3]);
        }
        constexpr uint32_t OLEND = (7u << 28) | ((RECN - 4) * 4);
        if (tid < NCW * OLN / 4) sts128(t16 + SM_OL, OLEND, OLEND, OLEND, OLEND);
        if (warp == 12) {
            sts32(sb + SM_CTR + lane * 16 + (lane >> 3) * 4,
                  sb + SM_R + ((lane & 0x19) ? (RP - 1) * 4 : (4 + SP) * 4 + (((lane >> 1) ^ (lane >> 2)) & 1) * 0x2000 + (lane & 4)));
            if (lane < 3) sts32(sb + SM_MISC + (lane ? 16 + lane * 4 : 4), 0);
            if (lane == 8) sts128(sb + SM_REC + (RECN - 4) * 4, pade, pade, pade, pade), sts128(sb + SM_MISC + 64, 0, 0, 0, 0);
            if (lane == 9) asm volatile("prefetch.tensormap [%0];" ::"l"(&tmx) : "memory");
        }
        __syncthreads();
        TLSTAMP(1);

        {
            uint32_t b[KE], r[KE];
#pragma unroll
            for (int k = 0; k < KE; k++) {
                b[k] = __umulhi(pd[k], npb_magic);
                r[k] = atoms_add(sb + SC_CNT + b[k] * 4, 4);
                if (k == KE - 1) b[k] = min(b[k], nbins);
            }
            if (tid == NT - 1) {
                sts32(sb + SM_MISC + 8, epoch % 3 + 1);
                asm volatile("{\n.reg .b64 t;\nmov.u64 t, %%globaltimer;\nred.relaxed.gpu.global.max.u64 [%0], t;\n"
                             "red.relaxed.gpu.global.add.u32 [%0+8], 1;\n}" ::"l"(g_sync) : "memory");
            }
            __syncwarp();
#pragma unroll
            for (int k = 0; k < KE; k++) {
                asm volatile(
                    "{\n.reg .pred p;\n.reg .b32 d, t, u;\nmad.lo.u32 d, %1, %3, %0;\nsetp.ge.u32 p, d, 40;\nmul.hi.u32 u, %2, %4;\n"
                    "mad.lo.u32 t, %2, %10, %5;\nmad.lo.u32 t, d, %11, t;\nmad.lo.u32 t, u, %12, t;\n@p add.u32 t, t, %7;\n"
                    "min.u32 d, %6, 188;\nmad.lo.u32 d, %1, %9, d;\nst.shared.b32 [d+%8], t;\n}" ::"r"(pd[k]),
                    "r"(b[k]), "r"(ps[k]), "r"(-npb), "r"(wmagic), "r"(((tid + k * NT) << 14) + 4), "r"(r[k]), "n"(2 - 40 * NWIN * 4),
                    "n"(sb + SC_STG), "n"(CP), "n"(CH << 14), "n"(NWIN * 4), "r"(4 - wsz * (CH << 14))
                    : "memory");
            }
        }
        if (tid < 264) sts128(sb + SC_WR + (tid >> 4) * 272 + (tid & 15) * 16, wv.x, wv.y, wv.z, wv.w);
        uint4* gp = g_cell + ((tid >> 3) * MAXB + blockIdx.x) * 8 + (tid & 7);
        uint4* gm = g_more + ((tid >> 2) * MAXB + blockIdx.x) * 4 + (tid & 3);
        __syncthreads();
        TLSTAMP(6);
        const uint32_t tag = lds32(sb + SM_MISC + 8), t0 = tag & 1, t1 = tag >> 1;
        {
            uint4 v[5];
#pragma unroll
            for (int k = 0; k < 5; k++)
                if (k != 2 && k != 4 || (k == 2 ? third : second)) v[k] = lds128(k < 3 ? sa + k * 64 * CP : sm + (k - 3) * 128 * CP);
#pragma unroll
            for (int k = 0; k < 5; k++)
                if (k != 2 && k != 4 || (k == 2 ? third : second))
                    st_cell(k < 3 ? gp + k * 64 * MAXB * 8 : gm + (k - 3) * 128 * MAXB * 4, v[k].x | t0, v[k].y | t1, v[k].z | t0, v[k].w | t1);
        }
        if (wrow) {
            const int k = blockIdx.x;
            uint4* dp = &g_wf[PH == 128 ? ((tid & 3) * 8 + ((k & 63) >> 3)) * 64 + (k >> 6) * 32 + (k & 7) : ((tid & 3) * 8 + (k >> 4)) * 64 + (k & 8) * 4 + (k & 7)];
            dp[0] = make_uint4(wv.x, wo[0].x, wo[1].x, wo[2].x);
            dp[8] = make_uint4(wv.y, wo[0].y, wo[1].y, wo[2].y);
            dp[16] = make_uint4(wv.z, wo[0].z, wo[1].z, wo[2].z);
            dp[24] = make_uint4(wv.w, wo[0].w, wo[1].w, wo[2].w);
        }
        if (warp < 15) { BARINIT(warp, 15) }
        __syncwarp();
        if (tid == NT - 1) {
            uint4 q;
            for (int n = 0; n < (1 << 22); n++) {
                q = ld_cell((const uint4*)g_sync);
                if ((int)(q.z - (epoch + 1) * nbins) >= 0) break;
            }
            sts128(sb + SM_MISC + 32, q.x, q.y, q.z, q.w), sts32(sb + SM_MISC + 16, (epoch + 1) * 512);
            asm volatile("mbarrier.init.shared.b64 [%0], 1;" ::"r"(sb + SM_MISC + 48) : "memory");
            while ((uint32_t)(gt_lo() - q.x) < polld) {}
        }
        __syncthreads();
        TLSTAMP(14);
        uint32_t m[20], rk[20], ia[20], eb[2];
        eb[0] = (((tid >> 3) * chunk) << 13) + ecomp + 1;
        eb[1] = eb[0] + (chunk << 19);
        asm volatile("" : "+r"(eb[0]), "+r"(eb[1]));
        bool ext;
        {
            const uint4* hp = g_cell + blockIdx.x * (MAXB * 8) + tid;
            const uint4* hm = g_more + blockIdx.x * (MAXB * 4) + tid;
            uint4 q[5];
            q[2] = q[4] = make_uint4(none | t0, none | t1, none | t0, none | t1);
            for (int n = 0; n < (1 << 22); n++) {
                q[0] = ld_cell(hp), q[1] = ld_cell(hp + NT), q[3] = ld_cell(hm);
                if ((tid >> 3) + 128 < nbins) q[2] = ld_cell(hp + 2 * NT);
                if ((tid >> 2) + 128 < nbins) q[4] = ld_cell(hm + NT);
                uint32_t bad = 0;
#pragma unroll
                for (int k = 0; k < 5; k++)
                    asm("{\n.reg .b32 a, b;\nlop3.b32 a, %1, %2, %5, 0x7e;\nlop3.b32 b, %3, %4, %6, 0x7e;\nlop3.b32 %0, %0, a, b, 0xfe;\n}"
                        : "+r"(bad) : "r"(q[k].x), "r"(q[k].z), "r"(q[k].y), "r"(q[k].w), "r"(t0), "r"(t1));
                if (!(bad & 1)) break;
            }
            __syncwarp();
            TLSTAMP(8);
#pragma unroll
            for (int k = 0; k < 5; k++) m[4 * k] = q[k].x, m[4 * k + 1] = q[k].y, m[4 * k + 2] = q[k].z, m[4 * k + 3] = q[k].w;
#pragma unroll
            for (int k = 0; k < 12; k++)
                if (k < 8 || third) ia[k] = m[k] & 0x3ffc, rk[k] = atoms_add(sb + SC_TABB + ia[k], 8);
            ext = __any_sync(0xffffffffu, min(m[12] & 0x3ffc, m[16] & 0x3ffc) < 40 * NWIN * 4);
            if (ext) {
#pragma unroll
                for (int k = 12; k < 20; k++) ia[k] = m[k] & 0x3ffc, rk[k] = atoms_add(sb + SC_TABB + ia[k], 8);
                if ((tid & 3) == 3 && min(m[15] & 0x3ffc, m[19] & 0x3ffc) < 40 * NWIN * 4) sts32(sb + SM_MISC + 4, 1);
            }
        }
        __syncthreads();
        TLSTAMP(5);
        const uint32_t tr = sb + warp * (NWIN * 4) + lane * 16;
        if (tid == NT - 1 && blockIdx.x == 0) g_epoch = epoch + 1;
        {
            uint4 c[3];
            uint32_t tt[3];
#pragma unroll
            for (int i = 0; i < 3; i++) {
                c[i] = make_uint4(0, 0, 0, 0);
                if ((i < 2 || warp < 8) && lane < NWIN / 4) c[i] = lds128(tr + SC_TABB + i * 16 * NWIN * 4);
                tt[i] = c[i].x + c[i].y + c[i].z + c[i].w;
            }
            const uint32_t sum = (tt[0] >> 3) + (tt[1] << 7) + (tt[2] << 17);
            const uint32_t tot = __reduce_add_sync(0xffffffffu, sum);
            uint32_t inc = scan_step(scan_step(sum, 1), 2);
            const uint32_t q = (tot + 0x300c03) & 0x3fcff3fc, q0 = q & 1023, q1 = q0 + ((q >> 10) & 1023);
            uint32_t base = atoms_add(sb + (lane ? SC_CNT + lane * 4 : SM_MISC + 20), q1 + (q >> 20));
            inc = scan_step(scan_step(scan_step(inc, 4), 8), 16);
            base = __shfl_sync(0xffffffffu, base, 0);
            const uint32_t l3 = min(lane, 2);
            sts32(sb + SC_KEY + (warp + 16 * l3) * 4, ((tot >> (10 * l3)) & 1023) * 64 + 63 - warp - 16 * l3);
            if (max(tt[0], max(tt[1], tt[2])) > 31 * 8) sts32(sb + SM_MISC + 4, 1);
            inc += q - tot - sum;
#pragma unroll
            for (int i = 0; i < 3; i++) {
                const uint32_t e = (((inc >> (10 * i)) & 1023) + base + (i == 0 ? 0 : i == 1 ? q0 : q1)) * 8;
                if ((i < 2 || warp < 8) && lane < NWIN / 4) sts128(tr + SC_TABB + i * 16 * NWIN * 4, e, e + c[i].x, e + c[i].x + c[i].y, e + tt[i] - c[i].w);
            }
        }
        __syncthreads();
        TLSTAMP(2);
        if (warp >= 11) {
            const uint32_t st = (tid - 352) >> 2, key = lds32(sb + SC_KEY + st * 4);
            uint32_t rank = 0;
#pragma unroll
            for (int i = 0; i < 5; i++) {
                const uint2 q = lds64(sb + SC_KEY + (lane & 3) * 40 + i * 8);
                rank += ((key - q.x) >> 31) + ((key - q.y) >> 31);
            }
            rank += __shfl_xor_sync(0xffffffffu, rank, 1);
            rank += __shfl_xor_sync(0xffffffffu, rank, 2);
            const uint32_t lv = rank >> 2, cw = ((0x969u >> (2 * lv)) & 3) * 4 + ((rank ^ -(lv & 1)) & 3);
            const uint32_t sid = (0xe4a50u >> (2 * lv)) & 3;
            sts32(sb + SC_MAP + st * 4, cw * (NWIN * 4) - st * (NWIN * 4) + 0x10000 + (sid << 28));
            asm volatile("st.shared.u8 [%0], %1;" ::"r"(sb + SM_INV + cw * 4 + sid), "r"(st) : "memory");
        }
        const int total = lds32(sb + SM_MISC + 20);
        fast = lds32(sb + SM_MISC + 4) == 0 && total <= RECN - 4;
        auto lookup = [&](int k) {
            asm volatile("{\n.reg .pred p;\n.reg .b32 t;\nsetp.lt.u32 p, %1, %2;\nmov.b32 t, 0x80000000;\n@p ld.shared.b32 t, [%1+%3];\nadd.u32 %0, %0, t;\n}"
                         : "+r"(rk[k]) : "r"(ia[k]), "n"(40 * NWIN * 4), "n"(sb + SC_TABB) : "memory");
        };
        auto place = [&](int k, uint32_t e) {
            asm volatile("{\n.reg .pred p;\nsetp.ge.s32 p, %0, 0;\n@p st.shared.v2.b32 [%0+%3], {%1, %2};\n}" ::"r"(rk[k]), "r"(m[k]), "r"(e),
                         "n"(sb + SC_TMP) : "memory");
        };
#pragma unroll
        for (int k = 0; k < 8; k++) lookup(k);
        if (fast) {
#pragma unroll
            for (int k = 0; k < 8; k++) place(k, eb[k >> 2]);
            if (third) {
#pragma unroll
                for (int k = 8; k < 12; k++) lookup(k);
#pragma unroll
                for (int k = 8; k < 12; k++) place(k, 2 * eb[1] - eb[0]);
            }
            if (ext) {
#pragma unroll
                for (int k = 12; k < 20; k++) lookup(k);
#pragma unroll
                for (int k = 12; k < 20; k++) place(k, ((((tid >> 2) + (k >> 4) * 128) * chunk) << 13) + ecomp + 1);
            }
            constexpr int KD = (RECN + NT - 1) / NT;
            const uint32_t P = (lane ^ (lane >> 1)) & 1;
            const uint32_t binc = (P ? 1u << 11 : 1u) + ((lane & 3) == 3 ? 1u << 22 : 0u);
            const bool last = warp * 32 + (KD - 1) * NT < total, q2 = warp * 128 + NT * 4 < total;
            const int rest = total - tid, restq = (total >> 2) - tid;
            uint2 en[KD];
            uint32_t bk[KD], r2[KD], ca[2], ol[2], r3[2];
            __syncthreads();
            TLSTAMP(9);
#pragma unroll
            for (int k = 0; k < KD; k++)
                if (k < KD - 1 || last) en[k] = lds64(sb + SC_TMP + tid * 8 + k * NT * 8);
#pragma unroll
            for (int k = 0; k < 2; k++)
                if (k == 0 || q2) ca[k] = lds32(sb + SC_TMP + (tid + k * NT) * 32 + 24);
#pragma unroll
            for (int k = 0; k < 2; k++)
                if (k == 0 || q2) ca[k] &= 0x3ffc, ol[k] = lds32(sb + SC_MAP + __umulhi(ca[k], 0xffffffffu / (NWIN * 4) + 1) * 4);
#pragma unroll
            for (int k = 0; k < KD; k++) {
                if (k < KD - 1 || last) {
                    const uint32_t v = en[k].x, f = v >> 14, i = v & 0x3ffc;
                    const uint32_t w4 = i - __umulhi(i, 0xffffffffu / (NWIN * 4) + 1) * (NWIN * 4);
                    const uint32_t o = __umulhi(f, 0xffffffffu / CH + 1) - wsz;
                    bk[k] = (__umulhi(f, bkm) + w4) * 4;
                    en[k].x = (w4 >> 2) * wsz + o;
                    en[k].y += ((v >> 1) & 0xffffe001u) - o * (CH << 13);
                    if (rest <= k * NT) bk[k] = 2048 + lane * 4;
                    r2[k] = atoms_add(sb + SC_TABA + bk[k], binc);
                }
            }
#pragma unroll
            for (int k = 0; k < 2; k++) {
                if (k == 0 || q2) {
                    ca[k] = (ca[k] + ol[k]) & 0xffff;
                    ol[k] = (tid + k * NT) * 16 + (ol[k] & 0x30000000);
                    r3[k] = atoms_add(sb + SC_TABC + ca[k], restq > k * NT ? 4 : 0);
                }
            }
            __syncthreads();
            TLSTAMP(12);
            if (warp < NCW) {
                uint4 c = make_uint4(0, 0, 0, 0);
                if (lane < NWIN / 4) c = lds128(tr + SC_TABC);
                const uint32_t tt = c.x + c.y + c.z + c.w;
                uint32_t inc = tt;
#pragma unroll
                for (int o = 1; o < 32; o <<= 1) inc = scan_step(inc, o);
                if (inc > (OLN - 6) * 4) sts32(sb + SM_MISC + 4, 1);
                inc += warp * (OLN * 4) - tt;
                if (lane < NWIN / 4) sts128(tr + SC_TABC, inc, inc + c.x, inc + c.x + c.y, inc + tt - c.w);
            } else {
                const uint32_t mine = (warp + lane) & 3;
                uint4 c;
                uint32_t cs, inc = 0, e = 4 + (4 << 11);
#pragma unroll
                for (int i = 0; i < 4; i++) {
                    const uint32_t pc = (mine + i) & 3;
                    const uint4 v = lds128(sb + SC_TABA + lane * 64 + (pc << 4));
                    const uint32_t sum = v.x + v.y + v.z + v.w;
                    inc += sum;
                    if (i == 0) c = v, cs = sum;
                    if (pc >= mine) e -= sum;
                }
#pragma unroll
                for (int o = 1; o < 32; o <<= 1) inc = scan_step(inc, o);
                e += inc;
                sts128(sb + SC_TABB + lane * 64 + (mine << 4), e, e + c.x, e + c.x + c.y, e + cs - c.w);
                if ((int)max((e + cs) & 0x7ff, ((e + cs) >> 11) & 0x7ff) - (int)(e >> 22) * 2 > SP) sts32(sb + SM_MISC + 4, 1);
                if (tid == NCW * 32) {
                    const uint32_t c0 = min(min(c.x & 0x7ff, (c.x >> 11) & 0x7ff), ZSL) >> 2;
                    sts32(sb + SM_MISC + 12, ((total >> 2) + 1) >> 1), sts32(sb + SM_MISC + 24, c0);
                }
            }
            __syncthreads();
            TLSTAMP(13);
            fast = lds32(sb + SM_MISC + 4) == 0;
            if (warp == 15 && lane < lds32(sb + SM_MISC + 24))
                asm volatile("mbarrier.arrive.shared.b64 _, [%0];" ::"r"(sb + SM_BAR + 8 + lane * 8) : "memory");
#pragma unroll
            for (int k = 0; k < KD; k++)
                if (k < KD - 1 || last) r2[k] += lds32(sb + SC_TABB + bk[k]);
#pragma unroll
            for (int k = 0; k < 2; k++)
                if (k == 0 || q2) r3[k] += lds32(sb + SC_TABC + ca[k]);
            if (fast) {
                const uint32_t rot = P ? 9 : 30;
#pragma unroll
                for (int k = 0; k < KD; k++) {
                    if (k < KD - 1 || last) {
                        const uint32_t k4 = __funnelshift_r(r2[k], r2[k], rot);
                        if (rest > k * NT) {
                            sts16(sb + SM_R + 2 + bitsel(k4, P << 13), en[k].x);
                            sts32(sb + SM_REC + tid * 4 + k * NT * 4, bitsel(k4, en[k].y));
                        }
                    }
                }
#pragma unroll
                for (int k = 0; k < 2; k++)
                    if ((k == 0 || q2) && restq > k * NT) sts32(sb + SM_OL + r3[k], ol[k]);
            }
        }
        asm volatile("fence.mbarrier_init.release.cluster;\nfence.proxy.async.shared::cta;" ::: "memory");
        __syncthreads();
        TLSTAMP(3);
        if (!fast && wrow) wf_done();
        if (fast && tid < NBAR) {
            const uint4 a = lds128(t16 + SM_R), b = lds128(t16 + SM_R + 0x2000);
            const int s = (((int)a.x >> 3) + ((int)a.y >> 3) + ((int)a.z >> 3) + ((int)a.w >> 3) + ((int)b.x >> 3) + ((int)b.y >> 3) +
                           ((int)b.z >> 3) + ((int)b.w >> 3)) >> 16;
            sts32(sb + SM_OFF + tid * 4, tdelay + ((s * tau + min(s, rampn) * ramp - max(s - sprn, 0) * spr) >> 10));
        }
        __syncwarp();
    }

    if (!fast) {
        float* accs = (float*)smem;
        constexpr int NACC = 96;
        const int node0 = blockIdx.x * npb, nnodes = max(0, min(npb, N - node0));
#pragma unroll 1
        for (int nb = 0; nb < nnodes; nb += NACC) {
            __syncthreads();
            for (int i = tid; i < NACC * 512; i += NT) accs[i] = 0.f;
            __syncthreads();
            const int lim = min(NACC, nnodes - nb);
#pragma unroll 1
            for (int base = warp * 32; base < E; base += NT) {
                const int e = base + lane;
                const int dl = e < E ? dst[e] - node0 - nb : -1;
                unsigned mask = __ballot_sync(0xffffffffu, dl >= 0 && dl < lim);
#pragma unroll 1
                while (mask) {
                    const int l = __ffs(mask) - 1;
                    mask &= mask - 1;
                    const int dd = __shfl_sync(0xffffffffu, dl, l);
                    slow_edge(base + l, src[base + l], accs + dd * 512, x, sh, ea, cg, wr, lane);
                }
            }
            __syncthreads();
#pragma unroll 1
            for (int nl = warp; nl < lim; nl += NT / 32) slow_out(accs + nl * 512, wout, out + (size_t)(node0 + nb + nl) * 512, lane);
        }
    } else if (warp >= NCW) {
        asm volatile("setmaxnreg.dec.sync.aligned.u32 %0;" ::"n"(PREG));
        producer(&tmx, warp - NCW);
    } else if (warp >= 4) {
        asm volatile("setmaxnreg.inc.sync.aligned.u32 %0;" ::"n"(R1));
        consumer<3>(sh, ea, out, N, npb);
        TLMAX(4);
    } else {
        asm volatile("setmaxnreg.inc.sync.aligned.u32 %0;" ::"n"(R0));
        consumer<4>(sh, ea, out, N, npb);
        TLMAX(4);
    }
}

typedef CUresult (*EncodeTiledFn)(CUtensorMap*, CUtensorMapDataType, cuuint32_t, void*, const cuuint64_t*,
                                  const cuuint64_t*, const cuuint32_t*, const cuuint32_t*, CUtensorMapInterleave,
                                  CUtensorMapSwizzle, CUtensorMapL2promotion, CUtensorMapFloatOOBfill);

extern "C" void kernel_launch(void* const* d_in, const int* in_sizes, int n_in, void* d_out, int out_size) {
    const __nv_bfloat16* x = (const __nv_bfloat16*)d_in[0];
    const int* src = (const int*)d_in[1];
    const int* dst = (const int*)d_in[2];
    const __nv_bfloat16* sh = (const __nv_bfloat16*)d_in[3];
    const __nv_bfloat16* ea = (const __nv_bfloat16*)d_in[4];
    const __nv_bfloat16* cg = (const __nv_bfloat16*)d_in[5];
    const __nv_bfloat16* wr = (const __nv_bfloat16*)d_in[6];
    const __nv_bfloat16* wout = (const __nv_bfloat16*)d_in[7];
    __nv_bfloat16* out = (__nv_bfloat16*)d_out;
    const int N = in_sizes[0] / 512;
    const int E = in_sizes[1];

    static int num_sms = 0, coresident = 0;
    static EncodeTiledFn encode = nullptr;
    if (num_sms == 0) {
        int dev = 0;
        cudaGetDevice(&dev);
        cudaDeviceGetAttribute(&num_sms, cudaDevAttrMultiProcessorCount, dev);
        cudaFuncSetAttribute(main_kernel, cudaFuncAttributeMaxDynamicSharedMemorySize, SM_TOTAL);
        int occ = 0;
        cudaOccupancyMaxActiveBlocksPerMultiprocessor(&occ, main_kernel, NT, SM_TOTAL);
        coresident = occ * num_sms;
        void* fn = nullptr;
        cudaDriverEntryPointQueryResult qr;
        cudaGetDriverEntryPoint("cuTensorMapEncodeTiled", &fn, cudaEnableDefault, &qr);
        encode = (EncodeTiledFn)fn;
    }
    CUtensorMap tmx;
    const int rank = 2;
    const cuuint64_t gd[2] = {64, (cuuint64_t)N * 8}, gs[1] = {128};
    const cuuint32_t bd[2] = {64, 8}, es[2] = {1, 1};
    encode(&tmx, CU_TENSOR_MAP_DATA_TYPE_BFLOAT16, rank, (void*)x, gd, gs, bd, es, CU_TENSOR_MAP_INTERLEAVE_NONE,
           CU_TENSOR_MAP_SWIZZLE_128B, CU_TENSOR_MAP_L2_PROMOTION_NONE, CU_TENSOR_MAP_FLOAT_OOB_FILL_NONE);

    int nbins = num_sms < MAXB ? num_sms : MAXB;
    int npb = (N + nbins - 1) / nbins;
    if (npb < 2) npb = 2;
    nbins = (N + npb - 1) / npb;
    const unsigned npb_magic = (unsigned)((0x100000000ull + npb - 1) / npb);
    int chunk = (E + nbins - 1) / nbins;
    const unsigned wsz = (N + NWIN - 2) / (NWIN - 1);
    if (nbins > coresident || nbins < 128 || npb > MAXNPB || chunk > CH || wsz > (1 << 18) / CH || N < 512 || E > (1 << 19)) chunk = 0;
    const unsigned wmagic = 0xffffffffu / wsz + 1, bkm = (unsigned)((4ull << 32) / (wsz * CH));
    double pace = PACE, rampt = RAMP, rampf = RAMPF, sprt = SPRINT, sprf = SPRINTF;
    int tdelay = TDELAY, polld = POLLD;
    const int tau = (int)(1024.0 * pace * ((double)E / nbins) / N);
    const int rampn = (int)(N * rampf), ramp = (int)(1024.0 * rampt / rampn);
    main_kernel<<<nbins, NT, SM_TOTAL, cudaStreamPerThread>>>(tmx, x, src, dst, sh, ea, cg, wr, wout, out, N, E, npb, npb_magic,
                                                              chunk, wsz, wmagic, bkm, tau, ramp, rampn, tdelay, polld, (int)(1024.0 * sprt / (N * sprf)), (int)(N * (1 - sprf)));
}
```

```cpp
#include <cuda_runtime.h>
#include <cuda.h>
#include <cuda_bf16.h>
#include <stdint.h>
#include <stdlib.h>

#define NT 512
#define NCW 12
#define MAXB 144
#define MAXNPB 80
#define KE 5
#define SP 97
#define RECN 2816
#define RP 1512
#define OLN 80
#define NBAR 360
#define R0 168
#define R1 160
#define PREG 24
#define PACE 10.05
#define TDELAY 4550
#define POLLD 1000
#define WFT 80
#define SLIPTH 500
#define SLIPSUB 250
#define SLIPFROM 36
#define AHEAD 96
#define EARLY 32
#define RAMPF 0.1
#define SPRINT 500
#define SPRINTF 0.5
#define SLIPEND 640
#define SPINT 96
#define BP 0
#define PIN 7
#define MAP3D
#define RAMP 600

__device__ __align__(1024) uint4 g_cell[MAXB * MAXB * 8];
__device__ __align__(1024) uint4 g_more[MAXB * MAXB * 4];
__device__ __align__(1024) uint4 g_wf[2048];
__device__ __align__(256) ulonglong2 g_sync[16];
__device__ __align__(256) unsigned g_epoch;
#define TLSTAMP(i)
#define TLMAX(i)

constexpr uint32_t sb = 1024;
#define PH 512
#define SHR "14"
#define SM_R (2 * SP * 1024 + PH)
#define SM_CTR (SM_R + RP * 4)
#define SM_MISC (SM_CTR + 528)
#define SM_INV (SM_MISC + 80)
#define SM_OFF (SM_INV + 48)
#define SM_REC (SM_R + 0x2000 + RP * 4)
#define SM_OL (SM_REC + RECN * 4)
#define SM_BAR (SM_OL + NCW * OLN * 4)
#define SM_TOTAL (SM_BAR + (NBAR + 16) * 8)
static_assert(SM_TOTAL <= 232448 && SM_OFF + NBAR * 4 <= SM_R + 0x2000, "shared memory");
static_assert(4 + RECN / 2 + SP + 2 <= RP && RECN / 8 + 8 <= NBAR && NBAR % 24 == 0, "tables");
#define ZSL 32
#define NWIN 96
#define CH 2432
#define CP 208
#define SC_STG ((SP + ZSL) * 1024 + PH)
#define SC_TMP (ZSL * 1024)
#define SC_TABB (SC_TMP + 3072 * 8)
#define SC_TABC (SC_TABB + 41 * NWIN * 4)
#define SC_TABA (SC_TABC + NCW * NWIN * 4)
#define SC_ZEND (SC_TABB + 3 * NT * 16)
#define SC_CNT SC_ZEND
#define SC_KEY (SC_CNT + (MAXB + 32) * 4)
#define SC_MAP (SC_KEY + 192)
#define WSL 5
#define SC_WR ((2 * SP - WSL) * 1024 + PH)
#define SC_CG (SC_WR + 16 * 272)
static_assert(SC_TABA + 2048 + 128 <= SC_ZEND && RECN <= 3072 && SC_MAP + 192 <= SP * 1024 && SC_STG + (MAXB + 1) * CP <= SC_WR, "scratch");

__device__ __forceinline__ uint32_t pack_bf16(float lo, float hi) {
    uint32_t r;
    asm("cvt.rn.bf16x2.f32 %0, %1, %2;" : "=r"(r) : "f"(hi), "f"(lo));
    return r;
}
__device__ __forceinline__ uint32_t s2u(const void* p) { return (uint32_t)__cvta_generic_to_shared(p); }
__device__ __forceinline__ void mbar_wait0(uint32_t a) {
    asm volatile(
        "{\n.reg .pred p, q;\n.reg .u32 n;\nmov.u32 n, 0;\n"
        "LAB_WAIT:\nmbarrier.try_wait.parity.shared.b64 p, [%0], 0;\nadd.u32 n, n, 1;\nsetp.lt.and.u32 q, n, 1000000, !p;\n@q bra LAB_WAIT;\n}" ::"r"(a)
        : "memory");
}
__device__ __forceinline__ uint32_t lds8(uint32_t a) { uint32_t v; asm volatile("ld.shared.u8 %0, [%1];" : "=r"(v) : "r"(a) : "memory"); return v; }
__device__ __forceinline__ uint32_t lds16(uint32_t a) { uint32_t v; asm volatile("ld.shared.u16 %0, [%1];" : "=r"(v) : "r"(a) : "memory"); return v; }
__device__ __forceinline__ uint32_t lds32(uint32_t a) { uint32_t v; asm volatile("ld.shared.u32 %0, [%1];" : "=r"(v) : "r"(a) : "memory"); return v; }
__device__ __forceinline__ uint2 lds64(uint32_t a) {
    uint2 v; asm volatile("ld.shared.v2.u32 {%0,%1}, [%2];" : "=r"(v.x), "=r"(v.y) : "r"(a) : "memory"); return v;
}
__device__ __forceinline__ uint4 lds128(uint32_t a) {
    uint4 v; asm volatile("ld.volatile.shared.v4.u32 {%0,%1,%2,%3}, [%4];" : "=r"(v.x), "=r"(v.y), "=r"(v.z), "=r"(v.w) : "r"(a) : "memory"); return v;
}
__device__ __forceinline__ void sts16(uint32_t a, uint32_t v) { asm volatile("st.shared.u16 [%0], %1;" ::"r"(a), "h"((unsigned short)v) : "memory"); }
__device__ __forceinline__ void sts32(uint32_t a, uint32_t v) { asm volatile("st.shared.u32 [%0], %1;" ::"r"(a), "r"(v) : "memory"); }
__device__ __forceinline__ void sts64(uint32_t a, uint32_t x, uint32_t y) { asm volatile("st.shared.v2.u32 [%0], {%1,%2};" ::"r"(a), "r"(x), "r"(y) : "memory"); }
__device__ __forceinline__ void sts128(uint32_t a, uint32_t x, uint32_t y, uint32_t z, uint32_t w) {
    asm volatile("st.shared.v4.u32 [%0], {%1,%2,%3,%4};" ::"r"(a), "r"(x), "r"(y), "r"(z), "r"(w) : "memory");
}
__device__ __forceinline__ uint32_t atoms_add(uint32_t a, uint32_t v) {
    uint32_t r;
    asm volatile("atom.shared.add.u32 %0, [%1], %2;" : "=r"(r) : "r"(a), "r"(v) : "memory");
    return r;
}
__device__ __forceinline__ uint4 ld_cell(const uint4* p) {
    uint4 v;
    asm volatile("{\n.reg .b64 a, b;\nld.relaxed.gpu.global.v2.b64 {a, b}, [%4];\nmov.b64 {%0,%1}, a;\nmov.b64 {%2,%3}, b;\n}"
                 : "=r"(v.x), "=r"(v.y), "=r"(v.z), "=r"(v.w) : "l"(p) : "memory");
    return v;
}
__device__ __forceinline__ void st_cell(uint4* p, uint32_t x, uint32_t y, uint32_t z, uint32_t w) {
    asm volatile("st.relaxed.gpu.global.v2.b64 [%0], {%1, %2};" ::"l"(p), "l"(x | (uint64_t)y << 32), "l"(z | (uint64_t)w << 32) : "memory");
}
__device__ __forceinline__ uint32_t scan_step(uint32_t v, int o) {
    asm volatile("{\n.reg .pred p;\n.reg .b32 y;\nshfl.sync.up.b32 y|p, %0, %1, 0, 0xffffffff;\n@p add.u32 %0, %0, y;\n}" : "+r"(v) : "r"(o));
    return v;
}
__device__ __forceinline__ uint32_t bitsel(uint32_t a, uint32_t b) {
    uint32_t r;
    asm("lop3.b32 %0, %1, %2, 0x1ffc, 0xe4;" : "=r"(r) : "r"(a), "r"(b));
    return r;
}
__device__ __forceinline__ uint32_t movm(uint32_t a) {
    uint32_t r;
    asm volatile("movmatrix.sync.aligned.m8n8.trans.b16 %0, %1;" : "=r"(r) : "r"(a));
    return r;
}
__device__ __forceinline__ uint32_t gt_lo() {
    uint32_t t;
    asm volatile("mov.u32 %0, %globaltimer_lo;" : "=r"(t));
    return t;
}
__device__ __forceinline__ bool elect() {
    uint32_t p;
    asm volatile("{\n.reg .pred P;\nelect.sync _|P, 0xffffffff;\nselp.u32 %0, 1, 0, P;\n}" : "=r"(p));
    return p;
}
__device__ __forceinline__ void project4(const uint32_t (&pk)[64], uint32_t ra, uint32_t ba, uint4* const (&p)[4], const uint32_t (&v)[4]) {
    asm volatile(
        "{\n.reg .pred p0, p1, q0, q1, nv, s<4>;\n.reg .b32 t, h, c<16>, a<32>, b<32>, k<16>;\n.reg .b64 d<16>;\n.reg .f32 o<32>;\nsetp.ne.b32 p0, 0, 0;\n"
        "setp.eq.b32 p1, 0, 0;\nmov.b32 h, 8;\nsetp.eq.u32 nv, %64, 0;\nvote.sync.any.pred nv, nv, 0xffffffff;\nsetp.ne.b32 s0, %69, 0;\n"
        "setp.ne.b32 s1, %70, 0;\nsetp.ne.b32 s2, %71, 0;\nsetp.ne.b32 s3, %72, 0;\nmovmatrix.sync.aligned.m8n8.trans.b16 a0, %0;\n"
        "movmatrix.sync.aligned.m8n8.trans.b16 a1, %16;\nmovmatrix.sync.aligned.m8n8.trans.b16 a2, %1;\nmovmatrix.sync.aligned.m8n8.trans.b16 a3, %17;\n"
        "movmatrix.sync.aligned.m8n8.trans.b16 a4, %2;\nmovmatrix.sync.aligned.m8n8.trans.b16 a5, %18;\nmovmatrix.sync.aligned.m8n8.trans.b16 a6, %3;\n"
        "movmatrix.sync.aligned.m8n8.trans.b16 a7, %19;\nmovmatrix.sync.aligned.m8n8.trans.b16 a8, %4;\nmovmatrix.sync.aligned.m8n8.trans.b16 a9, %20;\n"
        "movmatrix.sync.aligned.m8n8.trans.b16 a10, %5;\nmovmatrix.sync.aligned.m8n8.trans.b16 a11, %21;\nmovmatrix.sync.aligned.m8n8.trans.b16 a12, %6;\n"
        "movmatrix.sync.aligned.m8n8.trans.b16 a13, %22;\nmovmatrix.sync.aligned.m8n8.trans.b16 a14, %7;\nmovmatrix.sync.aligned.m8n8.trans.b16 a15, %23;\n"
        "movmatrix.sync.aligned.m8n8.trans.b16 a16, %8;\nmovmatrix.sync.aligned.m8n8.trans.b16 a17, %24;\nmovmatrix.sync.aligned.m8n8.trans.b16 a18, %9;\n"
        "movmatrix.sync.aligned.m8n8.trans.b16 a19, %25;\nmovmatrix.sync.aligned.m8n8.trans.b16 a20, %10;\nmovmatrix.sync.aligned.m8n8.trans.b16 a21, %26;\n"
        "movmatrix.sync.aligned.m8n8.trans.b16 a22, %11;\nmovmatrix.sync.aligned.m8n8.trans.b16 a23, %27;\nmovmatrix.sync.aligned.m8n8.trans.b16 a24, %12;\n"
        "movmatrix.sync.aligned.m8n8.trans.b16 a25, %28;\nmovmatrix.sync.aligned.m8n8.trans.b16 a26, %13;\nmovmatrix.sync.aligned.m8n8.trans.b16 a27, %29;\n"
        "movmatrix.sync.aligned.m8n8.trans.b16 a28, %14;\nmovmatrix.sync.aligned.m8n8.trans.b16 a29, %30;\nmovmatrix.sync.aligned.m8n8.trans.b16 a30, %15;\n"
        "movmatrix.sync.aligned.m8n8.trans.b16 a31, %31;\nmov.b32 t, 0;\n"
        "W0:\nmbarrier.try_wait.parity.shared.b64 q0, [%73+0], 0;\nadd.u32 t, t, 1;\nsetp.lt.and.u32 q1, t, 1000000, !q0;\n@q1 bra.uni W0;\nmov.b32 t, 0;\n"
        "W1:\nmbarrier.try_wait.parity.shared.b64 q0, [%73+8], 0;\nadd.u32 t, t, 1;\nsetp.lt.and.u32 q1, t, 1000000, !q0;\n@q1 bra.uni W1;\nmov.b32 t, 0;\n"
        "W2:\nmbarrier.try_wait.parity.shared.b64 q0, [%73+16], 0;\nadd.u32 t, t, 1;\nsetp.lt.and.u32 q1, t, 1000000, !q0;\n@q1 bra.uni W2;\nmov.b32 t, 0;\n"
        "W3:\nmbarrier.try_wait.parity.shared.b64 q0, [%73+24], 0;\nadd.u32 t, t, 1;\nsetp.lt.and.u32 q1, t, 1000000, !q0;\n@q1 bra.uni W3;\n"
        "ld.volatile.shared.v4.b32 {c0,c1,c2,c3}, [%64+0];\nld.volatile.shared.v4.b32 {c4,c5,c6,c7}, [%64+8192];\n"
        "ld.volatile.shared.v4.b32 {c8,c9,c10,c11}, [%64+16];\nld.volatile.shared.v4.b32 {c12,c13,c14,c15}, [%64+8208];\nand.b32 t, c0, 0xffe;\n"
        "mad.lo.u32 t, t, 4, 0x200000;\nmov.b64 d0, {t, h};\nand.b32 t, c1, 0xffe;\nmad.lo.u32 t, t, 4, 0x200000;\nmov.b64 d1, {t, h};\nand.b32 t, c2, 0xffe;\n"
        "mad.lo.u32 t, t, 4, 0x200000;\nmov.b64 d2, {t, h};\nand.b32 t, c3, 0xffe;\nmad.lo.u32 t, t, 4, 0x200000;\nmov.b64 d3, {t, h};\nand.b32 t, c4, 0xffe;\n"
        "mad.lo.u32 t, t, 4, 0x200000;\nmov.b64 d4, {t, h};\nand.b32 t, c5, 0xffe;\nmad.lo.u32 t, t, 4, 0x200000;\nmov.b64 d5, {t, h};\nand.b32 t, c6, 0xffe;\n"
        "mad.lo.u32 t, t, 4, 0x200000;\nmov.b64 d6, {t, h};\nand.b32 t, c7, 0xffe;\nmad.lo.u32 t, t, 4, 0x200000;\nmov.b64 d7, {t, h};\nand.b32 t, c8, 0xffe;\n"
        "mad.lo.u32 t, t, 4, 0x200000;\nmov.b64 d8, {t, h};\nand.b32 t, c9, 0xffe;\nmad.lo.u32 t, t, 4, 0x200000;\nmov.b64 d9, {t, h};\nand.b32 t, c10, 0xffe;\n"
        "mad.lo.u32 t, t, 4, 0x200000;\nmov.b64 d10, {t, h};\nand.b32 t, c11, 0xffe;\nmad.lo.u32 t, t, 4, 0x200000;\nmov.b64 d11, {t, h};\n"
        "and.b32 t, c12, 0xffe;\nmad.lo.u32 t, t, 4, 0x200000;\nmov.b64 d12, {t, h};\nand.b32 t, c13, 0xffe;\nmad.lo.u32 t, t, 4, 0x200000;\n"
        "mov.b64 d13, {t, h};\nand.b32 t, c14, 0xffe;\nmad.lo.u32 t, t, 4, 0x200000;\nmov.b64 d14, {t, h};\nand.b32 t, c15, 0xffe;\n"
        "mad.lo.u32 t, t, 4, 0x200000;\nmov.b64 d15, {t, h};\nwgmma.fence.sync.aligned;\n"
        "wgmma.mma_async.sync.aligned.m64n32k16.f32.bf16.bf16 {o0,o1,o2,o3,o4,o5,o6,o7,o8,o9,o10,o11,o12,o13,o14,o15}, {a0,a1,a2,a3}, d0, p0, 1, 1, 1;\n"
        "wgmma.mma_async.sync.aligned.m64n32k16.f32.bf16.bf16 {o16,o17,o18,o19,o20,o21,o22,o23,o24,o25,o26,o27,o28,o29,o30,o31}, {a0,a1,a2,a3}, d8, p0, 1, 1, 1;\n"
        "wgmma.mma_async.sync.aligned.m64n32k16.f32.bf16.bf16 {o0,o1,o2,o3,o4,o5,o6,o7,o8,o9,o10,o11,o12,o13,o14,o15}, {a4,a5,a6,a7}, d1, p1, 1, 1, 1;\n"
        "wgmma.mma_async.sync.aligned.m64n32k16.f32.bf16.bf16 {o16,o17,o18,o19,o20,o21,o22,o23,o24,o25,o26,o27,o28,o29,o30,o31}, {a4,a5,a6,a7}, d9, p1, 1, 1, 1;\n"
        "wgmma.mma_async.sync.aligned.m64n32k16.f32.bf16.bf16 {o0,o1,o2,o3,o4,o5,o6,o7,o8,o9,o10,o11,o12,o13,o14,o15}, {a8,a9,a10,a11}, d2, p1, 1, 1, 1;\n"
        "wgmma.mma_async.sync.aligned.m64n32k16.f32.bf16.bf16 {o16,o17,o18,o19,o20,o21,o22,o23,o24,o25,o26,o27,o28,o29,o30,o31}, {a8,a9,a10,a11}, d10, p1, 1, 1, 1;\n"
        "wgmma.mma_async.sync.aligned.m64n32k16.f32.bf16.bf16 {o0,o1,o2,o3,o4,o5,o6,o7,o8,o9,o10,o11,o12,o13,o14,o15}, {a12,a13,a14,a15}, d3, p1, 1, 1, 1;\n"
        "wgmma.mma_async.sync.aligned.m64n32k16.f32.bf16.bf16 {o16,o17,o18,o19,o20,o21,o22,o23,o24,o25,o26,o27,o28,o29,o30,o31}, {a12,a13,a14,a15}, d11, p1, 1, 1, 1;\n"
        "wgmma.mma_async.sync.aligned.m64n32k16.f32.bf16.bf16 {o0,o1,o2,o3,o4,o5,o6,o7,o8,o9,o10,o11,o12,o13,o14,o15}, {a16,a17,a18,a19}, d4, p1, 1, 1, 1;\n"
        "wgmma.mma_async.sync.aligned.m64n32k16.f32.bf16.bf16 {o16,o17,o18,o19,o20,o21,o22,o23,o24,o25,o26,o27,o28,o29,o30,o31}, {a16,a17,a18,a19}, d12, p1, 1, 1, 1;\n"
        "wgmma.mma_async.sync.aligned.m64n32k16.f32.bf16.bf16 {o0,o1,o2,o3,o4,o5,o6,o7,o8,o9,o10,o11,o12,o13,o14,o15}, {a20,a21,a22,a23}, d5, p1, 1, 1, 1;\n"
        "wgmma.mma_async.sync.aligned.m64n32k16.f32.bf16.bf16 {o16,o17,o18,o19,o20,o21,o22,o23,o24,o25,o26,o27,o28,o29,o30,o31}, {a20,a21,a22,a23}, d13, p1, 1, 1, 1;\n"
        "wgmma.mma_async.sync.aligned.m64n32k16.f32.bf16.bf16 {o0,o1,o2,o3,o4,o5,o6,o7,o8,o9,o10,o11,o12,o13,o14,o15}, {a24,a25,a26,a27}, d6, p1, 1, 1, 1;\n"
        "wgmma.mma_async.sync.aligned.m64n32k16.f32.bf16.bf16 {o16,o17,o18,o19,o20,o21,o22,o23,o24,o25,o26,o27,o28,o29,o30,o31}, {a24,a25,a26,a27}, d14, p1, 1, 1, 1;\n"
        "wgmma.mma_async.sync.aligned.m64n32k16.f32.bf16.bf16 {o0,o1,o2,o3,o4,o5,o6,o7,o8,o9,o10,o11,o12,o13,o14,o15}, {a28,a29,a30,a31}, d7, p1, 1, 1, 1;\n"
        "wgmma.mma_async.sync.aligned.m64n32k16.f32.bf16.bf16 {o16,o17,o18,o19,o20,o21,o22,o23,o24,o25,o26,o27,o28,o29,o30,o31}, {a28,a29,a30,a31}, d15, p1, 1, 1, 1;\n"
        "wgmma.commit_group.sync.aligned;\n@nv bra.uni END;\nmovmatrix.sync.aligned.m8n8.trans.b16 b0, %32;\nmovmatrix.sync.aligned.m8n8.trans.b16 b2, %33;\n"
        "movmatrix.sync.aligned.m8n8.trans.b16 b3, %49;\nmovmatrix.sync.aligned.m8n8.trans.b16 b4, %34;\nmovmatrix.sync.aligned.m8n8.trans.b16 b5, %50;\n"
        "movmatrix.sync.aligned.m8n8.trans.b16 b6, %35;\nmovmatrix.sync.aligned.m8n8.trans.b16 b7, %51;\nmovmatrix.sync.aligned.m8n8.trans.b16 b8, %36;\n"
        "movmatrix.sync.aligned.m8n8.trans.b16 b9, %52;\nmovmatrix.sync.aligned.m8n8.trans.b16 b20, %42;\nmovmatrix.sync.aligned.m8n8.trans.b16 b21, %58;\n"
        "movmatrix.sync.aligned.m8n8.trans.b16 b22, %43;\nmovmatrix.sync.aligned.m8n8.trans.b16 b23, %59;\nmovmatrix.sync.aligned.m8n8.trans.b16 b24, %44;\n"
        "movmatrix.sync.aligned.m8n8.trans.b16 b25, %60;\nmovmatrix.sync.aligned.m8n8.trans.b16 b26, %45;\nmovmatrix.sync.aligned.m8n8.trans.b16 b27, %61;\n"
        "movmatrix.sync.aligned.m8n8.trans.b16 b28, %46;\nmovmatrix.sync.aligned.m8n8.trans.b16 b29, %62;\nmovmatrix.sync.aligned.m8n8.trans.b16 b30, %47;\n"
        "movmatrix.sync.aligned.m8n8.trans.b16 b31, %63;\nmovmatrix.sync.aligned.m8n8.trans.b16 b1, %48;\nmovmatrix.sync.aligned.m8n8.trans.b16 b10, %37;\n"
        "movmatrix.sync.aligned.m8n8.trans.b16 b11, %53;\nmovmatrix.sync.aligned.m8n8.trans.b16 b12, %38;\nmovmatrix.sync.aligned.m8n8.trans.b16 b13, %54;\n"
        "movmatrix.sync.aligned.m8n8.trans.b16 b14, %39;\nmovmatrix.sync.aligned.m8n8.trans.b16 b15, %55;\nmovmatrix.sync.aligned.m8n8.trans.b16 b16, %40;\n"
        "movmatrix.sync.aligned.m8n8.trans.b16 b17, %56;\nmovmatrix.sync.aligned.m8n8.trans.b16 b18, %41;\nmovmatrix.sync.aligned.m8n8.trans.b16 b19, %57;\n"
        "@nv bra.uni END;\nwgmma.wait_group.sync.aligned 0;\ncvt.rn.bf16x2.f32 k0, o1, o0;\ncvt.rn.bf16x2.f32 k1, o5, o4;\ncvt.rn.bf16x2.f32 k2, o9, o8;\n"
        "cvt.rn.bf16x2.f32 k3, o13, o12;\ncvt.rn.bf16x2.f32 k4, o3, o2;\ncvt.rn.bf16x2.f32 k5, o7, o6;\ncvt.rn.bf16x2.f32 k6, o11, o10;\n"
        "cvt.rn.bf16x2.f32 k7, o15, o14;\ncvt.rn.bf16x2.f32 k8, o17, o16;\ncvt.rn.bf16x2.f32 k9, o21, o20;\ncvt.rn.bf16x2.f32 k10, o25, o24;\n"
        "cvt.rn.bf16x2.f32 k11, o29, o28;\ncvt.rn.bf16x2.f32 k12, o19, o18;\ncvt.rn.bf16x2.f32 k13, o23, o22;\ncvt.rn.bf16x2.f32 k14, o27, o26;\n"
        "cvt.rn.bf16x2.f32 k15, o31, o30;\nld.volatile.shared.v4.b32 {c0,c1,c2,c3}, [%64+32];\nld.volatile.shared.v4.b32 {c4,c5,c6,c7}, [%64+8224];\n"
        "ld.volatile.shared.v4.b32 {c8,c9,c10,c11}, [%64+48];\nld.volatile.shared.v4.b32 {c12,c13,c14,c15}, [%64+8240];\nand.b32 t, c0, 0xffe;\n"
        "mad.lo.u32 t, t, 4, 0x200000;\nmov.b64 d0, {t, h};\nand.b32 t, c1, 0xffe;\nmad.lo.u32 t, t, 4, 0x200000;\nmov.b64 d1, {t, h};\nand.b32 t, c2, 0xffe;\n"
        "mad.lo.u32 t, t, 4, 0x200000;\nmov.b64 d2, {t, h};\nand.b32 t, c3, 0xffe;\nmad.lo.u32 t, t, 4, 0x200000;\nmov.b64 d3, {t, h};\nand.b32 t, c4, 0xffe;\n"
        "mad.lo.u32 t, t, 4, 0x200000;\nmov.b64 d4, {t, h};\nand.b32 t, c5, 0xffe;\nmad.lo.u32 t, t, 4, 0x200000;\nmov.b64 d5, {t, h};\nand.b32 t, c6, 0xffe;\n"
        "mad.lo.u32 t, t, 4, 0x200000;\nmov.b64 d6, {t, h};\nand.b32 t, c7, 0xffe;\nmad.lo.u32 t, t, 4, 0x200000;\nmov.b64 d7, {t, h};\nand.b32 t, c8, 0xffe;\n"
        "mad.lo.u32 t, t, 4, 0x200000;\nmov.b64 d8, {t, h};\nand.b32 t, c9, 0xffe;\nmad.lo.u32 t, t, 4, 0x200000;\nmov.b64 d9, {t, h};\nand.b32 t, c10, 0xffe;\n"
        "mad.lo.u32 t, t, 4, 0x200000;\nmov.b64 d10, {t, h};\nand.b32 t, c11, 0xffe;\nmad.lo.u32 t, t, 4, 0x200000;\nmov.b64 d11, {t, h};\n"
        "and.b32 t, c12, 0xffe;\nmad.lo.u32 t, t, 4, 0x200000;\nmov.b64 d12, {t, h};\nand.b32 t, c13, 0xffe;\nmad.lo.u32 t, t, 4, 0x200000;\n"
        "mov.b64 d13, {t, h};\nand.b32 t, c14, 0xffe;\nmad.lo.u32 t, t, 4, 0x200000;\nmov.b64 d14, {t, h};\nand.b32 t, c15, 0xffe;\n"
        "mad.lo.u32 t, t, 4, 0x200000;\nmov.b64 d15, {t, h};\nwgmma.fence.sync.aligned;\n"
        "wgmma.mma_async.sync.aligned.m64n32k16.f32.bf16.bf16 {o0,o1,o2,o3,o4,o5,o6,o7,o8,o9,o10,o11,o12,o13,o14,o15}, {a0,a1,a2,a3}, d0, p0, 1, 1, 1;\n"
        "wgmma.mma_async.sync.aligned.m64n32k16.f32.bf16.bf16 {o16,o17,o18,o19,o20,o21,o22,o23,o24,o25,o26,o27,o28,o29,o30,o31}, {a0,a1,a2,a3}, d8, p0, 1, 1, 1;\n"
        "wgmma.mma_async.sync.aligned.m64n32k16.f32.bf16.bf16 {o0,o1,o2,o3,o4,o5,o6,o7,o8,o9,o10,o11,o12,o13,o14,o15}, {a4,a5,a6,a7}, d1, p1, 1, 1, 1;\n"
        "wgmma.mma_async.sync.aligned.m64n32k16.f32.bf16.bf16 {o16,o17,o18,o19,o20,o21,o22,o23,o24,o25,o26,o27,o28,o29,o30,o31}, {a4,a5,a6,a7}, d9, p1, 1, 1, 1;\n"
        "wgmma.mma_async.sync.aligned.m64n32k16.f32.bf16.bf16 {o0,o1,o2,o3,o4,o5,o6,o7,o8,o9,o10,o11,o12,o13,o14,o15}, {a8,a9,a10,a11}, d2, p1, 1, 1, 1;\n"
        "wgmma.mma_async.sync.aligned.m64n32k16.f32.bf16.bf16 {o16,o17,o18,o19,o20,o21,o22,o23,o24,o25,o26,o27,o28,o29,o30,o31}, {a8,a9,a10,a11}, d10, p1, 1, 1, 1;\n"
        "wgmma.mma_async.sync.aligned.m64n32k16.f32.bf16.bf16 {o0,o1,o2,o3,o4,o5,o6,o7,o8,o9,o10,o11,o12,o13,o14,o15}, {a12,a13,a14,a15}, d3, p1, 1, 1, 1;\n"
        "wgmma.mma_async.sync.aligned.m64n32k16.f32.bf16.bf16 {o16,o17,o18,o19,o20,o21,o22,o23,o24,o25,o26,o27,o28,o29,o30,o31}, {a12,a13,a14,a15}, d11, p1, 1, 1, 1;\n"
        "wgmma.mma_async.sync.aligned.m64n32k16.f32.bf16.bf16 {o0,o1,o2,o3,o4,o5,o6,o7,o8,o9,o10,o11,o12,o13,o14,o15}, {a16,a17,a18,a19}, d4, p1, 1, 1, 1;\n"
        "wgmma.mma_async.sync.aligned.m64n32k16.f32.bf16.bf16 {o16,o17,o18,o19,o20,o21,o22,o23,o24,o25,o26,o27,o28,o29,o30,o31}, {a16,a17,a18,a19}, d12, p1, 1, 1, 1;\n"
        "wgmma.mma_async.sync.aligned.m64n32k16.f32.bf16.bf16 {o0,o1,o2,o3,o4,o5,o6,o7,o8,o9,o10,o11,o12,o13,o14,o15}, {a20,a21,a22,a23}, d5, p1, 1, 1, 1;\n"
        "wgmma.mma_async.sync.aligned.m64n32k16.f32.bf16.bf16 {o16,o17,o18,o19,o20,o21,o22,o23,o24,o25,o26,o27,o28,o29,o30,o31}, {a20,a21,a22,a23}, d13, p1, 1, 1, 1;\n"
        "wgmma.mma_async.sync.aligned.m64n32k16.f32.bf16.bf16 {o0,o1,o2,o3,o4,o5,o6,o7,o8,o9,o10,o11,o12,o13,o14,o15}, {a24,a25,a26,a27}, d6, p1, 1, 1, 1;\n"
        "wgmma.mma_async.sync.aligned.m64n32k16.f32.bf16.bf16 {o16,o17,o18,o19,o20,o21,o22,o23,o24,o25,o26,o27,o28,o29,o30,o31}, {a24,a25,a26,a27}, d14, p1, 1, 1, 1;\n"
        "wgmma.mma_async.sync.aligned.m64n32k16.f32.bf16.bf16 {o0,o1,o2,o3,o4,o5,o6,o7,o8,o9,o10,o11,o12,o13,o14,o15}, {a28,a29,a30,a31}, d7, p1, 1, 1, 1;\n"
        "wgmma.mma_async.sync.aligned.m64n32k16.f32.bf16.bf16 {o16,o17,o18,o19,o20,o21,o22,o23,o24,o25,o26,o27,o28,o29,o30,o31}, {a28,a29,a30,a31}, d15, p1, 1, 1, 1;\n"
        "wgmma.commit_group.sync.aligned;\n@nv bra.uni END;\n@s0 st.global.v4.b32 [%65+0], {k0,k1,k2,k3};\n@s1 st.global.v4.b32 [%66+0], {k4,k5,k6,k7};\n"
        "@s0 st.global.v4.b32 [%65+64], {k8,k9,k10,k11};\n@s1 st.global.v4.b32 [%66+64], {k12,k13,k14,k15};\n@nv bra.uni END;\nwgmma.wait_group.sync.aligned 0;\n"
        "cvt.rn.bf16x2.f32 k0, o1, o0;\ncvt.rn.bf16x2.f32 k1, o5, o4;\ncvt.rn.bf16x2.f32 k2, o9, o8;\ncvt.rn.bf16x2.f32 k3, o13, o12;\n"
        "cvt.rn.bf16x2.f32 k4, o3, o2;\ncvt.rn.bf16x2.f32 k5, o7, o6;\ncvt.rn.bf16x2.f32 k6, o11, o10;\ncvt.rn.bf16x2.f32 k7, o15, o14;\n"
        "cvt.rn.bf16x2.f32 k8, o17, o16;\ncvt.rn.bf16x2.f32 k9, o21, o20;\ncvt.rn.bf16x2.f32 k10, o25, o24;\ncvt.rn.bf16x2.f32 k11, o29, o28;\n"
        "cvt.rn.bf16x2.f32 k12, o19, o18;\ncvt.rn.bf16x2.f32 k13, o23, o22;\ncvt.rn.bf16x2.f32 k14, o27, o26;\ncvt.rn.bf16x2.f32 k15, o31, o30;\n"
        "ld.volatile.shared.v4.b32 {c0,c1,c2,c3}, [%64+0];\nld.volatile.shared.v4.b32 {c4,c5,c6,c7}, [%64+8192];\n"
        "ld.volatile.shared.v4.b32 {c8,c9,c10,c11}, [%64+16];\nld.volatile.shared.v4.b32 {c12,c13,c14,c15}, [%64+8208];\nand.b32 t, c0, 0xffe;\n"
        "mad.lo.u32 t, t, 4, 0x200000;\nmov.b64 d0, {t, h};\nand.b32 t, c1, 0xffe;\nmad.lo.u32 t, t, 4, 0x200000;\nmov.b64 d1, {t, h};\nand.b32 t, c2, 0xffe;\n"
        "mad.lo.u32 t, t, 4, 0x200000;\nmov.b64 d2, {t, h};\nand.b32 t, c3, 0xffe;\nmad.lo.u32 t, t, 4, 0x200000;\nmov.b64 d3, {t, h};\nand.b32 t, c4, 0xffe;\n"
        "mad.lo.u32 t, t, 4, 0x200000;\nmov.b64 d4, {t, h};\nand.b32 t, c5, 0xffe;\nmad.lo.u32 t, t, 4, 0x200000;\nmov.b64 d5, {t, h};\nand.b32 t, c6, 0xffe;\n"
        "mad.lo.u32 t, t, 4, 0x200000;\nmov.b64 d6, {t, h};\nand.b32 t, c7, 0xffe;\nmad.lo.u32 t, t, 4, 0x200000;\nmov.b64 d7, {t, h};\nand.b32 t, c8, 0xffe;\n"
        "mad.lo.u32 t, t, 4, 0x200000;\nmov.b64 d8, {t, h};\nand.b32 t, c9, 0xffe;\nmad.lo.u32 t, t, 4, 0x200000;\nmov.b64 d9, {t, h};\nand.b32 t, c10, 0xffe;\n"
        "mad.lo.u32 t, t, 4, 0x200000;\nmov.b64 d10, {t, h};\nand.b32 t, c11, 0xffe;\nmad.lo.u32 t, t, 4, 0x200000;\nmov.b64 d11, {t, h};\n"
        "and.b32 t, c12, 0xffe;\nmad.lo.u32 t, t, 4, 0x200000;\nmov.b64 d12, {t, h};\nand.b32 t, c13, 0xffe;\nmad.lo.u32 t, t, 4, 0x200000;\n"
        "mov.b64 d13, {t, h};\nand.b32 t, c14, 0xffe;\nmad.lo.u32 t, t, 4, 0x200000;\nmov.b64 d14, {t, h};\nand.b32 t, c15, 0xffe;\n"
        "mad.lo.u32 t, t, 4, 0x200000;\nmov.b64 d15, {t, h};\nwgmma.fence.sync.aligned;\n"
        "wgmma.mma_async.sync.aligned.m64n32k16.f32.bf16.bf16 {o0,o1,o2,o3,o4,o5,o6,o7,o8,o9,o10,o11,o12,o13,o14,o15}, {b0,b1,b2,b3}, d0, p0, 1, 1, 1;\n"
        "wgmma.mma_async.sync.aligned.m64n32k16.f32.bf16.bf16 {o16,o17,o18,o19,o20,o21,o22,o23,o24,o25,o26,o27,o28,o29,o30,o31}, {b0,b1,b2,b3}, d8, p0, 1, 1, 1;\n"
        "wgmma.mma_async.sync.aligned.m64n32k16.f32.bf16.bf16 {o0,o1,o2,o3,o4,o5,o6,o7,o8,o9,o10,o11,o12,o13,o14,o15}, {b4,b5,b6,b7}, d1, p1, 1, 1, 1;\n"
        "wgmma.mma_async.sync.aligned.m64n32k16.f32.bf16.bf16 {o16,o17,o18,o19,o20,o21,o22,o23,o24,o25,o26,o27,o28,o29,o30,o31}, {b4,b5,b6,b7}, d9, p1, 1, 1, 1;\n"
        "wgmma.mma_async.sync.aligned.m64n32k16.f32.bf16.bf16 {o0,o1,o2,o3,o4,o5,o6,o7,o8,o9,o10,o11,o12,o13,o14,o15}, {b8,b9,b10,b11}, d2, p1, 1, 1, 1;\n"
        "wgmma.mma_async.sync.aligned.m64n32k16.f32.bf16.bf16 {o16,o17,o18,o19,o20,o21,o22,o23,o24,o25,o26,o27,o28,o29,o30,o31}, {b8,b9,b10,b11}, d10, p1, 1, 1, 1;\n"
        "wgmma.mma_async.sync.aligned.m64n32k16.f32.bf16.bf16 {o0,o1,o2,o3,o4,o5,o6,o7,o8,o9,o10,o11,o12,o13,o14,o15}, {b12,b13,b14,b15}, d3, p1, 1, 1, 1;\n"
        "wgmma.mma_async.sync.aligned.m64n32k16.f32.bf16.bf16 {o16,o17,o18,o19,o20,o21,o22,o23,o24,o25,o26,o27,o28,o29,o30,o31}, {b12,b13,b14,b15}, d11, p1, 1, 1, 1;\n"
        "wgmma.mma_async.sync.aligned.m64n32k16.f32.bf16.bf16 {o0,o1,o2,o3,o4,o5,o6,o7,o8,o9,o10,o11,o12,o13,o14,o15}, {b16,b17,b18,b19}, d4, p1, 1, 1, 1;\n"
        "wgmma.mma_async.sync.aligned.m64n32k16.f32.bf16.bf16 {o16,o17,o18,o19,o20,o21,o22,o23,o24,o25,o26,o27,o28,o29,o30,o31}, {b16,b17,b18,b19}, d12, p1, 1, 1, 1;\n"
        "wgmma.mma_async.sync.aligned.m64n32k16.f32.bf16.bf16 {o0,o1,o2,o3,o4,o5,o6,o7,o8,o9,o10,o11,o12,o13,o14,o15}, {b20,b21,b22,b23}, d5, p1, 1, 1, 1;\n"
        "wgmma.mma_async.sync.aligned.m64n32k16.f32.bf16.bf16 {o16,o17,o18,o19,o20,o21,o22,o23,o24,o25,o26,o27,o28,o29,o30,o31}, {b20,b21,b22,b23}, d13, p1, 1, 1, 1;\n"
        "wgmma.mma_async.sync.aligned.m64n32k16.f32.bf16.bf16 {o0,o1,o2,o3,o4,o5,o6,o7,o8,o9,o10,o11,o12,o13,o14,o15}, {b24,b25,b26,b27}, d6, p1, 1, 1, 1;\n"
        "wgmma.mma_async.sync.aligned.m64n32k16.f32.bf16.bf16 {o16,o17,o18,o19,o20,o21,o22,o23,o24,o25,o26,o27,o28,o29,o30,o31}, {b24,b25,b26,b27}, d14, p1, 1, 1, 1;\n"
        "wgmma.mma_async.sync.aligned.m64n32k16.f32.bf16.bf16 {o0,o1,o2,o3,o4,o5,o6,o7,o8,o9,o10,o11,o12,o13,o14,o15}, {b28,b29,b30,b31}, d7, p1, 1, 1, 1;\n"
        "wgmma.mma_async.sync.aligned.m64n32k16.f32.bf16.bf16 {o16,o17,o18,o19,o20,o21,o22,o23,o24,o25,o26,o27,o28,o29,o30,o31}, {b28,b29,b30,b31}, d15, p1, 1, 1, 1;\n"
        "wgmma.commit_group.sync.aligned;\n@nv bra.uni END;\n@s0 st.global.v4.b32 [%65+128], {k0,k1,k2,k3};\n@s1 st.global.v4.b32 [%66+128], {k4,k5,k6,k7};\n"
        "@s0 st.global.v4.b32 [%65+192], {k8,k9,k10,k11};\n@s1 st.global.v4.b32 [%66+192], {k12,k13,k14,k15};\n@nv bra.uni END;\n"
        "wgmma.wait_group.sync.aligned 0;\ncvt.rn.bf16x2.f32 k0, o1, o0;\ncvt.rn.bf16x2.f32 k1, o5, o4;\ncvt.rn.bf16x2.f32 k2, o9, o8;\n"
        "cvt.rn.bf16x2.f32 k3, o13, o12;\ncvt.rn.bf16x2.f32 k4, o3, o2;\ncvt.rn.bf16x2.f32 k5, o7, o6;\ncvt.rn.bf16x2.f32 k6, o11, o10;\n"
        "cvt.rn.bf16x2.f32 k7, o15, o14;\ncvt.rn.bf16x2.f32 k8, o17, o16;\ncvt.rn.bf16x2.f32 k9, o21, o20;\ncvt.rn.bf16x2.f32 k10, o25, o24;\n"
        "cvt.rn.bf16x2.f32 k11, o29, o28;\ncvt.rn.bf16x2.f32 k12, o19, o18;\ncvt.rn.bf16x2.f32 k13, o23, o22;\ncvt.rn.bf16x2.f32 k14, o27, o26;\n"
        "cvt.rn.bf16x2.f32 k15, o31, o30;\nld.volatile.shared.v4.b32 {c0,c1,c2,c3}, [%64+32];\nld.volatile.shared.v4.b32 {c4,c5,c6,c7}, [%64+8224];\n"
        "ld.volatile.shared.v4.b32 {c8,c9,c10,c11}, [%64+48];\nld.volatile.shared.v4.b32 {c12,c13,c14,c15}, [%64+8240];\nand.b32 t, c0, 0xffe;\n"
        "mad.lo.u32 t, t, 4, 0x200000;\nmov.b64 d0, {t, h};\nand.b32 t, c1, 0xffe;\nmad.lo.u32 t, t, 4, 0x200000;\nmov.b64 d1, {t, h};\nand.b32 t, c2, 0xffe;\n"
        "mad.lo.u32 t, t, 4, 0x200000;\nmov.b64 d2, {t, h};\nand.b32 t, c3, 0xffe;\nmad.lo.u32 t, t, 4, 0x200000;\nmov.b64 d3, {t, h};\nand.b32 t, c4, 0xffe;\n"
        "mad.lo.u32 t, t, 4, 0x200000;\nmov.b64 d4, {t, h};\nand.b32 t, c5, 0xffe;\nmad.lo.u32 t, t, 4, 0x200000;\nmov.b64 d5, {t, h};\nand.b32 t, c6, 0xffe;\n"
        "mad.lo.u32 t, t, 4, 0x200000;\nmov.b64 d6, {t, h};\nand.b32 t, c7, 0xffe;\nmad.lo.u32 t, t, 4, 0x200000;\nmov.b64 d7, {t, h};\nand.b32 t, c8, 0xffe;\n"
        "mad.lo.u32 t, t, 4, 0x200000;\nmov.b64 d8, {t, h};\nand.b32 t, c9, 0xffe;\nmad.lo.u32 t, t, 4, 0x200000;\nmov.b64 d9, {t, h};\nand.b32 t, c10, 0xffe;\n"
        "mad.lo.u32 t, t, 4, 0x200000;\nmov.b64 d10, {t, h};\nand.b32 t, c11, 0xffe;\nmad.lo.u32 t, t, 4, 0x200000;\nmov.b64 d11, {t, h};\n"
        "and.b32 t, c12, 0xffe;\nmad.lo.u32 t, t, 4, 0x200000;\nmov.b64 d12, {t, h};\nand.b32 t, c13, 0xffe;\nmad.lo.u32 t, t, 4, 0x200000;\n"
        "mov.b64 d13, {t, h};\nand.b32 t, c14, 0xffe;\nmad.lo.u32 t, t, 4, 0x200000;\nmov.b64 d14, {t, h};\nand.b32 t, c15, 0xffe;\n"
        "mad.lo.u32 t, t, 4, 0x200000;\nmov.b64 d15, {t, h};\nwgmma.fence.sync.aligned;\n"
        "wgmma.mma_async.sync.aligned.m64n32k16.f32.bf16.bf16 {o0,o1,o2,o3,o4,o5,o6,o7,o8,o9,o10,o11,o12,o13,o14,o15}, {b0,b1,b2,b3}, d0, p0, 1, 1, 1;\n"
        "wgmma.mma_async.sync.aligned.m64n32k16.f32.bf16.bf16 {o16,o17,o18,o19,o20,o21,o22,o23,o24,o25,o26,o27,o28,o29,o30,o31}, {b0,b1,b2,b3}, d8, p0, 1, 1, 1;\n"
        "wgmma.mma_async.sync.aligned.m64n32k16.f32.bf16.bf16 {o0,o1,o2,o3,o4,o5,o6,o7,o8,o9,o10,o11,o12,o13,o14,o15}, {b4,b5,b6,b7}, d1, p1, 1, 1, 1;\n"
        "wgmma.mma_async.sync.aligned.m64n32k16.f32.bf16.bf16 {o16,o17,o18,o19,o20,o21,o22,o23,o24,o25,o26,o27,o28,o29,o30,o31}, {b4,b5,b6,b7}, d9, p1, 1, 1, 1;\n"
        "wgmma.mma_async.sync.aligned.m64n32k16.f32.bf16.bf16 {o0,o1,o2,o3,o4,o5,o6,o7,o8,o9,o10,o11,o12,o13,o14,o15}, {b8,b9,b10,b11}, d2, p1, 1, 1, 1;\n"
        "wgmma.mma_async.sync.aligned.m64n32k16.f32.bf16.bf16 {o16,o17,o18,o19,o20,o21,o22,o23,o24,o25,o26,o27,o28,o29,o30,o31}, {b8,b9,b10,b11}, d10, p1, 1, 1, 1;\n"
        "wgmma.mma_async.sync.aligned.m64n32k16.f32.bf16.bf16 {o0,o1,o2,o3,o4,o5,o6,o7,o8,o9,o10,o11,o12,o13,o14,o15}, {b12,b13,b14,b15}, d3, p1, 1, 1, 1;\n"
        "wgmma.mma_async.sync.aligned.m64n32k16.f32.bf16.bf16 {o16,o17,o18,o19,o20,o21,o22,o23,o24,o25,o26,o27,o28,o29,o30,o31}, {b12,b13,b14,b15}, d11, p1, 1, 1, 1;\n"
        "wgmma.mma_async.sync.aligned.m64n32k16.f32.bf16.bf16 {o0,o1,o2,o3,o4,o5,o6,o7,o8,o9,o10,o11,o12,o13,o14,o15}, {b16,b17,b18,b19}, d4, p1, 1, 1, 1;\n"
        "wgmma.mma_async.sync.aligned.m64n32k16.f32.bf16.bf16 {o16,o17,o18,o19,o20,o21,o22,o23,o24,o25,o26,o27,o28,o29,o30,o31}, {b16,b17,b18,b19}, d12, p1, 1, 1, 1;\n"
        "wgmma.mma_async.sync.aligned.m64n32k16.f32.bf16.bf16 {o0,o1,o2,o3,o4,o5,o6,o7,o8,o9,o10,o11,o12,o13,o14,o15}, {b20,b21,b22,b23}, d5, p1, 1, 1, 1;\n"
        "wgmma.mma_async.sync.aligned.m64n32k16.f32.bf16.bf16 {o16,o17,o18,o19,o20,o21,o22,o23,o24,o25,o26,o27,o28,o29,o30,o31}, {b20,b21,b22,b23}, d13, p1, 1, 1, 1;\n"
        "wgmma.mma_async.sync.aligned.m64n32k16.f32.bf16.bf16 {o0,o1,o2,o3,o4,o5,o6,o7,o8,o9,o10,o11,o12,o13,o14,o15}, {b24,b25,b26,b27}, d6, p1, 1, 1, 1;\n"
        "wgmma.mma_async.sync.aligned.m64n32k16.f32.bf16.bf16 {o16,o17,o18,o19,o20,o21,o22,o23,o24,o25,o26,o27,o28,o29,o30,o31}, {b24,b25,b26,b27}, d14, p1, 1, 1, 1;\n"
        "wgmma.mma_async.sync.aligned.m64n32k16.f32.bf16.bf16 {o0,o1,o2,o3,o4,o5,o6,o7,o8,o9,o10,o11,o12,o13,o14,o15}, {b28,b29,b30,b31}, d7, p1, 1, 1, 1;\n"
        "wgmma.mma_async.sync.aligned.m64n32k16.f32.bf16.bf16 {o16,o17,o18,o19,o20,o21,o22,o23,o24,o25,o26,o27,o28,o29,o30,o31}, {b28,b29,b30,b31}, d15, p1, 1, 1, 1;\n"
        "wgmma.commit_group.sync.aligned;\n@nv bra.uni END;\n@s2 st.global.v4.b32 [%67+0], {k0,k1,k2,k3};\n@s3 st.global.v4.b32 [%68+0], {k4,k5,k6,k7};\n"
        "@s2 st.global.v4.b32 [%67+64], {k8,k9,k10,k11};\n@s3 st.global.v4.b32 [%68+64], {k12,k13,k14,k15};\n@nv bra.uni END;\nwgmma.wait_group.sync.aligned 0;\n"
        "cvt.rn.bf16x2.f32 k0, o1, o0;\ncvt.rn.bf16x2.f32 k1, o5, o4;\ncvt.rn.bf16x2.f32 k2, o9, o8;\ncvt.rn.bf16x2.f32 k3, o13, o12;\n"
        "cvt.rn.bf16x2.f32 k4, o3, o2;\ncvt.rn.bf16x2.f32 k5, o7, o6;\ncvt.rn.bf16x2.f32 k6, o11, o10;\ncvt.rn.bf16x2.f32 k7, o15, o14;\n"
        "cvt.rn.bf16x2.f32 k8, o17, o16;\ncvt.rn.bf16x2.f32 k9, o21, o20;\ncvt.rn.bf16x2.f32 k10, o25, o24;\ncvt.rn.bf16x2.f32 k11, o29, o28;\n"
        "cvt.rn.bf16x2.f32 k12, o19, o18;\ncvt.rn.bf16x2.f32 k13, o23, o22;\ncvt.rn.bf16x2.f32 k14, o27, o26;\ncvt.rn.bf16x2.f32 k15, o31, o30;\n"
        "@s2 st.global.v4.b32 [%67+128], {k0,k1,k2,k3};\n@s3 st.global.v4.b32 [%68+128], {k4,k5,k6,k7};\n@s2 st.global.v4.b32 [%67+192], {k8,k9,k10,k11};\n"
        "@s3 st.global.v4.b32 [%68+192], {k12,k13,k14,k15};\n"
        "END:\n}\n"
        ::"r"(pk[0]), "r"(pk[1]), "r"(pk[2]), "r"(pk[3]), "r"(pk[4]), "r"(pk[5]), "r"(pk[6]), "r"(pk[7]), "r"(pk[8]), "r"(pk[9]), "r"(pk[10]),
          "r"(pk[11]), "r"(pk[12]), "r"(pk[13]), "r"(pk[14]), "r"(pk[15]), "r"(pk[16]), "r"(pk[17]), "r"(pk[18]), "r"(pk[19]), "r"(pk[20]),
          "r"(pk[21]), "r"(pk[22]), "r"(pk[23]), "r"(pk[24]), "r"(pk[25]), "r"(pk[26]), "r"(pk[27]), "r"(pk[28]), "r"(pk[29]), "r"(pk[30]),
          "r"(pk[31]), "r"(pk[32]), "r"(pk[33]), "r"(pk[34]), "r"(pk[35]), "r"(pk[36]), "r"(pk[37]), "r"(pk[38]), "r"(pk[39]), "r"(pk[40]),
          "r"(pk[41]), "r"(pk[42]), "r"(pk[43]), "r"(pk[44]), "r"(pk[45]), "r"(pk[46]), "r"(pk[47]), "r"(pk[48]), "r"(pk[49]), "r"(pk[50]),
          "r"(pk[51]), "r"(pk[52]), "r"(pk[53]), "r"(pk[54]), "r"(pk[55]), "r"(pk[56]), "r"(pk[57]), "r"(pk[58]), "r"(pk[59]), "r"(pk[60]),
          "r"(pk[61]), "r"(pk[62]), "r"(pk[63]), "r"(ra), "l"(p[0]), "l"(p[1]), "l"(p[2]), "l"(p[3]), "r"(v[0]), "r"(v[1]), "r"(v[2]), "r"(v[3]),
          "r"(ba)
        : "memory");
}
__device__ __forceinline__ void project3(const uint32_t (&pk)[48], uint32_t ra, uint32_t ba, uint4* const (&p)[3], const uint32_t (&v)[3]) {
    asm volatile(
        "{\n.reg .pred p0, p1, q0, q1, nv, s<4>;\n.reg .b32 t, h, c<16>, a<32>, b<32>, k<16>;\n.reg .b64 d<16>;\n.reg .f32 o<32>;\nsetp.ne.b32 p0, 0, 0;\n"
        "setp.eq.b32 p1, 0, 0;\nmov.b32 h, 8;\nsetp.eq.u32 nv, %48, 0;\nvote.sync.any.pred nv, nv, 0xffffffff;\nsetp.ne.b32 s0, %52, 0;\n"
        "setp.ne.b32 s1, %53, 0;\nsetp.ne.b32 s2, %54, 0;\nmovmatrix.sync.aligned.m8n8.trans.b16 a0, %0;\nmovmatrix.sync.aligned.m8n8.trans.b16 a1, %16;\n"
        "movmatrix.sync.aligned.m8n8.trans.b16 a2, %1;\nmovmatrix.sync.aligned.m8n8.trans.b16 a3, %17;\nmovmatrix.sync.aligned.m8n8.trans.b16 a4, %2;\n"
        "movmatrix.sync.aligned.m8n8.trans.b16 a5, %18;\nmovmatrix.sync.aligned.m8n8.trans.b16 a6, %3;\nmovmatrix.sync.aligned.m8n8.trans.b16 a7, %19;\n"
        "movmatrix.sync.aligned.m8n8.trans.b16 a8, %4;\nmovmatrix.sync.aligned.m8n8.trans.b16 a9, %20;\nmovmatrix.sync.aligned.m8n8.trans.b16 a10, %5;\n"
        "movmatrix.sync.aligned.m8n8.trans.b16 a11, %21;\nmovmatrix.sync.aligned.m8n8.trans.b16 a12, %6;\nmovmatrix.sync.aligned.m8n8.trans.b16 a13, %22;\n"
        "movmatrix.sync.aligned.m8n8.trans.b16 a14, %7;\nmovmatrix.sync.aligned.m8n8.trans.b16 a15, %23;\nmovmatrix.sync.aligned.m8n8.trans.b16 a16, %8;\n"
        "movmatrix.sync.aligned.m8n8.trans.b16 a17, %24;\nmovmatrix.sync.aligned.m8n8.trans.b16 a18, %9;\nmovmatrix.sync.aligned.m8n8.trans.b16 a19, %25;\n"
        "movmatrix.sync.aligned.m8n8.trans.b16 a20, %10;\nmovmatrix.sync.aligned.m8n8.trans.b16 a21, %26;\nmovmatrix.sync.aligned.m8n8.trans.b16 a22, %11;\n"
        "movmatrix.sync.aligned.m8n8.trans.b16 a23, %27;\nmovmatrix.sync.aligned.m8n8.trans.b16 a24, %12;\nmovmatrix.sync.aligned.m8n8.trans.b16 a25, %28;\n"
        "movmatrix.sync.aligned.m8n8.trans.b16 a26, %13;\nmovmatrix.sync.aligned.m8n8.trans.b16 a27, %29;\nmovmatrix.sync.aligned.m8n8.trans.b16 a28, %14;\n"
        "movmatrix.sync.aligned.m8n8.trans.b16 a29, %30;\nmovmatrix.sync.aligned.m8n8.trans.b16 a30, %15;\nmovmatrix.sync.aligned.m8n8.trans.b16 a31, %31;\n"
        "mov.b32 t, 0;\n"
        "W0:\nmbarrier.try_wait.parity.shared.b64 q0, [%55+0], 0;\nadd.u32 t, t, 1;\nsetp.lt.and.u32 q1, t, 1000000, !q0;\n@q1 bra.uni W0;\nmov.b32 t, 0;\n"
        "W1:\nmbarrier.try_wait.parity.shared.b64 q0, [%55+8], 0;\nadd.u32 t, t, 1;\nsetp.lt.and.u32 q1, t, 1000000, !q0;\n@q1 bra.uni W1;\nmov.b32 t, 0;\n"
        "W2:\nmbarrier.try_wait.parity.shared.b64 q0, [%55+16], 0;\nadd.u32 t, t, 1;\nsetp.lt.and.u32 q1, t, 1000000, !q0;\n@q1 bra.uni W2;\nmov.b32 t, 0;\n"
        "W3:\nmbarrier.try_wait.parity.shared.b64 q0, [%55+24], 0;\nadd.u32 t, t, 1;\nsetp.lt.and.u32 q1, t, 1000000, !q0;\n@q1 bra.uni W3;\n"
        "ld.volatile.shared.v4.b32 {c0,c1,c2,c3}, [%48+0];\nld.volatile.shared.v4.b32 {c4,c5,c6,c7}, [%48+8192];\n"
        "ld.volatile.shared.v4.b32 {c8,c9,c10,c11}, [%48+16];\nld.volatile.shared.v4.b32 {c12,c13,c14,c15}, [%48+8208];\nand.b32 t, c0, 0xffe;\n"
        "mad.lo.u32 t, t, 4, 0x200000;\nmov.b64 d0, {t, h};\nand.b32 t, c1, 0xffe;\nmad.lo.u32 t, t, 4, 0x200000;\nmov.b64 d1, {t, h};\nand.b32 t, c2, 0xffe;\n"
        "mad.lo.u32 t, t, 4, 0x200000;\nmov.b64 d2, {t, h};\nand.b32 t, c3, 0xffe;\nmad.lo.u32 t, t, 4, 0x200000;\nmov.b64 d3, {t, h};\nand.b32 t, c4, 0xffe;\n"
        "mad.lo.u32 t, t, 4, 0x200000;\nmov.b64 d4, {t, h};\nand.b32 t, c5, 0xffe;\nmad.lo.u32 t, t, 4, 0x200000;\nmov.b64 d5, {t, h};\nand.b32 t, c6, 0xffe;\n"
        "mad.lo.u32 t, t, 4, 0x200000;\nmov.b64 d6, {t, h};\nand.b32 t, c7, 0xffe;\nmad.lo.u32 t, t, 4, 0x200000;\nmov.b64 d7, {t, h};\nand.b32 t, c8, 0xffe;\n"
        "mad.lo.u32 t, t, 4, 0x200000;\nmov.b64 d8, {t, h};\nand.b32 t, c9, 0xffe;\nmad.lo.u32 t, t, 4, 0x200000;\nmov.b64 d9, {t, h};\nand.b32 t, c10, 0xffe;\n"
        "mad.lo.u32 t, t, 4, 0x200000;\nmov.b64 d10, {t, h};\nand.b32 t, c11, 0xffe;\nmad.lo.u32 t, t, 4, 0x200000;\nmov.b64 d11, {t, h};\n"
        "and.b32 t, c12, 0xffe;\nmad.lo.u32 t, t, 4, 0x200000;\nmov.b64 d12, {t, h};\nand.b32 t, c13, 0xffe;\nmad.lo.u32 t, t, 4, 0x200000;\n"
        "mov.b64 d13, {t, h};\nand.b32 t, c14, 0xffe;\nmad.lo.u32 t, t, 4, 0x200000;\nmov.b64 d14, {t, h};\nand.b32 t, c15, 0xffe;\n"
        "mad.lo.u32 t, t, 4, 0x200000;\nmov.b64 d15, {t, h};\nwgmma.fence.sync.aligned;\n"
        "wgmma.mma_async.sync.aligned.m64n32k16.f32.bf16.bf16 {o0,o1,o2,o3,o4,o5,o6,o7,o8,o9,o10,o11,o12,o13,o14,o15}, {a0,a1,a2,a3}, d0, p0, 1, 1, 1;\n"
        "wgmma.mma_async.sync.aligned.m64n32k16.f32.bf16.bf16 {o16,o17,o18,o19,o20,o21,o22,o23,o24,o25,o26,o27,o28,o29,o30,o31}, {a0,a1,a2,a3}, d8, p0, 1, 1, 1;\n"
        "wgmma.mma_async.sync.aligned.m64n32k16.f32.bf16.bf16 {o0,o1,o2,o3,o4,o5,o6,o7,o8,o9,o10,o11,o12,o13,o14,o15}, {a4,a5,a6,a7}, d1, p1, 1, 1, 1;\n"
        "wgmma.mma_async.sync.aligned.m64n32k16.f32.bf16.bf16 {o16,o17,o18,o19,o20,o21,o22,o23,o24,o25,o26,o27,o28,o29,o30,o31}, {a4,a5,a6,a7}, d9, p1, 1, 1, 1;\n"
        "wgmma.mma_async.sync.aligned.m64n32k16.f32.bf16.bf16 {o0,o1,o2,o3,o4,o5,o6,o7,o8,o9,o10,o11,o12,o13,o14,o15}, {a8,a9,a10,a11}, d2, p1, 1, 1, 1;\n"
        "wgmma.mma_async.sync.aligned.m64n32k16.f32.bf16.bf16 {o16,o17,o18,o19,o20,o21,o22,o23,o24,o25,o26,o27,o28,o29,o30,o31}, {a8,a9,a10,a11}, d10, p1, 1, 1, 1;\n"
        "wgmma.mma_async.sync.aligned.m64n32k16.f32.bf16.bf16 {o0,o1,o2,o3,o4,o5,o6,o7,o8,o9,o10,o11,o12,o13,o14,o15}, {a12,a13,a14,a15}, d3, p1, 1, 1, 1;\n"
        "wgmma.mma_async.sync.aligned.m64n32k16.f32.bf16.bf16 {o16,o17,o18,o19,o20,o21,o22,o23,o24,o25,o26,o27,o28,o29,o30,o31}, {a12,a13,a14,a15}, d11, p1, 1, 1, 1;\n"
        "wgmma.mma_async.sync.aligned.m64n32k16.f32.bf16.bf16 {o0,o1,o2,o3,o4,o5,o6,o7,o8,o9,o10,o11,o12,o13,o14,o15}, {a16,a17,a18,a19}, d4, p1, 1, 1, 1;\n"
        "wgmma.mma_async.sync.aligned.m64n32k16.f32.bf16.bf16 {o16,o17,o18,o19,o20,o21,o22,o23,o24,o25,o26,o27,o28,o29,o30,o31}, {a16,a17,a18,a19}, d12, p1, 1, 1, 1;\n"
        "wgmma.mma_async.sync.aligned.m64n32k16.f32.bf16.bf16 {o0,o1,o2,o3,o4,o5,o6,o7,o8,o9,o10,o11,o12,o13,o14,o15}, {a20,a21,a22,a23}, d5, p1, 1, 1, 1;\n"
        "wgmma.mma_async.sync.aligned.m64n32k16.f32.bf16.bf16 {o16,o17,o18,o19,o20,o21,o22,o23,o24,o25,o26,o27,o28,o29,o30,o31}, {a20,a21,a22,a23}, d13, p1, 1, 1, 1;\n"
        "wgmma.mma_async.sync.aligned.m64n32k16.f32.bf16.bf16 {o0,o1,o2,o3,o4,o5,o6,o7,o8,o9,o10,o11,o12,o13,o14,o15}, {a24,a25,a26,a27}, d6, p1, 1, 1, 1;\n"
        "wgmma.mma_async.sync.aligned.m64n32k16.f32.bf16.bf16 {o16,o17,o18,o19,o20,o21,o22,o23,o24,o25,o26,o27,o28,o29,o30,o31}, {a24,a25,a26,a27}, d14, p1, 1, 1, 1;\n"
        "wgmma.mma_async.sync.aligned.m64n32k16.f32.bf16.bf16 {o0,o1,o2,o3,o4,o5,o6,o7,o8,o9,o10,o11,o12,o13,o14,o15}, {a28,a29,a30,a31}, d7, p1, 1, 1, 1;\n"
        "wgmma.mma_async.sync.aligned.m64n32k16.f32.bf16.bf16 {o16,o17,o18,o19,o20,o21,o22,o23,o24,o25,o26,o27,o28,o29,o30,o31}, {a28,a29,a30,a31}, d15, p1, 1, 1, 1;\n"
        "wgmma.commit_group.sync.aligned;\n@nv bra.uni END;\nmovmatrix.sync.aligned.m8n8.trans.b16 b0, %32;\nmovmatrix.sync.aligned.m8n8.trans.b16 b2, %33;\n"
        "movmatrix.sync.aligned.m8n8.trans.b16 b3, %33;\nmovmatrix.sync.aligned.m8n8.trans.b16 b4, %34;\nmovmatrix.sync.aligned.m8n8.trans.b16 b5, %34;\n"
        "movmatrix.sync.aligned.m8n8.trans.b16 b6, %35;\nmovmatrix.sync.aligned.m8n8.trans.b16 b7, %35;\nmovmatrix.sync.aligned.m8n8.trans.b16 b8, %36;\n"
        "movmatrix.sync.aligned.m8n8.trans.b16 b9, %36;\nmovmatrix.sync.aligned.m8n8.trans.b16 b20, %42;\nmovmatrix.sync.aligned.m8n8.trans.b16 b21, %42;\n"
        "movmatrix.sync.aligned.m8n8.trans.b16 b22, %43;\nmovmatrix.sync.aligned.m8n8.trans.b16 b23, %43;\nmovmatrix.sync.aligned.m8n8.trans.b16 b24, %44;\n"
        "movmatrix.sync.aligned.m8n8.trans.b16 b25, %44;\nmovmatrix.sync.aligned.m8n8.trans.b16 b26, %45;\nmovmatrix.sync.aligned.m8n8.trans.b16 b27, %45;\n"
        "movmatrix.sync.aligned.m8n8.trans.b16 b28, %46;\nmovmatrix.sync.aligned.m8n8.trans.b16 b29, %46;\nmovmatrix.sync.aligned.m8n8.trans.b16 b30, %47;\n"
        "movmatrix.sync.aligned.m8n8.trans.b16 b31, %47;\nmovmatrix.sync.aligned.m8n8.trans.b16 b1, %32;\nmovmatrix.sync.aligned.m8n8.trans.b16 b10, %37;\n"
        "movmatrix.sync.aligned.m8n8.trans.b16 b11, %37;\nmovmatrix.sync.aligned.m8n8.trans.b16 b12, %38;\nmovmatrix.sync.aligned.m8n8.trans.b16 b13, %38;\n"
        "movmatrix.sync.aligned.m8n8.trans.b16 b14, %39;\nmovmatrix.sync.aligned.m8n8.trans.b16 b15, %39;\nmovmatrix.sync.aligned.m8n8.trans.b16 b16, %40;\n"
        "movmatrix.sync.aligned.m8n8.trans.b16 b17, %40;\nmovmatrix.sync.aligned.m8n8.trans.b16 b18, %41;\nmovmatrix.sync.aligned.m8n8.trans.b16 b19, %41;\n"
        "@nv bra.uni END;\nwgmma.wait_group.sync.aligned 0;\ncvt.rn.bf16x2.f32 k0, o1, o0;\ncvt.rn.bf16x2.f32 k1, o5, o4;\ncvt.rn.bf16x2.f32 k2, o9, o8;\n"
        "cvt.rn.bf16x2.f32 k3, o13, o12;\ncvt.rn.bf16x2.f32 k4, o3, o2;\ncvt.rn.bf16x2.f32 k5, o7, o6;\ncvt.rn.bf16x2.f32 k6, o11, o10;\n"
        "cvt.rn.bf16x2.f32 k7, o15, o14;\ncvt.rn.bf16x2.f32 k8, o17, o16;\ncvt.rn.bf16x2.f32 k9, o21, o20;\ncvt.rn.bf16x2.f32 k10, o25, o24;\n"
        "cvt.rn.bf16x2.f32 k11, o29, o28;\ncvt.rn.bf16x2.f32 k12, o19, o18;\ncvt.rn.bf16x2.f32 k13, o23, o22;\ncvt.rn.bf16x2.f32 k14, o27, o26;\n"
        "cvt.rn.bf16x2.f32 k15, o31, o30;\nld.volatile.shared.v4.b32 {c0,c1,c2,c3}, [%48+32];\nld.volatile.shared.v4.b32 {c4,c5,c6,c7}, [%48+8224];\n"
        "ld.volatile.shared.v4.b32 {c8,c9,c10,c11}, [%48+48];\nld.volatile.shared.v4.b32 {c12,c13,c14,c15}, [%48+8240];\nand.b32 t, c0, 0xffe;\n"
        "mad.lo.u32 t, t, 4, 0x200000;\nmov.b64 d0, {t, h};\nand.b32 t, c1, 0xffe;\nmad.lo.u32 t, t, 4, 0x200000;\nmov.b64 d1, {t, h};\nand.b32 t, c2, 0xffe;\n"
        "mad.lo.u32 t, t, 4, 0x200000;\nmov.b64 d2, {t, h};\nand.b32 t, c3, 0xffe;\nmad.lo.u32 t, t, 4, 0x200000;\nmov.b64 d3, {t, h};\nand.b32 t, c4, 0xffe;\n"
        "mad.lo.u32 t, t, 4, 0x200000;\nmov.b64 d4, {t, h};\nand.b32 t, c5, 0xffe;\nmad.lo.u32 t, t, 4, 0x200000;\nmov.b64 d5, {t, h};\nand.b32 t, c6, 0xffe;\n"
        "mad.lo.u32 t, t, 4, 0x200000;\nmov.b64 d6, {t, h};\nand.b32 t, c7, 0xffe;\nmad.lo.u32 t, t, 4, 0x200000;\nmov.b64 d7, {t, h};\nand.b32 t, c8, 0xffe;\n"
        "mad.lo.u32 t, t, 4, 0x200000;\nmov.b64 d8, {t, h};\nand.b32 t, c9, 0xffe;\nmad.lo.u32 t, t, 4, 0x200000;\nmov.b64 d9, {t, h};\nand.b32 t, c10, 0xffe;\n"
        "mad.lo.u32 t, t, 4, 0x200000;\nmov.b64 d10, {t, h};\nand.b32 t, c11, 0xffe;\nmad.lo.u32 t, t, 4, 0x200000;\nmov.b64 d11, {t, h};\n"
        "and.b32 t, c12, 0xffe;\nmad.lo.u32 t, t, 4, 0x200000;\nmov.b64 d12, {t, h};\nand.b32 t, c13, 0xffe;\nmad.lo.u32 t, t, 4, 0x200000;\n"
        "mov.b64 d13, {t, h};\nand.b32 t, c14, 0xffe;\nmad.lo.u32 t, t, 4, 0x200000;\nmov.b64 d14, {t, h};\nand.b32 t, c15, 0xffe;\n"
        "mad.lo.u32 t, t, 4, 0x200000;\nmov.b64 d15, {t, h};\nwgmma.fence.sync.aligned;\n"
        "wgmma.mma_async.sync.aligned.m64n32k16.f32.bf16.bf16 {o0,o1,o2,o3,o4,o5,o6,o7,o8,o9,o10,o11,o12,o13,o14,o15}, {a0,a1,a2,a3}, d0, p0, 1, 1, 1;\n"
        "wgmma.mma_async.sync.aligned.m64n32k16.f32.bf16.bf16 {o16,o17,o18,o19,o20,o21,o22,o23,o24,o25,o26,o27,o28,o29,o30,o31}, {a0,a1,a2,a3}, d8, p0, 1, 1, 1;\n"
        "wgmma.mma_async.sync.aligned.m64n32k16.f32.bf16.bf16 {o0,o1,o2,o3,o4,o5,o6,o7,o8,o9,o10,o11,o12,o13,o14,o15}, {a4,a5,a6,a7}, d1, p1, 1, 1, 1;\n"
        "wgmma.mma_async.sync.aligned.m64n32k16.f32.bf16.bf16 {o16,o17,o18,o19,o20,o21,o22,o23,o24,o25,o26,o27,o28,o29,o30,o31}, {a4,a5,a6,a7}, d9, p1, 1, 1, 1;\n"
        "wgmma.mma_async.sync.aligned.m64n32k16.f32.bf16.bf16 {o0,o1,o2,o3,o4,o5,o6,o7,o8,o9,o10,o11,o12,o13,o14,o15}, {a8,a9,a10,a11}, d2, p1, 1, 1, 1;\n"
        "wgmma.mma_async.sync.aligned.m64n32k16.f32.bf16.bf16 {o16,o17,o18,o19,o20,o21,o22,o23,o24,o25,o26,o27,o28,o29,o30,o31}, {a8,a9,a10,a11}, d10, p1, 1, 1, 1;\n"
        "wgmma.mma_async.sync.aligned.m64n32k16.f32.bf16.bf16 {o0,o1,o2,o3,o4,o5,o6,o7,o8,o9,o10,o11,o12,o13,o14,o15}, {a12,a13,a14,a15}, d3, p1, 1, 1, 1;\n"
        "wgmma.mma_async.sync.aligned.m64n32k16.f32.bf16.bf16 {o16,o17,o18,o19,o20,o21,o22,o23,o24,o25,o26,o27,o28,o29,o30,o31}, {a12,a13,a14,a15}, d11, p1, 1, 1, 1;\n"
        "wgmma.mma_async.sync.aligned.m64n32k16.f32.bf16.bf16 {o0,o1,o2,o3,o4,o5,o6,o7,o8,o9,o10,o11,o12,o13,o14,o15}, {a16,a17,a18,a19}, d4, p1, 1, 1, 1;\n"
        "wgmma.mma_async.sync.aligned.m64n32k16.f32.bf16.bf16 {o16,o17,o18,o19,o20,o21,o22,o23,o24,o25,o26,o27,o28,o29,o30,o31}, {a16,a17,a18,a19}, d12, p1, 1, 1, 1;\n"
        "wgmma.mma_async.sync.aligned.m64n32k16.f32.bf16.bf16 {o0,o1,o2,o3,o4,o5,o6,o7,o8,o9,o10,o11,o12,o13,o14,o15}, {a20,a21,a22,a23}, d5, p1, 1, 1, 1;\n"
        "wgmma.mma_async.sync.aligned.m64n32k16.f32.bf16.bf16 {o16,o17,o18,o19,o20,o21,o22,o23,o24,o25,o26,o27,o28,o29,o30,o31}, {a20,a21,a22,a23}, d13, p1, 1, 1, 1;\n"
        "wgmma.mma_async.sync.aligned.m64n32k16.f32.bf16.bf16 {o0,o1,o2,o3,o4,o5,o6,o7,o8,o9,o10,o11,o12,o13,o14,o15}, {a24,a25,a26,a27}, d6, p1, 1, 1, 1;\n"
        "wgmma.mma_async.sync.aligned.m64n32k16.f32.bf16.bf16 {o16,o17,o18,o19,o20,o21,o22,o23,o24,o25,o26,o27,o28,o29,o30,o31}, {a24,a25,a26,a27}, d14, p1, 1, 1, 1;\n"
        "wgmma.mma_async.sync.aligned.m64n32k16.f32.bf16.bf16 {o0,o1,o2,o3,o4,o5,o6,o7,o8,o9,o10,o11,o12,o13,o14,o15}, {a28,a29,a30,a31}, d7, p1, 1, 1, 1;\n"
        "wgmma.mma_async.sync.aligned.m64n32k16.f32.bf16.bf16 {o16,o17,o18,o19,o20,o21,o22,o23,o24,o25,o26,o27,o28,o29,o30,o31}, {a28,a29,a30,a31}, d15, p1, 1, 1, 1;\n"
        "wgmma.commit_group.sync.aligned;\n@nv bra.uni END;\n@s0 st.global.v4.b32 [%49+0], {k0,k1,k2,k3};\n@s1 st.global.v4.b32 [%50+0], {k4,k5,k6,k7};\n"
        "@s0 st.global.v4.b32 [%49+64], {k8,k9,k10,k11};\n@s1 st.global.v4.b32 [%50+64], {k12,k13,k14,k15};\n@nv bra.uni END;\nwgmma.wait_group.sync.aligned 0;\n"
        "cvt.rn.bf16x2.f32 k0, o1, o0;\ncvt.rn.bf16x2.f32 k1, o5, o4;\ncvt.rn.bf16x2.f32 k2, o9, o8;\ncvt.rn.bf16x2.f32 k3, o13, o12;\n"
        "cvt.rn.bf16x2.f32 k4, o3, o2;\ncvt.rn.bf16x2.f32 k5, o7, o6;\ncvt.rn.bf16x2.f32 k6, o11, o10;\ncvt.rn.bf16x2.f32 k7, o15, o14;\n"
        "cvt.rn.bf16x2.f32 k8, o17, o16;\ncvt.rn.bf16x2.f32 k9, o21, o20;\ncvt.rn.bf16x2.f32 k10, o25, o24;\ncvt.rn.bf16x2.f32 k11, o29, o28;\n"
        "cvt.rn.bf16x2.f32 k12, o19, o18;\ncvt.rn.bf16x2.f32 k13, o23, o22;\ncvt.rn.bf16x2.f32 k14, o27, o26;\ncvt.rn.bf16x2.f32 k15, o31, o30;\n"
        "ld.volatile.shared.v4.b32 {c0,c1,c2,c3}, [%48+0];\nld.volatile.shared.v4.b32 {c4,c5,c6,c7}, [%48+8192];\n"
        "ld.volatile.shared.v4.b32 {c8,c9,c10,c11}, [%48+16];\nld.volatile.shared.v4.b32 {c12,c13,c14,c15}, [%48+8208];\nand.b32 t, c0, 0xffe;\n"
        "mad.lo.u32 t, t, 4, 0x200000;\nmov.b64 d0, {t, h};\nand.b32 t, c1, 0xffe;\nmad.lo.u32 t, t, 4, 0x200000;\nmov.b64 d1, {t, h};\nand.b32 t, c2, 0xffe;\n"
        "mad.lo.u32 t, t, 4, 0x200000;\nmov.b64 d2, {t, h};\nand.b32 t, c3, 0xffe;\nmad.lo.u32 t, t, 4, 0x200000;\nmov.b64 d3, {t, h};\nand.b32 t, c4, 0xffe;\n"
        "mad.lo.u32 t, t, 4, 0x200000;\nmov.b64 d4, {t, h};\nand.b32 t, c5, 0xffe;\nmad.lo.u32 t, t, 4, 0x200000;\nmov.b64 d5, {t, h};\nand.b32 t, c6, 0xffe;\n"
        "mad.lo.u32 t, t, 4, 0x200000;\nmov.b64 d6, {t, h};\nand.b32 t, c7, 0xffe;\nmad.lo.u32 t, t, 4, 0x200000;\nmov.b64 d7, {t, h};\nand.b32 t, c8, 0xffe;\n"
        "mad.lo.u32 t, t, 4, 0x200000;\nmov.b64 d8, {t, h};\nand.b32 t, c9, 0xffe;\nmad.lo.u32 t, t, 4, 0x200000;\nmov.b64 d9, {t, h};\nand.b32 t, c10, 0xffe;\n"
        "mad.lo.u32 t, t, 4, 0x200000;\nmov.b64 d10, {t, h};\nand.b32 t, c11, 0xffe;\nmad.lo.u32 t, t, 4, 0x200000;\nmov.b64 d11, {t, h};\n"
        "and.b32 t, c12, 0xffe;\nmad.lo.u32 t, t, 4, 0x200000;\nmov.b64 d12, {t, h};\nand.b32 t, c13, 0xffe;\nmad.lo.u32 t, t, 4, 0x200000;\n"
        "mov.b64 d13, {t, h};\nand.b32 t, c14, 0xffe;\nmad.lo.u32 t, t, 4, 0x200000;\nmov.b64 d14, {t, h};\nand.b32 t, c15, 0xffe;\n"
        "mad.lo.u32 t, t, 4, 0x200000;\nmov.b64 d15, {t, h};\nwgmma.fence.sync.aligned;\n"
        "wgmma.mma_async.sync.aligned.m64n32k16.f32.bf16.bf16 {o0,o1,o2,o3,o4,o5,o6,o7,o8,o9,o10,o11,o12,o13,o14,o15}, {b0,b1,b2,b3}, d0, p0, 1, 1, 1;\n"
        "wgmma.mma_async.sync.aligned.m64n32k16.f32.bf16.bf16 {o16,o17,o18,o19,o20,o21,o22,o23,o24,o25,o26,o27,o28,o29,o30,o31}, {b0,b1,b2,b3}, d8, p0, 1, 1, 1;\n"
        "wgmma.mma_async.sync.aligned.m64n32k16.f32.bf16.bf16 {o0,o1,o2,o3,o4,o5,o6,o7,o8,o9,o10,o11,o12,o13,o14,o15}, {b4,b5,b6,b7}, d1, p1, 1, 1, 1;\n"
        "wgmma.mma_async.sync.aligned.m64n32k16.f32.bf16.bf16 {o16,o17,o18,o19,o20,o21,o22,o23,o24,o25,o26,o27,o28,o29,o30,o31}, {b4,b5,b6,b7}, d9, p1, 1, 1, 1;\n"
        "wgmma.mma_async.sync.aligned.m64n32k16.f32.bf16.bf16 {o0,o1,o2,o3,o4,o5,o6,o7,o8,o9,o10,o11,o12,o13,o14,o15}, {b8,b9,b10,b11}, d2, p1, 1, 1, 1;\n"
        "wgmma.mma_async.sync.aligned.m64n32k16.f32.bf16.bf16 {o16,o17,o18,o19,o20,o21,o22,o23,o24,o25,o26,o27,o28,o29,o30,o31}, {b8,b9,b10,b11}, d10, p1, 1, 1, 1;\n"
        "wgmma.mma_async.sync.aligned.m64n32k16.f32.bf16.bf16 {o0,o1,o2,o3,o4,o5,o6,o7,o8,o9,o10,o11,o12,o13,o14,o15}, {b12,b13,b14,b15}, d3, p1, 1, 1, 1;\n"
        "wgmma.mma_async.sync.aligned.m64n32k16.f32.bf16.bf16 {o16,o17,o18,o19,o20,o21,o22,o23,o24,o25,o26,o27,o28,o29,o30,o31}, {b12,b13,b14,b15}, d11, p1, 1, 1, 1;\n"
        "wgmma.mma_async.sync.aligned.m64n32k16.f32.bf16.bf16 {o0,o1,o2,o3,o4,o5,o6,o7,o8,o9,o10,o11,o12,o13,o14,o15}, {b16,b17,b18,b19}, d4, p1, 1, 1, 1;\n"
        "wgmma.mma_async.sync.aligned.m64n32k16.f32.bf16.bf16 {o16,o17,o18,o19,o20,o21,o22,o23,o24,o25,o26,o27,o28,o29,o30,o31}, {b16,b17,b18,b19}, d12, p1, 1, 1, 1;\n"
        "wgmma.mma_async.sync.aligned.m64n32k16.f32.bf16.bf16 {o0,o1,o2,o3,o4,o5,o6,o7,o8,o9,o10,o11,o12,o13,o14,o15}, {b20,b21,b22,b23}, d5, p1, 1, 1, 1;\n"
        "wgmma.mma_async.sync.aligned.m64n32k16.f32.bf16.bf16 {o16,o17,o18,o19,o20,o21,o22,o23,o24,o25,o26,o27,o28,o29,o30,o31}, {b20,b21,b22,b23}, d13, p1, 1, 1, 1;\n"
        "wgmma.mma_async.sync.aligned.m64n32k16.f32.bf16.bf16 {o0,o1,o2,o3,o4,o5,o6,o7,o8,o9,o10,o11,o12,o13,o14,o15}, {b24,b25,b26,b27}, d6, p1, 1, 1, 1;\n"
        "wgmma.mma_async.sync.aligned.m64n32k16.f32.bf16.bf16 {o16,o17,o18,o19,o20,o21,o22,o23,o24,o25,o26,o27,o28,o29,o30,o31}, {b24,b25,b26,b27}, d14, p1, 1, 1, 1;\n"
        "wgmma.mma_async.sync.aligned.m64n32k16.f32.bf16.bf16 {o0,o1,o2,o3,o4,o5,o6,o7,o8,o9,o10,o11,o12,o13,o14,o15}, {b28,b29,b30,b31}, d7, p1, 1, 1, 1;\n"
        "wgmma.mma_async.sync.aligned.m64n32k16.f32.bf16.bf16 {o16,o17,o18,o19,o20,o21,o22,o23,o24,o25,o26,o27,o28,o29,o30,o31}, {b28,b29,b30,b31}, d15, p1, 1, 1, 1;\n"
        "wgmma.commit_group.sync.aligned;\n@nv bra.uni END;\n@s0 st.global.v4.b32 [%49+128], {k0,k1,k2,k3};\n@s1 st.global.v4.b32 [%50+128], {k4,k5,k6,k7};\n"
        "@s0 st.global.v4.b32 [%49+192], {k8,k9,k10,k11};\n@s1 st.global.v4.b32 [%50+192], {k12,k13,k14,k15};\n@nv bra.uni END;\n"
        "wgmma.wait_group.sync.aligned 0;\ncvt.rn.bf16x2.f32 k0, o1, o0;\ncvt.rn.bf16x2.f32 k1, o5, o4;\ncvt.rn.bf16x2.f32 k2, o9, o8;\n"
        "cvt.rn.bf16x2.f32 k3, o13, o12;\ncvt.rn.bf16x2.f32 k8, o17, o16;\ncvt.rn.bf16x2.f32 k9, o21, o20;\ncvt.rn.bf16x2.f32 k10, o25, o24;\n"
        "cvt.rn.bf16x2.f32 k11, o29, o28;\nld.volatile.shared.v4.b32 {c0,c1,c2,c3}, [%48+32];\nld.volatile.shared.v4.b32 {c4,c5,c6,c7}, [%48+8224];\n"
        "ld.volatile.shared.v4.b32 {c8,c9,c10,c11}, [%48+48];\nld.volatile.shared.v4.b32 {c12,c13,c14,c15}, [%48+8240];\nand.b32 t, c0, 0xffe;\n"
        "mad.lo.u32 t, t, 4, 0x200000;\nmov.b64 d0, {t, h};\nand.b32 t, c1, 0xffe;\nmad.lo.u32 t, t, 4, 0x200000;\nmov.b64 d1, {t, h};\nand.b32 t, c2, 0xffe;\n"
        "mad.lo.u32 t, t, 4, 0x200000;\nmov.b64 d2, {t, h};\nand.b32 t, c3, 0xffe;\nmad.lo.u32 t, t, 4, 0x200000;\nmov.b64 d3, {t, h};\nand.b32 t, c4, 0xffe;\n"
        "mad.lo.u32 t, t, 4, 0x200000;\nmov.b64 d4, {t, h};\nand.b32 t, c5, 0xffe;\nmad.lo.u32 t, t, 4, 0x200000;\nmov.b64 d5, {t, h};\nand.b32 t, c6, 0xffe;\n"
        "mad.lo.u32 t, t, 4, 0x200000;\nmov.b64 d6, {t, h};\nand.b32 t, c7, 0xffe;\nmad.lo.u32 t, t, 4, 0x200000;\nmov.b64 d7, {t, h};\nand.b32 t, c8, 0xffe;\n"
        "mad.lo.u32 t, t, 4, 0x200000;\nmov.b64 d8, {t, h};\nand.b32 t, c9, 0xffe;\nmad.lo.u32 t, t, 4, 0x200000;\nmov.b64 d9, {t, h};\nand.b32 t, c10, 0xffe;\n"
        "mad.lo.u32 t, t, 4, 0x200000;\nmov.b64 d10, {t, h};\nand.b32 t, c11, 0xffe;\nmad.lo.u32 t, t, 4, 0x200000;\nmov.b64 d11, {t, h};\n"
        "and.b32 t, c12, 0xffe;\nmad.lo.u32 t, t, 4, 0x200000;\nmov.b64 d12, {t, h};\nand.b32 t, c13, 0xffe;\nmad.lo.u32 t, t, 4, 0x200000;\n"
        "mov.b64 d13, {t, h};\nand.b32 t, c14, 0xffe;\nmad.lo.u32 t, t, 4, 0x200000;\nmov.b64 d14, {t, h};\nand.b32 t, c15, 0xffe;\n"
        "mad.lo.u32 t, t, 4, 0x200000;\nmov.b64 d15, {t, h};\nwgmma.fence.sync.aligned;\n"
        "wgmma.mma_async.sync.aligned.m64n32k16.f32.bf16.bf16 {o0,o1,o2,o3,o4,o5,o6,o7,o8,o9,o10,o11,o12,o13,o14,o15}, {b0,b1,b2,b3}, d0, p0, 1, 1, 1;\n"
        "wgmma.mma_async.sync.aligned.m64n32k16.f32.bf16.bf16 {o16,o17,o18,o19,o20,o21,o22,o23,o24,o25,o26,o27,o28,o29,o30,o31}, {b0,b1,b2,b3}, d8, p0, 1, 1, 1;\n"
        "wgmma.mma_async.sync.aligned.m64n32k16.f32.bf16.bf16 {o0,o1,o2,o3,o4,o5,o6,o7,o8,o9,o10,o11,o12,o13,o14,o15}, {b4,b5,b6,b7}, d1, p1, 1, 1, 1;\n"
        "wgmma.mma_async.sync.aligned.m64n32k16.f32.bf16.bf16 {o16,o17,o18,o19,o20,o21,o22,o23,o24,o25,o26,o27,o28,o29,o30,o31}, {b4,b5,b6,b7}, d9, p1, 1, 1, 1;\n"
        "wgmma.mma_async.sync.aligned.m64n32k16.f32.bf16.bf16 {o0,o1,o2,o3,o4,o5,o6,o7,o8,o9,o10,o11,o12,o13,o14,o15}, {b8,b9,b10,b11}, d2, p1, 1, 1, 1;\n"
        "wgmma.mma_async.sync.aligned.m64n32k16.f32.bf16.bf16 {o16,o17,o18,o19,o20,o21,o22,o23,o24,o25,o26,o27,o28,o29,o30,o31}, {b8,b9,b10,b11}, d10, p1, 1, 1, 1;\n"
        "wgmma.mma_async.sync.aligned.m64n32k16.f32.bf16.bf16 {o0,o1,o2,o3,o4,o5,o6,o7,o8,o9,o10,o11,o12,o13,o14,o15}, {b12,b13,b14,b15}, d3, p1, 1, 1, 1;\n"
        "wgmma.mma_async.sync.aligned.m64n32k16.f32.bf16.bf16 {o16,o17,o18,o19,o20,o21,o22,o23,o24,o25,o26,o27,o28,o29,o30,o31}, {b12,b13,b14,b15}, d11, p1, 1, 1, 1;\n"
        "wgmma.mma_async.sync.aligned.m64n32k16.f32.bf16.bf16 {o0,o1,o2,o3,o4,o5,o6,o7,o8,o9,o10,o11,o12,o13,o14,o15}, {b16,b17,b18,b19}, d4, p1, 1, 1, 1;\n"
        "wgmma.mma_async.sync.aligned.m64n32k16.f32.bf16.bf16 {o16,o17,o18,o19,o20,o21,o22,o23,o24,o25,o26,o27,o28,o29,o30,o31}, {b16,b17,b18,b19}, d12, p1, 1, 1, 1;\n"
        "wgmma.mma_async.sync.aligned.m64n32k16.f32.bf16.bf16 {o0,o1,o2,o3,o4,o5,o6,o7,o8,o9,o10,o11,o12,o13,o14,o15}, {b20,b21,b22,b23}, d5, p1, 1, 1, 1;\n"
        "wgmma.mma_async.sync.aligned.m64n32k16.f32.bf16.bf16 {o16,o17,o18,o19,o20,o21,o22,o23,o24,o25,o26,o27,o28,o29,o30,o31}, {b20,b21,b22,b23}, d13, p1, 1, 1, 1;\n"
        "wgmma.mma_async.sync.aligned.m64n32k16.f32.bf16.bf16 {o0,o1,o2,o3,o4,o5,o6,o7,o8,o9,o10,o11,o12,o13,o14,o15}, {b24,b25,b26,b27}, d6, p1, 1, 1, 1;\n"
        "wgmma.mma_async.sync.aligned.m64n32k16.f32.bf16.bf16 {o16,o17,o18,o19,o20,o21,o22,o23,o24,o25,o26,o27,o28,o29,o30,o31}, {b24,b25,b26,b27}, d14, p1, 1, 1, 1;\n"
        "wgmma.mma_async.sync.aligned.m64n32k16.f32.bf16.bf16 {o0,o1,o2,o3,o4,o5,o6,o7,o8,o9,o10,o11,o12,o13,o14,o15}, {b28,b29,b30,b31}, d7, p1, 1, 1, 1;\n"
        "wgmma.mma_async.sync.aligned.m64n32k16.f32.bf16.bf16 {o16,o17,o18,o19,o20,o21,o22,o23,o24,o25,o26,o27,o28,o29,o30,o31}, {b28,b29,b30,b31}, d15, p1, 1, 1, 1;\n"
        "wgmma.commit_group.sync.aligned;\n@nv bra.uni END;\n@s2 st.global.v4.b32 [%51+0], {k0,k1,k2,k3};\n@s2 st.global.v4.b32 [%51+64], {k8,k9,k10,k11};\n"
        "@nv bra.uni END;\nwgmma.wait_group.sync.aligned 0;\ncvt.rn.bf16x2.f32 k0, o1, o0;\ncvt.rn.bf16x2.f32 k1, o5, o4;\ncvt.rn.bf16x2.f32 k2, o9, o8;\n"
        "cvt.rn.bf16x2.f32 k3, o13, o12;\ncvt.rn.bf16x2.f32 k8, o17, o16;\ncvt.rn.bf16x2.f32 k9, o21, o20;\ncvt.rn.bf16x2.f32 k10, o25, o24;\n"
        "cvt.rn.bf16x2.f32 k11, o29, o28;\n@s2 st.global.v4.b32 [%51+128], {k0,k1,k2,k3};\n@s2 st.global.v4.b32 [%51+192], {k8,k9,k10,k11};\n"
        "END:\n}\n"
        ::"r"(pk[0]), "r"(pk[1]), "r"(pk[2]), "r"(pk[3]), "r"(pk[4]), "r"(pk[5]), "r"(pk[6]), "r"(pk[7]), "r"(pk[8]), "r"(pk[9]), "r"(pk[10]),
          "r"(pk[11]), "r"(pk[12]), "r"(pk[13]), "r"(pk[14]), "r"(pk[15]), "r"(pk[16]), "r"(pk[17]), "r"(pk[18]), "r"(pk[19]), "r"(pk[20]),
          "r"(pk[21]), "r"(pk[22]), "r"(pk[23]), "r"(pk[24]), "r"(pk[25]), "r"(pk[26]), "r"(pk[27]), "r"(pk[28]), "r"(pk[29]), "r"(pk[30]),
          "r"(pk[31]), "r"(pk[32]), "r"(pk[33]), "r"(pk[34]), "r"(pk[35]), "r"(pk[36]), "r"(pk[37]), "r"(pk[38]), "r"(pk[39]), "r"(pk[40]),
          "r"(pk[41]), "r"(pk[42]), "r"(pk[43]), "r"(pk[44]), "r"(pk[45]), "r"(pk[46]), "r"(pk[47]), "r"(ra), "l"(p[0]), "l"(p[1]), "l"(p[2]),
          "r"(v[0]), "r"(v[1]), "r"(v[2]), "r"(ba)
        : "memory");
}
__device__ __forceinline__ int cta_id() {
    int v;
    asm volatile("mov.u32 %0, %ctaid.x;" : "=r"(v));
    return v;
}
__device__ __forceinline__ int thread_id() {
    int v;
    asm volatile("mov.u32 %0, %tid.x;" : "=r"(v));
    return v;
}

__device__ __forceinline__ void slow_edge(int ee, int s, float* accn, const __nv_bfloat16* __restrict__ x,
                                          const __nv_bfloat16* __restrict__ sh, const __nv_bfloat16* __restrict__ ea,
                                          const __nv_bfloat16* __restrict__ cg, const __nv_bfloat16* __restrict__ wr,
                                          int lane) {
    float rwv[4] = {0.f, 0.f, 0.f, 0.f};
#pragma unroll 4
    for (int d = 0; d < 16; d++) {
        const float a = __bfloat162float(ea[(size_t)ee * 16 + d]);
        const uint2 wv = *(const uint2*)(wr + d * 128 + lane * 4);
        rwv[0] += a * __uint_as_float(wv.x << 16);
        rwv[1] += a * __uint_as_float(wv.x & 0xffff0000u);
        rwv[2] += a * __uint_as_float(wv.y << 16);
        rwv[3] += a * __uint_as_float(wv.y & 0xffff0000u);
    }
    float A = 0.f;
#pragma unroll
    for (int v = 0; v < 4; v++)
        A += __bfloat162float(cg[((lane >> 2) & 3) * 16 + v * 4 + (lane & 3)]) * __bfloat162float(sh[(size_t)ee * 4 + v]);
    float m[4][4];
#pragma unroll
    for (int w = 0; w < 4; w++)
#pragma unroll
        for (int j = 0; j < 4; j++) m[w][j] = 0.f;
#pragma unroll
    for (int u = 0; u < 4; u++) {
        const uint2 xv = *(const uint2*)(x + (size_t)s * 512 + u * 128 + lane * 4);
        const float x0 = __uint_as_float(xv.x << 16), x1 = __uint_as_float(xv.x & 0xffff0000u);
        const float x2 = __uint_as_float(xv.y << 16), x3 = __uint_as_float(xv.y & 0xffff0000u);
#pragma unroll
        for (int w = 0; w < 4; w++) {
            const float a = __shfl_sync(0xffffffffu, A, u * 4 + w);
            m[w][0] += a * x0;
            m[w][1] += a * x1;
            m[w][2] += a * x2;
            m[w][3] += a * x3;
        }
    }
#pragma unroll
    for (int w = 0; w < 4; w++)
#pragma unroll
        for (int j = 0; j < 4; j++) atomicAdd(accn + w * 128 + lane * 4 + j, m[w][j] * rwv[j]);
}

__device__ __forceinline__ void slow_out(const float* accn, const __nv_bfloat16* __restrict__ wout,
                                         __nv_bfloat16* __restrict__ outn, int lane) {
    float o[4][4];
#pragma unroll
    for (int w = 0; w < 4; w++)
#pragma unroll
        for (int j = 0; j < 4; j++) o[w][j] = 0.f;
#pragma unroll 2
    for (int c = 0; c < 128; c++) {
        const uint2 wv = *(const uint2*)(wout + c * 128 + lane * 4);
        const float w0 = __uint_as_float(wv.x << 16), w1 = __uint_as_float(wv.x & 0xffff0000u);
        const float w2 = __uint_as_float(wv.y << 16), w3 = __uint_as_float(wv.y & 0xffff0000u);
#pragma unroll
        for (int w = 0; w < 4; w++) {
            const float a = __bfloat162float(__float2bfloat16(accn[w * 128 + c]));
            o[w][0] += a * w0;
            o[w][1] += a * w1;
            o[w][2] += a * w2;
            o[w][3] += a * w3;
        }
    }
#pragma unroll
    for (int w = 0; w < 4; w++)
        *(uint2*)(outn + w * 128 + lane * 4) = make_uint2(pack_bf16(o[w][0], o[w][1]), pack_bf16(o[w][2], o[w][3]));
}

__device__ __forceinline__ void consume4(uint32_t (&pk)[64], const uint32_t (&w)[36], uint32_t olp, uint32_t xa, uint32_t ln,
                                      uint32_t lc, uint32_t linc, uint32_t lt, const __nv_bfloat16* ea, const __nv_bfloat16* sh, const void* wf) {
    ea += lt * 4, sh += lt & 2;
    asm volatile(
        "{\n.reg .pred p, q, psw, prdy, ps1, ps2, ps3, pz;\n.reg .f32 d<32>, fz;\n"
        ".reg .b32 h<64>, x<32>, y<32>, ra<8>, rb<8>, bA0, bA1, bB0, bB1, c0, c1, c2, c3, e0, e1, s0, kept;\n"
        ".reg .b32 olp, v, vB, m, id, ida, bar, xb, pos, t0, t1, t2, t3, n, z<16>;\n.reg .b16 lo, hi, i16;\n.reg .b64 pa, pb;\nmov.f32 fz, 0f00000000;\n"
        "mov.b32 h0, 0;\nmov.b32 h1, 0;\nmov.b32 h2, 0;\nmov.b32 h3, 0;\nmov.b32 h4, 0;\nmov.b32 h5, 0;\nmov.b32 h6, 0;\nmov.b32 h7, 0;\nmov.b32 h8, 0;\n"
        "mov.b32 h9, 0;\nmov.b32 h10, 0;\nmov.b32 h11, 0;\nmov.b32 h12, 0;\nmov.b32 h13, 0;\nmov.b32 h14, 0;\nmov.b32 h15, 0;\nmov.b32 h16, 0;\nmov.b32 h17, 0;\n"
        "mov.b32 h18, 0;\nmov.b32 h19, 0;\nmov.b32 h20, 0;\nmov.b32 h21, 0;\nmov.b32 h22, 0;\nmov.b32 h23, 0;\nmov.b32 h24, 0;\nmov.b32 h25, 0;\n"
        "mov.b32 h26, 0;\nmov.b32 h27, 0;\nmov.b32 h28, 0;\nmov.b32 h29, 0;\nmov.b32 h30, 0;\nmov.b32 h31, 0;\nmov.b32 h32, 0;\nmov.b32 h33, 0;\n"
        "mov.b32 h34, 0;\nmov.b32 h35, 0;\nmov.b32 h36, 0;\nmov.b32 h37, 0;\nmov.b32 h38, 0;\nmov.b32 h39, 0;\nmov.b32 h40, 0;\nmov.b32 h41, 0;\n"
        "mov.b32 h42, 0;\nmov.b32 h43, 0;\nmov.b32 h44, 0;\nmov.b32 h45, 0;\nmov.b32 h46, 0;\nmov.b32 h47, 0;\nmov.b32 h48, 0;\nmov.b32 h49, 0;\n"
        "mov.b32 h50, 0;\nmov.b32 h51, 0;\nmov.b32 h52, 0;\nmov.b32 h53, 0;\nmov.b32 h54, 0;\nmov.b32 h55, 0;\nmov.b32 h56, 0;\nmov.b32 h57, 0;\n"
        "mov.b32 h58, 0;\nmov.b32 h59, 0;\nmov.b32 h60, 0;\nmov.b32 h61, 0;\nmov.b32 h62, 0;\nmov.b32 h63, 0;\nmov.b32 olp, %64;\nand.b32 t0, %66, 32;\n"
        "setp.ne.u32 psw, t0, 0;\nsetp.eq.u32 pz, %64, 0;\nvote.sync.any.pred pz, pz, 0xffffffff;\nld.shared.b32 t0, [olp];\nadd.u32 olp, olp, 8;\n"
        "lop3.b32 t1, t0, %66, 0x3ff0, 0xe4;\nld.shared.b32 t1, [t1+%73];\nlop3.b32 kept, t1, t0, 0x1ffc, 0xe4;\nlop3.b32 t2, t1, %67, 3, 0x80;\n"
        "setp.ne.u32 q, t2, 0;\nshr.u32 t2, t1, 13;\nmad.wide.u32 pa, t2, 32, %70;\nmad.wide.u32 pb, t2, 8, %71;\nmov.b32 s0, 0;\n"
        "ld.global.cg.v2.b32 {e0,e1}, [pa];\n@q ld.global.cg.b32 s0, [pb];\nsetp.ne.u64 p, %72, 0;\n@p fence.proxy.async.global;\n"
        "@p red.release.gpu.global.add.u32 [%72+12], 1;\nbar.warp.sync 0xffffffff;\nshfl.sync.idx.b32 v, kept, %67, 0x1f, 0xffffffff;\nor.b32 t3, %67, 4;\n"
        "shfl.sync.idx.b32 vB, kept, t3, 0x1f, 0xffffffff;\n"
        "RW:\nmma.sync.aligned.m16n8k8.row.col.f32.bf16.bf16.f32 {d0,d1,d2,d3}, {%109,%110}, {s0}, {fz,fz,fz,fz};\n"
        "mma.sync.aligned.m16n8k8.row.col.f32.bf16.bf16.f32 {d4,d5,d6,d7}, {%111,%112}, {s0}, {fz,fz,fz,fz};\ncvt.rn.bf16x2.f32 c0, d2, d0;\n"
        "cvt.rn.bf16x2.f32 c1, d3, d1;\ncvt.rn.bf16x2.f32 c2, d6, d4;\ncvt.rn.bf16x2.f32 c3, d7, d5;\nselp.b32 bA0, c2, c0, psw;\nselp.b32 bA1, c0, c2, psw;\n"
        "selp.b32 bB0, c3, c1, psw;\nselp.b32 bB1, c1, c3, psw;\n"
        "mma.sync.aligned.m16n8k16.row.col.f32.bf16.bf16.f32 {d0,d1,d2,d3}, {%77,%78,%79,%80}, {e0,e1}, {fz,fz,fz,fz};\ncvt.rn.bf16x2.f32 ra0, d2, d0;\n"
        "cvt.rn.bf16x2.f32 rb0, d3, d1;\nmma.sync.aligned.m16n8k16.row.col.f32.bf16.bf16.f32 {d4,d5,d6,d7}, {%81,%82,%83,%84}, {e0,e1}, {fz,fz,fz,fz};\n"
        "cvt.rn.bf16x2.f32 ra1, d6, d4;\ncvt.rn.bf16x2.f32 rb1, d7, d5;\n"
        "mma.sync.aligned.m16n8k16.row.col.f32.bf16.bf16.f32 {d8,d9,d10,d11}, {%85,%86,%87,%88}, {e0,e1}, {fz,fz,fz,fz};\ncvt.rn.bf16x2.f32 ra2, d10, d8;\n"
        "cvt.rn.bf16x2.f32 rb2, d11, d9;\nmma.sync.aligned.m16n8k16.row.col.f32.bf16.bf16.f32 {d12,d13,d14,d15}, {%89,%90,%91,%92}, {e0,e1}, {fz,fz,fz,fz};\n"
        "cvt.rn.bf16x2.f32 ra3, d14, d12;\ncvt.rn.bf16x2.f32 rb3, d15, d13;\n"
        "mma.sync.aligned.m16n8k16.row.col.f32.bf16.bf16.f32 {d16,d17,d18,d19}, {%93,%94,%95,%96}, {e0,e1}, {fz,fz,fz,fz};\ncvt.rn.bf16x2.f32 ra4, d18, d16;\n"
        "cvt.rn.bf16x2.f32 rb4, d19, d17;\nmma.sync.aligned.m16n8k16.row.col.f32.bf16.bf16.f32 {d20,d21,d22,d23}, {%97,%98,%99,%100}, {e0,e1}, {fz,fz,fz,fz};\n"
        "cvt.rn.bf16x2.f32 ra5, d22, d20;\ncvt.rn.bf16x2.f32 rb5, d23, d21;\n"
        "mma.sync.aligned.m16n8k16.row.col.f32.bf16.bf16.f32 {d24,d25,d26,d27}, {%101,%102,%103,%104}, {e0,e1}, {fz,fz,fz,fz};\n"
        "cvt.rn.bf16x2.f32 ra6, d26, d24;\ncvt.rn.bf16x2.f32 rb6, d27, d25;\n"
        "mma.sync.aligned.m16n8k16.row.col.f32.bf16.bf16.f32 {d28,d29,d30,d31}, {%105,%106,%107,%108}, {e0,e1}, {fz,fz,fz,fz};\n"
        "cvt.rn.bf16x2.f32 ra7, d30, d28;\ncvt.rn.bf16x2.f32 rb7, d31, d29;\nld.shared.b32 t0, [olp];\nadd.u32 olp, olp, 8;\n"
        "lop3.b32 t1, t0, %66, 0x3ff0, 0xe4;\nld.shared.b32 t1, [t1+%73];\nlop3.b32 kept, t1, t0, 0x1ffc, 0xe4;\nlop3.b32 t2, t1, %67, 3, 0x80;\n"
        "setp.ne.u32 q, t2, 0;\nshr.u32 t2, t1, 13;\nmad.wide.u32 pa, t2, 32, %70;\nmad.wide.u32 pb, t2, 8, %71;\nmov.b32 s0, 0;\n"
        "ld.global.cg.v2.b32 {e0,e1}, [pa];\n@q ld.global.cg.b32 s0, [pb];\nshr.u32 bar, v, 1;\nand.b32 bar, bar, 0xff8;\n"
        "mbarrier.test_wait.parity.shared.b64 p, [bar+%75], 0;\nlop3.b32 ida, v, %67, 0x1fff, 0xe4;\nld.volatile.shared.u16 id, [ida+%74];\n"
        "vote.sync.all.pred prdy, p, 0xffffffff;\n@!prdy bra.uni WA;\n"
        "HA:\nmad.lo.u32 xb, id, 64, %65;\ncvt.u16.u32 i16, id;\natom.shared.add.u32 pos, [%66+%76], %68;\n"
        "ldmatrix.sync.aligned.m8n8.x4.trans.shared.b16 {x0,x1,x2,x3}, [xb];\nldmatrix.sync.aligned.m8n8.x4.trans.shared.b16 {x24,x25,x26,x27}, [xb+512];\n"
        "xor.b32 t1, xb, 32;\nldmatrix.sync.aligned.m8n8.x4.trans.shared.b16 {x4,x5,x6,x7}, [t1];\n"
        "ldmatrix.sync.aligned.m8n8.x4.trans.shared.b16 {x28,x29,x30,x31}, [t1+512];\nxor.b32 t1, xb, 64;\n"
        "ldmatrix.sync.aligned.m8n8.x4.trans.shared.b16 {x8,x9,x10,x11}, [t1];\nldmatrix.sync.aligned.m8n8.x4.trans.shared.b16 {x16,x17,x18,x19}, [t1+512];\n"
        "xor.b32 t1, xb, 96;\nldmatrix.sync.aligned.m8n8.x4.trans.shared.b16 {x12,x13,x14,x15}, [t1];\n"
        "ldmatrix.sync.aligned.m8n8.x4.trans.shared.b16 {x20,x21,x22,x23}, [t1+512];\nst.volatile.shared.u16 [pos], i16;\nand.b32 t0, v, 268435456;\n"
        "setp.ne.u32 ps1, t0, 0;\nvote.sync.any.pred ps1, ps1, 0xffffffff;\nand.b32 t0, v, 536870912;\nsetp.ne.u32 ps2, t0, 0;\n"
        "vote.sync.any.pred ps2, ps2, 0xffffffff;\nmov.b32 v, vB;\nshr.u32 bar, v, 1;\nand.b32 bar, bar, 0xff8;\n"
        "mbarrier.test_wait.parity.shared.b64 p, [bar+%75], 0;\nlop3.b32 ida, v, %67, 0x1fff, 0xe4;\nld.volatile.shared.u16 id, [ida+%74];\n"
        "vote.sync.all.pred prdy, p, 0xffffffff;\nmov.b32 {lo, hi}, ra0;\nmov.b32 t2, {lo, lo};\nmul.rn.bf16x2 y0, x0, t2;\nmul.rn.bf16x2 y2, x2, t2;\n"
        "mov.b32 t2, {hi, hi};\nmul.rn.bf16x2 y1, x1, t2;\nmul.rn.bf16x2 y3, x3, t2;\n"
        "mma.sync.aligned.m16n8k16.row.col.f32.bf16.bf16.f32 {d0,d1,d2,d3}, {y0,y1,y2,y3}, {bA0,bA1}, {fz,fz,fz,fz};\ncvt.rn.bf16x2.f32 z0, d1, d0;\n"
        "cvt.rn.bf16x2.f32 z1, d3, d2;\nmov.b32 {lo, hi}, ra6;\nmov.b32 t2, {lo, lo};\nmul.rn.bf16x2 y24, x24, t2;\nmul.rn.bf16x2 y26, x26, t2;\n"
        "mov.b32 t2, {hi, hi};\nmul.rn.bf16x2 y25, x25, t2;\nmul.rn.bf16x2 y27, x27, t2;\n"
        "mma.sync.aligned.m16n8k16.row.col.f32.bf16.bf16.f32 {d24,d25,d26,d27}, {y24,y25,y26,y27}, {bA0,bA1}, {fz,fz,fz,fz};\ncvt.rn.bf16x2.f32 z12, d25, d24;\n"
        "cvt.rn.bf16x2.f32 z13, d27, d26;\nmov.b32 {lo, hi}, ra1;\nmov.b32 t2, {lo, lo};\nmul.rn.bf16x2 y4, x4, t2;\nmul.rn.bf16x2 y6, x6, t2;\n"
        "mov.b32 t2, {hi, hi};\nmul.rn.bf16x2 y5, x5, t2;\nmul.rn.bf16x2 y7, x7, t2;\n"
        "mma.sync.aligned.m16n8k16.row.col.f32.bf16.bf16.f32 {d4,d5,d6,d7}, {y4,y5,y6,y7}, {bA0,bA1}, {fz,fz,fz,fz};\ncvt.rn.bf16x2.f32 z2, d5, d4;\n"
        "cvt.rn.bf16x2.f32 z3, d7, d6;\nmov.b32 {lo, hi}, ra7;\nmov.b32 t2, {lo, lo};\nmul.rn.bf16x2 y28, x28, t2;\nmul.rn.bf16x2 y30, x30, t2;\n"
        "mov.b32 t2, {hi, hi};\nmul.rn.bf16x2 y29, x29, t2;\nmul.rn.bf16x2 y31, x31, t2;\n"
        "mma.sync.aligned.m16n8k16.row.col.f32.bf16.bf16.f32 {d28,d29,d30,d31}, {y28,y29,y30,y31}, {bA0,bA1}, {fz,fz,fz,fz};\ncvt.rn.bf16x2.f32 z14, d29, d28;\n"
        "cvt.rn.bf16x2.f32 z15, d31, d30;\nmov.b32 {lo, hi}, ra2;\nmov.b32 t2, {lo, lo};\nmul.rn.bf16x2 y8, x8, t2;\nmul.rn.bf16x2 y10, x10, t2;\n"
        "mov.b32 t2, {hi, hi};\nmul.rn.bf16x2 y9, x9, t2;\nmul.rn.bf16x2 y11, x11, t2;\n"
        "mma.sync.aligned.m16n8k16.row.col.f32.bf16.bf16.f32 {d8,d9,d10,d11}, {y8,y9,y10,y11}, {bA0,bA1}, {fz,fz,fz,fz};\ncvt.rn.bf16x2.f32 z4, d9, d8;\n"
        "cvt.rn.bf16x2.f32 z5, d11, d10;\nmov.b32 {lo, hi}, ra4;\nmov.b32 t2, {lo, lo};\nmul.rn.bf16x2 y16, x16, t2;\nmul.rn.bf16x2 y18, x18, t2;\n"
        "mov.b32 t2, {hi, hi};\nmul.rn.bf16x2 y17, x17, t2;\nmul.rn.bf16x2 y19, x19, t2;\n"
        "mma.sync.aligned.m16n8k16.row.col.f32.bf16.bf16.f32 {d16,d17,d18,d19}, {y16,y17,y18,y19}, {bA0,bA1}, {fz,fz,fz,fz};\ncvt.rn.bf16x2.f32 z8, d17, d16;\n"
        "cvt.rn.bf16x2.f32 z9, d19, d18;\nmov.b32 {lo, hi}, ra3;\nmov.b32 t2, {lo, lo};\nmul.rn.bf16x2 y12, x12, t2;\nmul.rn.bf16x2 y14, x14, t2;\n"
        "mov.b32 t2, {hi, hi};\nmul.rn.bf16x2 y13, x13, t2;\nmul.rn.bf16x2 y15, x15, t2;\n"
        "mma.sync.aligned.m16n8k16.row.col.f32.bf16.bf16.f32 {d12,d13,d14,d15}, {y12,y13,y14,y15}, {bA0,bA1}, {fz,fz,fz,fz};\ncvt.rn.bf16x2.f32 z6, d13, d12;\n"
        "cvt.rn.bf16x2.f32 z7, d15, d14;\nmov.b32 {lo, hi}, ra5;\nmov.b32 t2, {lo, lo};\nmul.rn.bf16x2 y20, x20, t2;\nmul.rn.bf16x2 y22, x22, t2;\n"
        "mov.b32 t2, {hi, hi};\nmul.rn.bf16x2 y21, x21, t2;\nmul.rn.bf16x2 y23, x23, t2;\n"
        "mma.sync.aligned.m16n8k16.row.col.f32.bf16.bf16.f32 {d20,d21,d22,d23}, {y20,y21,y22,y23}, {bA0,bA1}, {fz,fz,fz,fz};\ncvt.rn.bf16x2.f32 z10, d21, d20;\n"
        "cvt.rn.bf16x2.f32 z11, d23, d22;\n@ps2 bra.uni TA2;\n@ps1 bra.uni TA1;\n"
        "TA0:\nadd.rn.bf16x2 h0, h0, z0;\nadd.rn.bf16x2 h1, h1, z1;\nadd.rn.bf16x2 h2, h2, z2;\nadd.rn.bf16x2 h3, h3, z3;\nadd.rn.bf16x2 h4, h4, z4;\n"
        "add.rn.bf16x2 h5, h5, z5;\nadd.rn.bf16x2 h6, h6, z6;\nadd.rn.bf16x2 h7, h7, z7;\nadd.rn.bf16x2 h8, h8, z8;\nadd.rn.bf16x2 h9, h9, z9;\n"
        "add.rn.bf16x2 h10, h10, z10;\nadd.rn.bf16x2 h11, h11, z11;\nadd.rn.bf16x2 h12, h12, z12;\nadd.rn.bf16x2 h13, h13, z13;\nadd.rn.bf16x2 h14, h14, z14;\n"
        "add.rn.bf16x2 h15, h15, z15;\n@prdy bra.uni HB;\nbra.uni WB;\n"
        "TA1:\nadd.rn.bf16x2 h16, h16, z0;\nadd.rn.bf16x2 h17, h17, z1;\nadd.rn.bf16x2 h18, h18, z2;\nadd.rn.bf16x2 h19, h19, z3;\nadd.rn.bf16x2 h20, h20, z4;\n"
        "add.rn.bf16x2 h21, h21, z5;\nadd.rn.bf16x2 h22, h22, z6;\nadd.rn.bf16x2 h23, h23, z7;\nadd.rn.bf16x2 h24, h24, z8;\nadd.rn.bf16x2 h25, h25, z9;\n"
        "add.rn.bf16x2 h26, h26, z10;\nadd.rn.bf16x2 h27, h27, z11;\nadd.rn.bf16x2 h28, h28, z12;\nadd.rn.bf16x2 h29, h29, z13;\nadd.rn.bf16x2 h30, h30, z14;\n"
        "add.rn.bf16x2 h31, h31, z15;\n@prdy bra.uni HB;\nbra.uni WB;\n"
        "TA2:\n@ps1 bra.uni TA3;\nadd.rn.bf16x2 h32, h32, z0;\nadd.rn.bf16x2 h33, h33, z1;\nadd.rn.bf16x2 h34, h34, z2;\nadd.rn.bf16x2 h35, h35, z3;\n"
        "add.rn.bf16x2 h36, h36, z4;\nadd.rn.bf16x2 h37, h37, z5;\nadd.rn.bf16x2 h38, h38, z6;\nadd.rn.bf16x2 h39, h39, z7;\nadd.rn.bf16x2 h40, h40, z8;\n"
        "add.rn.bf16x2 h41, h41, z9;\nadd.rn.bf16x2 h42, h42, z10;\nadd.rn.bf16x2 h43, h43, z11;\nadd.rn.bf16x2 h44, h44, z12;\nadd.rn.bf16x2 h45, h45, z13;\n"
        "add.rn.bf16x2 h46, h46, z14;\nadd.rn.bf16x2 h47, h47, z15;\n@prdy bra.uni HB;\nbra.uni WB;\n"
        "TA3:\nadd.rn.bf16x2 h48, h48, z0;\nadd.rn.bf16x2 h49, h49, z1;\nadd.rn.bf16x2 h50, h50, z2;\nadd.rn.bf16x2 h51, h51, z3;\nadd.rn.bf16x2 h52, h52, z4;\n"
        "add.rn.bf16x2 h53, h53, z5;\nadd.rn.bf16x2 h54, h54, z6;\nadd.rn.bf16x2 h55, h55, z7;\nadd.rn.bf16x2 h56, h56, z8;\nadd.rn.bf16x2 h57, h57, z9;\n"
        "add.rn.bf16x2 h58, h58, z10;\nadd.rn.bf16x2 h59, h59, z11;\nadd.rn.bf16x2 h60, h60, z12;\nadd.rn.bf16x2 h61, h61, z13;\nadd.rn.bf16x2 h62, h62, z14;\n"
        "add.rn.bf16x2 h63, h63, z15;\n@prdy bra.uni HB;\nbra.uni WB;\n"
        "HB:\nmad.lo.u32 xb, id, 64, %65;\ncvt.u16.u32 i16, id;\natom.shared.add.u32 pos, [%66+%76], %68;\n"
        "ldmatrix.sync.aligned.m8n8.x4.trans.shared.b16 {x0,x1,x2,x3}, [xb];\nldmatrix.sync.aligned.m8n8.x4.trans.shared.b16 {x24,x25,x26,x27}, [xb+512];\n"
        "xor.b32 t1, xb, 32;\nldmatrix.sync.aligned.m8n8.x4.trans.shared.b16 {x4,x5,x6,x7}, [t1];\n"
        "ldmatrix.sync.aligned.m8n8.x4.trans.shared.b16 {x28,x29,x30,x31}, [t1+512];\nxor.b32 t1, xb, 64;\n"
        "ldmatrix.sync.aligned.m8n8.x4.trans.shared.b16 {x8,x9,x10,x11}, [t1];\nldmatrix.sync.aligned.m8n8.x4.trans.shared.b16 {x16,x17,x18,x19}, [t1+512];\n"
        "xor.b32 t1, xb, 96;\nldmatrix.sync.aligned.m8n8.x4.trans.shared.b16 {x12,x13,x14,x15}, [t1];\n"
        "ldmatrix.sync.aligned.m8n8.x4.trans.shared.b16 {x20,x21,x22,x23}, [t1+512];\nst.volatile.shared.u16 [pos], i16;\nand.b32 t0, v, 268435456;\n"
        "setp.ne.u32 ps1, t0, 0;\nvote.sync.any.pred ps1, ps1, 0xffffffff;\nand.b32 t0, v, 536870912;\nsetp.ne.u32 ps2, t0, 0;\n"
        "vote.sync.any.pred ps2, ps2, 0xffffffff;\nshfl.sync.idx.b32 v, kept, %67, 0x1f, 0xffffffff;\nor.b32 t3, %67, 4;\n"
        "shfl.sync.idx.b32 vB, kept, t3, 0x1f, 0xffffffff;\nmov.b32 {lo, hi}, rb0;\nmov.b32 t2, {lo, lo};\nmul.rn.bf16x2 y0, x0, t2;\nmul.rn.bf16x2 y2, x2, t2;\n"
        "mov.b32 t2, {hi, hi};\nmul.rn.bf16x2 y1, x1, t2;\nmul.rn.bf16x2 y3, x3, t2;\n"
        "mma.sync.aligned.m16n8k16.row.col.f32.bf16.bf16.f32 {d0,d1,d2,d3}, {y0,y1,y2,y3}, {bB0,bB1}, {fz,fz,fz,fz};\ncvt.rn.bf16x2.f32 z0, d1, d0;\n"
        "cvt.rn.bf16x2.f32 z1, d3, d2;\nmov.b32 {lo, hi}, rb6;\nmov.b32 t2, {lo, lo};\nmul.rn.bf16x2 y24, x24, t2;\nmul.rn.bf16x2 y26, x26, t2;\n"
        "mov.b32 t2, {hi, hi};\nmul.rn.bf16x2 y25, x25, t2;\nmul.rn.bf16x2 y27, x27, t2;\n"
        "mma.sync.aligned.m16n8k16.row.col.f32.bf16.bf16.f32 {d24,d25,d26,d27}, {y24,y25,y26,y27}, {bB0,bB1}, {fz,fz,fz,fz};\ncvt.rn.bf16x2.f32 z12, d25, d24;\n"
        "cvt.rn.bf16x2.f32 z13, d27, d26;\nmov.b32 {lo, hi}, rb1;\nmov.b32 t2, {lo, lo};\nmul.rn.bf16x2 y4, x4, t2;\nmul.rn.bf16x2 y6, x6, t2;\n"
        "mov.b32 t2, {hi, hi};\nmul.rn.bf16x2 y5, x5, t2;\nmul.rn.bf16x2 y7, x7, t2;\n"
        "mma.sync.aligned.m16n8k16.row.col.f32.bf16.bf16.f32 {d4,d5,d6,d7}, {y4,y5,y6,y7}, {bB0,bB1}, {fz,fz,fz,fz};\ncvt.rn.bf16x2.f32 z2, d5, d4;\n"
        "cvt.rn.bf16x2.f32 z3, d7, d6;\nmov.b32 {lo, hi}, rb7;\nmov.b32 t2, {lo, lo};\nmul.rn.bf16x2 y28, x28, t2;\nmul.rn.bf16x2 y30, x30, t2;\n"
        "mov.b32 t2, {hi, hi};\nmul.rn.bf16x2 y29, x29, t2;\nmul.rn.bf16x2 y31, x31, t2;\n"
        "mma.sync.aligned.m16n8k16.row.col.f32.bf16.bf16.f32 {d28,d29,d30,d31}, {y28,y29,y30,y31}, {bB0,bB1}, {fz,fz,fz,fz};\ncvt.rn.bf16x2.f32 z14, d29, d28;\n"
        "cvt.rn.bf16x2.f32 z15, d31, d30;\nmov.b32 {lo, hi}, rb2;\nmov.b32 t2, {lo, lo};\nmul.rn.bf16x2 y8, x8, t2;\nmul.rn.bf16x2 y10, x10, t2;\n"
        "mov.b32 t2, {hi, hi};\nmul.rn.bf16x2 y9, x9, t2;\nmul.rn.bf16x2 y11, x11, t2;\n"
        "mma.sync.aligned.m16n8k16.row.col.f32.bf16.bf16.f32 {d8,d9,d10,d11}, {y8,y9,y10,y11}, {bB0,bB1}, {fz,fz,fz,fz};\ncvt.rn.bf16x2.f32 z4, d9, d8;\n"
        "cvt.rn.bf16x2.f32 z5, d11, d10;\nmov.b32 {lo, hi}, rb4;\nmov.b32 t2, {lo, lo};\nmul.rn.bf16x2 y16, x16, t2;\nmul.rn.bf16x2 y18, x18, t2;\n"
        "mov.b32 t2, {hi, hi};\nmul.rn.bf16x2 y17, x17, t2;\nmul.rn.bf16x2 y19, x19, t2;\n"
        "mma.sync.aligned.m16n8k16.row.col.f32.bf16.bf16.f32 {d16,d17,d18,d19}, {y16,y17,y18,y19}, {bB0,bB1}, {fz,fz,fz,fz};\ncvt.rn.bf16x2.f32 z8, d17, d16;\n"
        "cvt.rn.bf16x2.f32 z9, d19, d18;\nmov.b32 {lo, hi}, rb3;\nmov.b32 t2, {lo, lo};\nmul.rn.bf16x2 y12, x12, t2;\nmul.rn.bf16x2 y14, x14, t2;\n"
        "mov.b32 t2, {hi, hi};\nmul.rn.bf16x2 y13, x13, t2;\nmul.rn.bf16x2 y15, x15, t2;\n"
        "mma.sync.aligned.m16n8k16.row.col.f32.bf16.bf16.f32 {d12,d13,d14,d15}, {y12,y13,y14,y15}, {bB0,bB1}, {fz,fz,fz,fz};\ncvt.rn.bf16x2.f32 z6, d13, d12;\n"
        "cvt.rn.bf16x2.f32 z7, d15, d14;\nmov.b32 {lo, hi}, rb5;\nmov.b32 t2, {lo, lo};\nmul.rn.bf16x2 y20, x20, t2;\nmul.rn.bf16x2 y22, x22, t2;\n"
        "mov.b32 t2, {hi, hi};\nmul.rn.bf16x2 y21, x21, t2;\nmul.rn.bf16x2 y23, x23, t2;\n"
        "mma.sync.aligned.m16n8k16.row.col.f32.bf16.bf16.f32 {d20,d21,d22,d23}, {y20,y21,y22,y23}, {bB0,bB1}, {fz,fz,fz,fz};\ncvt.rn.bf16x2.f32 z10, d21, d20;\n"
        "cvt.rn.bf16x2.f32 z11, d23, d22;\n@ps2 bra.uni TB2;\n@ps1 bra.uni TB1;\n"
        "TB0:\nadd.rn.bf16x2 h0, h0, z0;\nadd.rn.bf16x2 h1, h1, z1;\nadd.rn.bf16x2 h2, h2, z2;\nadd.rn.bf16x2 h3, h3, z3;\nadd.rn.bf16x2 h4, h4, z4;\n"
        "add.rn.bf16x2 h5, h5, z5;\nadd.rn.bf16x2 h6, h6, z6;\nadd.rn.bf16x2 h7, h7, z7;\nadd.rn.bf16x2 h8, h8, z8;\nadd.rn.bf16x2 h9, h9, z9;\n"
        "add.rn.bf16x2 h10, h10, z10;\nadd.rn.bf16x2 h11, h11, z11;\nadd.rn.bf16x2 h12, h12, z12;\nadd.rn.bf16x2 h13, h13, z13;\nadd.rn.bf16x2 h14, h14, z14;\n"
        "add.rn.bf16x2 h15, h15, z15;\nbra.uni RW;\n"
        "TB1:\nadd.rn.bf16x2 h16, h16, z0;\nadd.rn.bf16x2 h17, h17, z1;\nadd.rn.bf16x2 h18, h18, z2;\nadd.rn.bf16x2 h19, h19, z3;\nadd.rn.bf16x2 h20, h20, z4;\n"
        "add.rn.bf16x2 h21, h21, z5;\nadd.rn.bf16x2 h22, h22, z6;\nadd.rn.bf16x2 h23, h23, z7;\nadd.rn.bf16x2 h24, h24, z8;\nadd.rn.bf16x2 h25, h25, z9;\n"
        "add.rn.bf16x2 h26, h26, z10;\nadd.rn.bf16x2 h27, h27, z11;\nadd.rn.bf16x2 h28, h28, z12;\nadd.rn.bf16x2 h29, h29, z13;\nadd.rn.bf16x2 h30, h30, z14;\n"
        "add.rn.bf16x2 h31, h31, z15;\nbra.uni RW;\n"
        "TB2:\n@ps1 bra.uni TB3;\nadd.rn.bf16x2 h32, h32, z0;\nadd.rn.bf16x2 h33, h33, z1;\nadd.rn.bf16x2 h34, h34, z2;\nadd.rn.bf16x2 h35, h35, z3;\n"
        "add.rn.bf16x2 h36, h36, z4;\nadd.rn.bf16x2 h37, h37, z5;\nadd.rn.bf16x2 h38, h38, z6;\nadd.rn.bf16x2 h39, h39, z7;\nadd.rn.bf16x2 h40, h40, z8;\n"
        "add.rn.bf16x2 h41, h41, z9;\nadd.rn.bf16x2 h42, h42, z10;\nadd.rn.bf16x2 h43, h43, z11;\nadd.rn.bf16x2 h44, h44, z12;\nadd.rn.bf16x2 h45, h45, z13;\n"
        "add.rn.bf16x2 h46, h46, z14;\nadd.rn.bf16x2 h47, h47, z15;\nbra.uni RW;\n"
        "TB3:\nadd.rn.bf16x2 h48, h48, z0;\nadd.rn.bf16x2 h49, h49, z1;\nadd.rn.bf16x2 h50, h50, z2;\nadd.rn.bf16x2 h51, h51, z3;\nadd.rn.bf16x2 h52, h52, z4;\n"
        "add.rn.bf16x2 h53, h53, z5;\nadd.rn.bf16x2 h54, h54, z6;\nadd.rn.bf16x2 h55, h55, z7;\nadd.rn.bf16x2 h56, h56, z8;\nadd.rn.bf16x2 h57, h57, z9;\n"
        "add.rn.bf16x2 h58, h58, z10;\nadd.rn.bf16x2 h59, h59, z11;\nadd.rn.bf16x2 h60, h60, z12;\nadd.rn.bf16x2 h61, h61, z13;\nadd.rn.bf16x2 h62, h62, z14;\n"
        "add.rn.bf16x2 h63, h63, z15;\nbra.uni RW;\n"
        "WA:\nshr.u32 t2, v, 1;\nand.b32 t2, t2, 0xff8;\nsetp.ge.u32 p, v, 1073741824;\nvote.sync.all.pred p, p, 0xffffffff;\n@p bra.uni DONE;\nmov.b32 n, 0;\n"
        "WA3:\nmbarrier.try_wait.parity.shared.b64 p, [t2+%75], 0;\nvote.sync.all.pred p, p, 0xffffffff;\nadd.u32 n, n, 1;\nsetp.lt.and.u32 q, n, 1000000, !p;\n"
        "@q bra.uni WA3;\nlop3.b32 ida, v, %67, 0x1fff, 0xe4;\nld.volatile.shared.u16 id, [ida+%74];\nbra.uni HA;\n"
        "WB:\nshr.u32 t2, v, 1;\nand.b32 t2, t2, 0xff8;\nsetp.ge.u32 p, v, 1073741824;\nvote.sync.all.pred p, p, 0xffffffff;\n@p bra.uni DONE;\nmov.b32 n, 0;\n"
        "WB3:\nmbarrier.try_wait.parity.shared.b64 p, [t2+%75], 0;\nvote.sync.all.pred p, p, 0xffffffff;\nadd.u32 n, n, 1;\nsetp.lt.and.u32 q, n, 1000000, !p;\n"
        "@q bra.uni WB3;\nlop3.b32 ida, v, %67, 0x1fff, 0xe4;\nld.volatile.shared.u16 id, [ida+%74];\nbra.uni HB;\n"
        "DONE:\nmov.b32 %0, h0;\nmov.b32 %1, h1;\nmov.b32 %2, h2;\nmov.b32 %3, h3;\nmov.b32 %4, h4;\nmov.b32 %5, h5;\nmov.b32 %6, h6;\nmov.b32 %7, h7;\n"
        "mov.b32 %8, h8;\nmov.b32 %9, h9;\nmov.b32 %10, h10;\nmov.b32 %11, h11;\nmov.b32 %12, h12;\nmov.b32 %13, h13;\nmov.b32 %14, h14;\nmov.b32 %15, h15;\n"
        "mov.b32 %16, h16;\nmov.b32 %17, h17;\nmov.b32 %18, h18;\nmov.b32 %19, h19;\nmov.b32 %20, h20;\nmov.b32 %21, h21;\nmov.b32 %22, h22;\nmov.b32 %23, h23;\n"
        "mov.b32 %24, h24;\nmov.b32 %25, h25;\nmov.b32 %26, h26;\nmov.b32 %27, h27;\nmov.b32 %28, h28;\nmov.b32 %29, h29;\nmov.b32 %30, h30;\nmov.b32 %31, h31;\n"
        "mov.b32 %32, h32;\nmov.b32 %33, h33;\nmov.b32 %34, h34;\nmov.b32 %35, h35;\nmov.b32 %36, h36;\nmov.b32 %37, h37;\nmov.b32 %38, h38;\nmov.b32 %39, h39;\n"
        "mov.b32 %40, h40;\nmov.b32 %41, h41;\nmov.b32 %42, h42;\nmov.b32 %43, h43;\nmov.b32 %44, h44;\nmov.b32 %45, h45;\nmov.b32 %46, h46;\nmov.b32 %47, h47;\n"
        "mov.b32 %48, h48;\nmov.b32 %49, h49;\nmov.b32 %50, h50;\nmov.b32 %51, h51;\nmov.b32 %52, h52;\nmov.b32 %53, h53;\nmov.b32 %54, h54;\nmov.b32 %55, h55;\n"
        "mov.b32 %56, h56;\nmov.b32 %57, h57;\nmov.b32 %58, h58;\nmov.b32 %59, h59;\nmov.b32 %60, h60;\nmov.b32 %61, h61;\nmov.b32 %62, h62;\nmov.b32 %63, h63;\n"
        "}\n"
        : "=r"(pk[0]), "=r"(pk[1]), "=r"(pk[2]), "=r"(pk[3]), "=r"(pk[4]), "=r"(pk[5]), "=r"(pk[6]), "=r"(pk[7]), "=r"(pk[8]), "=r"(pk[9]),
          "=r"(pk[10]), "=r"(pk[11]), "=r"(pk[12]), "=r"(pk[13]), "=r"(pk[14]), "=r"(pk[15]), "=r"(pk[16]), "=r"(pk[17]), "=r"(pk[18]), "=r"(pk[19]),
          "=r"(pk[20]), "=r"(pk[21]), "=r"(pk[22]), "=r"(pk[23]), "=r"(pk[24]), "=r"(pk[25]), "=r"(pk[26]), "=r"(pk[27]), "=r"(pk[28]), "=r"(pk[29]),
          "=r"(pk[30]), "=r"(pk[31]), "=r"(pk[32]), "=r"(pk[33]), "=r"(pk[34]), "=r"(pk[35]), "=r"(pk[36]), "=r"(pk[37]), "=r"(pk[38]), "=r"(pk[39]),
          "=r"(pk[40]), "=r"(pk[41]), "=r"(pk[42]), "=r"(pk[43]), "=r"(pk[44]), "=r"(pk[45]), "=r"(pk[46]), "=r"(pk[47]), "=r"(pk[48]), "=r"(pk[49]),
          "=r"(pk[50]), "=r"(pk[51]), "=r"(pk[52]), "=r"(pk[53]), "=r"(pk[54]), "=r"(pk[55]), "=r"(pk[56]), "=r"(pk[57]), "=r"(pk[58]), "=r"(pk[59]),
          "=r"(pk[60]), "=r"(pk[61]), "=r"(pk[62]), "=r"(pk[63])
        : "r"(olp), "r"(xa), "r"(ln), "r"(lc), "r"(linc), "r"(lt), "l"(ea), "l"(sh), "l"(wf),
          "n"(sb + SM_REC), "n"(sb + SM_R), "n"(sb + SM_BAR), "n"(sb + SM_CTR),
          "r"(w[0]), "r"(w[1]), "r"(w[2]), "r"(w[3]), "r"(w[4]), "r"(w[5]), "r"(w[6]), "r"(w[7]), "r"(w[8]), "r"(w[9]), "r"(w[10]), "r"(w[11]),
          "r"(w[12]), "r"(w[13]), "r"(w[14]), "r"(w[15]), "r"(w[16]), "r"(w[17]), "r"(w[18]), "r"(w[19]), "r"(w[20]), "r"(w[21]), "r"(w[22]),
          "r"(w[23]), "r"(w[24]), "r"(w[25]), "r"(w[26]), "r"(w[27]), "r"(w[28]), "r"(w[29]), "r"(w[30]), "r"(w[31]), "r"(w[32]), "r"(w[33]),
          "r"(w[34]), "r"(w[35])
        : "memory");
}
__device__ __forceinline__ void consume3(uint32_t (&pk)[48], const uint32_t (&w)[36], uint32_t olp, uint32_t xa, uint32_t ln,
                                      uint32_t lc, uint32_t linc, uint32_t lt, const __nv_bfloat16* ea, const __nv_bfloat16* sh, const void* wf) {
    ea += lt * 4, sh += lt & 2;
    asm volatile(
        "{\n.reg .pred p, q, psw, prdy, ps1, ps2, ps3, pz;\n.reg .f32 d<32>, fz;\n"
        ".reg .b32 h<48>, x<32>, y<32>, ra<8>, rb<8>, bA0, bA1, bB0, bB1, c0, c1, c2, c3, e0, e1, s0, kept;\n"
        ".reg .b32 olp, v, vB, m, id, ida, bar, xb, pos, t0, t1, t2, t3, n, z<16>;\n.reg .b16 lo, hi, i16;\n.reg .b64 pa, pb;\nmov.f32 fz, 0f00000000;\n"
        "mov.b32 h0, 0;\nmov.b32 h1, 0;\nmov.b32 h2, 0;\nmov.b32 h3, 0;\nmov.b32 h4, 0;\nmov.b32 h5, 0;\nmov.b32 h6, 0;\nmov.b32 h7, 0;\nmov.b32 h8, 0;\n"
        "mov.b32 h9, 0;\nmov.b32 h10, 0;\nmov.b32 h11, 0;\nmov.b32 h12, 0;\nmov.b32 h13, 0;\nmov.b32 h14, 0;\nmov.b32 h15, 0;\nmov.b32 h16, 0;\nmov.b32 h17, 0;\n"
        "mov.b32 h18, 0;\nmov.b32 h19, 0;\nmov.b32 h20, 0;\nmov.b32 h21, 0;\nmov.b32 h22, 0;\nmov.b32 h23, 0;\nmov.b32 h24, 0;\nmov.b32 h25, 0;\n"
        "mov.b32 h26, 0;\nmov.b32 h27, 0;\nmov.b32 h28, 0;\nmov.b32 h29, 0;\nmov.b32 h30, 0;\nmov.b32 h31, 0;\nmov.b32 h32, 0;\nmov.b32 h33, 0;\n"
        "mov.b32 h34, 0;\nmov.b32 h35, 0;\nmov.b32 h36, 0;\nmov.b32 h37, 0;\nmov.b32 h38, 0;\nmov.b32 h39, 0;\nmov.b32 h40, 0;\nmov.b32 h41, 0;\n"
        "mov.b32 h42, 0;\nmov.b32 h43, 0;\nmov.b32 h44, 0;\nmov.b32 h45, 0;\nmov.b32 h46, 0;\nmov.b32 h47, 0;\nmov.b32 olp, %48;\nor.b32 t3, %51, 4;\n"
        "shfl.sync.bfly.b32 t3, t3, 8, 0x1f, 0xffffffff;\nand.b32 t0, %50, 32;\nsetp.ne.u32 psw, t0, 0;\nsetp.eq.u32 pz, %48, 0;\n"
        "vote.sync.any.pred pz, pz, 0xffffffff;\nld.shared.b32 t0, [olp];\nadd.u32 olp, olp, 8;\nlop3.b32 t1, t0, %50, 0x3ff0, 0xe4;\n"
        "ld.shared.b32 t1, [t1+%57];\nlop3.b32 kept, t1, t0, 0x1ffc, 0xe4;\nlop3.b32 t2, t1, %51, 3, 0x80;\nsetp.ne.u32 q, t2, 0;\nshr.u32 t2, t1, 13;\n"
        "mad.wide.u32 pa, t2, 32, %54;\nmad.wide.u32 pb, t2, 8, %55;\nmov.b32 s0, 0;\nld.global.cg.v2.b32 {e0,e1}, [pa];\n@q ld.global.cg.b32 s0, [pb];\n"
        "setp.ne.u64 p, %56, 0;\n@p fence.proxy.async.global;\n@p red.release.gpu.global.add.u32 [%56+12], 1;\nbar.warp.sync 0xffffffff;\n"
        "shfl.sync.idx.b32 v, kept, %51, 0x1f, 0xffffffff;\nshfl.sync.idx.b32 vB, kept, t3, 0x1f, 0xffffffff;\n"
        "RW:\nmma.sync.aligned.m16n8k8.row.col.f32.bf16.bf16.f32 {d0,d1,d2,d3}, {%93,%94}, {s0}, {fz,fz,fz,fz};\n"
        "mma.sync.aligned.m16n8k8.row.col.f32.bf16.bf16.f32 {d4,d5,d6,d7}, {%95,%96}, {s0}, {fz,fz,fz,fz};\ncvt.rn.bf16x2.f32 c0, d2, d0;\n"
        "cvt.rn.bf16x2.f32 c1, d3, d1;\ncvt.rn.bf16x2.f32 c2, d6, d4;\ncvt.rn.bf16x2.f32 c3, d7, d5;\nselp.b32 bA0, c2, c0, psw;\nselp.b32 bA1, c0, c2, psw;\n"
        "selp.b32 bB0, c3, c1, psw;\nselp.b32 bB1, c1, c3, psw;\n"
        "mma.sync.aligned.m16n8k16.row.col.f32.bf16.bf16.f32 {d0,d1,d2,d3}, {%61,%62,%63,%64}, {e0,e1}, {fz,fz,fz,fz};\ncvt.rn.bf16x2.f32 ra0, d2, d0;\n"
        "cvt.rn.bf16x2.f32 rb0, d3, d1;\nmma.sync.aligned.m16n8k16.row.col.f32.bf16.bf16.f32 {d4,d5,d6,d7}, {%65,%66,%67,%68}, {e0,e1}, {fz,fz,fz,fz};\n"
        "cvt.rn.bf16x2.f32 ra1, d6, d4;\ncvt.rn.bf16x2.f32 rb1, d7, d5;\n"
        "mma.sync.aligned.m16n8k16.row.col.f32.bf16.bf16.f32 {d8,d9,d10,d11}, {%69,%70,%71,%72}, {e0,e1}, {fz,fz,fz,fz};\ncvt.rn.bf16x2.f32 ra2, d10, d8;\n"
        "cvt.rn.bf16x2.f32 rb2, d11, d9;\nmma.sync.aligned.m16n8k16.row.col.f32.bf16.bf16.f32 {d12,d13,d14,d15}, {%73,%74,%75,%76}, {e0,e1}, {fz,fz,fz,fz};\n"
        "cvt.rn.bf16x2.f32 ra3, d14, d12;\ncvt.rn.bf16x2.f32 rb3, d15, d13;\n"
        "mma.sync.aligned.m16n8k16.row.col.f32.bf16.bf16.f32 {d16,d17,d18,d19}, {%77,%78,%79,%80}, {e0,e1}, {fz,fz,fz,fz};\ncvt.rn.bf16x2.f32 ra4, d18, d16;\n"
        "cvt.rn.bf16x2.f32 rb4, d19, d17;\nmma.sync.aligned.m16n8k16.row.col.f32.bf16.bf16.f32 {d20,d21,d22,d23}, {%81,%82,%83,%84}, {e0,e1}, {fz,fz,fz,fz};\n"
        "cvt.rn.bf16x2.f32 ra5, d22, d20;\ncvt.rn.bf16x2.f32 rb5, d23, d21;\n"
        "mma.sync.aligned.m16n8k16.row.col.f32.bf16.bf16.f32 {d24,d25,d26,d27}, {%85,%86,%87,%88}, {e0,e1}, {fz,fz,fz,fz};\ncvt.rn.bf16x2.f32 ra6, d26, d24;\n"
        "cvt.rn.bf16x2.f32 rb6, d27, d25;\nmma.sync.aligned.m16n8k16.row.col.f32.bf16.bf16.f32 {d28,d29,d30,d31}, {%89,%90,%91,%92}, {e0,e1}, {fz,fz,fz,fz};\n"
        "cvt.rn.bf16x2.f32 ra7, d30, d28;\ncvt.rn.bf16x2.f32 rb7, d31, d29;\nld.shared.b32 t0, [olp];\nadd.u32 olp, olp, 8;\n"
        "lop3.b32 t1, t0, %50, 0x3ff0, 0xe4;\nld.shared.b32 t1, [t1+%57];\nlop3.b32 kept, t1, t0, 0x1ffc, 0xe4;\nlop3.b32 t2, t1, %51, 3, 0x80;\n"
        "setp.ne.u32 q, t2, 0;\nshr.u32 t2, t1, 13;\nmad.wide.u32 pa, t2, 32, %54;\nmad.wide.u32 pb, t2, 8, %55;\nmov.b32 s0, 0;\n"
        "ld.global.cg.v2.b32 {e0,e1}, [pa];\n@q ld.global.cg.b32 s0, [pb];\nshr.u32 bar, v, 1;\nand.b32 bar, bar, 0xff8;\n"
        "mbarrier.test_wait.parity.shared.b64 p, [bar+%59], 0;\nlop3.b32 ida, v, %51, 0x1fff, 0xe4;\nld.volatile.shared.u16 id, [ida+%58];\n"
        "vote.sync.all.pred prdy, p, 0xffffffff;\n@!prdy bra.uni WA;\n"
        "HA:\nmad.lo.u32 xb, id, 64, %49;\ncvt.u16.u32 i16, id;\natom.shared.add.u32 pos, [%50+%60], %52;\n"
        "ldmatrix.sync.aligned.m8n8.x4.trans.shared.b16 {x0,x1,x2,x3}, [xb];\nldmatrix.sync.aligned.m8n8.x4.trans.shared.b16 {x24,x25,x26,x27}, [xb+512];\n"
        "xor.b32 t1, xb, 32;\nldmatrix.sync.aligned.m8n8.x4.trans.shared.b16 {x4,x5,x6,x7}, [t1];\n"
        "ldmatrix.sync.aligned.m8n8.x4.trans.shared.b16 {x28,x29,x30,x31}, [t1+512];\nxor.b32 t1, xb, 64;\n"
        "ldmatrix.sync.aligned.m8n8.x4.trans.shared.b16 {x8,x9,x10,x11}, [t1];\nldmatrix.sync.aligned.m8n8.x4.trans.shared.b16 {x16,x17,x18,x19}, [t1+512];\n"
        "xor.b32 t1, xb, 96;\nldmatrix.sync.aligned.m8n8.x4.trans.shared.b16 {x12,x13,x14,x15}, [t1];\n"
        "ldmatrix.sync.aligned.m8n8.x4.trans.shared.b16 {x20,x21,x22,x23}, [t1+512];\nst.volatile.shared.u16 [pos], i16;\nand.b32 t0, v, 268435456;\n"
        "setp.ne.u32 ps1, t0, 0;\nvote.sync.any.pred ps1, ps1, 0xffffffff;\nand.b32 t0, v, 536870912;\nsetp.ne.u32 ps2, t0, 0;\n"
        "vote.sync.any.pred ps2, ps2, 0xffffffff;\nmov.b32 v, vB;\nshr.u32 bar, v, 1;\nand.b32 bar, bar, 0xff8;\n"
        "mbarrier.test_wait.parity.shared.b64 p, [bar+%59], 0;\nlop3.b32 ida, v, %51, 0x1fff, 0xe4;\nld.volatile.shared.u16 id, [ida+%58];\n"
        "vote.sync.all.pred prdy, p, 0xffffffff;\nmov.b32 {lo, hi}, ra0;\nmov.b32 t2, {lo, lo};\nmul.rn.bf16x2 y0, x0, t2;\nmul.rn.bf16x2 y2, x2, t2;\n"
        "mov.b32 t2, {hi, hi};\nmul.rn.bf16x2 y1, x1, t2;\nmul.rn.bf16x2 y3, x3, t2;\n"
        "mma.sync.aligned.m16n8k16.row.col.f32.bf16.bf16.f32 {d0,d1,d2,d3}, {y0,y1,y2,y3}, {bA0,bA1}, {fz,fz,fz,fz};\ncvt.rn.bf16x2.f32 z0, d1, d0;\n"
        "cvt.rn.bf16x2.f32 z1, d3, d2;\nmov.b32 {lo, hi}, ra6;\nmov.b32 t2, {lo, lo};\nmul.rn.bf16x2 y24, x24, t2;\nmul.rn.bf16x2 y26, x26, t2;\n"
        "mov.b32 t2, {hi, hi};\nmul.rn.bf16x2 y25, x25, t2;\nmul.rn.bf16x2 y27, x27, t2;\n"
        "mma.sync.aligned.m16n8k16.row.col.f32.bf16.bf16.f32 {d24,d25,d26,d27}, {y24,y25,y26,y27}, {bA0,bA1}, {fz,fz,fz,fz};\ncvt.rn.bf16x2.f32 z12, d25, d24;\n"
        "cvt.rn.bf16x2.f32 z13, d27, d26;\nmov.b32 {lo, hi}, ra1;\nmov.b32 t2, {lo, lo};\nmul.rn.bf16x2 y4, x4, t2;\nmul.rn.bf16x2 y6, x6, t2;\n"
        "mov.b32 t2, {hi, hi};\nmul.rn.bf16x2 y5, x5, t2;\nmul.rn.bf16x2 y7, x7, t2;\n"
        "mma.sync.aligned.m16n8k16.row.col.f32.bf16.bf16.f32 {d4,d5,d6,d7}, {y4,y5,y6,y7}, {bA0,bA1}, {fz,fz,fz,fz};\ncvt.rn.bf16x2.f32 z2, d5, d4;\n"
        "cvt.rn.bf16x2.f32 z3, d7, d6;\nmov.b32 {lo, hi}, ra7;\nmov.b32 t2, {lo, lo};\nmul.rn.bf16x2 y28, x28, t2;\nmul.rn.bf16x2 y30, x30, t2;\n"
        "mov.b32 t2, {hi, hi};\nmul.rn.bf16x2 y29, x29, t2;\nmul.rn.bf16x2 y31, x31, t2;\n"
        "mma.sync.aligned.m16n8k16.row.col.f32.bf16.bf16.f32 {d28,d29,d30,d31}, {y28,y29,y30,y31}, {bA0,bA1}, {fz,fz,fz,fz};\ncvt.rn.bf16x2.f32 z14, d29, d28;\n"
        "cvt.rn.bf16x2.f32 z15, d31, d30;\nmov.b32 {lo, hi}, ra2;\nmov.b32 t2, {lo, lo};\nmul.rn.bf16x2 y8, x8, t2;\nmul.rn.bf16x2 y10, x10, t2;\n"
        "mov.b32 t2, {hi, hi};\nmul.rn.bf16x2 y9, x9, t2;\nmul.rn.bf16x2 y11, x11, t2;\n"
        "mma.sync.aligned.m16n8k16.row.col.f32.bf16.bf16.f32 {d8,d9,d10,d11}, {y8,y9,y10,y11}, {bA0,bA1}, {fz,fz,fz,fz};\ncvt.rn.bf16x2.f32 z4, d9, d8;\n"
        "cvt.rn.bf16x2.f32 z5, d11, d10;\nmov.b32 {lo, hi}, ra4;\nmov.b32 t2, {lo, lo};\nmul.rn.bf16x2 y16, x16, t2;\nmul.rn.bf16x2 y18, x18, t2;\n"
        "mov.b32 t2, {hi, hi};\nmul.rn.bf16x2 y17, x17, t2;\nmul.rn.bf16x2 y19, x19, t2;\n"
        "mma.sync.aligned.m16n8k16.row.col.f32.bf16.bf16.f32 {d16,d17,d18,d19}, {y16,y17,y18,y19}, {bA0,bA1}, {fz,fz,fz,fz};\ncvt.rn.bf16x2.f32 z8, d17, d16;\n"
        "cvt.rn.bf16x2.f32 z9, d19, d18;\nmov.b32 {lo, hi}, ra3;\nmov.b32 t2, {lo, lo};\nmul.rn.bf16x2 y12, x12, t2;\nmul.rn.bf16x2 y14, x14, t2;\n"
        "mov.b32 t2, {hi, hi};\nmul.rn.bf16x2 y13, x13, t2;\nmul.rn.bf16x2 y15, x15, t2;\n"
        "mma.sync.aligned.m16n8k16.row.col.f32.bf16.bf16.f32 {d12,d13,d14,d15}, {y12,y13,y14,y15}, {bA0,bA1}, {fz,fz,fz,fz};\ncvt.rn.bf16x2.f32 z6, d13, d12;\n"
        "cvt.rn.bf16x2.f32 z7, d15, d14;\nmov.b32 {lo, hi}, ra5;\nmov.b32 t2, {lo, lo};\nmul.rn.bf16x2 y20, x20, t2;\nmul.rn.bf16x2 y22, x22, t2;\n"
        "mov.b32 t2, {hi, hi};\nmul.rn.bf16x2 y21, x21, t2;\nmul.rn.bf16x2 y23, x23, t2;\n"
        "mma.sync.aligned.m16n8k16.row.col.f32.bf16.bf16.f32 {d20,d21,d22,d23}, {y20,y21,y22,y23}, {bA0,bA1}, {fz,fz,fz,fz};\ncvt.rn.bf16x2.f32 z10, d21, d20;\n"
        "cvt.rn.bf16x2.f32 z11, d23, d22;\n@ps2 bra.uni TA2;\n@ps1 bra.uni TA1;\n"
        "TA0:\nadd.rn.bf16x2 h0, h0, z0;\nadd.rn.bf16x2 h1, h1, z1;\nadd.rn.bf16x2 h2, h2, z2;\nadd.rn.bf16x2 h3, h3, z3;\nadd.rn.bf16x2 h4, h4, z4;\n"
        "add.rn.bf16x2 h5, h5, z5;\nadd.rn.bf16x2 h6, h6, z6;\nadd.rn.bf16x2 h7, h7, z7;\nadd.rn.bf16x2 h8, h8, z8;\nadd.rn.bf16x2 h9, h9, z9;\n"
        "add.rn.bf16x2 h10, h10, z10;\nadd.rn.bf16x2 h11, h11, z11;\nadd.rn.bf16x2 h12, h12, z12;\nadd.rn.bf16x2 h13, h13, z13;\nadd.rn.bf16x2 h14, h14, z14;\n"
        "add.rn.bf16x2 h15, h15, z15;\n@prdy bra.uni HB;\nbra.uni WB;\n"
        "TA1:\nadd.rn.bf16x2 h16, h16, z0;\nadd.rn.bf16x2 h17, h17, z1;\nadd.rn.bf16x2 h18, h18, z2;\nadd.rn.bf16x2 h19, h19, z3;\nadd.rn.bf16x2 h20, h20, z4;\n"
        "add.rn.bf16x2 h21, h21, z5;\nadd.rn.bf16x2 h22, h22, z6;\nadd.rn.bf16x2 h23, h23, z7;\nadd.rn.bf16x2 h24, h24, z8;\nadd.rn.bf16x2 h25, h25, z9;\n"
        "add.rn.bf16x2 h26, h26, z10;\nadd.rn.bf16x2 h27, h27, z11;\nadd.rn.bf16x2 h28, h28, z12;\nadd.rn.bf16x2 h29, h29, z13;\nadd.rn.bf16x2 h30, h30, z14;\n"
        "add.rn.bf16x2 h31, h31, z15;\n@prdy bra.uni HB;\nbra.uni WB;\n"
        "TA2:\nadd.rn.bf16x2 h32, h32, z0;\nadd.rn.bf16x2 h33, h33, z1;\nadd.rn.bf16x2 h34, h34, z2;\nadd.rn.bf16x2 h35, h35, z3;\nadd.rn.bf16x2 h36, h36, z4;\n"
        "add.rn.bf16x2 h37, h37, z5;\nadd.rn.bf16x2 h38, h38, z6;\nadd.rn.bf16x2 h39, h39, z7;\nadd.rn.bf16x2 h40, h40, z8;\nadd.rn.bf16x2 h41, h41, z9;\n"
        "add.rn.bf16x2 h42, h42, z10;\nadd.rn.bf16x2 h43, h43, z11;\nadd.rn.bf16x2 h44, h44, z12;\nadd.rn.bf16x2 h45, h45, z13;\nadd.rn.bf16x2 h46, h46, z14;\n"
        "add.rn.bf16x2 h47, h47, z15;\n@prdy bra.uni HB;\nbra.uni WB;\n"
        "HB:\nmad.lo.u32 xb, id, 64, %49;\ncvt.u16.u32 i16, id;\natom.shared.add.u32 pos, [%50+%60], %52;\n"
        "ldmatrix.sync.aligned.m8n8.x4.trans.shared.b16 {x0,x1,x2,x3}, [xb];\nldmatrix.sync.aligned.m8n8.x4.trans.shared.b16 {x24,x25,x26,x27}, [xb+512];\n"
        "xor.b32 t1, xb, 32;\nldmatrix.sync.aligned.m8n8.x4.trans.shared.b16 {x4,x5,x6,x7}, [t1];\n"
        "ldmatrix.sync.aligned.m8n8.x4.trans.shared.b16 {x28,x29,x30,x31}, [t1+512];\nxor.b32 t1, xb, 64;\n"
        "ldmatrix.sync.aligned.m8n8.x4.trans.shared.b16 {x8,x9,x10,x11}, [t1];\nldmatrix.sync.aligned.m8n8.x4.trans.shared.b16 {x16,x17,x18,x19}, [t1+512];\n"
        "xor.b32 t1, xb, 96;\nldmatrix.sync.aligned.m8n8.x4.trans.shared.b16 {x12,x13,x14,x15}, [t1];\n"
        "ldmatrix.sync.aligned.m8n8.x4.trans.shared.b16 {x20,x21,x22,x23}, [t1+512];\nst.volatile.shared.u16 [pos], i16;\nand.b32 t0, v, 268435456;\n"
        "setp.ne.u32 ps1, t0, 0;\nvote.sync.any.pred ps1, ps1, 0xffffffff;\nand.b32 t0, v, 536870912;\nsetp.ne.u32 ps2, t0, 0;\n"
        "vote.sync.any.pred ps2, ps2, 0xffffffff;\nshfl.sync.idx.b32 v, kept, %51, 0x1f, 0xffffffff;\nshfl.sync.idx.b32 vB, kept, t3, 0x1f, 0xffffffff;\n"
        "mov.b32 {lo, hi}, rb0;\nmov.b32 t2, {lo, lo};\nmul.rn.bf16x2 y0, x0, t2;\nmul.rn.bf16x2 y2, x2, t2;\nmov.b32 t2, {hi, hi};\nmul.rn.bf16x2 y1, x1, t2;\n"
        "mul.rn.bf16x2 y3, x3, t2;\nmma.sync.aligned.m16n8k16.row.col.f32.bf16.bf16.f32 {d0,d1,d2,d3}, {y0,y1,y2,y3}, {bB0,bB1}, {fz,fz,fz,fz};\n"
        "cvt.rn.bf16x2.f32 z0, d1, d0;\ncvt.rn.bf16x2.f32 z1, d3, d2;\nmov.b32 {lo, hi}, rb6;\nmov.b32 t2, {lo, lo};\nmul.rn.bf16x2 y24, x24, t2;\n"
        "mul.rn.bf16x2 y26, x26, t2;\nmov.b32 t2, {hi, hi};\nmul.rn.bf16x2 y25, x25, t2;\nmul.rn.bf16x2 y27, x27, t2;\n"
        "mma.sync.aligned.m16n8k16.row.col.f32.bf16.bf16.f32 {d24,d25,d26,d27}, {y24,y25,y26,y27}, {bB0,bB1}, {fz,fz,fz,fz};\ncvt.rn.bf16x2.f32 z12, d25, d24;\n"
        "cvt.rn.bf16x2.f32 z13, d27, d26;\nmov.b32 {lo, hi}, rb1;\nmov.b32 t2, {lo, lo};\nmul.rn.bf16x2 y4, x4, t2;\nmul.rn.bf16x2 y6, x6, t2;\n"
        "mov.b32 t2, {hi, hi};\nmul.rn.bf16x2 y5, x5, t2;\nmul.rn.bf16x2 y7, x7, t2;\n"
        "mma.sync.aligned.m16n8k16.row.col.f32.bf16.bf16.f32 {d4,d5,d6,d7}, {y4,y5,y6,y7}, {bB0,bB1}, {fz,fz,fz,fz};\ncvt.rn.bf16x2.f32 z2, d5, d4;\n"
        "cvt.rn.bf16x2.f32 z3, d7, d6;\nmov.b32 {lo, hi}, rb7;\nmov.b32 t2, {lo, lo};\nmul.rn.bf16x2 y28, x28, t2;\nmul.rn.bf16x2 y30, x30, t2;\n"
        "mov.b32 t2, {hi, hi};\nmul.rn.bf16x2 y29, x29, t2;\nmul.rn.bf16x2 y31, x31, t2;\n"
        "mma.sync.aligned.m16n8k16.row.col.f32.bf16.bf16.f32 {d28,d29,d30,d31}, {y28,y29,y30,y31}, {bB0,bB1}, {fz,fz,fz,fz};\ncvt.rn.bf16x2.f32 z14, d29, d28;\n"
        "cvt.rn.bf16x2.f32 z15, d31, d30;\nmov.b32 {lo, hi}, rb2;\nmov.b32 t2, {lo, lo};\nmul.rn.bf16x2 y8, x8, t2;\nmul.rn.bf16x2 y10, x10, t2;\n"
        "mov.b32 t2, {hi, hi};\nmul.rn.bf16x2 y9, x9, t2;\nmul.rn.bf16x2 y11, x11, t2;\n"
        "mma.sync.aligned.m16n8k16.row.col.f32.bf16.bf16.f32 {d8,d9,d10,d11}, {y8,y9,y10,y11}, {bB0,bB1}, {fz,fz,fz,fz};\ncvt.rn.bf16x2.f32 z4, d9, d8;\n"
        "cvt.rn.bf16x2.f32 z5, d11, d10;\nmov.b32 {lo, hi}, rb4;\nmov.b32 t2, {lo, lo};\nmul.rn.bf16x2 y16, x16, t2;\nmul.rn.bf16x2 y18, x18, t2;\n"
        "mov.b32 t2, {hi, hi};\nmul.rn.bf16x2 y17, x17, t2;\nmul.rn.bf16x2 y19, x19, t2;\n"
        "mma.sync.aligned.m16n8k16.row.col.f32.bf16.bf16.f32 {d16,d17,d18,d19}, {y16,y17,y18,y19}, {bB0,bB1}, {fz,fz,fz,fz};\ncvt.rn.bf16x2.f32 z8, d17, d16;\n"
        "cvt.rn.bf16x2.f32 z9, d19, d18;\nmov.b32 {lo, hi}, rb3;\nmov.b32 t2, {lo, lo};\nmul.rn.bf16x2 y12, x12, t2;\nmul.rn.bf16x2 y14, x14, t2;\n"
        "mov.b32 t2, {hi, hi};\nmul.rn.bf16x2 y13, x13, t2;\nmul.rn.bf16x2 y15, x15, t2;\n"
        "mma.sync.aligned.m16n8k16.row.col.f32.bf16.bf16.f32 {d12,d13,d14,d15}, {y12,y13,y14,y15}, {bB0,bB1}, {fz,fz,fz,fz};\ncvt.rn.bf16x2.f32 z6, d13, d12;\n"
        "cvt.rn.bf16x2.f32 z7, d15, d14;\nmov.b32 {lo, hi}, rb5;\nmov.b32 t2, {lo, lo};\nmul.rn.bf16x2 y20, x20, t2;\nmul.rn.bf16x2 y22, x22, t2;\n"
        "mov.b32 t2, {hi, hi};\nmul.rn.bf16x2 y21, x21, t2;\nmul.rn.bf16x2 y23, x23, t2;\n"
        "mma.sync.aligned.m16n8k16.row.col.f32.bf16.bf16.f32 {d20,d21,d22,d23}, {y20,y21,y22,y23}, {bB0,bB1}, {fz,fz,fz,fz};\ncvt.rn.bf16x2.f32 z10, d21, d20;\n"
        "cvt.rn.bf16x2.f32 z11, d23, d22;\n@ps2 bra.uni TB2;\n@ps1 bra.uni TB1;\n"
        "TB0:\nadd.rn.bf16x2 h0, h0, z0;\nadd.rn.bf16x2 h1, h1, z1;\nadd.rn.bf16x2 h2, h2, z2;\nadd.rn.bf16x2 h3, h3, z3;\nadd.rn.bf16x2 h4, h4, z4;\n"
        "add.rn.bf16x2 h5, h5, z5;\nadd.rn.bf16x2 h6, h6, z6;\nadd.rn.bf16x2 h7, h7, z7;\nadd.rn.bf16x2 h8, h8, z8;\nadd.rn.bf16x2 h9, h9, z9;\n"
        "add.rn.bf16x2 h10, h10, z10;\nadd.rn.bf16x2 h11, h11, z11;\nadd.rn.bf16x2 h12, h12, z12;\nadd.rn.bf16x2 h13, h13, z13;\nadd.rn.bf16x2 h14, h14, z14;\n"
        "add.rn.bf16x2 h15, h15, z15;\nbra.uni RW;\n"
        "TB1:\nadd.rn.bf16x2 h16, h16, z0;\nadd.rn.bf16x2 h17, h17, z1;\nadd.rn.bf16x2 h18, h18, z2;\nadd.rn.bf16x2 h19, h19, z3;\nadd.rn.bf16x2 h20, h20, z4;\n"
        "add.rn.bf16x2 h21, h21, z5;\nadd.rn.bf16x2 h22, h22, z6;\nadd.rn.bf16x2 h23, h23, z7;\nadd.rn.bf16x2 h24, h24, z8;\nadd.rn.bf16x2 h25, h25, z9;\n"
        "add.rn.bf16x2 h26, h26, z10;\nadd.rn.bf16x2 h27, h27, z11;\nadd.rn.bf16x2 h28, h28, z12;\nadd.rn.bf16x2 h29, h29, z13;\nadd.rn.bf16x2 h30, h30, z14;\n"
        "add.rn.bf16x2 h31, h31, z15;\nbra.uni RW;\n"
        "TB2:\nadd.rn.bf16x2 h32, h32, z0;\nadd.rn.bf16x2 h33, h33, z1;\nadd.rn.bf16x2 h34, h34, z2;\nadd.rn.bf16x2 h35, h35, z3;\nadd.rn.bf16x2 h36, h36, z4;\n"
        "add.rn.bf16x2 h37, h37, z5;\nadd.rn.bf16x2 h38, h38, z6;\nadd.rn.bf16x2 h39, h39, z7;\nadd.rn.bf16x2 h40, h40, z8;\nadd.rn.bf16x2 h41, h41, z9;\n"
        "add.rn.bf16x2 h42, h42, z10;\nadd.rn.bf16x2 h43, h43, z11;\nadd.rn.bf16x2 h44, h44, z12;\nadd.rn.bf16x2 h45, h45, z13;\nadd.rn.bf16x2 h46, h46, z14;\n"
        "add.rn.bf16x2 h47, h47, z15;\nbra.uni RW;\n"
        "WA:\nshr.u32 t2, v, 1;\nand.b32 t2, t2, 0xff8;\nsetp.ge.u32 p, v, 805306368;\nvote.sync.all.pred p, p, 0xffffffff;\n@p bra.uni DONE;\nmov.b32 n, 0;\n"
        "WA3:\nmbarrier.try_wait.parity.shared.b64 p, [t2+%59], 0;\nvote.sync.all.pred p, p, 0xffffffff;\nadd.u32 n, n, 1;\nsetp.lt.and.u32 q, n, 1000000, !p;\n"
        "@q bra.uni WA3;\nlop3.b32 ida, v, %51, 0x1fff, 0xe4;\nld.volatile.shared.u16 id, [ida+%58];\nbra.uni HA;\n"
        "WB:\nshr.u32 t2, v, 1;\nand.b32 t2, t2, 0xff8;\nsetp.ge.u32 p, v, 805306368;\nvote.sync.all.pred p, p, 0xffffffff;\n@p bra.uni DONE;\nmov.b32 n, 0;\n"
        "WB3:\nmbarrier.try_wait.parity.shared.b64 p, [t2+%59], 0;\nvote.sync.all.pred p, p, 0xffffffff;\nadd.u32 n, n, 1;\nsetp.lt.and.u32 q, n, 1000000, !p;\n"
        "@q bra.uni WB3;\nlop3.b32 ida, v, %51, 0x1fff, 0xe4;\nld.volatile.shared.u16 id, [ida+%58];\nbra.uni HB;\n"
        "DONE:\nmov.b32 %0, h0;\nmov.b32 %1, h1;\nmov.b32 %2, h2;\nmov.b32 %3, h3;\nmov.b32 %4, h4;\nmov.b32 %5, h5;\nmov.b32 %6, h6;\nmov.b32 %7, h7;\n"
        "mov.b32 %8, h8;\nmov.b32 %9, h9;\nmov.b32 %10, h10;\nmov.b32 %11, h11;\nmov.b32 %12, h12;\nmov.b32 %13, h13;\nmov.b32 %14, h14;\nmov.b32 %15, h15;\n"
        "mov.b32 %16, h16;\nmov.b32 %17, h17;\nmov.b32 %18, h18;\nmov.b32 %19, h19;\nmov.b32 %20, h20;\nmov.b32 %21, h21;\nmov.b32 %22, h22;\nmov.b32 %23, h23;\n"
        "mov.b32 %24, h24;\nmov.b32 %25, h25;\nmov.b32 %26, h26;\nmov.b32 %27, h27;\nmov.b32 %28, h28;\nmov.b32 %29, h29;\nmov.b32 %30, h30;\nmov.b32 %31, h31;\n"
        "mov.b32 %32, h32;\nmov.b32 %33, h33;\nmov.b32 %34, h34;\nmov.b32 %35, h35;\nmov.b32 %36, h36;\nmov.b32 %37, h37;\nmov.b32 %38, h38;\nmov.b32 %39, h39;\n"
        "mov.b32 %40, h40;\nmov.b32 %41, h41;\nmov.b32 %42, h42;\nmov.b32 %43, h43;\nmov.b32 %44, h44;\nmov.b32 %45, h45;\nmov.b32 %46, h46;\nmov.b32 %47, h47;\n"
        "}\n"
        : "=r"(pk[0]), "=r"(pk[1]), "=r"(pk[2]), "=r"(pk[3]), "=r"(pk[4]), "=r"(pk[5]), "=r"(pk[6]), "=r"(pk[7]), "=r"(pk[8]), "=r"(pk[9]),
          "=r"(pk[10]), "=r"(pk[11]), "=r"(pk[12]), "=r"(pk[13]), "=r"(pk[14]), "=r"(pk[15]), "=r"(pk[16]), "=r"(pk[17]), "=r"(pk[18]), "=r"(pk[19]),
          "=r"(pk[20]), "=r"(pk[21]), "=r"(pk[22]), "=r"(pk[23]), "=r"(pk[24]), "=r"(pk[25]), "=r"(pk[26]), "=r"(pk[27]), "=r"(pk[28]), "=r"(pk[29]),
          "=r"(pk[30]), "=r"(pk[31]), "=r"(pk[32]), "=r"(pk[33]), "=r"(pk[34]), "=r"(pk[35]), "=r"(pk[36]), "=r"(pk[37]), "=r"(pk[38]), "=r"(pk[39]),
          "=r"(pk[40]), "=r"(pk[41]), "=r"(pk[42]), "=r"(pk[43]), "=r"(pk[44]), "=r"(pk[45]), "=r"(pk[46]), "=r"(pk[47])
        : "r"(olp), "r"(xa), "r"(ln), "r"(lc), "r"(linc), "r"(lt), "l"(ea), "l"(sh), "l"(wf),
          "n"(sb + SM_REC), "n"(sb + SM_R), "n"(sb + SM_BAR), "n"(sb + SM_CTR),
          "r"(w[0]), "r"(w[1]), "r"(w[2]), "r"(w[3]), "r"(w[4]), "r"(w[5]), "r"(w[6]), "r"(w[7]), "r"(w[8]), "r"(w[9]), "r"(w[10]), "r"(w[11]),
          "r"(w[12]), "r"(w[13]), "r"(w[14]), "r"(w[15]), "r"(w[16]), "r"(w[17]), "r"(w[18]), "r"(w[19]), "r"(w[20]), "r"(w[21]), "r"(w[22]),
          "r"(w[23]), "r"(w[24]), "r"(w[25]), "r"(w[26]), "r"(w[27]), "r"(w[28]), "r"(w[29]), "r"(w[30]), "r"(w[31]), "r"(w[32]), "r"(w[33]),
          "r"(w[34]), "r"(w[35])
        : "memory");
}

__device__ __forceinline__ void wf_done() {
    asm volatile("fence.proxy.async.global;\nred.release.gpu.global.add.u32 [%0+12], 1;" ::"l"(g_sync) : "memory");
}

template <int NS>
__device__ __forceinline__ void consumer(const __nv_bfloat16* __restrict__ sh,
                                         const __nv_bfloat16* __restrict__ ea, __nv_bfloat16* __restrict__ out, int N, int npb) {
    uint32_t pk[NS * 16];
    {
        const int lane = threadIdx.x & 31, warp = threadIdx.x >> 5;
        const int mi = lane >> 3, r = lane & 7, j = r >> 1;
        const int u = 2 * ((mi >> 1) ^ (j >> 1)) + (r & 1), ph = (j ^ (j >> 1)) & 1;
        uint32_t w[36];
        {
            const uint32_t a = sb + SC_WR + (4 * j + (r & 1) + (mi & 2)) * 272 + (mi & 1) * (PH == 128 ? 128 : 16);
#pragma unroll
            for (int c = 0; c < 8; c++)
                asm volatile("ldmatrix.sync.aligned.m8n8.x4.trans.shared.b16 {%0,%1,%2,%3}, [%4];"
                             : "=r"(w[4 * c]), "=r"(w[4 * c + 1]), "=r"(w[4 * c + 2]), "=r"(w[4 * c + 3]) : "r"(a + c * (PH == 128 ? 16 : 32)) : "memory");
            const uint32_t ca = sb + SC_CG + (lane & 2) * 8 + ((lane >> 2) & 3) * 2;
#pragma unroll
            for (int k = 0; k < 4; k++) {
                const uint32_t f = lds16(ca + 32 * k) | (lds16(ca + 32 * k + 8) << 16);
                w[32 + k] = (lane & 1) == (lane >> 4) ? f : 0;
            }
            asm volatile("fence.proxy.async.shared::cta;\nbar.sync 2, %0;" ::"n"(NCW * 32) : "memory");
            if (threadIdx.x < WSL) sts16(sb + SM_R + 0x2000 + (4 + SP - WSL + lane) * 4, (sb + SC_WR) / 64 + lane * 16);
        }
        const int L = 2 * u + (mi & 1);
        const uint32_t xa = __shfl_sync(0xffffffffu, PH == 128 ? L * 128 + (((L + ph) & 7) << 4) : u * 128 + (((u + 4 * ph) ^ (mi & 1)) << 4), lane);
        const uint32_t ln = __shfl_sync(0xffffffffu, lane * 16 + (lane >> 3) * 4, lane);
        const uint32_t lc = __shfl_sync(0xffffffffu, j * 8 + (1 << (lane & 1)) + (ph << 13), lane);
        const uint32_t linc = __shfl_sync(0xffffffffu, (lane & 0x19) ? 0 : 8, lane);
        const uint32_t lt = __shfl_sync(0xffffffffu, lane & 3, lane);
        const void* wfp = (threadIdx.x >> 2) == WFT && blockIdx.x < 128 ? g_sync : nullptr;
        const uint32_t olp = sb + SM_OL + warp * (OLN * 4) + (lane & 4);
        if constexpr (NS == 4) consume4(pk, w, olp, xa, ln, lc, linc, lt, ea, sh, wfp);
        else consume3(pk, w, olp, xa, ln, lc, linc, lt, ea, sh, wfp);
    }
    TLMAX(10);
    const int tid = thread_id(), lane = tid & 31, warp = tid >> 5, g = lane >> 2, t = lane & 3;
    const uint32_t wc = lds32(sb + SM_MISC + 12) + 1;
    const uint32_t inv = lds32(sb + SM_INV + warp * 4);
    const int node0 = cta_id() * npb, nnodes = min(npb, N - node0);
    uint4* op[NS];
    uint32_t on[NS];
#pragma unroll
    for (int s = 0; s < NS; s++) {
        const int nl = ((inv >> (8 * s)) & 255) + (g >> 2) * 40;
        op[s] = (uint4*)(out + ((size_t)(node0 + nl) * 4 + (g & 3)) * 128 + 8 * t);
        on[s] = nl < nnodes;
    }
    if constexpr (NS == 4) project4(pk, sb + SM_R + wc * 16, sb + SM_BAR + wc * 8, op, on);
    else project3(pk, sb + SM_R + wc * 16, sb + SM_BAR + wc * 8, op, on);
}

#define TLHI "shl.b32 d, tb, 16;\n"
#define RAOFF ((threadIdx.x & 96) >> 1)
#define UNPACK(v) "dp2a.lo.u32.u32 d, " #v ", " K64 ", 0;\nshr.s32 r, " #v ", " SHR ";\n"
#define K64 "k64"
#define KTX "ktx"
#define TMP "tm"
#define XSTR(x) XSTR2(x)
#define XSTR2(x) #x
__device__ __forceinline__ void producer(const CUtensorMap* tmx, int pw) {
    const uint32_t nch = lds32(sb + SM_MISC + 12), c0 = lds32(sb + SM_MISC + 24);
    if (elect()) {
        asm volatile(
            "{\n.reg .pred p, q, lead, never;\n.reg .b32 ra, oa, off, poff, due, now, a<4>, b<4>, d, r, z<8>, bar<4>, t, n, tb, ta, prev, k64, ktx;\n"
            ".reg .b64 lg, t64, tm;\n"
            "mov.b32 ta, %5;\nld.volatile.shared.v4.b32 {z0,z1,z2,z3}, [ta+32];\nld.volatile.shared.v4.b32 {z4,z5,z6,z7}, [ta+32];\n"
            "mov.b32 ra, %9;\nmad.lo.u32 t, %0, 8, %10;\n"
            "add.u32 bar0, t, z0;\nadd.u32 bar1, t, z1;\nadd.u32 bar2, t, z2;\nadd.u32 bar3, t, z3;\nsetp.ne.u32 never, z0, 0;\n"
            "add.u32 k64, z4, 64;\nadd.u32 ktx, z5, 8192;\ncvt.u64.u32 tm, z6;\nadd.u64 tm, tm, %3;\n"
            "mov.b32 n, 0;\nld.volatile.shared.b32 prev, [ta];\nmov.b32 poff, 1000000;\nsetp.eq.u32 lead, %0, 0;\n"
            "mov.u32 due, %%globaltimer_lo;\n"
            "setp.gt.u32 p, ra, %1;\n@p bra.uni END;\nshr.u32 oa, ra, 2;\n"
            "FIRST:\n"
            "ld.volatile.shared.b32 off, [oa+%11-16];\nmov.u32 now, %%globaltimer_lo;\nadd.u32 due, prev, off;\nsub.u32 t, due, now;\n"
            "setp.gt.s32 p, t, %12;\n@p bra.uni FIRST;\n"
            "GO:\n"
            "ld.volatile.shared.v4.b32 {a0,a1,a2,a3}, [ra];\nld.volatile.shared.v4.b32 {b0,b1,b2,b3}, [ra+0x2000];\n"
            "shr.u32 oa, ra, 2;\nld.volatile.shared.b32 off, [oa+%11];\nld.volatile.shared.b32 tb, [ta];\n"
            "mov.u32 now, %%globaltimer_lo;\n"
            "lop3.b32 t, a0, a1, a2, 0xfe;\nlop3.b32 d, a3, b0, b1, 0xfe;\nlop3.b32 t, t, d, b2, 0xfe;\nor.b32 t, t, b3;\nand.b32 t, t, 1;\n"
            "setp.ne.u32 p, t, 0;\n"
            "@p bra.uni BACK;\n"
            "add.u32 t, oa, oa;\nmbarrier.arrive.expect_tx.shared.b64 _, [t+%13], " KTX ";\n"
            "add.u32 bar0, bar0, 32;\nadd.u32 bar1, bar1, 32;\nadd.u32 bar2, bar2, 32;\nadd.u32 bar3, bar3, 32;\n"
            UNPACK(a0)
            "cp.async.bulk.tensor.3d.shared::cluster.global.mbarrier::complete_tx::bytes [d], [" TMP ", {z0, r, z1}], [bar0];\n"
            UNPACK(b0)
            "cp.async.bulk.tensor.3d.shared::cluster.global.mbarrier::complete_tx::bytes [d], [" TMP ", {z2, r, z3}], [bar1];\n"
            UNPACK(a1)
            "cp.async.bulk.tensor.3d.shared::cluster.global.mbarrier::complete_tx::bytes [d], [" TMP ", {z4, r, z5}], [bar2];\n"
            UNPACK(b1)
            "cp.async.bulk.tensor.3d.shared::cluster.global.mbarrier::complete_tx::bytes [d], [" TMP ", {z6, r, z7}], [bar3];\n"
            "@never bra.uni END;\n"
            "add.u32 ra, ra, 64;\nadd.u32 due, off, tb;\nsub.u32 t, due, now;\nsetp.le.and.u32 q, ra, %1, !lead;\nsetp.le.and.s32 q, t, %2, q;\n"
            UNPACK(a2)
            "cp.async.bulk.tensor.3d.shared::cluster.global.mbarrier::complete_tx::bytes [d], [" TMP ", {z0, r, z1}], [bar0];\n"
            UNPACK(b2)
            "cp.async.bulk.tensor.3d.shared::cluster.global.mbarrier::complete_tx::bytes [d], [" TMP ", {z2, r, z3}], [bar1];\n"
            UNPACK(a3)
            "cp.async.bulk.tensor.3d.shared::cluster.global.mbarrier::complete_tx::bytes [d], [" TMP ", {z4, r, z5}], [bar2];\n"
            UNPACK(b3)
            "cp.async.bulk.tensor.3d.shared::cluster.global.mbarrier::complete_tx::bytes [d], [" TMP ", {z6, r, z7}], [bar3];\n"
            "@q bra.uni GO;\n"
            "setp.gt.u32 p, ra, %1;\n@p bra.uni END;\n@!lead bra.uni WAIT0;\n"
            "add.u32 d, ta, 16;\ncp.async.bulk.shared::cluster.global.mbarrier::complete_tx::bytes [ta], [%4], 16, [d];\n"
            "sub.u32 r, now, poff;\nmov.b32 poff, off;\nsub.u32 d, prev, tb;\nmov.b32 prev, r;\nsub.u32 r, r, tb;\nmin.s32 d, d, r;\n"
            "setp.le.s32 p, d, %6;\n@p bra.uni NOSLIP;\n"
            "setp.lt.u32 p, ra, %8;\n@p bra.uni NOSLIP;\nadd.u32 r, ra, " XSTR(SLIPEND) ";\nsetp.gt.u32 p, r, %1;\n@p bra.uni NOSLIP;\n"
            "ld.volatile.shared.b64 t64, [ta];\ncvt.u32.u64 r, t64;\nsub.u32 r, tb, r;\nsub.u32 d, d, %7;\nadd.s32 d, d, r;\n"
            "cvt.s64.s32 lg, d;\nadd.u64 t64, t64, lg;\n"
            "red.relaxed.gpu.global.max.u64 [%4], t64;\n"
            "NOSLIP:\n"
            "setp.le.s32 p, t, %2;\n@p bra.uni GO;\n"
            "WAIT0:\n"
            "ld.volatile.shared.b32 tb, [ta];\nld.volatile.shared.b32 off, [oa+%11];\nmov.u32 now, %%globaltimer_lo;\nadd.u32 due, tb, off;\nsub.u32 t, due, now;\n"
            "setp.le.s32 p, t, %12;\n@p bra.uni GO;\n"
            "setp.gt.s32 p, t, " XSTR(SPINT) ";\n@p nanosleep.u32 32;\nbra.uni WAIT0;\n"
            "BACK:\n"
            "nanosleep.u32 32;\nsub.u32 t, now, tb;\nsetp.lt.s32 p, t, 200000000;\n@p bra.uni GO;\n"
            "END:\n}" ::"r"(pw),
            "r"(sb + SM_R + nch * 16), "n"(AHEAD + EARLY), "l"(tmx), "l"(g_sync), "n"(sb + SM_MISC + 32), "n"(SLIPTH), "n"(SLIPSUB),
            "n"(sb + SM_R + SLIPFROM * 16), "r"(sb + SM_R + 16 + c0 * 16 + RAOFF), "r"(sb + SM_BAR + 8 - 32 + c0 * 8),
            "n"(sb + SM_OFF + 16 - (sb + SM_R) / 4), "n"(EARLY), "n"(sb + SM_BAR - (sb + SM_R) / 2)
            : "memory");
        const uint32_t wch = lds32(sb + SM_MISC + 12) + 1 + pw;
        const uint32_t ra = sb + SM_R + wch * 16, bar = sb + SM_BAR + wch * 8;
        const uint32_t target = lds32(sb + SM_MISC + 16);
        uint32_t cnt = lds128(sb + SM_MISC + 32).w;
        for (int n = 0; n < 1000000 && (int)(cnt - target) < 0; n++)
            asm volatile("ld.acquire.gpu.global.u32 %0, [%1+12];" : "=r"(cnt) : "l"(g_sync) : "memory");
        uint4 a, b;
        for (int n = 0; n < 1000000; n++) {
            a = lds128(ra), b = lds128(ra + 0x2000);
            if (!((a.x | a.y | a.z | a.w | b.x | b.y | b.z | b.w) & 1)) break;
        }
        asm volatile("fence.proxy.async.global;" ::: "memory");
        asm volatile("mbarrier.arrive.expect_tx.shared.b64 _, [%0], 8192;" ::"r"(bar) : "memory");
        const uint32_t c[8] = {a.x, a.y, a.z, a.w, b.x, b.y, b.z, b.w};
#pragma unroll
        for (int i = 0; i < 8; i++)
            asm volatile("cp.async.bulk.shared::cluster.global.mbarrier::complete_tx::bytes [%0], [%1], 1024, [%2];" ::"r"(
                             (c[i] & 0xffe) << 6),
                         "l"(g_wf + (pw * 8 + i) * 64), "r"(bar)
                         : "memory");
    }
}

#define BARINIT(w, n)                                                                                              \
    if (elect()) {                                                                                                 \
        _Pragma("unroll") for (int k = 0; k < (NBAR + n - 1) / n; k++)                                             \
            asm volatile("mbarrier.init.shared.b64 [%0], 1;" ::"r"(sb + SM_BAR + ((w) * ((NBAR + n - 1) / n) + k) * 8)); \
        asm volatile("fence.mbarrier_init.release.cluster;" ::: "memory");                                         \
    }                                                                                                              \
    __syncwarp();

#define BARINIT2(from, n)                                                                                          \
    _Pragma("unroll") for (int k = 0; k < n; k++)                                                                  \
        asm volatile("mbarrier.init.shared.b64 [%0], 1;" ::"r"(sb + SM_BAR + (from + warp * n + k) * 8));

__global__ void __launch_bounds__(NT, 1)
main_kernel(const __grid_constant__ CUtensorMap tmx, const __nv_bfloat16* __restrict__ x, const int* __restrict__ src,
            const int* __restrict__ dst, const __nv_bfloat16* __restrict__ sh, const __nv_bfloat16* __restrict__ ea,
            const __nv_bfloat16* __restrict__ cg, const __nv_bfloat16* __restrict__ wr,
            const __nv_bfloat16* __restrict__ wout, __nv_bfloat16* __restrict__ out, int N, int E, int npb,
            unsigned npb_magic, int chunk, unsigned wsz, unsigned wmagic, unsigned bkm, int tau, int ramp, int rampn, int tdelay, unsigned polld, int spr, int sprn) {
    extern __shared__ __align__(1024) unsigned char smem[];
    if (s2u(smem) != sb) __trap();
    const int tid = threadIdx.x, lane = tid & 31;
    const int warp = __shfl_sync(0xffffffffu, tid >> 5, 0);
    const int nbins = gridDim.x;
    bool fast = chunk > 0;
    TLSTAMP(0);
    if (fast) {
        const int e0 = blockIdx.x * chunk + tid, left = min(E, (int)(blockIdx.x + 1) * chunk) - e0;
        uint32_t pd[KE], ps[KE];
        {
            const int* dp = dst + e0;
            const int* sp = src + e0;
#pragma unroll
            for (int k = 0; k < KE; k++) {
                pd[k] = (nbins + (k == KE - 1 ? lane : 0)) * npb, ps[k] = 0;
                asm volatile("{\n.reg .pred p;\nsetp.gt.s32 p, %4, %5;\n@p ld.global.nc.u32 %0, [%2];\n@p ld.global.nc.u32 %1, [%3];\n}"
                             : "+r"(pd[k]), "+r"(ps[k]) : "l"(dp + k * NT), "l"(sp + k * NT), "r"(left), "r"(k * NT));
            }
        }
        uint32_t epoch = 0;
        if (tid == NT - 1) asm volatile("ld.relaxed.gpu.global.u32 %0, [%1];" : "=r"(epoch) : "l"(&g_epoch) : "memory");
        uint4 wv, wo[3];
        const bool wrow = (tid >> 2) == WFT && blockIdx.x < 128;
        {
            const uint4* wp = tid < 256 ? (const uint4*)wr + tid
                              : wrow    ? (const uint4*)(wout + blockIdx.x * 128 + (tid & 3) * 32)
                                        : (const uint4*)cg + (tid & 7);
            if (tid < 264 || wrow) wv = __ldg(wp);
            if (wrow) wo[0] = __ldg(wp + 1), wo[1] = __ldg(wp + 2), wo[2] = __ldg(wp + 3);
        }
        const uint32_t t16 = sb + tid * 16;
        const uint32_t sa = sb + SC_STG + (tid >> 3) * CP + (tid & 7) * 16;
        const uint32_t sm = sb + SC_STG + (tid >> 2) * CP + (tid & 3) * 16 + 128;
        const uint32_t none = (40 * NWIN + (lane & 7) + (blockIdx.x & 3) * 8) << 2;
        const uint32_t pade = min(blockIdx.x * chunk, E - 1) << 13;
        const bool third = warp * 4 + 128 < nbins, second = warp * 8 + 128 < nbins;
#pragma unroll
        for (int k = 0; k < 3; k++)
            if (k < 2 || third) sts128(sa + k * 64 * CP, none, none, none, none);
#pragma unroll
        for (int k = 0; k < 2; k++)
            if (k < 1 || second) sts128(sm + k * 128 * CP, none, none, none, none);
        if (tid < MAXB + 32) sts32(sb + SC_CNT + tid * 4, 0);
        if (tid < NBAR) sts32(sb + SM_OFF + tid * 4, 1000000);
#pragma unroll
        for (int k = 0; k < 3; k++) sts128(t16 + SC_TABB + k * NT * 16, 0, 0, 0, 0);
        const uint32_t ecomp = -(wsz * (CH << 13));
#pragma unroll
        for (int k = 0; k < 3; k++)
            sts128(t16 + SC_TMP + k * NT * 16, 0, pade + ecomp, 0, pade + ecomp);
#pragma unroll
        for (int k = 0; k < ZSL / 8; k++) sts128(t16 + k * NT * 16, 0, 0, 0, 0), sts128(t16 + SP * 1024 + PH + k * NT * 16, 0, 0, 0, 0);
        if (tid < RP / 4) {
            uint32_t c[4], d[4];
#pragma unroll
            for (int i = 0; i < 4; i++) {
                const uint32_t k = tid * 4 - 4 + i;
                c[i] = d[i] = 0xc0000001u;
                if (warp == 0 && k < SP) c[i] += sb / 64 - 1 + k * 16;
                if (warp == 0 && k < SP - WSL) d[i] = c[i] + (SP * 1024 + PH) / 64;
            }
            static_assert(SP + 4 <= 128, "first warp");
            sts128(t16 + SM_R, c[0], c[1], c[2], c[3]);
            sts128(t16 + SM_R + 0x2000, d[0], d[1], d[2], d[3]);
        }
        constexpr uint32_t OLEND = (7u << 28) | ((RECN - 4) * 4);
        if (tid < NCW * OLN / 4) sts128(t16 + SM_OL, OLEND, OLEND, OLEND, OLEND);
        if (warp == 12) {
            sts32(sb + SM_CTR + lane * 16 + (lane >> 3) * 4,
                  sb + SM_R + ((lane & 0x19) ? (RP - 1) * 4 : (4 + SP) * 4 + (((lane >> 1) ^ (lane >> 2)) & 1) * 0x2000 + (lane & 4)));
            if (lane < 3) sts32(sb + SM_MISC + (lane ? 16 + lane * 4 : 4), 0);
            if (lane == 8) sts128(sb + SM_REC + (RECN - 4) * 4, pade, pade, pade, pade), sts128(sb + SM_MISC + 64, 0, 0, 0, 0);
            if (lane == 9) asm volatile("prefetch.tensormap [%0];" ::"l"(&tmx) : "memory");
        }
        __syncthreads();
        TLSTAMP(1);

        {
            uint32_t b[KE], r[KE];
#pragma unroll
            for (int k = 0; k < KE; k++) {
                b[k] = __umulhi(pd[k], npb_magic);
                r[k] = atoms_add(sb + SC_CNT + b[k] * 4, 4);
                if (k == KE - 1) b[k] = min(b[k], nbins);
            }
            if (tid == NT - 1) {
                sts32(sb + SM_MISC + 8, epoch % 3 + 1);
                asm volatile("{\n.reg .b64 t;\nmov.u64 t, %%globaltimer;\nred.relaxed.gpu.global.max.u64 [%0], t;\n"
                             "red.relaxed.gpu.global.add.u32 [%0+8], 1;\n}" ::"l"(g_sync) : "memory");
            }
            __syncwarp();
#pragma unroll
            for (int k = 0; k < KE; k++) {
                asm volatile(
                    "{\n.reg .pred p;\n.reg .b32 d, t, u;\nmad.lo.u32 d, %1, %3, %0;\nsetp.ge.u32 p, d, 40;\nmul.hi.u32 u, %2, %4;\n"
                    "mad.lo.u32 t, %2, %10, %5;\nmad.lo.u32 t, d, %11, t;\nmad.lo.u32 t, u, %12, t;\n@p add.u32 t, t, %7;\n"
                    "min.u32 d, %6, 188;\nmad.lo.u32 d, %1, %9, d;\nst.shared.b32 [d+%8], t;\n}" ::"r"(pd[k]),
                    "r"(b[k]), "r"(ps[k]), "r"(-npb), "r"(wmagic), "r"(((tid + k * NT) << 14) + 4), "r"(r[k]), "n"(2 - 40 * NWIN * 4),
                    "n"(sb + SC_STG), "n"(CP), "n"(CH << 14), "n"(NWIN * 4), "r"(4 - wsz * (CH << 14))
                    : "memory");
            }
        }
        if (tid < 264) sts128(sb + SC_WR + (tid >> 4) * 272 + (tid & 15) * 16, wv.x, wv.y, wv.z, wv.w);
        uint4* gp = g_cell + ((tid >> 3) * MAXB + blockIdx.x) * 8 + (tid & 7);
        uint4* gm = g_more + ((tid >> 2) * MAXB + blockIdx.x) * 4 + (tid & 3);
        __syncthreads();
        TLSTAMP(6);
        const uint32_t tag = lds32(sb + SM_MISC + 8), t0 = tag & 1, t1 = tag >> 1;
        {
            uint4 v[5];
#pragma unroll
            for (int k = 0; k < 5; k++)
                if (k != 2 && k != 4 || (k == 2 ? third : second)) v[k] = lds128(k < 3 ? sa + k * 64 * CP : sm + (k - 3) * 128 * CP);
#pragma unroll
            for (int k = 0; k < 5; k++)
                if (k != 2 && k != 4 || (k == 2 ? third : second))
                    st_cell(k < 3 ? gp + k * 64 * MAXB * 8 : gm + (k - 3) * 128 * MAXB * 4, v[k].x | t0, v[k].y | t1, v[k].z | t0, v[k].w | t1);
        }
        if (wrow) {
            const int k = blockIdx.x;
            uint4* dp = &g_wf[PH == 128 ? ((tid & 3) * 8 + ((k & 63) >> 3)) * 64 + (k >> 6) * 32 + (k & 7) : ((tid & 3) * 8 + (k >> 4)) * 64 + (k & 8) * 4 + (k & 7)];
            dp[0] = make_uint4(wv.x, wo[0].x, wo[1].x, wo[2].x);
            dp[8] = make_uint4(wv.y, wo[0].y, wo[1].y, wo[2].y);
            dp[16] = make_uint4(wv.z, wo[0].z, wo[1].z, wo[2].z);
            dp[24] = make_uint4(wv.w, wo[0].w, wo[1].w, wo[2].w);
        }
        if (warp < 15) { BARINIT(warp, 15) }
        __syncwarp();
        if (tid == NT - 1) {
            uint4 q;
            for (int n = 0; n < (1 << 22); n++) {
                q = ld_cell((const uint4*)g_sync);
                if ((int)(q.z - (epoch + 1) * nbins) >= 0) break;
            }
            sts128(sb + SM_MISC + 32, q.x, q.y, q.z, q.w), sts32(sb + SM_MISC + 16, (epoch + 1) * 512);
            asm volatile("mbarrier.init.shared.b64 [%0], 1;" ::"r"(sb + SM_MISC + 48) : "memory");
            while ((uint32_t)(gt_lo() - q.x) < polld) {}
        }
        __syncthreads();
        TLSTAMP(14);
        uint32_t m[20], rk[20], ia[20], eb[2];
        eb[0] = (((tid >> 3) * chunk) << 13) + ecomp + 1;
        eb[1] = eb[0] + (chunk << 19);
        asm volatile("" : "+r"(eb[0]), "+r"(eb[1]));
        bool ext;
        {
            const uint4* hp = g_cell + blockIdx.x * (MAXB * 8) + tid;
            const uint4* hm = g_more + blockIdx.x * (MAXB * 4) + tid;
            uint4 q[5];
            q[2] = q[4] = make_uint4(none | t0, none | t1, none | t0, none | t1);
            for (int n = 0; n < (1 << 22); n++) {
                q[0] = ld_cell(hp), q[1] = ld_cell(hp + NT), q[3] = ld_cell(hm);
                if ((tid >> 3) + 128 < nbins) q[2] = ld_cell(hp + 2 * NT);
                if ((tid >> 2) + 128 < nbins) q[4] = ld_cell(hm + NT);
                uint32_t bad = 0;
#pragma unroll
                for (int k = 0; k < 5; k++)
                    asm("{\n.reg .b32 a, b;\nlop3.b32 a, %1, %2, %5, 0x7e;\nlop3.b32 b, %3, %4, %6, 0x7e;\nlop3.b32 %0, %0, a, b, 0xfe;\n}"
                        : "+r"(bad) : "r"(q[k].x), "r"(q[k].z), "r"(q[k].y), "r"(q[k].w), "r"(t0), "r"(t1));
                if (!(bad & 1)) break;
            }
            __syncwarp();
            TLSTAMP(8);
#pragma unroll
            for (int k = 0; k < 5; k++) m[4 * k] = q[k].x, m[4 * k + 1] = q[k].y, m[4 * k + 2] = q[k].z, m[4 * k + 3] = q[k].w;
#pragma unroll
            for (int k = 0; k < 12; k++)
                if (k < 8 || third) ia[k] = m[k] & 0x3ffc, rk[k] = atoms_add(sb + SC_TABB + ia[k], 8);
            ext = __any_sync(0xffffffffu, min(m[12] & 0x3ffc, m[16] & 0x3ffc) < 40 * NWIN * 4);
            if (ext) {
#pragma unroll
                for (int k = 12; k < 20; k++) ia[k] = m[k] & 0x3ffc, rk[k] = atoms_add(sb + SC_TABB + ia[k], 8);
                if ((tid & 3) == 3 && min(m[15] & 0x3ffc, m[19] & 0x3ffc) < 40 * NWIN * 4) sts32(sb + SM_MISC + 4, 1);
            }
        }
        __syncthreads();
        TLSTAMP(5);
        const uint32_t tr = sb + warp * (NWIN * 4) + lane * 16;
        if (tid == NT - 1 && blockIdx.x == 0) g_epoch = epoch + 1;
        {
            uint4 c[3];
            uint32_t tt[3];
#pragma unroll
            for (int i = 0; i < 3; i++) {
                c[i] = make_uint4(0, 0, 0, 0);
                if ((i < 2 || warp < 8) && lane < NWIN / 4) c[i] = lds128(tr + SC_TABB + i * 16 * NWIN * 4);
                tt[i] = c[i].x + c[i].y + c[i].z + c[i].w;
            }
            const uint32_t sum = (tt[0] >> 3) + (tt[1] << 7) + (tt[2] << 17);
            const uint32_t tot = __reduce_add_sync(0xffffffffu, sum);
            uint32_t inc = scan_step(scan_step(sum, 1), 2);
            const uint32_t q = (tot + 0x300c03) & 0x3fcff3fc, q0 = q & 1023, q1 = q0 + ((q >> 10) & 1023);
            uint32_t base = atoms_add(sb + (lane ? SC_CNT + lane * 4 : SM_MISC + 20), q1 + (q >> 20));
            inc = scan_step(scan_step(scan_step(inc, 4), 8), 16);
            base = __shfl_sync(0xffffffffu, base, 0);
            const uint32_t l3 = min(lane, 2);
            sts32(sb + SC_KEY + (warp + 16 * l3) * 4, ((tot >> (10 * l3)) & 1023) * 64 + 63 - warp - 16 * l3);
            if (max(tt[0], max(tt[1], tt[2])) > 31 * 8) sts32(sb + SM_MISC + 4, 1);
            inc += q - tot - sum;
#pragma unroll
            for (int i = 0; i < 3; i++) {
                const uint32_t e = (((inc >> (10 * i)) & 1023) + base + (i == 0 ? 0 : i == 1 ? q0 : q1)) * 8;
                if ((i < 2 || warp < 8) && lane < NWIN / 4) sts128(tr + SC_TABB + i * 16 * NWIN * 4, e, e + c[i].x, e + c[i].x + c[i].y, e + tt[i] - c[i].w);
            }
        }
        __syncthreads();
        TLSTAMP(2);
        if (warp >= 11) {
            const uint32_t st = (tid - 352) >> 2, key = lds32(sb + SC_KEY + st * 4);
            uint32_t rank = 0;
#pragma unroll
            for (int i = 0; i < 5; i++) {
                const uint2 q = lds64(sb + SC_KEY + (lane & 3) * 40 + i * 8);
                rank += ((key - q.x) >> 31) + ((key - q.y) >> 31);
            }
            rank += __shfl_xor_sync(0xffffffffu, rank, 1);
            rank += __shfl_xor_sync(0xffffffffu, rank, 2);
            const uint32_t lv = rank >> 2, cw = ((0x969u >> (2 * lv)) & 3) * 4 + ((rank ^ -(lv & 1)) & 3);
            const uint32_t sid = (0xe4a50u >> (2 * lv)) & 3;
            sts32(sb + SC_MAP + st * 4, cw * (NWIN * 4) - st * (NWIN * 4) + 0x10000 + (sid << 28));
            asm volatile("st.shared.u8 [%0], %1;" ::"r"(sb + SM_INV + cw * 4 + sid), "r"(st) : "memory");
        }
        const int total = lds32(sb + SM_MISC + 20);
        fast = lds32(sb + SM_MISC + 4) == 0 && total <= RECN - 4;
        auto lookup = [&](int k) {
            asm volatile("{\n.reg .pred p;\n.reg .b32 t;\nsetp.lt.u32 p, %1, %2;\nmov.b32 t, 0x80000000;\n@p ld.shared.b32 t, [%1+%3];\nadd.u32 %0, %0, t;\n}"
                         : "+r"(rk[k]) : "r"(ia[k]), "n"(40 * NWIN * 4), "n"(sb + SC_TABB) : "memory");
        };
        auto place = [&](int k, uint32_t e) {
            asm volatile("{\n.reg .pred p;\nsetp.ge.s32 p, %0, 0;\n@p st.shared.v2.b32 [%0+%3], {%1, %2};\n}" ::"r"(rk[k]), "r"(m[k]), "r"(e),
                         "n"(sb + SC_TMP) : "memory");
        };
#pragma unroll
        for (int k = 0; k < 8; k++) lookup(k);
        if (fast) {
#pragma unroll
            for (int k = 0; k < 8; k++) place(k, eb[k >> 2]);
            if (third) {
#pragma unroll
                for (int k = 8; k < 12; k++) lookup(k);
#pragma unroll
                for (int k = 8; k < 12; k++) place(k, 2 * eb[1] - eb[0]);
            }
            if (ext) {
#pragma unroll
                for (int k = 12; k < 20; k++) lookup(k);
#pragma unroll
                for (int k = 12; k < 20; k++) place(k, ((((tid >> 2) + (k >> 4) * 128) * chunk) << 13) + ecomp + 1);
            }
            constexpr int KD = (RECN + NT - 1) / NT;
            const uint32_t P = (lane ^ (lane >> 1)) & 1;
            const uint32_t binc = (P ? 1u << 11 : 1u) + ((lane & 3) == 3 ? 1u << 22 : 0u);
            const bool last = warp * 32 + (KD - 1) * NT < total, q2 = warp * 128 + NT * 4 < total;
            const int rest = total - tid, restq = (total >> 2) - tid;
            uint2 en[KD];
            uint32_t bk[KD], r2[KD], ca[2], ol[2], r3[2];
            __syncthreads();
            TLSTAMP(9);
#pragma unroll
            for (int k = 0; k < KD; k++)
                if (k < KD - 1 || last) en[k] = lds64(sb + SC_TMP + tid * 8 + k * NT * 8);
#pragma unroll
            for (int k = 0; k < 2; k++)
                if (k == 0 || q2) ca[k] = lds32(sb + SC_TMP + (tid + k * NT) * 32 + 24);
#pragma unroll
            for (int k = 0; k < 2; k++)
                if (k == 0 || q2) ca[k] &= 0x3ffc, ol[k] = lds32(sb + SC_MAP + __umulhi(ca[k], 0xffffffffu / (NWIN * 4) + 1) * 4);
#pragma unroll
            for (int k = 0; k < KD; k++) {
                if (k < KD - 1 || last) {
                    const uint32_t v = en[k].x, f = v >> 14, i = v & 0x3ffc;
                    const uint32_t w4 = i - __umulhi(i, 0xffffffffu / (NWIN * 4) + 1) * (NWIN * 4);
                    const uint32_t o = __umulhi(f, 0xffffffffu / CH + 1) - wsz;
                    bk[k] = (__umulhi(f, bkm) + w4) * 4;
                    en[k].x = (w4 >> 2) * wsz + o;
                    en[k].y += ((v >> 1) & 0xffffe001u) - o * (CH << 13);
                    if (rest <= k * NT) bk[k] = 2048 + lane * 4;
                    r2[k] = atoms_add(sb + SC_TABA + bk[k], binc);
                }
            }
#pragma unroll
            for (int k = 0; k < 2; k++) {
                if (k == 0 || q2) {
                    ca[k] = (ca[k] + ol[k]) & 0xffff;
                    ol[k] = (tid + k * NT) * 16 + (ol[k] & 0x30000000);
                    r3[k] = atoms_add(sb + SC_TABC + ca[k], restq > k * NT ? 4 : 0);
                }
            }
            __syncthreads();
            TLSTAMP(12);
            if (warp < NCW) {
                uint4 c = make_uint4(0, 0, 0, 0);
                if (lane < NWIN / 4) c = lds128(tr + SC_TABC);
                const uint32_t tt = c.x + c.y + c.z + c.w;
                uint32_t inc = tt;
#pragma unroll
                for (int o = 1; o < 32; o <<= 1) inc = scan_step(inc, o);
                if (inc > (OLN - 6) * 4) sts32(sb + SM_MISC + 4, 1);
                inc += warp * (OLN * 4) - tt;
                if (lane < NWIN / 4) sts128(tr + SC_TABC, inc, inc + c.x, inc + c.x + c.y, inc + tt - c.w);
            } else {
                const uint32_t mine = (warp + lane) & 3;
                uint4 c;
                uint32_t cs, inc = 0, e = 4 + (4 << 11);
#pragma unroll
                for (int i = 0; i < 4; i++) {
                    const uint32_t pc = (mine + i) & 3;
                    const uint4 v = lds128(sb + SC_TABA + lane * 64 + (pc << 4));
                    const uint32_t sum = v.x + v.y + v.z + v.w;
                    inc += sum;
                    if (i == 0) c = v, cs = sum;
                    if (pc >= mine) e -= sum;
                }
#pragma unroll
                for (int o = 1; o < 32; o <<= 1) inc = scan_step(inc, o);
                e += inc;
                sts128(sb + SC_TABB + lane * 64 + (mine << 4), e, e + c.x, e + c.x + c.y, e + cs - c.w);
                if ((int)max((e + cs) & 0x7ff, ((e + cs) >> 11) & 0x7ff) - (int)(e >> 22) * 2 > SP) sts32(sb + SM_MISC + 4, 1);
                if (tid == NCW * 32) {
                    const uint32_t c0 = min(min(c.x & 0x7ff, (c.x >> 11) & 0x7ff), ZSL) >> 2;
                    sts32(sb + SM_MISC + 12, ((total >> 2) + 1) >> 1), sts32(sb + SM_MISC + 24, c0);
                }
            }
            __syncthreads();
            TLSTAMP(13);
            fast = lds32(sb + SM_MISC + 4) == 0;
            if (warp == 15 && lane < lds32(sb + SM_MISC + 24))
                asm volatile("mbarrier.arrive.shared.b64 _, [%0];" ::"r"(sb + SM_BAR + 8 + lane * 8) : "memory");
#pragma unroll
            for (int k = 0; k < KD; k++)
                if (k < KD - 1 || last) r2[k] += lds32(sb + SC_TABB + bk[k]);
#pragma unroll
            for (int k = 0; k < 2; k++)
                if (k == 0 || q2) r3[k] += lds32(sb + SC_TABC + ca[k]);
            if (fast) {
                const uint32_t rot = P ? 9 : 30;
#pragma unroll
                for (int k = 0; k < KD; k++) {
                    if (k < KD - 1 || last) {
                        const uint32_t k4 = __funnelshift_r(r2[k], r2[k], rot);
                        if (rest > k * NT) {
                            sts16(sb + SM_R + 2 + bitsel(k4, P << 13), en[k].x);
                            sts32(sb + SM_REC + tid * 4 + k * NT * 4, bitsel(k4, en[k].y));
                        }
                    }
                }
#pragma unroll
                for (int k = 0; k < 2; k++)
                    if ((k == 0 || q2) && restq > k * NT) sts32(sb + SM_OL + r3[k], ol[k]);
            }
        }
        asm volatile("fence.mbarrier_init.release.cluster;\nfence.proxy.async.shared::cta;" ::: "memory");
        __syncthreads();
        TLSTAMP(3);
        if (!fast && wrow) wf_done();
        if (fast && tid < NBAR) {
            const uint4 a = lds128(t16 + SM_R), b = lds128(t16 + SM_R + 0x2000);
            const int s = (((int)a.x >> 3) + ((int)a.y >> 3) + ((int)a.z >> 3) + ((int)a.w >> 3) + ((int)b.x >> 3) + ((int)b.y >> 3) +
                           ((int)b.z >> 3) + ((int)b.w >> 3)) >> 16;
            sts32(sb + SM_OFF + tid * 4, tdelay + ((s * tau + min(s, rampn) * ramp - max(s - sprn, 0) * spr) >> 10));
        }
        __syncwarp();
    }

    if (!fast) {
        float* accs = (float*)smem;
        constexpr int NACC = 96;
        const int node0 = blockIdx.x * npb, nnodes = max(0, min(npb, N - node0));
#pragma unroll 1
        for (int nb = 0; nb < nnodes; nb += NACC) {
            __syncthreads();
            for (int i = tid; i < NACC * 512; i += NT) accs[i] = 0.f;
            __syncthreads();
            const int lim = min(NACC, nnodes - nb);
#pragma unroll 1
            for (int base = warp * 32; base < E; base += NT) {
                const int e = base + lane;
                const int dl = e < E ? dst[e] - node0 - nb : -1;
                unsigned mask = __ballot_sync(0xffffffffu, dl >= 0 && dl < lim);
#pragma unroll 1
                while (mask) {
                    const int l = __ffs(mask) - 1;
                    mask &= mask - 1;
                    const int dd = __shfl_sync(0xffffffffu, dl, l);
                    slow_edge(base + l, src[base + l], accs + dd * 512, x, sh, ea, cg, wr, lane);
                }
            }
            __syncthreads();
#pragma unroll 1
            for (int nl = warp; nl < lim; nl += NT / 32) slow_out(accs + nl * 512, wout, out + (size_t)(node0 + nb + nl) * 512, lane);
        }
    } else if (warp >= NCW) {
        asm volatile("setmaxnreg.dec.sync.aligned.u32 %0;" ::"n"(PREG));
        producer(&tmx, warp - NCW);
    } else if (warp >= 4) {
        asm volatile("setmaxnreg.inc.sync.aligned.u32 %0;" ::"n"(R1));
        consumer<3>(sh, ea, out, N, npb);
        TLMAX(4);
    } else {
        asm volatile("setmaxnreg.inc.sync.aligned.u32 %0;" ::"n"(R0));
        consumer<4>(sh, ea, out, N, npb);
        TLMAX(4);
    }
}

typedef CUresult (*EncodeTiledFn)(CUtensorMap*, CUtensorMapDataType, cuuint32_t, void*, const cuuint64_t*,
                                  const cuuint64_t*, const cuuint32_t*, const cuuint32_t*, CUtensorMapInterleave,
                                  CUtensorMapSwizzle, CUtensorMapL2promotion, CUtensorMapFloatOOBfill);

extern "C" void kernel_launch(void* const* d_in, const int* in_sizes, int n_in, void* d_out, int out_size) {
    const __nv_bfloat16* x = (const __nv_bfloat16*)d_in[0];
    const int* src = (const int*)d_in[1];
    const int* dst = (const int*)d_in[2];
    const __nv_bfloat16* sh = (const __nv_bfloat16*)d_in[3];
    const __nv_bfloat16* ea = (const __nv_bfloat16*)d_in[4];
    const __nv_bfloat16* cg = (const __nv_bfloat16*)d_in[5];
    const __nv_bfloat16* wr = (const __nv_bfloat16*)d_in[6];
    const __nv_bfloat16* wout = (const __nv_bfloat16*)d_in[7];
    __nv_bfloat16* out = (__nv_bfloat16*)d_out;
    const int N = in_sizes[0] / 512;
    const int E = in_sizes[1];

    static int num_sms = 0, coresident = 0;
    static EncodeTiledFn encode = nullptr;
    if (num_sms == 0) {
        int dev = 0;
        cudaGetDevice(&dev);
        cudaDeviceGetAttribute(&num_sms, cudaDevAttrMultiProcessorCount, dev);
        cudaFuncSetAttribute(main_kernel, cudaFuncAttributeMaxDynamicSharedMemorySize, SM_TOTAL);
        int occ = 0;
        cudaOccupancyMaxActiveBlocksPerMultiprocessor(&occ, main_kernel, NT, SM_TOTAL);
        coresident = occ * num_sms;
        void* fn = nullptr;
        cudaDriverEntryPointQueryResult qr;
        cudaGetDriverEntryPoint("cuTensorMapEncodeTiled", &fn, cudaEnableDefault, &qr);
        encode = (EncodeTiledFn)fn;
    }
    CUtensorMap tmx;
    const int rank = 3;
    const cuuint64_t gd[3] = {64, (cuuint64_t)N * 4, 2}, gs[2] = {256, 128};
    const cuuint32_t bd[3] = {64, 4, 2}, es[3] = {1, 1, 1};
    encode(&tmx, CU_TENSOR_MAP_DATA_TYPE_BFLOAT16, rank, (void*)x, gd, gs, bd, es, CU_TENSOR_MAP_INTERLEAVE_NONE,
           CU_TENSOR_MAP_SWIZZLE_128B, CU_TENSOR_MAP_L2_PROMOTION_NONE, CU_TENSOR_MAP_FLOAT_OOB_FILL_NONE);

    int nbins = num_sms < MAXB ? num_sms : MAXB;
    int npb = (N + nbins - 1) / nbins;
    if (npb < 2) npb = 2;
    nbins = (N + npb - 1) / npb;
    const unsigned npb_magic = (unsigned)((0x100000000ull + npb - 1) / npb);
    int chunk = (E + nbins - 1) / nbins;
    const unsigned wsz = (N + NWIN - 2) / (NWIN - 1);
    if (nbins > coresident || nbins < 128 || npb > MAXNPB || chunk > CH || wsz > (1 << 18) / CH || N < 512 || E > (1 << 19)) chunk = 0;
    const unsigned wmagic = 0xffffffffu / wsz + 1, bkm = (unsigned)((4ull << 32) / (wsz * CH));
    double pace = PACE, rampt = RAMP, rampf = RAMPF, sprt = SPRINT, sprf = SPRINTF;
    int tdelay = TDELAY, polld = POLLD;
    const int tau = (int)(1024.0 * pace * ((double)E / nbins) / N);
    const int rampn = (int)(N * rampf), ramp = (int)(1024.0 * rampt / rampn);
    main_kernel<<<nbins, NT, SM_TOTAL, cudaStreamPerThread>>>(tmx, x, src, dst, sh, ea, cg, wr, wout, out, N, E, npb, npb_magic,
                                                              chunk, wsz, wmagic, bkm, tau, ramp, rampn, tdelay, polld, (int)(1024.0 * sprt / (N * sprf)), (int)(N * (1 - sprf)));
}
```

```cpp
#include <cuda_runtime.h>
#include <cuda.h>
#include <cuda_bf16.h>
#include <stdint.h>
#include <stdlib.h>

#define NT 512
#define NCW 12
#define MAXB 144
#define MAXNPB 80
#define KE 5
#define SP 99
#define RECN 2752
#define RP 1484
#define OLN 80
#define NBAR 350
#define NOFF 352
#define R0 168
#define R1 160
#define PREG 24
#define PACE 10.05
#define TDELAY 4550
#define POLLD 1000
#define WFT 80
#define SLIPTH 500
#define SLIPSUB 250
#define SLIPFROM 36
#define AHEAD 96
#define EARLY 32
#define RAMPF 0.1
#define SPRINT 500
#define SPRINTF 0.5
#define SLIPEND 640
#define SPINT 96
#define RAMP 600

__device__ __align__(1024) uint4 g_cell[MAXB * MAXB * 8];
__device__ __align__(1024) uint4 g_more[MAXB * MAXB * 4];
__device__ __align__(1024) uint4 g_wf[2048];
__device__ __align__(256) ulonglong2 g_sync[16];
__device__ __align__(256) unsigned g_epoch;
#define TLSTAMP(i)
#define TLMAX(i)

constexpr uint32_t sb = 1024;
#define PH 512
#define SM_R (2 * SP * 1024 + PH)
#define SM_CTR (SP * 1024)
#define SM_MISC (SM_R + RP * 4)
#define SM_INV (SM_MISC + 80)
#define SM_OL (SM_INV + 48)
#define SM_REC (SM_R + 0x2000 + RP * 4)
#define SM_OFF (SM_REC + RECN * 4)
#define SM_BAR (SM_OFF + NOFF * 2)
#define SM_TOTAL (SM_BAR + NBAR * 8)
static_assert(SM_TOTAL <= 232448 && SM_OL + NCW * OLN * 2 <= SM_R + 0x2000 && SM_OL % 16 == 0 && SM_BAR % 16 == 0, "shared memory");
static_assert(4 + RECN / 2 + SP + 2 <= RP && RECN / 8 + 5 <= NBAR && NBAR % 14 == 0 && RECN / 8 + 4 <= NOFF, "tables");
#define ZSL 32
#define NWIN 96
#define CH 2432
#define CP 208
#define SC_STG ((SP + ZSL) * 1024 + PH)
#define SC_TMP (ZSL * 1024)
#define SC_TABB (SC_TMP + 3072 * 8)
#define SC_TABC (SC_TABB + 41 * NWIN * 4)
#define SC_TABA (SC_TABC + NCW * NWIN * 4)
#define SC_ZEND (SC_TABB + 3 * NT * 16)
#define SC_CNT SC_ZEND
#define SC_KEY (SC_CNT + (MAXB + 32) * 4)
#define SC_MAP (SC_KEY + 192)
#define WSL 5
#define SC_WR ((2 * SP - WSL) * 1024 + PH)
#define SC_CG (SC_WR + 16 * 272)
static_assert(SC_TABA + 2048 + 128 <= SC_ZEND && RECN <= 3072 && SC_MAP + 192 <= SP * 1024 && SC_STG + (MAXB + 1) * CP <= SC_WR, "scratch");

__device__ __forceinline__ uint32_t pack_bf16(float lo, float hi) {
    uint32_t r;
    asm("cvt.rn.bf16x2.f32 %0, %1, %2;" : "=r"(r) : "f"(hi), "f"(lo));
    return r;
}
__device__ __forceinline__ uint32_t s2u(const void* p) { return (uint32_t)__cvta_generic_to_shared(p); }
__device__ __forceinline__ void mbar_wait0(uint32_t a) {
    asm volatile(
        "{\n.reg .pred p, q;\n.reg .u32 n;\nmov.u32 n, 0;\n"
        "LAB_WAIT:\nmbarrier.try_wait.parity.shared.b64 p, [%0], 0;\nadd.u32 n, n, 1;\nsetp.lt.and.u32 q, n, 1000000, !p;\n@q bra LAB_WAIT;\n}" ::"r"(a)
        : "memory");
}
__device__ __forceinline__ uint32_t lds8(uint32_t a) { uint32_t v; asm volatile("ld.shared.u8 %0, [%1];" : "=r"(v) : "r"(a) : "memory"); return v; }
__device__ __forceinline__ uint32_t lds16(uint32_t a) { uint32_t v; asm volatile("ld.shared.u16 %0, [%1];" : "=r"(v) : "r"(a) : "memory"); return v; }
__device__ __forceinline__ uint32_t lds32(uint32_t a) { uint32_t v; asm volatile("ld.shared.u32 %0, [%1];" : "=r"(v) : "r"(a) : "memory"); return v; }
__device__ __forceinline__ uint2 lds64(uint32_t a) {
    uint2 v; asm volatile("ld.shared.v2.u32 {%0,%1}, [%2];" : "=r"(v.x), "=r"(v.y) : "r"(a) : "memory"); return v;
}
__device__ __forceinline__ uint4 lds128(uint32_t a) {
    uint4 v; asm volatile("ld.volatile.shared.v4.u32 {%0,%1,%2,%3}, [%4];" : "=r"(v.x), "=r"(v.y), "=r"(v.z), "=r"(v.w) : "r"(a) : "memory"); return v;
}
__device__ __forceinline__ void sts16(uint32_t a, uint32_t v) { asm volatile("st.shared.u16 [%0], %1;" ::"r"(a), "h"((unsigned short)v) : "memory"); }
__device__ __forceinline__ void sts32(uint32_t a, uint32_t v) { asm volatile("st.shared.u32 [%0], %1;" ::"r"(a), "r"(v) : "memory"); }
__device__ __forceinline__ void sts64(uint32_t a, uint32_t x, uint32_t y) { asm volatile("st.shared.v2.u32 [%0], {%1,%2};" ::"r"(a), "r"(x), "r"(y) : "memory"); }
__device__ __forceinline__ void sts128(uint32_t a, uint32_t x, uint32_t y, uint32_t z, uint32_t w) {
    asm volatile("st.shared.v4.u32 [%0], {%1,%2,%3,%4};" ::"r"(a), "r"(x), "r"(y), "r"(z), "r"(w) : "memory");
}
__device__ __forceinline__ uint32_t atoms_add(uint32_t a, uint32_t v) {
    uint32_t r;
    asm volatile("atom.shared.add.u32 %0, [%1], %2;" : "=r"(r) : "r"(a), "r"(v) : "memory");
    return r;
}
__device__ __forceinline__ uint4 ld_cell(const uint4* p) {
    uint4 v;
    asm volatile("{\n.reg .b64 a, b;\nld.relaxed.gpu.global.v2.b64 {a, b}, [%4];\nmov.b64 {%0,%1}, a;\nmov.b64 {%2,%3}, b;\n}"
                 : "=r"(v.x), "=r"(v.y), "=r"(v.z), "=r"(v.w) : "l"(p) : "memory");
    return v;
}
__device__ __forceinline__ void st_cell(uint4* p, uint32_t x, uint32_t y, uint32_t z, uint32_t w) {
    asm volatile("st.relaxed.gpu.global.v2.b64 [%0], {%1, %2};" ::"l"(p), "l"(x | (uint64_t)y << 32), "l"(z | (uint64_t)w << 32) : "memory");
}
__device__ __forceinline__ uint32_t scan_step(uint32_t v, int o) {
    asm volatile("{\n.reg .pred p;\n.reg .b32 y;\nshfl.sync.up.b32 y|p, %0, %1, 0, 0xffffffff;\n@p add.u32 %0, %0, y;\n}" : "+r"(v) : "r"(o));
    return v;
}
__device__ __forceinline__ uint32_t bitsel(uint32_t a, uint32_t b) {
    uint32_t r;
    asm("lop3.b32 %0, %1, %2, 0x1ffc, 0xe4;" : "=r"(r) : "r"(a), "r"(b));
    return r;
}
__device__ __forceinline__ uint32_t movm(uint32_t a) {
    uint32_t r;
    asm volatile("movmatrix.sync.aligned.m8n8.trans.b16 %0, %1;" : "=r"(r) : "r"(a));
    return r;
}
__device__ __forceinline__ uint32_t gt_lo() {
    uint32_t t;
    asm volatile("mov.u32 %0, %globaltimer_lo;" : "=r"(t));
    return t;
}
__device__ __forceinline__ bool elect() {
    uint32_t p;
    asm volatile("{\n.reg .pred P;\nelect.sync _|P, 0xffffffff;\nselp.u32 %0, 1, 0, P;\n}" : "=r"(p));
    return p;
}
__device__ __forceinline__ void project4(const uint32_t (&pk)[64], uint32_t ra, uint32_t ba, uint4* const (&p)[4], const uint32_t (&v)[4]) {
    asm volatile(
        "{\n.reg .pred p0, p1, q0, q1, nv, s<4>;\n.reg .b32 t, h, c<16>, a<32>, b<32>, k<16>;\n.reg .b64 d<16>;\n.reg .f32 o<32>;\nsetp.ne.b32 p0, 0, 0;\n"
        "setp.eq.b32 p1, 0, 0;\nmov.b32 h, 8;\nsetp.eq.u32 nv, %64, 0;\nvote.sync.any.pred nv, nv, 0xffffffff;\nsetp.ne.b32 s0, %69, 0;\n"
        "setp.ne.b32 s1, %70, 0;\nsetp.ne.b32 s2, %71, 0;\nsetp.ne.b32 s3, %72, 0;\nmovmatrix.sync.aligned.m8n8.trans.b16 a0, %0;\n"
        "movmatrix.sync.aligned.m8n8.trans.b16 a1, %16;\nmovmatrix.sync.aligned.m8n8.trans.b16 a2, %1;\nmovmatrix.sync.aligned.m8n8.trans.b16 a3, %17;\n"
        "movmatrix.sync.aligned.m8n8.trans.b16 a4, %2;\nmovmatrix.sync.aligned.m8n8.trans.b16 a5, %18;\nmovmatrix.sync.aligned.m8n8.trans.b16 a6, %3;\n"
        "movmatrix.sync.aligned.m8n8.trans.b16 a7, %19;\nmovmatrix.sync.aligned.m8n8.trans.b16 a8, %4;\nmovmatrix.sync.aligned.m8n8.trans.b16 a9, %20;\n"
        "movmatrix.sync.aligned.m8n8.trans.b16 a10, %5;\nmovmatrix.sync.aligned.m8n8.trans.b16 a11, %21;\nmovmatrix.sync.aligned.m8n8.trans.b16 a12, %6;\n"
        "movmatrix.sync.aligned.m8n8.trans.b16 a13, %22;\nmovmatrix.sync.aligned.m8n8.trans.b16 a14, %7;\nmovmatrix.sync.aligned.m8n8.trans.b16 a15, %23;\n"
        "movmatrix.sync.aligned.m8n8.trans.b16 a16, %8;\nmovmatrix.sync.aligned.m8n8.trans.b16 a17, %24;\nmovmatrix.sync.aligned.m8n8.trans.b16 a18, %9;\n"
        "movmatrix.sync.aligned.m8n8.trans.b16 a19, %25;\nmovmatrix.sync.aligned.m8n8.trans.b16 a20, %10;\nmovmatrix.sync.aligned.m8n8.trans.b16 a21, %26;\n"
        "movmatrix.sync.aligned.m8n8.trans.b16 a22, %11;\nmovmatrix.sync.aligned.m8n8.trans.b16 a23, %27;\nmovmatrix.sync.aligned.m8n8.trans.b16 a24, %12;\n"
        "movmatrix.sync.aligned.m8n8.trans.b16 a25, %28;\nmovmatrix.sync.aligned.m8n8.trans.b16 a26, %13;\nmovmatrix.sync.aligned.m8n8.trans.b16 a27, %29;\n"
        "movmatrix.sync.aligned.m8n8.trans.b16 a28, %14;\nmovmatrix.sync.aligned.m8n8.trans.b16 a29, %30;\nmovmatrix.sync.aligned.m8n8.trans.b16 a30, %15;\n"
        "movmatrix.sync.aligned.m8n8.trans.b16 a31, %31;\nmov.b32 t, 0;\n"
        "W0:\nmbarrier.try_wait.parity.shared.b64 q0, [%73+0], 0;\nadd.u32 t, t, 1;\nsetp.lt.and.u32 q1, t, 1000000, !q0;\n@q1 bra.uni W0;\nmov.b32 t, 0;\n"
        "W1:\nmbarrier.try_wait.parity.shared.b64 q0, [%73+8], 0;\nadd.u32 t, t, 1;\nsetp.lt.and.u32 q1, t, 1000000, !q0;\n@q1 bra.uni W1;\nmov.b32 t, 0;\n"
        "W2:\nmbarrier.try_wait.parity.shared.b64 q0, [%73+16], 0;\nadd.u32 t, t, 1;\nsetp.lt.and.u32 q1, t, 1000000, !q0;\n@q1 bra.uni W2;\nmov.b32 t, 0;\n"
        "W3:\nmbarrier.try_wait.parity.shared.b64 q0, [%73+24], 0;\nadd.u32 t, t, 1;\nsetp.lt.and.u32 q1, t, 1000000, !q0;\n@q1 bra.uni W3;\n"
        "ld.volatile.shared.v4.b32 {c0,c1,c2,c3}, [%64+0];\nld.volatile.shared.v4.b32 {c4,c5,c6,c7}, [%64+8192];\n"
        "ld.volatile.shared.v4.b32 {c8,c9,c10,c11}, [%64+16];\nld.volatile.shared.v4.b32 {c12,c13,c14,c15}, [%64+8208];\nand.b32 t, c0, 0xffe;\n"
        "mad.lo.u32 t, t, 4, 0x200000;\nmov.b64 d0, {t, h};\nand.b32 t, c1, 0xffe;\nmad.lo.u32 t, t, 4, 0x200000;\nmov.b64 d1, {t, h};\nand.b32 t, c2, 0xffe;\n"
        "mad.lo.u32 t, t, 4, 0x200000;\nmov.b64 d2, {t, h};\nand.b32 t, c3, 0xffe;\nmad.lo.u32 t, t, 4, 0x200000;\nmov.b64 d3, {t, h};\nand.b32 t, c4, 0xffe;\n"
        "mad.lo.u32 t, t, 4, 0x200000;\nmov.b64 d4, {t, h};\nand.b32 t, c5, 0xffe;\nmad.lo.u32 t, t, 4, 0x200000;\nmov.b64 d5, {t, h};\nand.b32 t, c6, 0xffe;\n"
        "mad.lo.u32 t, t, 4, 0x200000;\nmov.b64 d6, {t, h};\nand.b32 t, c7, 0xffe;\nmad.lo.u32 t, t, 4, 0x200000;\nmov.b64 d7, {t, h};\nand.b32 t, c8, 0xffe;\n"
        "mad.lo.u32 t, t, 4, 0x200000;\nmov.b64 d8, {t, h};\nand.b32 t, c9, 0xffe;\nmad.lo.u32 t, t, 4, 0x200000;\nmov.b64 d9, {t, h};\nand.b32 t, c10, 0xffe;\n"
        "mad.lo.u32 t, t, 4, 0x200000;\nmov.b64 d10, {t, h};\nand.b32 t, c11, 0xffe;\nmad.lo.u32 t, t, 4, 0x200000;\nmov.b64 d11, {t, h};\n"
        "and.b32 t, c12, 0xffe;\nmad.lo.u32 t, t, 4, 0x200000;\nmov.b64 d12, {t, h};\nand.b32 t, c13, 0xffe;\nmad.lo.u32 t, t, 4, 0x200000;\n"
        "mov.b64 d13, {t, h};\nand.b32 t, c14, 0xffe;\nmad.lo.u32 t, t, 4, 0x200000;\nmov.b64 d14, {t, h};\nand.b32 t, c15, 0xffe;\n"
        "mad.lo.u32 t, t, 4, 0x200000;\nmov.b64 d15, {t, h};\nwgmma.fence.sync.aligned;\n"
        "wgmma.mma_async.sync.aligned.m64n32k16.f32.bf16.bf16 {o0,o1,o2,o3,o4,o5,o6,o7,o8,o9,o10,o11,o12,o13,o14,o15}, {a0,a1,a2,a3}, d0, p0, 1, 1, 1;\n"
        "wgmma.mma_async.sync.aligned.m64n32k16.f32.bf16.bf16 {o16,o17,o18,o19,o20,o21,o22,o23,o24,o25,o26,o27,o28,o29,o30,o31}, {a0,a1,a2,a3}, d8, p0, 1, 1, 1;\n"
        "wgmma.mma_async.sync.aligned.m64n32k16.f32.bf16.bf16 {o0,o1,o2,o3,o4,o5,o6,o7,o8,o9,o10,o11,o12,o13,o14,o15}, {a4,a5,a6,a7}, d1, p1, 1, 1, 1;\n"
        "wgmma.mma_async.sync.aligned.m64n32k16.f32.bf16.bf16 {o16,o17,o18,o19,o20,o21,o22,o23,o24,o25,o26,o27,o28,o29,o30,o31}, {a4,a5,a6,a7}, d9, p1, 1, 1, 1;\n"
        "wgmma.mma_async.sync.aligned.m64n32k16.f32.bf16.bf16 {o0,o1,o2,o3,o4,o5,o6,o7,o8,o9,o10,o11,o12,o13,o14,o15}, {a8,a9,a10,a11}, d2, p1, 1, 1, 1;\n"
        "wgmma.mma_async.sync.aligned.m64n32k16.f32.bf16.bf16 {o16,o17,o18,o19,o20,o21,o22,o23,o24,o25,o26,o27,o28,o29,o30,o31}, {a8,a9,a10,a11}, d10, p1, 1, 1, 1;\n"
        "wgmma.mma_async.sync.aligned.m64n32k16.f32.bf16.bf16 {o0,o1,o2,o3,o4,o5,o6,o7,o8,o9,o10,o11,o12,o13,o14,o15}, {a12,a13,a14,a15}, d3, p1, 1, 1, 1;\n"
        "wgmma.mma_async.sync.aligned.m64n32k16.f32.bf16.bf16 {o16,o17,o18,o19,o20,o21,o22,o23,o24,o25,o26,o27,o28,o29,o30,o31}, {a12,a13,a14,a15}, d11, p1, 1, 1, 1;\n"
        "wgmma.mma_async.sync.aligned.m64n32k16.f32.bf16.bf16 {o0,o1,o2,o3,o4,o5,o6,o7,o8,o9,o10,o11,o12,o13,o14,o15}, {a16,a17,a18,a19}, d4, p1, 1, 1, 1;\n"
        "wgmma.mma_async.sync.aligned.m64n32k16.f32.bf16.bf16 {o16,o17,o18,o19,o20,o21,o22,o23,o24,o25,o26,o27,o28,o29,o30,o31}, {a16,a17,a18,a19}, d12, p1, 1, 1, 1;\n"
        "wgmma.mma_async.sync.aligned.m64n32k16.f32.bf16.bf16 {o0,o1,o2,o3,o4,o5,o6,o7,o8,o9,o10,o11,o12,o13,o14,o15}, {a20,a21,a22,a23}, d5, p1, 1, 1, 1;\n"
        "wgmma.mma_async.sync.aligned.m64n32k16.f32.bf16.bf16 {o16,o17,o18,o19,o20,o21,o22,o23,o24,o25,o26,o27,o28,o29,o30,o31}, {a20,a21,a22,a23}, d13, p1, 1, 1, 1;\n"
        "wgmma.mma_async.sync.aligned.m64n32k16.f32.bf16.bf16 {o0,o1,o2,o3,o4,o5,o6,o7,o8,o9,o10,o11,o12,o13,o14,o15}, {a24,a25,a26,a27}, d6, p1, 1, 1, 1;\n"
        "wgmma.mma_async.sync.aligned.m64n32k16.f32.bf16.bf16 {o16,o17,o18,o19,o20,o21,o22,o23,o24,o25,o26,o27,o28,o29,o30,o31}, {a24,a25,a26,a27}, d14, p1, 1, 1, 1;\n"
        "wgmma.mma_async.sync.aligned.m64n32k16.f32.bf16.bf16 {o0,o1,o2,o3,o4,o5,o6,o7,o8,o9,o10,o11,o12,o13,o14,o15}, {a28,a29,a30,a31}, d7, p1, 1, 1, 1;\n"
        "wgmma.mma_async.sync.aligned.m64n32k16.f32.bf16.bf16 {o16,o17,o18,o19,o20,o21,o22,o23,o24,o25,o26,o27,o28,o29,o30,o31}, {a28,a29,a30,a31}, d15, p1, 1, 1, 1;\n"
        "wgmma.commit_group.sync.aligned;\n@nv bra.uni END;\nmovmatrix.sync.aligned.m8n8.trans.b16 b0, %32;\nmovmatrix.sync.aligned.m8n8.trans.b16 b2, %33;\n"
        "movmatrix.sync.aligned.m8n8.trans.b16 b3, %49;\nmovmatrix.sync.aligned.m8n8.trans.b16 b4, %34;\nmovmatrix.sync.aligned.m8n8.trans.b16 b5, %50;\n"
        "movmatrix.sync.aligned.m8n8.trans.b16 b6, %35;\nmovmatrix.sync.aligned.m8n8.trans.b16 b7, %51;\nmovmatrix.sync.aligned.m8n8.trans.b16 b8, %36;\n"
        "movmatrix.sync.aligned.m8n8.trans.b16 b9, %52;\nmovmatrix.sync.aligned.m8n8.trans.b16 b20, %42;\nmovmatrix.sync.aligned.m8n8.trans.b16 b21, %58;\n"
        "movmatrix.sync.aligned.m8n8.trans.b16 b22, %43;\nmovmatrix.sync.aligned.m8n8.trans.b16 b23, %59;\nmovmatrix.sync.aligned.m8n8.trans.b16 b24, %44;\n"
        "movmatrix.sync.aligned.m8n8.trans.b16 b25, %60;\nmovmatrix.sync.aligned.m8n8.trans.b16 b26, %45;\nmovmatrix.sync.aligned.m8n8.trans.b16 b27, %61;\n"
        "movmatrix.sync.aligned.m8n8.trans.b16 b28, %46;\nmovmatrix.sync.aligned.m8n8.trans.b16 b29, %62;\nmovmatrix.sync.aligned.m8n8.trans.b16 b30, %47;\n"
        "movmatrix.sync.aligned.m8n8.trans.b16 b31, %63;\nmovmatrix.sync.aligned.m8n8.trans.b16 b1, %48;\nmovmatrix.sync.aligned.m8n8.trans.b16 b10, %37;\n"
        "movmatrix.sync.aligned.m8n8.trans.b16 b11, %53;\nmovmatrix.sync.aligned.m8n8.trans.b16 b12, %38;\nmovmatrix.sync.aligned.m8n8.trans.b16 b13, %54;\n"
        "movmatrix.sync.aligned.m8n8.trans.b16 b14, %39;\nmovmatrix.sync.aligned.m8n8.trans.b16 b15, %55;\nmovmatrix.sync.aligned.m8n8.trans.b16 b16, %40;\n"
        "movmatrix.sync.aligned.m8n8.trans.b16 b17, %56;\nmovmatrix.sync.aligned.m8n8.trans.b16 b18, %41;\nmovmatrix.sync.aligned.m8n8.trans.b16 b19, %57;\n"
        "@nv bra.uni END;\nwgmma.wait_group.sync.aligned 0;\ncvt.rn.bf16x2.f32 k0, o1, o0;\ncvt.rn.bf16x2.f32 k1, o5, o4;\ncvt.rn.bf16x2.f32 k2, o9, o8;\n"
        "cvt.rn.bf16x2.f32 k3, o13, o12;\ncvt.rn.bf16x2.f32 k4, o3, o2;\ncvt.rn.bf16x2.f32 k5, o7, o6;\ncvt.rn.bf16x2.f32 k6, o11, o10;\n"
        "cvt.rn.bf16x2.f32 k7, o15, o14;\ncvt.rn.bf16x2.f32 k8, o17, o16;\ncvt.rn.bf16x2.f32 k9, o21, o20;\ncvt.rn.bf16x2.f32 k10, o25, o24;\n"
        "cvt.rn.bf16x2.f32 k11, o29, o28;\ncvt.rn.bf16x2.f32 k12, o19, o18;\ncvt.rn.bf16x2.f32 k13, o23, o22;\ncvt.rn.bf16x2.f32 k14, o27, o26;\n"
        "cvt.rn.bf16x2.f32 k15, o31, o30;\nld.volatile.shared.v4.b32 {c0,c1,c2,c3}, [%64+32];\nld.volatile.shared.v4.b32 {c4,c5,c6,c7}, [%64+8224];\n"
        "ld.volatile.shared.v4.b32 {c8,c9,c10,c11}, [%64+48];\nld.volatile.shared.v4.b32 {c12,c13,c14,c15}, [%64+8240];\nand.b32 t, c0, 0xffe;\n"
        "mad.lo.u32 t, t, 4, 0x200000;\nmov.b64 d0, {t, h};\nand.b32 t, c1, 0xffe;\nmad.lo.u32 t, t, 4, 0x200000;\nmov.b64 d1, {t, h};\nand.b32 t, c2, 0xffe;\n"
        "mad.lo.u32 t, t, 4, 0x200000;\nmov.b64 d2, {t, h};\nand.b32 t, c3, 0xffe;\nmad.lo.u32 t, t, 4, 0x200000;\nmov.b64 d3, {t, h};\nand.b32 t, c4, 0xffe;\n"
        "mad.lo.u32 t, t, 4, 0x200000;\nmov.b64 d4, {t, h};\nand.b32 t, c5, 0xffe;\nmad.lo.u32 t, t, 4, 0x200000;\nmov.b64 d5, {t, h};\nand.b32 t, c6, 0xffe;\n"
        "mad.lo.u32 t, t, 4, 0x200000;\nmov.b64 d6, {t, h};\nand.b32 t, c7, 0xffe;\nmad.lo.u32 t, t, 4, 0x200000;\nmov.b64 d7, {t, h};\nand.b32 t, c8, 0xffe;\n"
        "mad.lo.u32 t, t, 4, 0x200000;\nmov.b64 d8, {t, h};\nand.b32 t, c9, 0xffe;\nmad.lo.u32 t, t, 4, 0x200000;\nmov.b64 d9, {t, h};\nand.b32 t, c10, 0xffe;\n"
        "mad.lo.u32 t, t, 4, 0x200000;\nmov.b64 d10, {t, h};\nand.b32 t, c11, 0xffe;\nmad.lo.u32 t, t, 4, 0x200000;\nmov.b64 d11, {t, h};\n"
        "and.b32 t, c12, 0xffe;\nmad.lo.u32 t, t, 4, 0x200000;\nmov.b64 d12, {t, h};\nand.b32 t, c13, 0xffe;\nmad.lo.u32 t, t, 4, 0x200000;\n"
        "mov.b64 d13, {t, h};\nand.b32 t, c14, 0xffe;\nmad.lo.u32 t, t, 4, 0x200000;\nmov.b64 d14, {t, h};\nand.b32 t, c15, 0xffe;\n"
        "mad.lo.u32 t, t, 4, 0x200000;\nmov.b64 d15, {t, h};\nwgmma.fence.sync.aligned;\n"
        "wgmma.mma_async.sync.aligned.m64n32k16.f32.bf16.bf16 {o0,o1,o2,o3,o4,o5,o6,o7,o8,o9,o10,o11,o12,o13,o14,o15}, {a0,a1,a2,a3}, d0, p0, 1, 1, 1;\n"
        "wgmma.mma_async.sync.aligned.m64n32k16.f32.bf16.bf16 {o16,o17,o18,o19,o20,o21,o22,o23,o24,o25,o26,o27,o28,o29,o30,o31}, {a0,a1,a2,a3}, d8, p0, 1, 1, 1;\n"
        "wgmma.mma_async.sync.aligned.m64n32k16.f32.bf16.bf16 {o0,o1,o2,o3,o4,o5,o6,o7,o8,o9,o10,o11,o12,o13,o14,o15}, {a4,a5,a6,a7}, d1, p1, 1, 1, 1;\n"
        "wgmma.mma_async.sync.aligned.m64n32k16.f32.bf16.bf16 {o16,o17,o18,o19,o20,o21,o22,o23,o24,o25,o26,o27,o28,o29,o30,o31}, {a4,a5,a6,a7}, d9, p1, 1, 1, 1;\n"
        "wgmma.mma_async.sync.aligned.m64n32k16.f32.bf16.bf16 {o0,o1,o2,o3,o4,o5,o6,o7,o8,o9,o10,o11,o12,o13,o14,o15}, {a8,a9,a10,a11}, d2, p1, 1, 1, 1;\n"
        "wgmma.mma_async.sync.aligned.m64n32k16.f32.bf16.bf16 {o16,o17,o18,o19,o20,o21,o22,o23,o24,o25,o26,o27,o28,o29,o30,o31}, {a8,a9,a10,a11}, d10, p1, 1, 1, 1;\n"
        "wgmma.mma_async.sync.aligned.m64n32k16.f32.bf16.bf16 {o0,o1,o2,o3,o4,o5,o6,o7,o8,o9,o10,o11,o12,o13,o14,o15}, {a12,a13,a14,a15}, d3, p1, 1, 1, 1;\n"
        "wgmma.mma_async.sync.aligned.m64n32k16.f32.bf16.bf16 {o16,o17,o18,o19,o20,o21,o22,o23,o24,o25,o26,o27,o28,o29,o30,o31}, {a12,a13,a14,a15}, d11, p1, 1, 1, 1;\n"
        "wgmma.mma_async.sync.aligned.m64n32k16.f32.bf16.bf16 {o0,o1,o2,o3,o4,o5,o6,o7,o8,o9,o10,o11,o12,o13,o14,o15}, {a16,a17,a18,a19}, d4, p1, 1, 1, 1;\n"
        "wgmma.mma_async.sync.aligned.m64n32k16.f32.bf16.bf16 {o16,o17,o18,o19,o20,o21,o22,o23,o24,o25,o26,o27,o28,o29,o30,o31}, {a16,a17,a18,a19}, d12, p1, 1, 1, 1;\n"
        "wgmma.mma_async.sync.aligned.m64n32k16.f32.bf16.bf16 {o0,o1,o2,o3,o4,o5,o6,o7,o8,o9,o10,o11,o12,o13,o14,o15}, {a20,a21,a22,a23}, d5, p1, 1, 1, 1;\n"
        "wgmma.mma_async.sync.aligned.m64n32k16.f32.bf16.bf16 {o16,o17,o18,o19,o20,o21,o22,o23,o24,o25,o26,o27,o28,o29,o30,o31}, {a20,a21,a22,a23}, d13, p1, 1, 1, 1;\n"
        "wgmma.mma_async.sync.aligned.m64n32k16.f32.bf16.bf16 {o0,o1,o2,o3,o4,o5,o6,o7,o8,o9,o10,o11,o12,o13,o14,o15}, {a24,a25,a26,a27}, d6, p1, 1, 1, 1;\n"
        "wgmma.mma_async.sync.aligned.m64n32k16.f32.bf16.bf16 {o16,o17,o18,o19,o20,o21,o22,o23,o24,o25,o26,o27,o28,o29,o30,o31}, {a24,a25,a26,a27}, d14, p1, 1, 1, 1;\n"
        "wgmma.mma_async.sync.aligned.m64n32k16.f32.bf16.bf16 {o0,o1,o2,o3,o4,o5,o6,o7,o8,o9,o10,o11,o12,o13,o14,o15}, {a28,a29,a30,a31}, d7, p1, 1, 1, 1;\n"
        "wgmma.mma_async.sync.aligned.m64n32k16.f32.bf16.bf16 {o16,o17,o18,o19,o20,o21,o22,o23,o24,o25,o26,o27,o28,o29,o30,o31}, {a28,a29,a30,a31}, d15, p1, 1, 1, 1;\n"
        "wgmma.commit_group.sync.aligned;\n@nv bra.uni END;\n@s0 st.global.v4.b32 [%65+0], {k0,k1,k2,k3};\n@s1 st.global.v4.b32 [%66+0], {k4,k5,k6,k7};\n"
        "@s0 st.global.v4.b32 [%65+64], {k8,k9,k10,k11};\n@s1 st.global.v4.b32 [%66+64], {k12,k13,k14,k15};\n@nv bra.uni END;\nwgmma.wait_group.sync.aligned 0;\n"
        "cvt.rn.bf16x2.f32 k0, o1, o0;\ncvt.rn.bf16x2.f32 k1, o5, o4;\ncvt.rn.bf16x2.f32 k2, o9, o8;\ncvt.rn.bf16x2.f32 k3, o13, o12;\n"
        "cvt.rn.bf16x2.f32 k4, o3, o2;\ncvt.rn.bf16x2.f32 k5, o7, o6;\ncvt.rn.bf16x2.f32 k6, o11, o10;\ncvt.rn.bf16x2.f32 k7, o15, o14;\n"
        "cvt.rn.bf16x2.f32 k8, o17, o16;\ncvt.rn.bf16x2.f32 k9, o21, o20;\ncvt.rn.bf16x2.f32 k10, o25, o24;\ncvt.rn.bf16x2.f32 k11, o29, o28;\n"
        "cvt.rn.bf16x2.f32 k12, o19, o18;\ncvt.rn.bf16x2.f32 k13, o23, o22;\ncvt.rn.bf16x2.f32 k14, o27, o26;\ncvt.rn.bf16x2.f32 k15, o31, o30;\n"
        "ld.volatile.shared.v4.b32 {c0,c1,c2,c3}, [%64+0];\nld.volatile.shared.v4.b32 {c4,c5,c6,c7}, [%64+8192];\n"
        "ld.volatile.shared.v4.b32 {c8,c9,c10,c11}, [%64+16];\nld.volatile.shared.v4.b32 {c12,c13,c14,c15}, [%64+8208];\nand.b32 t, c0, 0xffe;\n"
        "mad.lo.u32 t, t, 4, 0x200000;\nmov.b64 d0, {t, h};\nand.b32 t, c1, 0xffe;\nmad.lo.u32 t, t, 4, 0x200000;\nmov.b64 d1, {t, h};\nand.b32 t, c2, 0xffe;\n"
        "mad.lo.u32 t, t, 4, 0x200000;\nmov.b64 d2, {t, h};\nand.b32 t, c3, 0xffe;\nmad.lo.u32 t, t, 4, 0x200000;\nmov.b64 d3, {t, h};\nand.b32 t, c4, 0xffe;\n"
        "mad.lo.u32 t, t, 4, 0x200000;\nmov.b64 d4, {t, h};\nand.b32 t, c5, 0xffe;\nmad.lo.u32 t, t, 4, 0x200000;\nmov.b64 d5, {t, h};\nand.b32 t, c6, 0xffe;\n"
        "mad.lo.u32 t, t, 4, 0x200000;\nmov.b64 d6, {t, h};\nand.b32 t, c7, 0xffe;\nmad.lo.u32 t, t, 4, 0x200000;\nmov.b64 d7, {t, h};\nand.b32 t, c8, 0xffe;\n"
        "mad.lo.u32 t, t, 4, 0x200000;\nmov.b64 d8, {t, h};\nand.b32 t, c9, 0xffe;\nmad.lo.u32 t, t, 4, 0x200000;\nmov.b64 d9, {t, h};\nand.b32 t, c10, 0xffe;\n"
        "mad.lo.u32 t, t, 4, 0x200000;\nmov.b64 d10, {t, h};\nand.b32 t, c11, 0xffe;\nmad.lo.u32 t, t, 4, 0x200000;\nmov.b64 d11, {t, h};\n"
        "and.b32 t, c12, 0xffe;\nmad.lo.u32 t, t, 4, 0x200000;\nmov.b64 d12, {t, h};\nand.b32 t, c13, 0xffe;\nmad.lo.u32 t, t, 4, 0x200000;\n"
        "mov.b64 d13, {t, h};\nand.b32 t, c14, 0xffe;\nmad.lo.u32 t, t, 4, 0x200000;\nmov.b64 d14, {t, h};\nand.b32 t, c15, 0xffe;\n"
        "mad.lo.u32 t, t, 4, 0x200000;\nmov.b64 d15, {t, h};\nwgmma.fence.sync.aligned;\n"
        "wgmma.mma_async.sync.aligned.m64n32k16.f32.bf16.bf16 {o0,o1,o2,o3,o4,o5,o6,o7,o8,o9,o10,o11,o12,o13,o14,o15}, {b0,b1,b2,b3}, d0, p0, 1, 1, 1;\n"
        "wgmma.mma_async.sync.aligned.m64n32k16.f32.bf16.bf16 {o16,o17,o18,o19,o20,o21,o22,o23,o24,o25,o26,o27,o28,o29,o30,o31}, {b0,b1,b2,b3}, d8, p0, 1, 1, 1;\n"
        "wgmma.mma_async.sync.aligned.m64n32k16.f32.bf16.bf16 {o0,o1,o2,o3,o4,o5,o6,o7,o8,o9,o10,o11,o12,o13,o14,o15}, {b4,b5,b6,b7}, d1, p1, 1, 1, 1;\n"
        "wgmma.mma_async.sync.aligned.m64n32k16.f32.bf16.bf16 {o16,o17,o18,o19,o20,o21,o22,o23,o24,o25,o26,o27,o28,o29,o30,o31}, {b4,b5,b6,b7}, d9, p1, 1, 1, 1;\n"
        "wgmma.mma_async.sync.aligned.m64n32k16.f32.bf16.bf16 {o0,o1,o2,o3,o4,o5,o6,o7,o8,o9,o10,o11,o12,o13,o14,o15}, {b8,b9,b10,b11}, d2, p1, 1, 1, 1;\n"
        "wgmma.mma_async.sync.aligned.m64n32k16.f32.bf16.bf16 {o16,o17,o18,o19,o20,o21,o22,o23,o24,o25,o26,o27,o28,o29,o30,o31}, {b8,b9,b10,b11}, d10, p1, 1, 1, 1;\n"
        "wgmma.mma_async.sync.aligned.m64n32k16.f32.bf16.bf16 {o0,o1,o2,o3,o4,o5,o6,o7,o8,o9,o10,o11,o12,o13,o14,o15}, {b12,b13,b14,b15}, d3, p1, 1, 1, 1;\n"
        "wgmma.mma_async.sync.aligned.m64n32k16.f32.bf16.bf16 {o16,o17,o18,o19,o20,o21,o22,o23,o24,o25,o26,o27,o28,o29,o30,o31}, {b12,b13,b14,b15}, d11, p1, 1, 1, 1;\n"
        "wgmma.mma_async.sync.aligned.m64n32k16.f32.bf16.bf16 {o0,o1,o2,o3,o4,o5,o6,o7,o8,o9,o10,o11,o12,o13,o14,o15}, {b16,b17,b18,b19}, d4, p1, 1, 1, 1;\n"
        "wgmma.mma_async.sync.aligned.m64n32k16.f32.bf16.bf16 {o16,o17,o18,o19,o20,o21,o22,o23,o24,o25,o26,o27,o28,o29,o30,o31}, {b16,b17,b18,b19}, d12, p1, 1, 1, 1;\n"
        "wgmma.mma_async.sync.aligned.m64n32k16.f32.bf16.bf16 {o0,o1,o2,o3,o4,o5,o6,o7,o8,o9,o10,o11,o12,o13,o14,o15}, {b20,b21,b22,b23}, d5, p1, 1, 1, 1;\n"
        "wgmma.mma_async.sync.aligned.m64n32k16.f32.bf16.bf16 {o16,o17,o18,o19,o20,o21,o22,o23,o24,o25,o26,o27,o28,o29,o30,o31}, {b20,b21,b22,b23}, d13, p1, 1, 1, 1;\n"
        "wgmma.mma_async.sync.aligned.m64n32k16.f32.bf16.bf16 {o0,o1,o2,o3,o4,o5,o6,o7,o8,o9,o10,o11,o12,o13,o14,o15}, {b24,b25,b26,b27}, d6, p1, 1, 1, 1;\n"
        "wgmma.mma_async.sync.aligned.m64n32k16.f32.bf16.bf16 {o16,o17,o18,o19,o20,o21,o22,o23,o24,o25,o26,o27,o28,o29,o30,o31}, {b24,b25,b26,b27}, d14, p1, 1, 1, 1;\n"
        "wgmma.mma_async.sync.aligned.m64n32k16.f32.bf16.bf16 {o0,o1,o2,o3,o4,o5,o6,o7,o8,o9,o10,o11,o12,o13,o14,o15}, {b28,b29,b30,b31}, d7, p1, 1, 1, 1;\n"
        "wgmma.mma_async.sync.aligned.m64n32k16.f32.bf16.bf16 {o16,o17,o18,o19,o20,o21,o22,o23,o24,o25,o26,o27,o28,o29,o30,o31}, {b28,b29,b30,b31}, d15, p1, 1, 1, 1;\n"
        "wgmma.commit_group.sync.aligned;\n@nv bra.uni END;\n@s0 st.global.v4.b32 [%65+128], {k0,k1,k2,k3};\n@s1 st.global.v4.b32 [%66+128], {k4,k5,k6,k7};\n"
        "@s0 st.global.v4.b32 [%65+192], {k8,k9,k10,k11};\n@s1 st.global.v4.b32 [%66+192], {k12,k13,k14,k15};\n@nv bra.uni END;\n"
        "wgmma.wait_group.sync.aligned 0;\ncvt.rn.bf16x2.f32 k0, o1, o0;\ncvt.rn.bf16x2.f32 k1, o5, o4;\ncvt.rn.bf16x2.f32 k2, o9, o8;\n"
        "cvt.rn.bf16x2.f32 k3, o13, o12;\ncvt.rn.bf16x2.f32 k4, o3, o2;\ncvt.rn.bf16x2.f32 k5, o7, o6;\ncvt.rn.bf16x2.f32 k6, o11, o10;\n"
        "cvt.rn.bf16x2.f32 k7, o15, o14;\ncvt.rn.bf16x2.f32 k8, o17, o16;\ncvt.rn.bf16x2.f32 k9, o21, o20;\ncvt.rn.bf16x2.f32 k10, o25, o24;\n"
        "cvt.rn.bf16x2.f32 k11, o29, o28;\ncvt.rn.bf16x2.f32 k12, o19, o18;\ncvt.rn.bf16x2.f32 k13, o23, o22;\ncvt.rn.bf16x2.f32 k14, o27, o26;\n"
        "cvt.rn.bf16x2.f32 k15, o31, o30;\nld.volatile.shared.v4.b32 {c0,c1,c2,c3}, [%64+32];\nld.volatile.shared.v4.b32 {c4,c5,c6,c7}, [%64+8224];\n"
        "ld.volatile.shared.v4.b32 {c8,c9,c10,c11}, [%64+48];\nld.volatile.shared.v4.b32 {c12,c13,c14,c15}, [%64+8240];\nand.b32 t, c0, 0xffe;\n"
        "mad.lo.u32 t, t, 4, 0x200000;\nmov.b64 d0, {t, h};\nand.b32 t, c1, 0xffe;\nmad.lo.u32 t, t, 4, 0x200000;\nmov.b64 d1, {t, h};\nand.b32 t, c2, 0xffe;\n"
        "mad.lo.u32 t, t, 4, 0x200000;\nmov.b64 d2, {t, h};\nand.b32 t, c3, 0xffe;\nmad.lo.u32 t, t, 4, 0x200000;\nmov.b64 d3, {t, h};\nand.b32 t, c4, 0xffe;\n"
        "mad.lo.u32 t, t, 4, 0x200000;\nmov.b64 d4, {t, h};\nand.b32 t, c5, 0xffe;\nmad.lo.u32 t, t, 4, 0x200000;\nmov.b64 d5, {t, h};\nand.b32 t, c6, 0xffe;\n"
        "mad.lo.u32 t, t, 4, 0x200000;\nmov.b64 d6, {t, h};\nand.b32 t, c7, 0xffe;\nmad.lo.u32 t, t, 4, 0x200000;\nmov.b64 d7, {t, h};\nand.b32 t, c8, 0xffe;\n"
        "mad.lo.u32 t, t, 4, 0x200000;\nmov.b64 d8, {t, h};\nand.b32 t, c9, 0xffe;\nmad.lo.u32 t, t, 4, 0x200000;\nmov.b64 d9, {t, h};\nand.b32 t, c10, 0xffe;\n"
        "mad.lo.u32 t, t, 4, 0x200000;\nmov.b64 d10, {t, h};\nand.b32 t, c11, 0xffe;\nmad.lo.u32 t, t, 4, 0x200000;\nmov.b64 d11, {t, h};\n"
        "and.b32 t, c12, 0xffe;\nmad.lo.u32 t, t, 4, 0x200000;\nmov.b64 d12, {t, h};\nand.b32 t, c13, 0xffe;\nmad.lo.u32 t, t, 4, 0x200000;\n"
        "mov.b64 d13, {t, h};\nand.b32 t, c14, 0xffe;\nmad.lo.u32 t, t, 4, 0x200000;\nmov.b64 d14, {t, h};\nand.b32 t, c15, 0xffe;\n"
        "mad.lo.u32 t, t, 4, 0x200000;\nmov.b64 d15, {t, h};\nwgmma.fence.sync.aligned;\n"
        "wgmma.mma_async.sync.aligned.m64n32k16.f32.bf16.bf16 {o0,o1,o2,o3,o4,o5,o6,o7,o8,o9,o10,o11,o12,o13,o14,o15}, {b0,b1,b2,b3}, d0, p0, 1, 1, 1;\n"
        "wgmma.mma_async.sync.aligned.m64n32k16.f32.bf16.bf16 {o16,o17,o18,o19,o20,o21,o22,o23,o24,o25,o26,o27,o28,o29,o30,o31}, {b0,b1,b2,b3}, d8, p0, 1, 1, 1;\n"
        "wgmma.mma_async.sync.aligned.m64n32k16.f32.bf16.bf16 {o0,o1,o2,o3,o4,o5,o6,o7,o8,o9,o10,o11,o12,o13,o14,o15}, {b4,b5,b6,b7}, d1, p1, 1, 1, 1;\n"
        "wgmma.mma_async.sync.aligned.m64n32k16.f32.bf16.bf16 {o16,o17,o18,o19,o20,o21,o22,o23,o24,o25,o26,o27,o28,o29,o30,o31}, {b4,b5,b6,b7}, d9, p1, 1, 1, 1;\n"
        "wgmma.mma_async.sync.aligned.m64n32k16.f32.bf16.bf16 {o0,o1,o2,o3,o4,o5,o6,o7,o8,o9,o10,o11,o12,o13,o14,o15}, {b8,b9,b10,b11}, d2, p1, 1, 1, 1;\n"
        "wgmma.mma_async.sync.aligned.m64n32k16.f32.bf16.bf16 {o16,o17,o18,o19,o20,o21,o22,o23,o24,o25,o26,o27,o28,o29,o30,o31}, {b8,b9,b10,b11}, d10, p1, 1, 1, 1;\n"
        "wgmma.mma_async.sync.aligned.m64n32k16.f32.bf16.bf16 {o0,o1,o2,o3,o4,o5,o6,o7,o8,o9,o10,o11,o12,o13,o14,o15}, {b12,b13,b14,b15}, d3, p1, 1, 1, 1;\n"
        "wgmma.mma_async.sync.aligned.m64n32k16.f32.bf16.bf16 {o16,o17,o18,o19,o20,o21,o22,o23,o24,o25,o26,o27,o28,o29,o30,o31}, {b12,b13,b14,b15}, d11, p1, 1, 1, 1;\n"
        "wgmma.mma_async.sync.aligned.m64n32k16.f32.bf16.bf16 {o0,o1,o2,o3,o4,o5,o6,o7,o8,o9,o10,o11,o12,o13,o14,o15}, {b16,b17,b18,b19}, d4, p1, 1, 1, 1;\n"
        "wgmma.mma_async.sync.aligned.m64n32k16.f32.bf16.bf16 {o16,o17,o18,o19,o20,o21,o22,o23,o24,o25,o26,o27,o28,o29,o30,o31}, {b16,b17,b18,b19}, d12, p1, 1, 1, 1;\n"
        "wgmma.mma_async.sync.aligned.m64n32k16.f32.bf16.bf16 {o0,o1,o2,o3,o4,o5,o6,o7,o8,o9,o10,o11,o12,o13,o14,o15}, {b20,b21,b22,b23}, d5, p1, 1, 1, 1;\n"
        "wgmma.mma_async.sync.aligned.m64n32k16.f32.bf16.bf16 {o16,o17,o18,o19,o20,o21,o22,o23,o24,o25,o26,o27,o28,o29,o30,o31}, {b20,b21,b22,b23}, d13, p1, 1, 1, 1;\n"
        "wgmma.mma_async.sync.aligned.m64n32k16.f32.bf16.bf16 {o0,o1,o2,o3,o4,o5,o6,o7,o8,o9,o10,o11,o12,o13,o14,o15}, {b24,b25,b26,b27}, d6, p1, 1, 1, 1;\n"
        "wgmma.mma_async.sync.aligned.m64n32k16.f32.bf16.bf16 {o16,o17,o18,o19,o20,o21,o22,o23,o24,o25,o26,o27,o28,o29,o30,o31}, {b24,b25,b26,b27}, d14, p1, 1, 1, 1;\n"
        "wgmma.mma_async.sync.aligned.m64n32k16.f32.bf16.bf16 {o0,o1,o2,o3,o4,o5,o6,o7,o8,o9,o10,o11,o12,o13,o14,o15}, {b28,b29,b30,b31}, d7, p1, 1, 1, 1;\n"
        "wgmma.mma_async.sync.aligned.m64n32k16.f32.bf16.bf16 {o16,o17,o18,o19,o20,o21,o22,o23,o24,o25,o26,o27,o28,o29,o30,o31}, {b28,b29,b30,b31}, d15, p1, 1, 1, 1;\n"
        "wgmma.commit_group.sync.aligned;\n@nv bra.uni END;\n@s2 st.global.v4.b32 [%67+0], {k0,k1,k2,k3};\n@s3 st.global.v4.b32 [%68+0], {k4,k5,k6,k7};\n"
        "@s2 st.global.v4.b32 [%67+64], {k8,k9,k10,k11};\n@s3 st.global.v4.b32 [%68+64], {k12,k13,k14,k15};\n@nv bra.uni END;\nwgmma.wait_group.sync.aligned 0;\n"
        "cvt.rn.bf16x2.f32 k0, o1, o0;\ncvt.rn.bf16x2.f32 k1, o5, o4;\ncvt.rn.bf16x2.f32 k2, o9, o8;\ncvt.rn.bf16x2.f32 k3, o13, o12;\n"
        "cvt.rn.bf16x2.f32 k4, o3, o2;\ncvt.rn.bf16x2.f32 k5, o7, o6;\ncvt.rn.bf16x2.f32 k6, o11, o10;\ncvt.rn.bf16x2.f32 k7, o15, o14;\n"
        "cvt.rn.bf16x2.f32 k8, o17, o16;\ncvt.rn.bf16x2.f32 k9, o21, o20;\ncvt.rn.bf16x2.f32 k10, o25, o24;\ncvt.rn.bf16x2.f32 k11, o29, o28;\n"
        "cvt.rn.bf16x2.f32 k12, o19, o18;\ncvt.rn.bf16x2.f32 k13, o23, o22;\ncvt.rn.bf16x2.f32 k14, o27, o26;\ncvt.rn.bf16x2.f32 k15, o31, o30;\n"
        "@s2 st.global.v4.b32 [%67+128], {k0,k1,k2,k3};\n@s3 st.global.v4.b32 [%68+128], {k4,k5,k6,k7};\n@s2 st.global.v4.b32 [%67+192], {k8,k9,k10,k11};\n"
        "@s3 st.global.v4.b32 [%68+192], {k12,k13,k14,k15};\n"
        "END:\n}\n"
        ::"r"(pk[0]), "r"(pk[1]), "r"(pk[2]), "r"(pk[3]), "r"(pk[4]), "r"(pk[5]), "r"(pk[6]), "r"(pk[7]), "r"(pk[8]), "r"(pk[9]), "r"(pk[10]),
          "r"(pk[11]), "r"(pk[12]), "r"(pk[13]), "r"(pk[14]), "r"(pk[15]), "r"(pk[16]), "r"(pk[17]), "r"(pk[18]), "r"(pk[19]), "r"(pk[20]),
          "r"(pk[21]), "r"(pk[22]), "r"(pk[23]), "r"(pk[24]), "r"(pk[25]), "r"(pk[26]), "r"(pk[27]), "r"(pk[28]), "r"(pk[29]), "r"(pk[30]),
          "r"(pk[31]), "r"(pk[32]), "r"(pk[33]), "r"(pk[34]), "r"(pk[35]), "r"(pk[36]), "r"(pk[37]), "r"(pk[38]), "r"(pk[39]), "r"(pk[40]),
          "r"(pk[41]), "r"(pk[42]), "r"(pk[43]), "r"(pk[44]), "r"(pk[45]), "r"(pk[46]), "r"(pk[47]), "r"(pk[48]), "r"(pk[49]), "r"(pk[50]),
          "r"(pk[51]), "r"(pk[52]), "r"(pk[53]), "r"(pk[54]), "r"(pk[55]), "r"(pk[56]), "r"(pk[57]), "r"(pk[58]), "r"(pk[59]), "r"(pk[60]),
          "r"(pk[61]), "r"(pk[62]), "r"(pk[63]), "r"(ra), "l"(p[0]), "l"(p[1]), "l"(p[2]), "l"(p[3]), "r"(v[0]), "r"(v[1]), "r"(v[2]), "r"(v[3]),
          "r"(ba)
        : "memory");
}
__device__ __forceinline__ void project3(const uint32_t (&pk)[48], uint32_t ra, uint32_t ba, uint4* const (&p)[3], const uint32_t (&v)[3]) {
    asm volatile(
        "{\n.reg .pred p0, p1, q0, q1, nv, s<4>;\n.reg .b32 t, h, c<16>, a<32>, b<32>, k<16>;\n.reg .b64 d<16>;\n.reg .f32 o<32>;\nsetp.ne.b32 p0, 0, 0;\n"
        "setp.eq.b32 p1, 0, 0;\nmov.b32 h, 8;\nsetp.eq.u32 nv, %48, 0;\nvote.sync.any.pred nv, nv, 0xffffffff;\nsetp.ne.b32 s0, %52, 0;\n"
        "setp.ne.b32 s1, %53, 0;\nsetp.ne.b32 s2, %54, 0;\nmovmatrix.sync.aligned.m8n8.trans.b16 a0, %0;\nmovmatrix.sync.aligned.m8n8.trans.b16 a1, %16;\n"
        "movmatrix.sync.aligned.m8n8.trans.b16 a2, %1;\nmovmatrix.sync.aligned.m8n8.trans.b16 a3, %17;\nmovmatrix.sync.aligned.m8n8.trans.b16 a4, %2;\n"
        "movmatrix.sync.aligned.m8n8.trans.b16 a5, %18;\nmovmatrix.sync.aligned.m8n8.trans.b16 a6, %3;\nmovmatrix.sync.aligned.m8n8.trans.b16 a7, %19;\n"
        "movmatrix.sync.aligned.m8n8.trans.b16 a8, %4;\nmovmatrix.sync.aligned.m8n8.trans.b16 a9, %20;\nmovmatrix.sync.aligned.m8n8.trans.b16 a10, %5;\n"
        "movmatrix.sync.aligned.m8n8.trans.b16 a11, %21;\nmovmatrix.sync.aligned.m8n8.trans.b16 a12, %6;\nmovmatrix.sync.aligned.m8n8.trans.b16 a13, %22;\n"
        "movmatrix.sync.aligned.m8n8.trans.b16 a14, %7;\nmovmatrix.sync.aligned.m8n8.trans.b16 a15, %23;\nmovmatrix.sync.aligned.m8n8.trans.b16 a16, %8;\n"
        "movmatrix.sync.aligned.m8n8.trans.b16 a17, %24;\nmovmatrix.sync.aligned.m8n8.trans.b16 a18, %9;\nmovmatrix.sync.aligned.m8n8.trans.b16 a19, %25;\n"
        "movmatrix.sync.aligned.m8n8.trans.b16 a20, %10;\nmovmatrix.sync.aligned.m8n8.trans.b16 a21, %26;\nmovmatrix.sync.aligned.m8n8.trans.b16 a22, %11;\n"
        "movmatrix.sync.aligned.m8n8.trans.b16 a23, %27;\nmovmatrix.sync.aligned.m8n8.trans.b16 a24, %12;\nmovmatrix.sync.aligned.m8n8.trans.b16 a25, %28;\n"
        "movmatrix.sync.aligned.m8n8.trans.b16 a26, %13;\nmovmatrix.sync.aligned.m8n8.trans.b16 a27, %29;\nmovmatrix.sync.aligned.m8n8.trans.b16 a28, %14;\n"
        "movmatrix.sync.aligned.m8n8.trans.b16 a29, %30;\nmovmatrix.sync.aligned.m8n8.trans.b16 a30, %15;\nmovmatrix.sync.aligned.m8n8.trans.b16 a31, %31;\n"
        "mov.b32 t, 0;\n"
        "W0:\nmbarrier.try_wait.parity.shared.b64 q0, [%55+0], 0;\nadd.u32 t, t, 1;\nsetp.lt.and.u32 q1, t, 1000000, !q0;\n@q1 bra.uni W0;\nmov.b32 t, 0;\n"
        "W1:\nmbarrier.try_wait.parity.shared.b64 q0, [%55+8], 0;\nadd.u32 t, t, 1;\nsetp.lt.and.u32 q1, t, 1000000, !q0;\n@q1 bra.uni W1;\nmov.b32 t, 0;\n"
        "W2:\nmbarrier.try_wait.parity.shared.b64 q0, [%55+16], 0;\nadd.u32 t, t, 1;\nsetp.lt.and.u32 q1, t, 1000000, !q0;\n@q1 bra.uni W2;\nmov.b32 t, 0;\n"
        "W3:\nmbarrier.try_wait.parity.shared.b64 q0, [%55+24], 0;\nadd.u32 t, t, 1;\nsetp.lt.and.u32 q1, t, 1000000, !q0;\n@q1 bra.uni W3;\n"
        "ld.volatile.shared.v4.b32 {c0,c1,c2,c3}, [%48+0];\nld.volatile.shared.v4.b32 {c4,c5,c6,c7}, [%48+8192];\n"
        "ld.volatile.shared.v4.b32 {c8,c9,c10,c11}, [%48+16];\nld.volatile.shared.v4.b32 {c12,c13,c14,c15}, [%48+8208];\nand.b32 t, c0, 0xffe;\n"
        "mad.lo.u32 t, t, 4, 0x200000;\nmov.b64 d0, {t, h};\nand.b32 t, c1, 0xffe;\nmad.lo.u32 t, t, 4, 0x200000;\nmov.b64 d1, {t, h};\nand.b32 t, c2, 0xffe;\n"
        "mad.lo.u32 t, t, 4, 0x200000;\nmov.b64 d2, {t, h};\nand.b32 t, c3, 0xffe;\nmad.lo.u32 t, t, 4, 0x200000;\nmov.b64 d3, {t, h};\nand.b32 t, c4, 0xffe;\n"
        "mad.lo.u32 t, t, 4, 0x200000;\nmov.b64 d4, {t, h};\nand.b32 t, c5, 0xffe;\nmad.lo.u32 t, t, 4, 0x200000;\nmov.b64 d5, {t, h};\nand.b32 t, c6, 0xffe;\n"
        "mad.lo.u32 t, t, 4, 0x200000;\nmov.b64 d6, {t, h};\nand.b32 t, c7, 0xffe;\nmad.lo.u32 t, t, 4, 0x200000;\nmov.b64 d7, {t, h};\nand.b32 t, c8, 0xffe;\n"
        "mad.lo.u32 t, t, 4, 0x200000;\nmov.b64 d8, {t, h};\nand.b32 t, c9, 0xffe;\nmad.lo.u32 t, t, 4, 0x200000;\nmov.b64 d9, {t, h};\nand.b32 t, c10, 0xffe;\n"
        "mad.lo.u32 t, t, 4, 0x200000;\nmov.b64 d10, {t, h};\nand.b32 t, c11, 0xffe;\nmad.lo.u32 t, t, 4, 0x200000;\nmov.b64 d11, {t, h};\n"
        "and.b32 t, c12, 0xffe;\nmad.lo.u32 t, t, 4, 0x200000;\nmov.b64 d12, {t, h};\nand.b32 t, c13, 0xffe;\nmad.lo.u32 t, t, 4, 0x200000;\n"
        "mov.b64 d13, {t, h};\nand.b32 t, c14, 0xffe;\nmad.lo.u32 t, t, 4, 0x200000;\nmov.b64 d14, {t, h};\nand.b32 t, c15, 0xffe;\n"
        "mad.lo.u32 t, t, 4, 0x200000;\nmov.b64 d15, {t, h};\nwgmma.fence.sync.aligned;\n"
        "wgmma.mma_async.sync.aligned.m64n32k16.f32.bf16.bf16 {o0,o1,o2,o3,o4,o5,o6,o7,o8,o9,o10,o11,o12,o13,o14,o15}, {a0,a1,a2,a3}, d0, p0, 1, 1, 1;\n"
        "wgmma.mma_async.sync.aligned.m64n32k16.f32.bf16.bf16 {o16,o17,o18,o19,o20,o21,o22,o23,o24,o25,o26,o27,o28,o29,o30,o31}, {a0,a1,a2,a3}, d8, p0, 1, 1, 1;\n"
        "wgmma.mma_async.sync.aligned.m64n32k16.f32.bf16.bf16 {o0,o1,o2,o3,o4,o5,o6,o7,o8,o9,o10,o11,o12,o13,o14,o15}, {a4,a5,a6,a7}, d1, p1, 1, 1, 1;\n"
        "wgmma.mma_async.sync.aligned.m64n32k16.f32.bf16.bf16 {o16,o17,o18,o19,o20,o21,o22,o23,o24,o25,o26,o27,o28,o29,o30,o31}, {a4,a5,a6,a7}, d9, p1, 1, 1, 1;\n"
        "wgmma.mma_async.sync.aligned.m64n32k16.f32.bf16.bf16 {o0,o1,o2,o3,o4,o5,o6,o7,o8,o9,o10,o11,o12,o13,o14,o15}, {a8,a9,a10,a11}, d2, p1, 1, 1, 1;\n"
        "wgmma.mma_async.sync.aligned.m64n32k16.f32.bf16.bf16 {o16,o17,o18,o19,o20,o21,o22,o23,o24,o25,o26,o27,o28,o29,o30,o31}, {a8,a9,a10,a11}, d10, p1, 1, 1, 1;\n"
        "wgmma.mma_async.sync.aligned.m64n32k16.f32.bf16.bf16 {o0,o1,o2,o3,o4,o5,o6,o7,o8,o9,o10,o11,o12,o13,o14,o15}, {a12,a13,a14,a15}, d3, p1, 1, 1, 1;\n"
        "wgmma.mma_async.sync.aligned.m64n32k16.f32.bf16.bf16 {o16,o17,o18,o19,o20,o21,o22,o23,o24,o25,o26,o27,o28,o29,o30,o31}, {a12,a13,a14,a15}, d11, p1, 1, 1, 1;\n"
        "wgmma.mma_async.sync.aligned.m64n32k16.f32.bf16.bf16 {o0,o1,o2,o3,o4,o5,o6,o7,o8,o9,o10,o11,o12,o13,o14,o15}, {a16,a17,a18,a19}, d4, p1, 1, 1, 1;\n"
        "wgmma.mma_async.sync.aligned.m64n32k16.f32.bf16.bf16 {o16,o17,o18,o19,o20,o21,o22,o23,o24,o25,o26,o27,o28,o29,o30,o31}, {a16,a17,a18,a19}, d12, p1, 1, 1, 1;\n"
        "wgmma.mma_async.sync.aligned.m64n32k16.f32.bf16.bf16 {o0,o1,o2,o3,o4,o5,o6,o7,o8,o9,o10,o11,o12,o13,o14,o15}, {a20,a21,a22,a23}, d5, p1, 1, 1, 1;\n"
        "wgmma.mma_async.sync.aligned.m64n32k16.f32.bf16.bf16 {o16,o17,o18,o19,o20,o21,o22,o23,o24,o25,o26,o27,o28,o29,o30,o31}, {a20,a21,a22,a23}, d13, p1, 1, 1, 1;\n"
        "wgmma.mma_async.sync.aligned.m64n32k16.f32.bf16.bf16 {o0,o1,o2,o3,o4,o5,o6,o7,o8,o9,o10,o11,o12,o13,o14,o15}, {a24,a25,a26,a27}, d6, p1, 1, 1, 1;\n"
        "wgmma.mma_async.sync.aligned.m64n32k16.f32.bf16.bf16 {o16,o17,o18,o19,o20,o21,o22,o23,o24,o25,o26,o27,o28,o29,o30,o31}, {a24,a25,a26,a27}, d14, p1, 1, 1, 1;\n"
        "wgmma.mma_async.sync.aligned.m64n32k16.f32.bf16.bf16 {o0,o1,o2,o3,o4,o5,o6,o7,o8,o9,o10,o11,o12,o13,o14,o15}, {a28,a29,a30,a31}, d7, p1, 1, 1, 1;\n"
        "wgmma.mma_async.sync.aligned.m64n32k16.f32.bf16.bf16 {o16,o17,o18,o19,o20,o21,o22,o23,o24,o25,o26,o27,o28,o29,o30,o31}, {a28,a29,a30,a31}, d15, p1, 1, 1, 1;\n"
        "wgmma.commit_group.sync.aligned;\n@nv bra.uni END;\nmovmatrix.sync.aligned.m8n8.trans.b16 b0, %32;\nmovmatrix.sync.aligned.m8n8.trans.b16 b2, %33;\n"
        "movmatrix.sync.aligned.m8n8.trans.b16 b3, %33;\nmovmatrix.sync.aligned.m8n8.trans.b16 b4, %34;\nmovmatrix.sync.aligned.m8n8.trans.b16 b5, %34;\n"
        "movmatrix.sync.aligned.m8n8.trans.b16 b6, %35;\nmovmatrix.sync.aligned.m8n8.trans.b16 b7, %35;\nmovmatrix.sync.aligned.m8n8.trans.b16 b8, %36;\n"
        "movmatrix.sync.aligned.m8n8.trans.b16 b9, %36;\nmovmatrix.sync.aligned.m8n8.trans.b16 b20, %42;\nmovmatrix.sync.aligned.m8n8.trans.b16 b21, %42;\n"
        "movmatrix.sync.aligned.m8n8.trans.b16 b22, %43;\nmovmatrix.sync.aligned.m8n8.trans.b16 b23, %43;\nmovmatrix.sync.aligned.m8n8.trans.b16 b24, %44;\n"
        "movmatrix.sync.aligned.m8n8.trans.b16 b25, %44;\nmovmatrix.sync.aligned.m8n8.trans.b16 b26, %45;\nmovmatrix.sync.aligned.m8n8.trans.b16 b27, %45;\n"
        "movmatrix.sync.aligned.m8n8.trans.b16 b28, %46;\nmovmatrix.sync.aligned.m8n8.trans.b16 b29, %46;\nmovmatrix.sync.aligned.m8n8.trans.b16 b30, %47;\n"
        "movmatrix.sync.aligned.m8n8.trans.b16 b31, %47;\nmovmatrix.sync.aligned.m8n8.trans.b16 b1, %32;\nmovmatrix.sync.aligned.m8n8.trans.b16 b10, %37;\n"
        "movmatrix.sync.aligned.m8n8.trans.b16 b11, %37;\nmovmatrix.sync.aligned.m8n8.trans.b16 b12, %38;\nmovmatrix.sync.aligned.m8n8.trans.b16 b13, %38;\n"
        "movmatrix.sync.aligned.m8n8.trans.b16 b14, %39;\nmovmatrix.sync.aligned.m8n8.trans.b16 b15, %39;\nmovmatrix.sync.aligned.m8n8.trans.b16 b16, %40;\n"
        "movmatrix.sync.aligned.m8n8.trans.b16 b17, %40;\nmovmatrix.sync.aligned.m8n8.trans.b16 b18, %41;\nmovmatrix.sync.aligned.m8n8.trans.b16 b19, %41;\n"
        "@nv bra.uni END;\nwgmma.wait_group.sync.aligned 0;\ncvt.rn.bf16x2.f32 k0, o1, o0;\ncvt.rn.bf16x2.f32 k1, o5, o4;\ncvt.rn.bf16x2.f32 k2, o9, o8;\n"
        "cvt.rn.bf16x2.f32 k3, o13, o12;\ncvt.rn.bf16x2.f32 k4, o3, o2;\ncvt.rn.bf16x2.f32 k5, o7, o6;\ncvt.rn.bf16x2.f32 k6, o11, o10;\n"
        "cvt.rn.bf16x2.f32 k7, o15, o14;\ncvt.rn.bf16x2.f32 k8, o17, o16;\ncvt.rn.bf16x2.f32 k9, o21, o20;\ncvt.rn.bf16x2.f32 k10, o25, o24;\n"
        "cvt.rn.bf16x2.f32 k11, o29, o28;\ncvt.rn.bf16x2.f32 k12, o19, o18;\ncvt.rn.bf16x2.f32 k13, o23, o22;\ncvt.rn.bf16x2.f32 k14, o27, o26;\n"
        "cvt.rn.bf16x2.f32 k15, o31, o30;\nld.volatile.shared.v4.b32 {c0,c1,c2,c3}, [%48+32];\nld.volatile.shared.v4.b32 {c4,c5,c6,c7}, [%48+8224];\n"
        "ld.volatile.shared.v4.b32 {c8,c9,c10,c11}, [%48+48];\nld.volatile.shared.v4.b32 {c12,c13,c14,c15}, [%48+8240];\nand.b32 t, c0, 0xffe;\n"
        "mad.lo.u32 t, t, 4, 0x200000;\nmov.b64 d0, {t, h};\nand.b32 t, c1, 0xffe;\nmad.lo.u32 t, t, 4, 0x200000;\nmov.b64 d1, {t, h};\nand.b32 t, c2, 0xffe;\n"
        "mad.lo.u32 t, t, 4, 0x200000;\nmov.b64 d2, {t, h};\nand.b32 t, c3, 0xffe;\nmad.lo.u32 t, t, 4, 0x200000;\nmov.b64 d3, {t, h};\nand.b32 t, c4, 0xffe;\n"
        "mad.lo.u32 t, t, 4, 0x200000;\nmov.b64 d4, {t, h};\nand.b32 t, c5, 0xffe;\nmad.lo.u32 t, t, 4, 0x200000;\nmov.b64 d5, {t, h};\nand.b32 t, c6, 0xffe;\n"
        "mad.lo.u32 t, t, 4, 0x200000;\nmov.b64 d6, {t, h};\nand.b32 t, c7, 0xffe;\nmad.lo.u32 t, t, 4, 0x200000;\nmov.b64 d7, {t, h};\nand.b32 t, c8, 0xffe;\n"
        "mad.lo.u32 t, t, 4, 0x200000;\nmov.b64 d8, {t, h};\nand.b32 t, c9, 0xffe;\nmad.lo.u32 t, t, 4, 0x200000;\nmov.b64 d9, {t, h};\nand.b32 t, c10, 0xffe;\n"
        "mad.lo.u32 t, t, 4, 0x200000;\nmov.b64 d10, {t, h};\nand.b32 t, c11, 0xffe;\nmad.lo.u32 t, t, 4, 0x200000;\nmov.b64 d11, {t, h};\n"
        "and.b32 t, c12, 0xffe;\nmad.lo.u32 t, t, 4, 0x200000;\nmov.b64 d12, {t, h};\nand.b32 t, c13, 0xffe;\nmad.lo.u32 t, t, 4, 0x200000;\n"
        "mov.b64 d13, {t, h};\nand.b32 t, c14, 0xffe;\nmad.lo.u32 t, t, 4, 0x200000;\nmov.b64 d14, {t, h};\nand.b32 t, c15, 0xffe;\n"
        "mad.lo.u32 t, t, 4, 0x200000;\nmov.b64 d15, {t, h};\nwgmma.fence.sync.aligned;\n"
        "wgmma.mma_async.sync.aligned.m64n32k16.f32.bf16.bf16 {o0,o1,o2,o3,o4,o5,o6,o7,o8,o9,o10,o11,o12,o13,o14,o15}, {a0,a1,a2,a3}, d0, p0, 1, 1, 1;\n"
        "wgmma.mma_async.sync.aligned.m64n32k16.f32.bf16.bf16 {o16,o17,o18,o19,o20,o21,o22,o23,o24,o25,o26,o27,o28,o29,o30,o31}, {a0,a1,a2,a3}, d8, p0, 1, 1, 1;\n"
        "wgmma.mma_async.sync.aligned.m64n32k16.f32.bf16.bf16 {o0,o1,o2,o3,o4,o5,o6,o7,o8,o9,o10,o11,o12,o13,o14,o15}, {a4,a5,a6,a7}, d1, p1, 1, 1, 1;\n"
        "wgmma.mma_async.sync.aligned.m64n32k16.f32.bf16.bf16 {o16,o17,o18,o19,o20,o21,o22,o23,o24,o25,o26,o27,o28,o29,o30,o31}, {a4,a5,a6,a7}, d9, p1, 1, 1, 1;\n"
        "wgmma.mma_async.sync.aligned.m64n32k16.f32.bf16.bf16 {o0,o1,o2,o3,o4,o5,o6,o7,o8,o9,o10,o11,o12,o13,o14,o15}, {a8,a9,a10,a11}, d2, p1, 1, 1, 1;\n"
        "wgmma.mma_async.sync.aligned.m64n32k16.f32.bf16.bf16 {o16,o17,o18,o19,o20,o21,o22,o23,o24,o25,o26,o27,o28,o29,o30,o31}, {a8,a9,a10,a11}, d10, p1, 1, 1, 1;\n"
        "wgmma.mma_async.sync.aligned.m64n32k16.f32.bf16.bf16 {o0,o1,o2,o3,o4,o5,o6,o7,o8,o9,o10,o11,o12,o13,o14,o15}, {a12,a13,a14,a15}, d3, p1, 1, 1, 1;\n"
        "wgmma.mma_async.sync.aligned.m64n32k16.f32.bf16.bf16 {o16,o17,o18,o19,o20,o21,o22,o23,o24,o25,o26,o27,o28,o29,o30,o31}, {a12,a13,a14,a15}, d11, p1, 1, 1, 1;\n"
        "wgmma.mma_async.sync.aligned.m64n32k16.f32.bf16.bf16 {o0,o1,o2,o3,o4,o5,o6,o7,o8,o9,o10,o11,o12,o13,o14,o15}, {a16,a17,a18,a19}, d4, p1, 1, 1, 1;\n"
        "wgmma.mma_async.sync.aligned.m64n32k16.f32.bf16.bf16 {o16,o17,o18,o19,o20,o21,o22,o23,o24,o25,o26,o27,o28,o29,o30,o31}, {a16,a17,a18,a19}, d12, p1, 1, 1, 1;\n"
        "wgmma.mma_async.sync.aligned.m64n32k16.f32.bf16.bf16 {o0,o1,o2,o3,o4,o5,o6,o7,o8,o9,o10,o11,o12,o13,o14,o15}, {a20,a21,a22,a23}, d5, p1, 1, 1, 1;\n"
        "wgmma.mma_async.sync.aligned.m64n32k16.f32.bf16.bf16 {o16,o17,o18,o19,o20,o21,o22,o23,o24,o25,o26,o27,o28,o29,o30,o31}, {a20,a21,a22,a23}, d13, p1, 1, 1, 1;\n"
        "wgmma.mma_async.sync.aligned.m64n32k16.f32.bf16.bf16 {o0,o1,o2,o3,o4,o5,o6,o7,o8,o9,o10,o11,o12,o13,o14,o15}, {a24,a25,a26,a27}, d6, p1, 1, 1, 1;\n"
        "wgmma.mma_async.sync.aligned.m64n32k16.f32.bf16.bf16 {o16,o17,o18,o19,o20,o21,o22,o23,o24,o25,o26,o27,o28,o29,o30,o31}, {a24,a25,a26,a27}, d14, p1, 1, 1, 1;\n"
        "wgmma.mma_async.sync.aligned.m64n32k16.f32.bf16.bf16 {o0,o1,o2,o3,o4,o5,o6,o7,o8,o9,o10,o11,o12,o13,o14,o15}, {a28,a29,a30,a31}, d7, p1, 1, 1, 1;\n"
        "wgmma.mma_async.sync.aligned.m64n32k16.f32.bf16.bf16 {o16,o17,o18,o19,o20,o21,o22,o23,o24,o25,o26,o27,o28,o29,o30,o31}, {a28,a29,a30,a31}, d15, p1, 1, 1, 1;\n"
        "wgmma.commit_group.sync.aligned;\n@nv bra.uni END;\n@s0 st.global.v4.b32 [%49+0], {k0,k1,k2,k3};\n@s1 st.global.v4.b32 [%50+0], {k4,k5,k6,k7};\n"
        "@s0 st.global.v4.b32 [%49+64], {k8,k9,k10,k11};\n@s1 st.global.v4.b32 [%50+64], {k12,k13,k14,k15};\n@nv bra.uni END;\nwgmma.wait_group.sync.aligned 0;\n"
        "cvt.rn.bf16x2.f32 k0, o1, o0;\ncvt.rn.bf16x2.f32 k1, o5, o4;\ncvt.rn.bf16x2.f32 k2, o9, o8;\ncvt.rn.bf16x2.f32 k3, o13, o12;\n"
        "cvt.rn.bf16x2.f32 k4, o3, o2;\ncvt.rn.bf16x2.f32 k5, o7, o6;\ncvt.rn.bf16x2.f32 k6, o11, o10;\ncvt.rn.bf16x2.f32 k7, o15, o14;\n"
        "cvt.rn.bf16x2.f32 k8, o17, o16;\ncvt.rn.bf16x2.f32 k9, o21, o20;\ncvt.rn.bf16x2.f32 k10, o25, o24;\ncvt.rn.bf16x2.f32 k11, o29, o28;\n"
        "cvt.rn.bf16x2.f32 k12, o19, o18;\ncvt.rn.bf16x2.f32 k13, o23, o22;\ncvt.rn.bf16x2.f32 k14, o27, o26;\ncvt.rn.bf16x2.f32 k15, o31, o30;\n"
        "ld.volatile.shared.v4.b32 {c0,c1,c2,c3}, [%48+0];\nld.volatile.shared.v4.b32 {c4,c5,c6,c7}, [%48+8192];\n"
        "ld.volatile.shared.v4.b32 {c8,c9,c10,c11}, [%48+16];\nld.volatile.shared.v4.b32 {c12,c13,c14,c15}, [%48+8208];\nand.b32 t, c0, 0xffe;\n"
        "mad.lo.u32 t, t, 4, 0x200000;\nmov.b64 d0, {t, h};\nand.b32 t, c1, 0xffe;\nmad.lo.u32 t, t, 4, 0x200000;\nmov.b64 d1, {t, h};\nand.b32 t, c2, 0xffe;\n"
        "mad.lo.u32 t, t, 4, 0x200000;\nmov.b64 d2, {t, h};\nand.b32 t, c3, 0xffe;\nmad.lo.u32 t, t, 4, 0x200000;\nmov.b64 d3, {t, h};\nand.b32 t, c4, 0xffe;\n"
        "mad.lo.u32 t, t, 4, 0x200000;\nmov.b64 d4, {t, h};\nand.b32 t, c5, 0xffe;\nmad.lo.u32 t, t, 4, 0x200000;\nmov.b64 d5, {t, h};\nand.b32 t, c6, 0xffe;\n"
        "mad.lo.u32 t, t, 4, 0x200000;\nmov.b64 d6, {t, h};\nand.b32 t, c7, 0xffe;\nmad.lo.u32 t, t, 4, 0x200000;\nmov.b64 d7, {t, h};\nand.b32 t, c8, 0xffe;\n"
        "mad.lo.u32 t, t, 4, 0x200000;\nmov.b64 d8, {t, h};\nand.b32 t, c9, 0xffe;\nmad.lo.u32 t, t, 4, 0x200000;\nmov.b64 d9, {t, h};\nand.b32 t, c10, 0xffe;\n"
        "mad.lo.u32 t, t, 4, 0x200000;\nmov.b64 d10, {t, h};\nand.b32 t, c11, 0xffe;\nmad.lo.u32 t, t, 4, 0x200000;\nmov.b64 d11, {t, h};\n"
        "and.b32 t, c12, 0xffe;\nmad.lo.u32 t, t, 4, 0x200000;\nmov.b64 d12, {t, h};\nand.b32 t, c13, 0xffe;\nmad.lo.u32 t, t, 4, 0x200000;\n"
        "mov.b64 d13, {t, h};\nand.b32 t, c14, 0xffe;\nmad.lo.u32 t, t, 4, 0x200000;\nmov.b64 d14, {t, h};\nand.b32 t, c15, 0xffe;\n"
        "mad.lo.u32 t, t, 4, 0x200000;\nmov.b64 d15, {t, h};\nwgmma.fence.sync.aligned;\n"
        "wgmma.mma_async.sync.aligned.m64n32k16.f32.bf16.bf16 {o0,o1,o2,o3,o4,o5,o6,o7,o8,o9,o10,o11,o12,o13,o14,o15}, {b0,b1,b2,b3}, d0, p0, 1, 1, 1;\n"
        "wgmma.mma_async.sync.aligned.m64n32k16.f32.bf16.bf16 {o16,o17,o18,o19,o20,o21,o22,o23,o24,o25,o26,o27,o28,o29,o30,o31}, {b0,b1,b2,b3}, d8, p0, 1, 1, 1;\n"
        "wgmma.mma_async.sync.aligned.m64n32k16.f32.bf16.bf16 {o0,o1,o2,o3,o4,o5,o6,o7,o8,o9,o10,o11,o12,o13,o14,o15}, {b4,b5,b6,b7}, d1, p1, 1, 1, 1;\n"
        "wgmma.mma_async.sync.aligned.m64n32k16.f32.bf16.bf16 {o16,o17,o18,o19,o20,o21,o22,o23,o24,o25,o26,o27,o28,o29,o30,o31}, {b4,b5,b6,b7}, d9, p1, 1, 1, 1;\n"
        "wgmma.mma_async.sync.aligned.m64n32k16.f32.bf16.bf16 {o0,o1,o2,o3,o4,o5,o6,o7,o8,o9,o10,o11,o12,o13,o14,o15}, {b8,b9,b10,b11}, d2, p1, 1, 1, 1;\n"
        "wgmma.mma_async.sync.aligned.m64n32k16.f32.bf16.bf16 {o16,o17,o18,o19,o20,o21,o22,o23,o24,o25,o26,o27,o28,o29,o30,o31}, {b8,b9,b10,b11}, d10, p1, 1, 1, 1;\n"
        "wgmma.mma_async.sync.aligned.m64n32k16.f32.bf16.bf16 {o0,o1,o2,o3,o4,o5,o6,o7,o8,o9,o10,o11,o12,o13,o14,o15}, {b12,b13,b14,b15}, d3, p1, 1, 1, 1;\n"
        "wgmma.mma_async.sync.aligned.m64n32k16.f32.bf16.bf16 {o16,o17,o18,o19,o20,o21,o22,o23,o24,o25,o26,o27,o28,o29,o30,o31}, {b12,b13,b14,b15}, d11, p1, 1, 1, 1;\n"
        "wgmma.mma_async.sync.aligned.m64n32k16.f32.bf16.bf16 {o0,o1,o2,o3,o4,o5,o6,o7,o8,o9,o10,o11,o12,o13,o14,o15}, {b16,b17,b18,b19}, d4, p1, 1, 1, 1;\n"
        "wgmma.mma_async.sync.aligned.m64n32k16.f32.bf16.bf16 {o16,o17,o18,o19,o20,o21,o22,o23,o24,o25,o26,o27,o28,o29,o30,o31}, {b16,b17,b18,b19}, d12, p1, 1, 1, 1;\n"
        "wgmma.mma_async.sync.aligned.m64n32k16.f32.bf16.bf16 {o0,o1,o2,o3,o4,o5,o6,o7,o8,o9,o10,o11,o12,o13,o14,o15}, {b20,b21,b22,b23}, d5, p1, 1, 1, 1;\n"
        "wgmma.mma_async.sync.aligned.m64n32k16.f32.bf16.bf16 {o16,o17,o18,o19,o20,o21,o22,o23,o24,o25,o26,o27,o28,o29,o30,o31}, {b20,b21,b22,b23}, d13, p1, 1, 1, 1;\n"
        "wgmma.mma_async.sync.aligned.m64n32k16.f32.bf16.bf16 {o0,o1,o2,o3,o4,o5,o6,o7,o8,o9,o10,o11,o12,o13,o14,o15}, {b24,b25,b26,b27}, d6, p1, 1, 1, 1;\n"
        "wgmma.mma_async.sync.aligned.m64n32k16.f32.bf16.bf16 {o16,o17,o18,o19,o20,o21,o22,o23,o24,o25,o26,o27,o28,o29,o30,o31}, {b24,b25,b26,b27}, d14, p1, 1, 1, 1;\n"
        "wgmma.mma_async.sync.aligned.m64n32k16.f32.bf16.bf16 {o0,o1,o2,o3,o4,o5,o6,o7,o8,o9,o10,o11,o12,o13,o14,o15}, {b28,b29,b30,b31}, d7, p1, 1, 1, 1;\n"
        "wgmma.mma_async.sync.aligned.m64n32k16.f32.bf16.bf16 {o16,o17,o18,o19,o20,o21,o22,o23,o24,o25,o26,o27,o28,o29,o30,o31}, {b28,b29,b30,b31}, d15, p1, 1, 1, 1;\n"
        "wgmma.commit_group.sync.aligned;\n@nv bra.uni END;\n@s0 st.global.v4.b32 [%49+128], {k0,k1,k2,k3};\n@s1 st.global.v4.b32 [%50+128], {k4,k5,k6,k7};\n"
        "@s0 st.global.v4.b32 [%49+192], {k8,k9,k10,k11};\n@s1 st.global.v4.b32 [%50+192], {k12,k13,k14,k15};\n@nv bra.uni END;\n"
        "wgmma.wait_group.sync.aligned 0;\ncvt.rn.bf16x2.f32 k0, o1, o0;\ncvt.rn.bf16x2.f32 k1, o5, o4;\ncvt.rn.bf16x2.f32 k2, o9, o8;\n"
        "cvt.rn.bf16x2.f32 k3, o13, o12;\ncvt.rn.bf16x2.f32 k8, o17, o16;\ncvt.rn.bf16x2.f32 k9, o21, o20;\ncvt.rn.bf16x2.f32 k10, o25, o24;\n"
        "cvt.rn.bf16x2.f32 k11, o29, o28;\nld.volatile.shared.v4.b32 {c0,c1,c2,c3}, [%48+32];\nld.volatile.shared.v4.b32 {c4,c5,c6,c7}, [%48+8224];\n"
        "ld.volatile.shared.v4.b32 {c8,c9,c10,c11}, [%48+48];\nld.volatile.shared.v4.b32 {c12,c13,c14,c15}, [%48+8240];\nand.b32 t, c0, 0xffe;\n"
        "mad.lo.u32 t, t, 4, 0x200000;\nmov.b64 d0, {t, h};\nand.b32 t, c1, 0xffe;\nmad.lo.u32 t, t, 4, 0x200000;\nmov.b64 d1, {t, h};\nand.b32 t, c2, 0xffe;\n"
        "mad.lo.u32 t, t, 4, 0x200000;\nmov.b64 d2, {t, h};\nand.b32 t, c3, 0xffe;\nmad.lo.u32 t, t, 4, 0x200000;\nmov.b64 d3, {t, h};\nand.b32 t, c4, 0xffe;\n"
        "mad.lo.u32 t, t, 4, 0x200000;\nmov.b64 d4, {t, h};\nand.b32 t, c5, 0xffe;\nmad.lo.u32 t, t, 4, 0x200000;\nmov.b64 d5, {t, h};\nand.b32 t, c6, 0xffe;\n"
        "mad.lo.u32 t, t, 4, 0x200000;\nmov.b64 d6, {t, h};\nand.b32 t, c7, 0xffe;\nmad.lo.u32 t, t, 4, 0x200000;\nmov.b64 d7, {t, h};\nand.b32 t, c8, 0xffe;\n"
        "mad.lo.u32 t, t, 4, 0x200000;\nmov.b64 d8, {t, h};\nand.b32 t, c9, 0xffe;\nmad.lo.u32 t, t, 4, 0x200000;\nmov.b64 d9, {t, h};\nand.b32 t, c10, 0xffe;\n"
        "mad.lo.u32 t, t, 4, 0x200000;\nmov.b64 d10, {t, h};\nand.b32 t, c11, 0xffe;\nmad.lo.u32 t, t, 4, 0x200000;\nmov.b64 d11, {t, h};\n"
        "and.b32 t, c12, 0xffe;\nmad.lo.u32 t, t, 4, 0x200000;\nmov.b64 d12, {t, h};\nand.b32 t, c13, 0xffe;\nmad.lo.u32 t, t, 4, 0x200000;\n"
        "mov.b64 d13, {t, h};\nand.b32 t, c14, 0xffe;\nmad.lo.u32 t, t, 4, 0x200000;\nmov.b64 d14, {t, h};\nand.b32 t, c15, 0xffe;\n"
        "mad.lo.u32 t, t, 4, 0x200000;\nmov.b64 d15, {t, h};\nwgmma.fence.sync.aligned;\n"
        "wgmma.mma_async.sync.aligned.m64n32k16.f32.bf16.bf16 {o0,o1,o2,o3,o4,o5,o6,o7,o8,o9,o10,o11,o12,o13,o14,o15}, {b0,b1,b2,b3}, d0, p0, 1, 1, 1;\n"
        "wgmma.mma_async.sync.aligned.m64n32k16.f32.bf16.bf16 {o16,o17,o18,o19,o20,o21,o22,o23,o24,o25,o26,o27,o28,o29,o30,o31}, {b0,b1,b2,b3}, d8, p0, 1, 1, 1;\n"
        "wgmma.mma_async.sync.aligned.m64n32k16.f32.bf16.bf16 {o0,o1,o2,o3,o4,o5,o6,o7,o8,o9,o10,o11,o12,o13,o14,o15}, {b4,b5,b6,b7}, d1, p1, 1, 1, 1;\n"
        "wgmma.mma_async.sync.aligned.m64n32k16.f32.bf16.bf16 {o16,o17,o18,o19,o20,o21,o22,o23,o24,o25,o26,o27,o28,o29,o30,o31}, {b4,b5,b6,b7}, d9, p1, 1, 1, 1;\n"
        "wgmma.mma_async.sync.aligned.m64n32k16.f32.bf16.bf16 {o0,o1,o2,o3,o4,o5,o6,o7,o8,o9,o10,o11,o12,o13,o14,o15}, {b8,b9,b10,b11}, d2, p1, 1, 1, 1;\n"
        "wgmma.mma_async.sync.aligned.m64n32k16.f32.bf16.bf16 {o16,o17,o18,o19,o20,o21,o22,o23,o24,o25,o26,o27,o28,o29,o30,o31}, {b8,b9,b10,b11}, d10, p1, 1, 1, 1;\n"
        "wgmma.mma_async.sync.aligned.m64n32k16.f32.bf16.bf16 {o0,o1,o2,o3,o4,o5,o6,o7,o8,o9,o10,o11,o12,o13,o14,o15}, {b12,b13,b14,b15}, d3, p1, 1, 1, 1;\n"
        "wgmma.mma_async.sync.aligned.m64n32k16.f32.bf16.bf16 {o16,o17,o18,o19,o20,o21,o22,o23,o24,o25,o26,o27,o28,o29,o30,o31}, {b12,b13,b14,b15}, d11, p1, 1, 1, 1;\n"
        "wgmma.mma_async.sync.aligned.m64n32k16.f32.bf16.bf16 {o0,o1,o2,o3,o4,o5,o6,o7,o8,o9,o10,o11,o12,o13,o14,o15}, {b16,b17,b18,b19}, d4, p1, 1, 1, 1;\n"
        "wgmma.mma_async.sync.aligned.m64n32k16.f32.bf16.bf16 {o16,o17,o18,o19,o20,o21,o22,o23,o24,o25,o26,o27,o28,o29,o30,o31}, {b16,b17,b18,b19}, d12, p1, 1, 1, 1;\n"
        "wgmma.mma_async.sync.aligned.m64n32k16.f32.bf16.bf16 {o0,o1,o2,o3,o4,o5,o6,o7,o8,o9,o10,o11,o12,o13,o14,o15}, {b20,b21,b22,b23}, d5, p1, 1, 1, 1;\n"
        "wgmma.mma_async.sync.aligned.m64n32k16.f32.bf16.bf16 {o16,o17,o18,o19,o20,o21,o22,o23,o24,o25,o26,o27,o28,o29,o30,o31}, {b20,b21,b22,b23}, d13, p1, 1, 1, 1;\n"
        "wgmma.mma_async.sync.aligned.m64n32k16.f32.bf16.bf16 {o0,o1,o2,o3,o4,o5,o6,o7,o8,o9,o10,o11,o12,o13,o14,o15}, {b24,b25,b26,b27}, d6, p1, 1, 1, 1;\n"
        "wgmma.mma_async.sync.aligned.m64n32k16.f32.bf16.bf16 {o16,o17,o18,o19,o20,o21,o22,o23,o24,o25,o26,o27,o28,o29,o30,o31}, {b24,b25,b26,b27}, d14, p1, 1, 1, 1;\n"
        "wgmma.mma_async.sync.aligned.m64n32k16.f32.bf16.bf16 {o0,o1,o2,o3,o4,o5,o6,o7,o8,o9,o10,o11,o12,o13,o14,o15}, {b28,b29,b30,b31}, d7, p1, 1, 1, 1;\n"
        "wgmma.mma_async.sync.aligned.m64n32k16.f32.bf16.bf16 {o16,o17,o18,o19,o20,o21,o22,o23,o24,o25,o26,o27,o28,o29,o30,o31}, {b28,b29,b30,b31}, d15, p1, 1, 1, 1;\n"
        "wgmma.commit_group.sync.aligned;\n@nv bra.uni END;\n@s2 st.global.v4.b32 [%51+0], {k0,k1,k2,k3};\n@s2 st.global.v4.b32 [%51+64], {k8,k9,k10,k11};\n"
        "@nv bra.uni END;\nwgmma.wait_group.sync.aligned 0;\ncvt.rn.bf16x2.f32 k0, o1, o0;\ncvt.rn.bf16x2.f32 k1, o5, o4;\ncvt.rn.bf16x2.f32 k2, o9, o8;\n"
        "cvt.rn.bf16x2.f32 k3, o13, o12;\ncvt.rn.bf16x2.f32 k8, o17, o16;\ncvt.rn.bf16x2.f32 k9, o21, o20;\ncvt.rn.bf16x2.f32 k10, o25, o24;\n"
        "cvt.rn.bf16x2.f32 k11, o29, o28;\n@s2 st.global.v4.b32 [%51+128], {k0,k1,k2,k3};\n@s2 st.global.v4.b32 [%51+192], {k8,k9,k10,k11};\n"
        "END:\n}\n"
        ::"r"(pk[0]), "r"(pk[1]), "r"(pk[2]), "r"(pk[3]), "r"(pk[4]), "r"(pk[5]), "r"(pk[6]), "r"(pk[7]), "r"(pk[8]), "r"(pk[9]), "r"(pk[10]),
          "r"(pk[11]), "r"(pk[12]), "r"(pk[13]), "r"(pk[14]), "r"(pk[15]), "r"(pk[16]), "r"(pk[17]), "r"(pk[18]), "r"(pk[19]), "r"(pk[20]),
          "r"(pk[21]), "r"(pk[22]), "r"(pk[23]), "r"(pk[24]), "r"(pk[25]), "r"(pk[26]), "r"(pk[27]), "r"(pk[28]), "r"(pk[29]), "r"(pk[30]),
          "r"(pk[31]), "r"(pk[32]), "r"(pk[33]), "r"(pk[34]), "r"(pk[35]), "r"(pk[36]), "r"(pk[37]), "r"(pk[38]), "r"(pk[39]), "r"(pk[40]),
          "r"(pk[41]), "r"(pk[42]), "r"(pk[43]), "r"(pk[44]), "r"(pk[45]), "r"(pk[46]), "r"(pk[47]), "r"(ra), "l"(p[0]), "l"(p[1]), "l"(p[2]),
          "r"(v[0]), "r"(v[1]), "r"(v[2]), "r"(ba)
        : "memory");
}
__device__ __forceinline__ int cta_id() {
    int v;
    asm volatile("mov.u32 %0, %ctaid.x;" : "=r"(v));
    return v;
}
__device__ __forceinline__ int thread_id() {
    int v;
    asm volatile("mov.u32 %0, %tid.x;" : "=r"(v));
    return v;
}

__device__ __forceinline__ void slow_edge(int ee, int s, float* accn, const __nv_bfloat16* __restrict__ x,
                                          const __nv_bfloat16* __restrict__ sh, const __nv_bfloat16* __restrict__ ea,
                                          const __nv_bfloat16* __restrict__ cg, const __nv_bfloat16* __restrict__ wr,
                                          int lane) {
    float rwv[4] = {0.f, 0.f, 0.f, 0.f};
#pragma unroll 4
    for (int d = 0; d < 16; d++) {
        const float a = __bfloat162float(ea[(size_t)ee * 16 + d]);
        const uint2 wv = *(const uint2*)(wr + d * 128 + lane * 4);
        rwv[0] += a * __uint_as_float(wv.x << 16);
        rwv[1] += a * __uint_as_float(wv.x & 0xffff0000u);
        rwv[2] += a * __uint_as_float(wv.y << 16);
        rwv[3] += a * __uint_as_float(wv.y & 0xffff0000u);
    }
    float A = 0.f;
#pragma unroll
    for (int v = 0; v < 4; v++)
        A += __bfloat162float(cg[((lane >> 2) & 3) * 16 + v * 4 + (lane & 3)]) * __bfloat162float(sh[(size_t)ee * 4 + v]);
    float m[4][4];
#pragma unroll
    for (int w = 0; w < 4; w++)
#pragma unroll
        for (int j = 0; j < 4; j++) m[w][j] = 0.f;
#pragma unroll
    for (int u = 0; u < 4; u++) {
        const uint2 xv = *(const uint2*)(x + (size_t)s * 512 + u * 128 + lane * 4);
        const float x0 = __uint_as_float(xv.x << 16), x1 = __uint_as_float(xv.x & 0xffff0000u);
        const float x2 = __uint_as_float(xv.y << 16), x3 = __uint_as_float(xv.y & 0xffff0000u);
#pragma unroll
        for (int w = 0; w < 4; w++) {
            const float a = __shfl_sync(0xffffffffu, A, u * 4 + w);
            m[w][0] += a * x0;
            m[w][1] += a * x1;
            m[w][2] += a * x2;
            m[w][3] += a * x3;
        }
    }
#pragma unroll
    for (int w = 0; w < 4; w++)
#pragma unroll
        for (int j = 0; j < 4; j++) atomicAdd(accn + w * 128 + lane * 4 + j, m[w][j] * rwv[j]);
}

__device__ __forceinline__ void slow_out(const float* accn, const __nv_bfloat16* __restrict__ wout,
                                         __nv_bfloat16* __restrict__ outn, int lane) {
    float o[4][4];
#pragma unroll
    for (int w = 0; w < 4; w++)
#pragma unroll
        for (int j = 0; j < 4; j++) o[w][j] = 0.f;
#pragma unroll 2
    for (int c = 0; c < 128; c++) {
        const uint2 wv = *(const uint2*)(wout + c * 128 + lane * 4);
        const float w0 = __uint_as_float(wv.x << 16), w1 = __uint_as_float(wv.x & 0xffff0000u);
        const float w2 = __uint_as_float(wv.y << 16), w3 = __uint_as_float(wv.y & 0xffff0000u);
#pragma unroll
        for (int w = 0; w < 4; w++) {
            const float a = __bfloat162float(__float2bfloat16(accn[w * 128 + c]));
            o[w][0] += a * w0;
            o[w][1] += a * w1;
            o[w][2] += a * w2;
            o[w][3] += a * w3;
        }
    }
#pragma unroll
    for (int w = 0; w < 4; w++)
        *(uint2*)(outn + w * 128 + lane * 4) = make_uint2(pack_bf16(o[w][0], o[w][1]), pack_bf16(o[w][2], o[w][3]));
}

__device__ __forceinline__ void consume4(uint32_t (&pk)[64], const uint32_t (&w)[36], uint32_t olp, uint32_t xa, uint32_t ln,
                                      uint32_t lc, uint32_t linc, uint32_t lt, const __nv_bfloat16* ea, const __nv_bfloat16* sh, const void* wf) {
    ea += lt * 4, sh += lt & 2;
    asm volatile(
        "{\n.reg .pred p, q, psw, prdy, ps1, ps2, ps3, pz;\n.reg .f32 d<32>, fz;\n"
        ".reg .b32 h<64>, x<32>, y<32>, ra<8>, rb<8>, bA0, bA1, bB0, bB1, c0, c1, c2, c3, e0, e1, s0, kept;\n"
        ".reg .b32 olp, v, vB, m, id, ida, bar, xb, pos, t0, t1, t2, t3, n, z<16>;\n.reg .b16 lo, hi, i16;\n.reg .b64 pa, pb;\nmov.f32 fz, 0f00000000;\n"
        "mov.b32 h0, 0;\nmov.b32 h1, 0;\nmov.b32 h2, 0;\nmov.b32 h3, 0;\nmov.b32 h4, 0;\nmov.b32 h5, 0;\nmov.b32 h6, 0;\nmov.b32 h7, 0;\nmov.b32 h8, 0;\n"
        "mov.b32 h9, 0;\nmov.b32 h10, 0;\nmov.b32 h11, 0;\nmov.b32 h12, 0;\nmov.b32 h13, 0;\nmov.b32 h14, 0;\nmov.b32 h15, 0;\nmov.b32 h16, 0;\nmov.b32 h17, 0;\n"
        "mov.b32 h18, 0;\nmov.b32 h19, 0;\nmov.b32 h20, 0;\nmov.b32 h21, 0;\nmov.b32 h22, 0;\nmov.b32 h23, 0;\nmov.b32 h24, 0;\nmov.b32 h25, 0;\n"
        "mov.b32 h26, 0;\nmov.b32 h27, 0;\nmov.b32 h28, 0;\nmov.b32 h29, 0;\nmov.b32 h30, 0;\nmov.b32 h31, 0;\nmov.b32 h32, 0;\nmov.b32 h33, 0;\n"
        "mov.b32 h34, 0;\nmov.b32 h35, 0;\nmov.b32 h36, 0;\nmov.b32 h37, 0;\nmov.b32 h38, 0;\nmov.b32 h39, 0;\nmov.b32 h40, 0;\nmov.b32 h41, 0;\n"
        "mov.b32 h42, 0;\nmov.b32 h43, 0;\nmov.b32 h44, 0;\nmov.b32 h45, 0;\nmov.b32 h46, 0;\nmov.b32 h47, 0;\nmov.b32 h48, 0;\nmov.b32 h49, 0;\n"
        "mov.b32 h50, 0;\nmov.b32 h51, 0;\nmov.b32 h52, 0;\nmov.b32 h53, 0;\nmov.b32 h54, 0;\nmov.b32 h55, 0;\nmov.b32 h56, 0;\nmov.b32 h57, 0;\n"
        "mov.b32 h58, 0;\nmov.b32 h59, 0;\nmov.b32 h60, 0;\nmov.b32 h61, 0;\nmov.b32 h62, 0;\nmov.b32 h63, 0;\nmov.b32 olp, %64;\nand.b32 t0, %66, 32;\n"
        "setp.ne.u32 psw, t0, 0;\nsetp.eq.u32 pz, %64, 0;\nvote.sync.any.pred pz, pz, 0xffffffff;\nld.shared.u16 t0, [olp];\nadd.u32 olp, olp, 4;\n"
        "lop3.b32 t1, t0, %66, 0x3ff0, 0xe4;\nld.shared.b32 t1, [t1+%73];\nlop3.b32 kept, t1, t0, 0x1ffc, 0xe4;\nlop3.b32 t2, t1, %67, 3, 0x80;\n"
        "setp.ne.u32 q, t2, 0;\nshr.u32 t2, t1, 13;\nmad.wide.u32 pa, t2, 32, %70;\nmad.wide.u32 pb, t2, 8, %71;\nmov.b32 s0, 0;\n"
        "ld.global.cg.v2.b32 {e0,e1}, [pa];\n@q ld.global.cg.b32 s0, [pb];\nsetp.ne.u64 p, %72, 0;\n@p fence.proxy.async.global;\n"
        "@p red.release.gpu.global.add.u32 [%72+12], 1;\nbar.warp.sync 0xffffffff;\nshfl.sync.idx.b32 v, kept, %67, 0x1f, 0xffffffff;\nor.b32 t3, %67, 4;\n"
        "shfl.sync.idx.b32 vB, kept, t3, 0x1f, 0xffffffff;\n"
        "RW:\nmma.sync.aligned.m16n8k8.row.col.f32.bf16.bf16.f32 {d0,d1,d2,d3}, {%109,%110}, {s0}, {fz,fz,fz,fz};\n"
        "mma.sync.aligned.m16n8k8.row.col.f32.bf16.bf16.f32 {d4,d5,d6,d7}, {%111,%112}, {s0}, {fz,fz,fz,fz};\ncvt.rn.bf16x2.f32 c0, d2, d0;\n"
        "cvt.rn.bf16x2.f32 c1, d3, d1;\ncvt.rn.bf16x2.f32 c2, d6, d4;\ncvt.rn.bf16x2.f32 c3, d7, d5;\nselp.b32 bA0, c2, c0, psw;\nselp.b32 bA1, c0, c2, psw;\n"
        "selp.b32 bB0, c3, c1, psw;\nselp.b32 bB1, c1, c3, psw;\n"
        "mma.sync.aligned.m16n8k16.row.col.f32.bf16.bf16.f32 {d0,d1,d2,d3}, {%77,%78,%79,%80}, {e0,e1}, {fz,fz,fz,fz};\ncvt.rn.bf16x2.f32 ra0, d2, d0;\n"
        "cvt.rn.bf16x2.f32 rb0, d3, d1;\nmma.sync.aligned.m16n8k16.row.col.f32.bf16.bf16.f32 {d4,d5,d6,d7}, {%81,%82,%83,%84}, {e0,e1}, {fz,fz,fz,fz};\n"
        "cvt.rn.bf16x2.f32 ra1, d6, d4;\ncvt.rn.bf16x2.f32 rb1, d7, d5;\n"
        "mma.sync.aligned.m16n8k16.row.col.f32.bf16.bf16.f32 {d8,d9,d10,d11}, {%85,%86,%87,%88}, {e0,e1}, {fz,fz,fz,fz};\ncvt.rn.bf16x2.f32 ra2, d10, d8;\n"
        "cvt.rn.bf16x2.f32 rb2, d11, d9;\nmma.sync.aligned.m16n8k16.row.col.f32.bf16.bf16.f32 {d12,d13,d14,d15}, {%89,%90,%91,%92}, {e0,e1}, {fz,fz,fz,fz};\n"
        "cvt.rn.bf16x2.f32 ra3, d14, d12;\ncvt.rn.bf16x2.f32 rb3, d15, d13;\n"
        "mma.sync.aligned.m16n8k16.row.col.f32.bf16.bf16.f32 {d16,d17,d18,d19}, {%93,%94,%95,%96}, {e0,e1}, {fz,fz,fz,fz};\ncvt.rn.bf16x2.f32 ra4, d18, d16;\n"
        "cvt.rn.bf16x2.f32 rb4, d19, d17;\nmma.sync.aligned.m16n8k16.row.col.f32.bf16.bf16.f32 {d20,d21,d22,d23}, {%97,%98,%99,%100}, {e0,e1}, {fz,fz,fz,fz};\n"
        "cvt.rn.bf16x2.f32 ra5, d22, d20;\ncvt.rn.bf16x2.f32 rb5, d23, d21;\n"
        "mma.sync.aligned.m16n8k16.row.col.f32.bf16.bf16.f32 {d24,d25,d26,d27}, {%101,%102,%103,%104}, {e0,e1}, {fz,fz,fz,fz};\n"
        "cvt.rn.bf16x2.f32 ra6, d26, d24;\ncvt.rn.bf16x2.f32 rb6, d27, d25;\n"
        "mma.sync.aligned.m16n8k16.row.col.f32.bf16.bf16.f32 {d28,d29,d30,d31}, {%105,%106,%107,%108}, {e0,e1}, {fz,fz,fz,fz};\n"
        "cvt.rn.bf16x2.f32 ra7, d30, d28;\ncvt.rn.bf16x2.f32 rb7, d31, d29;\nld.shared.u16 t0, [olp];\nadd.u32 olp, olp, 4;\n"
        "lop3.b32 t1, t0, %66, 0x3ff0, 0xe4;\nld.shared.b32 t1, [t1+%73];\nlop3.b32 kept, t1, t0, 0x1ffc, 0xe4;\nlop3.b32 t2, t1, %67, 3, 0x80;\n"
        "setp.ne.u32 q, t2, 0;\nshr.u32 t2, t1, 13;\nmad.wide.u32 pa, t2, 32, %70;\nmad.wide.u32 pb, t2, 8, %71;\nmov.b32 s0, 0;\n"
        "ld.global.cg.v2.b32 {e0,e1}, [pa];\n@q ld.global.cg.b32 s0, [pb];\nshr.u32 bar, v, 1;\nand.b32 bar, bar, 0xff8;\n"
        "mbarrier.test_wait.parity.shared.b64 p, [bar+%75], 0;\nlop3.b32 ida, v, %67, 0x1fff, 0xe4;\nld.volatile.shared.u16 id, [ida+%74];\n"
        "vote.sync.all.pred prdy, p, 0xffffffff;\n@!prdy bra.uni WA;\n"
        "HA:\nmad.lo.u32 xb, id, 64, %65;\ncvt.u16.u32 i16, id;\natom.shared.add.u32 pos, [%66+%76], %68;\n"
        "ldmatrix.sync.aligned.m8n8.x4.trans.shared.b16 {x0,x1,x2,x3}, [xb];\nldmatrix.sync.aligned.m8n8.x4.trans.shared.b16 {x24,x25,x26,x27}, [xb+512];\n"
        "xor.b32 t1, xb, 32;\nldmatrix.sync.aligned.m8n8.x4.trans.shared.b16 {x4,x5,x6,x7}, [t1];\n"
        "ldmatrix.sync.aligned.m8n8.x4.trans.shared.b16 {x28,x29,x30,x31}, [t1+512];\nxor.b32 t1, xb, 64;\n"
        "ldmatrix.sync.aligned.m8n8.x4.trans.shared.b16 {x8,x9,x10,x11}, [t1];\nldmatrix.sync.aligned.m8n8.x4.trans.shared.b16 {x16,x17,x18,x19}, [t1+512];\n"
        "xor.b32 t1, xb, 96;\nldmatrix.sync.aligned.m8n8.x4.trans.shared.b16 {x12,x13,x14,x15}, [t1];\n"
        "ldmatrix.sync.aligned.m8n8.x4.trans.shared.b16 {x20,x21,x22,x23}, [t1+512];\nst.volatile.shared.u16 [pos], i16;\nand.b32 t0, v, 16384;\n"
        "setp.ne.u32 ps1, t0, 0;\nvote.sync.any.pred ps1, ps1, 0xffffffff;\nand.b32 t0, v, 32768;\nsetp.ne.u32 ps2, t0, 0;\n"
        "vote.sync.any.pred ps2, ps2, 0xffffffff;\nmov.b32 v, vB;\nshr.u32 bar, v, 1;\nand.b32 bar, bar, 0xff8;\n"
        "mbarrier.test_wait.parity.shared.b64 p, [bar+%75], 0;\nlop3.b32 ida, v, %67, 0x1fff, 0xe4;\nld.volatile.shared.u16 id, [ida+%74];\n"
        "vote.sync.all.pred prdy, p, 0xffffffff;\nmov.b32 {lo, hi}, ra0;\nmov.b32 t2, {lo, lo};\nmul.rn.bf16x2 y0, x0, t2;\nmul.rn.bf16x2 y2, x2, t2;\n"
        "mov.b32 t2, {hi, hi};\nmul.rn.bf16x2 y1, x1, t2;\nmul.rn.bf16x2 y3, x3, t2;\n"
        "mma.sync.aligned.m16n8k16.row.col.f32.bf16.bf16.f32 {d0,d1,d2,d3}, {y0,y1,y2,y3}, {bA0,bA1}, {fz,fz,fz,fz};\ncvt.rn.bf16x2.f32 z0, d1, d0;\n"
        "cvt.rn.bf16x2.f32 z1, d3, d2;\nmov.b32 {lo, hi}, ra6;\nmov.b32 t2, {lo, lo};\nmul.rn.bf16x2 y24, x24, t2;\nmul.rn.bf16x2 y26, x26, t2;\n"
        "mov.b32 t2, {hi, hi};\nmul.rn.bf16x2 y25, x25, t2;\nmul.rn.bf16x2 y27, x27, t2;\n"
        "mma.sync.aligned.m16n8k16.row.col.f32.bf16.bf16.f32 {d24,d25,d26,d27}, {y24,y25,y26,y27}, {bA0,bA1}, {fz,fz,fz,fz};\ncvt.rn.bf16x2.f32 z12, d25, d24;\n"
        "cvt.rn.bf16x2.f32 z13, d27, d26;\nmov.b32 {lo, hi}, ra1;\nmov.b32 t2, {lo, lo};\nmul.rn.bf16x2 y4, x4, t2;\nmul.rn.bf16x2 y6, x6, t2;\n"
        "mov.b32 t2, {hi, hi};\nmul.rn.bf16x2 y5, x5, t2;\nmul.rn.bf16x2 y7, x7, t2;\n"
        "mma.sync.aligned.m16n8k16.row.col.f32.bf16.bf16.f32 {d4,d5,d6,d7}, {y4,y5,y6,y7}, {bA0,bA1}, {fz,fz,fz,fz};\ncvt.rn.bf16x2.f32 z2, d5, d4;\n"
        "cvt.rn.bf16x2.f32 z3, d7, d6;\nmov.b32 {lo, hi}, ra7;\nmov.b32 t2, {lo, lo};\nmul.rn.bf16x2 y28, x28, t2;\nmul.rn.bf16x2 y30, x30, t2;\n"
        "mov.b32 t2, {hi, hi};\nmul.rn.bf16x2 y29, x29, t2;\nmul.rn.bf16x2 y31, x31, t2;\n"
        "mma.sync.aligned.m16n8k16.row.col.f32.bf16.bf16.f32 {d28,d29,d30,d31}, {y28,y29,y30,y31}, {bA0,bA1}, {fz,fz,fz,fz};\ncvt.rn.bf16x2.f32 z14, d29, d28;\n"
        "cvt.rn.bf16x2.f32 z15, d31, d30;\nmov.b32 {lo, hi}, ra2;\nmov.b32 t2, {lo, lo};\nmul.rn.bf16x2 y8, x8, t2;\nmul.rn.bf16x2 y10, x10, t2;\n"
        "mov.b32 t2, {hi, hi};\nmul.rn.bf16x2 y9, x9, t2;\nmul.rn.bf16x2 y11, x11, t2;\n"
        "mma.sync.aligned.m16n8k16.row.col.f32.bf16.bf16.f32 {d8,d9,d10,d11}, {y8,y9,y10,y11}, {bA0,bA1}, {fz,fz,fz,fz};\ncvt.rn.bf16x2.f32 z4, d9, d8;\n"
        "cvt.rn.bf16x2.f32 z5, d11, d10;\nmov.b32 {lo, hi}, ra4;\nmov.b32 t2, {lo, lo};\nmul.rn.bf16x2 y16, x16, t2;\nmul.rn.bf16x2 y18, x18, t2;\n"
        "mov.b32 t2, {hi, hi};\nmul.rn.bf16x2 y17, x17, t2;\nmul.rn.bf16x2 y19, x19, t2;\n"
        "mma.sync.aligned.m16n8k16.row.col.f32.bf16.bf16.f32 {d16,d17,d18,d19}, {y16,y17,y18,y19}, {bA0,bA1}, {fz,fz,fz,fz};\ncvt.rn.bf16x2.f32 z8, d17, d16;\n"
        "cvt.rn.bf16x2.f32 z9, d19, d18;\nmov.b32 {lo, hi}, ra3;\nmov.b32 t2, {lo, lo};\nmul.rn.bf16x2 y12, x12, t2;\nmul.rn.bf16x2 y14, x14, t2;\n"
        "mov.b32 t2, {hi, hi};\nmul.rn.bf16x2 y13, x13, t2;\nmul.rn.bf16x2 y15, x15, t2;\n"
        "mma.sync.aligned.m16n8k16.row.col.f32.bf16.bf16.f32 {d12,d13,d14,d15}, {y12,y13,y14,y15}, {bA0,bA1}, {fz,fz,fz,fz};\ncvt.rn.bf16x2.f32 z6, d13, d12;\n"
        "cvt.rn.bf16x2.f32 z7, d15, d14;\nmov.b32 {lo, hi}, ra5;\nmov.b32 t2, {lo, lo};\nmul.rn.bf16x2 y20, x20, t2;\nmul.rn.bf16x2 y22, x22, t2;\n"
        "mov.b32 t2, {hi, hi};\nmul.rn.bf16x2 y21, x21, t2;\nmul.rn.bf16x2 y23, x23, t2;\n"
        "mma.sync.aligned.m16n8k16.row.col.f32.bf16.bf16.f32 {d20,d21,d22,d23}, {y20,y21,y22,y23}, {bA0,bA1}, {fz,fz,fz,fz};\ncvt.rn.bf16x2.f32 z10, d21, d20;\n"
        "cvt.rn.bf16x2.f32 z11, d23, d22;\n@ps2 bra.uni TA2;\n@ps1 bra.uni TA1;\n"
        "TA0:\nadd.rn.bf16x2 h0, h0, z0;\nadd.rn.bf16x2 h1, h1, z1;\nadd.rn.bf16x2 h2, h2, z2;\nadd.rn.bf16x2 h3, h3, z3;\nadd.rn.bf16x2 h4, h4, z4;\n"
        "add.rn.bf16x2 h5, h5, z5;\nadd.rn.bf16x2 h6, h6, z6;\nadd.rn.bf16x2 h7, h7, z7;\nadd.rn.bf16x2 h8, h8, z8;\nadd.rn.bf16x2 h9, h9, z9;\n"
        "add.rn.bf16x2 h10, h10, z10;\nadd.rn.bf16x2 h11, h11, z11;\nadd.rn.bf16x2 h12, h12, z12;\nadd.rn.bf16x2 h13, h13, z13;\nadd.rn.bf16x2 h14, h14, z14;\n"
        "add.rn.bf16x2 h15, h15, z15;\n@prdy bra.uni HB;\nbra.uni WB;\n"
        "TA1:\nadd.rn.bf16x2 h16, h16, z0;\nadd.rn.bf16x2 h17, h17, z1;\nadd.rn.bf16x2 h18, h18, z2;\nadd.rn.bf16x2 h19, h19, z3;\nadd.rn.bf16x2 h20, h20, z4;\n"
        "add.rn.bf16x2 h21, h21, z5;\nadd.rn.bf16x2 h22, h22, z6;\nadd.rn.bf16x2 h23, h23, z7;\nadd.rn.bf16x2 h24, h24, z8;\nadd.rn.bf16x2 h25, h25, z9;\n"
        "add.rn.bf16x2 h26, h26, z10;\nadd.rn.bf16x2 h27, h27, z11;\nadd.rn.bf16x2 h28, h28, z12;\nadd.rn.bf16x2 h29, h29, z13;\nadd.rn.bf16x2 h30, h30, z14;\n"
        "add.rn.bf16x2 h31, h31, z15;\n@prdy bra.uni HB;\nbra.uni WB;\n"
        "TA2:\n@ps1 bra.uni TA3;\nadd.rn.bf16x2 h32, h32, z0;\nadd.rn.bf16x2 h33, h33, z1;\nadd.rn.bf16x2 h34, h34, z2;\nadd.rn.bf16x2 h35, h35, z3;\n"
        "add.rn.bf16x2 h36, h36, z4;\nadd.rn.bf16x2 h37, h37, z5;\nadd.rn.bf16x2 h38, h38, z6;\nadd.rn.bf16x2 h39, h39, z7;\nadd.rn.bf16x2 h40, h40, z8;\n"
        "add.rn.bf16x2 h41, h41, z9;\nadd.rn.bf16x2 h42, h42, z10;\nadd.rn.bf16x2 h43, h43, z11;\nadd.rn.bf16x2 h44, h44, z12;\nadd.rn.bf16x2 h45, h45, z13;\n"
        "add.rn.bf16x2 h46, h46, z14;\nadd.rn.bf16x2 h47, h47, z15;\n@prdy bra.uni HB;\nbra.uni WB;\n"
        "TA3:\nadd.rn.bf16x2 h48, h48, z0;\nadd.rn.bf16x2 h49, h49, z1;\nadd.rn.bf16x2 h50, h50, z2;\nadd.rn.bf16x2 h51, h51, z3;\nadd.rn.bf16x2 h52, h52, z4;\n"
        "add.rn.bf16x2 h53, h53, z5;\nadd.rn.bf16x2 h54, h54, z6;\nadd.rn.bf16x2 h55, h55, z7;\nadd.rn.bf16x2 h56, h56, z8;\nadd.rn.bf16x2 h57, h57, z9;\n"
        "add.rn.bf16x2 h58, h58, z10;\nadd.rn.bf16x2 h59, h59, z11;\nadd.rn.bf16x2 h60, h60, z12;\nadd.rn.bf16x2 h61, h61, z13;\nadd.rn.bf16x2 h62, h62, z14;\n"
        "add.rn.bf16x2 h63, h63, z15;\n@prdy bra.uni HB;\nbra.uni WB;\n"
        "HB:\nmad.lo.u32 xb, id, 64, %65;\ncvt.u16.u32 i16, id;\natom.shared.add.u32 pos, [%66+%76], %68;\n"
        "ldmatrix.sync.aligned.m8n8.x4.trans.shared.b16 {x0,x1,x2,x3}, [xb];\nldmatrix.sync.aligned.m8n8.x4.trans.shared.b16 {x24,x25,x26,x27}, [xb+512];\n"
        "xor.b32 t1, xb, 32;\nldmatrix.sync.aligned.m8n8.x4.trans.shared.b16 {x4,x5,x6,x7}, [t1];\n"
        "ldmatrix.sync.aligned.m8n8.x4.trans.shared.b16 {x28,x29,x30,x31}, [t1+512];\nxor.b32 t1, xb, 64;\n"
        "ldmatrix.sync.aligned.m8n8.x4.trans.shared.b16 {x8,x9,x10,x11}, [t1];\nldmatrix.sync.aligned.m8n8.x4.trans.shared.b16 {x16,x17,x18,x19}, [t1+512];\n"
        "xor.b32 t1, xb, 96;\nldmatrix.sync.aligned.m8n8.x4.trans.shared.b16 {x12,x13,x14,x15}, [t1];\n"
        "ldmatrix.sync.aligned.m8n8.x4.trans.shared.b16 {x20,x21,x22,x23}, [t1+512];\nst.volatile.shared.u16 [pos], i16;\nand.b32 t0, v, 16384;\n"
        "setp.ne.u32 ps1, t0, 0;\nvote.sync.any.pred ps1, ps1, 0xffffffff;\nand.b32 t0, v, 32768;\nsetp.ne.u32 ps2, t0, 0;\n"
        "vote.sync.any.pred ps2, ps2, 0xffffffff;\nshfl.sync.idx.b32 v, kept, %67, 0x1f, 0xffffffff;\nor.b32 t3, %67, 4;\n"
        "shfl.sync.idx.b32 vB, kept, t3, 0x1f, 0xffffffff;\nmov.b32 {lo, hi}, rb0;\nmov.b32 t2, {lo, lo};\nmul.rn.bf16x2 y0, x0, t2;\nmul.rn.bf16x2 y2, x2, t2;\n"
        "mov.b32 t2, {hi, hi};\nmul.rn.bf16x2 y1, x1, t2;\nmul.rn.bf16x2 y3, x3, t2;\n"
        "mma.sync.aligned.m16n8k16.row.col.f32.bf16.bf16.f32 {d0,d1,d2,d3}, {y0,y1,y2,y3}, {bB0,bB1}, {fz,fz,fz,fz};\ncvt.rn.bf16x2.f32 z0, d1, d0;\n"
        "cvt.rn.bf16x2.f32 z1, d3, d2;\nmov.b32 {lo, hi}, rb6;\nmov.b32 t2, {lo, lo};\nmul.rn.bf16x2 y24, x24, t2;\nmul.rn.bf16x2 y26, x26, t2;\n"
        "mov.b32 t2, {hi, hi};\nmul.rn.bf16x2 y25, x25, t2;\nmul.rn.bf16x2 y27, x27, t2;\n"
        "mma.sync.aligned.m16n8k16.row.col.f32.bf16.bf16.f32 {d24,d25,d26,d27}, {y24,y25,y26,y27}, {bB0,bB1}, {fz,fz,fz,fz};\ncvt.rn.bf16x2.f32 z12, d25, d24;\n"
        "cvt.rn.bf16x2.f32 z13, d27, d26;\nmov.b32 {lo, hi}, rb1;\nmov.b32 t2, {lo, lo};\nmul.rn.bf16x2 y4, x4, t2;\nmul.rn.bf16x2 y6, x6, t2;\n"
        "mov.b32 t2, {hi, hi};\nmul.rn.bf16x2 y5, x5, t2;\nmul.rn.bf16x2 y7, x7, t2;\n"
        "mma.sync.aligned.m16n8k16.row.col.f32.bf16.bf16.f32 {d4,d5,d6,d7}, {y4,y5,y6,y7}, {bB0,bB1}, {fz,fz,fz,fz};\ncvt.rn.bf16x2.f32 z2, d5, d4;\n"
        "cvt.rn.bf16x2.f32 z3, d7, d6;\nmov.b32 {lo, hi}, rb7;\nmov.b32 t2, {lo, lo};\nmul.rn.bf16x2 y28, x28, t2;\nmul.rn.bf16x2 y30, x30, t2;\n"
        "mov.b32 t2, {hi, hi};\nmul.rn.bf16x2 y29, x29, t2;\nmul.rn.bf16x2 y31, x31, t2;\n"
        "mma.sync.aligned.m16n8k16.row.col.f32.bf16.bf16.f32 {d28,d29,d30,d31}, {y28,y29,y30,y31}, {bB0,bB1}, {fz,fz,fz,fz};\ncvt.rn.bf16x2.f32 z14, d29, d28;\n"
        "cvt.rn.bf16x2.f32 z15, d31, d30;\nmov.b32 {lo, hi}, rb2;\nmov.b32 t2, {lo, lo};\nmul.rn.bf16x2 y8, x8, t2;\nmul.rn.bf16x2 y10, x10, t2;\n"
        "mov.b32 t2, {hi, hi};\nmul.rn.bf16x2 y9, x9, t2;\nmul.rn.bf16x2 y11, x11, t2;\n"
        "mma.sync.aligned.m16n8k16.row.col.f32.bf16.bf16.f32 {d8,d9,d10,d11}, {y8,y9,y10,y11}, {bB0,bB1}, {fz,fz,fz,fz};\ncvt.rn.bf16x2.f32 z4, d9, d8;\n"
        "cvt.rn.bf16x2.f32 z5, d11, d10;\nmov.b32 {lo, hi}, rb4;\nmov.b32 t2, {lo, lo};\nmul.rn.bf16x2 y16, x16, t2;\nmul.rn.bf16x2 y18, x18, t2;\n"
        "mov.b32 t2, {hi, hi};\nmul.rn.bf16x2 y17, x17, t2;\nmul.rn.bf16x2 y19, x19, t2;\n"
        "mma.sync.aligned.m16n8k16.row.col.f32.bf16.bf16.f32 {d16,d17,d18,d19}, {y16,y17,y18,y19}, {bB0,bB1}, {fz,fz,fz,fz};\ncvt.rn.bf16x2.f32 z8, d17, d16;\n"
        "cvt.rn.bf16x2.f32 z9, d19, d18;\nmov.b32 {lo, hi}, rb3;\nmov.b32 t2, {lo, lo};\nmul.rn.bf16x2 y12, x12, t2;\nmul.rn.bf16x2 y14, x14, t2;\n"
        "mov.b32 t2, {hi, hi};\nmul.rn.bf16x2 y13, x13, t2;\nmul.rn.bf16x2 y15, x15, t2;\n"
        "mma.sync.aligned.m16n8k16.row.col.f32.bf16.bf16.f32 {d12,d13,d14,d15}, {y12,y13,y14,y15}, {bB0,bB1}, {fz,fz,fz,fz};\ncvt.rn.bf16x2.f32 z6, d13, d12;\n"
        "cvt.rn.bf16x2.f32 z7, d15, d14;\nmov.b32 {lo, hi}, rb5;\nmov.b32 t2, {lo, lo};\nmul.rn.bf16x2 y20, x20, t2;\nmul.rn.bf16x2 y22, x22, t2;\n"
        "mov.b32 t2, {hi, hi};\nmul.rn.bf16x2 y21, x21, t2;\nmul.rn.bf16x2 y23, x23, t2;\n"
        "mma.sync.aligned.m16n8k16.row.col.f32.bf16.bf16.f32 {d20,d21,d22,d23}, {y20,y21,y22,y23}, {bB0,bB1}, {fz,fz,fz,fz};\ncvt.rn.bf16x2.f32 z10, d21, d20;\n"
        "cvt.rn.bf16x2.f32 z11, d23, d22;\n@ps2 bra.uni TB2;\n@ps1 bra.uni TB1;\n"
        "TB0:\nadd.rn.bf16x2 h0, h0, z0;\nadd.rn.bf16x2 h1, h1, z1;\nadd.rn.bf16x2 h2, h2, z2;\nadd.rn.bf16x2 h3, h3, z3;\nadd.rn.bf16x2 h4, h4, z4;\n"
        "add.rn.bf16x2 h5, h5, z5;\nadd.rn.bf16x2 h6, h6, z6;\nadd.rn.bf16x2 h7, h7, z7;\nadd.rn.bf16x2 h8, h8, z8;\nadd.rn.bf16x2 h9, h9, z9;\n"
        "add.rn.bf16x2 h10, h10, z10;\nadd.rn.bf16x2 h11, h11, z11;\nadd.rn.bf16x2 h12, h12, z12;\nadd.rn.bf16x2 h13, h13, z13;\nadd.rn.bf16x2 h14, h14, z14;\n"
        "add.rn.bf16x2 h15, h15, z15;\nbra.uni RW;\n"
        "TB1:\nadd.rn.bf16x2 h16, h16, z0;\nadd.rn.bf16x2 h17, h17, z1;\nadd.rn.bf16x2 h18, h18, z2;\nadd.rn.bf16x2 h19, h19, z3;\nadd.rn.bf16x2 h20, h20, z4;\n"
        "add.rn.bf16x2 h21, h21, z5;\nadd.rn.bf16x2 h22, h22, z6;\nadd.rn.bf16x2 h23, h23, z7;\nadd.rn.bf16x2 h24, h24, z8;\nadd.rn.bf16x2 h25, h25, z9;\n"
        "add.rn.bf16x2 h26, h26, z10;\nadd.rn.bf16x2 h27, h27, z11;\nadd.rn.bf16x2 h28, h28, z12;\nadd.rn.bf16x2 h29, h29, z13;\nadd.rn.bf16x2 h30, h30, z14;\n"
        "add.rn.bf16x2 h31, h31, z15;\nbra.uni RW;\n"
        "TB2:\n@ps1 bra.uni TB3;\nadd.rn.bf16x2 h32, h32, z0;\nadd.rn.bf16x2 h33, h33, z1;\nadd.rn.bf16x2 h34, h34, z2;\nadd.rn.bf16x2 h35, h35, z3;\n"
        "add.rn.bf16x2 h36, h36, z4;\nadd.rn.bf16x2 h37, h37, z5;\nadd.rn.bf16x2 h38, h38, z6;\nadd.rn.bf16x2 h39, h39, z7;\nadd.rn.bf16x2 h40, h40, z8;\n"
        "add.rn.bf16x2 h41, h41, z9;\nadd.rn.bf16x2 h42, h42, z10;\nadd.rn.bf16x2 h43, h43, z11;\nadd.rn.bf16x2 h44, h44, z12;\nadd.rn.bf16x2 h45, h45, z13;\n"
        "add.rn.bf16x2 h46, h46, z14;\nadd.rn.bf16x2 h47, h47, z15;\nbra.uni RW;\n"
        "TB3:\nadd.rn.bf16x2 h48, h48, z0;\nadd.rn.bf16x2 h49, h49, z1;\nadd.rn.bf16x2 h50, h50, z2;\nadd.rn.bf16x2 h51, h51, z3;\nadd.rn.bf16x2 h52, h52, z4;\n"
        "add.rn.bf16x2 h53, h53, z5;\nadd.rn.bf16x2 h54, h54, z6;\nadd.rn.bf16x2 h55, h55, z7;\nadd.rn.bf16x2 h56, h56, z8;\nadd.rn.bf16x2 h57, h57, z9;\n"
        "add.rn.bf16x2 h58, h58, z10;\nadd.rn.bf16x2 h59, h59, z11;\nadd.rn.bf16x2 h60, h60, z12;\nadd.rn.bf16x2 h61, h61, z13;\nadd.rn.bf16x2 h62, h62, z14;\n"
        "add.rn.bf16x2 h63, h63, z15;\nbra.uni RW;\n"
        "WA:\nshr.u32 t2, v, 1;\nand.b32 t2, t2, 0xff8;\nsetp.eq.u32 p, t2, 0;\nvote.sync.all.pred p, p, 0xffffffff;\n@p bra.uni DONE;\nmov.b32 n, 0;\n"
        "WA3:\nmbarrier.try_wait.parity.shared.b64 p, [t2+%75], 0;\nvote.sync.all.pred p, p, 0xffffffff;\nadd.u32 n, n, 1;\nsetp.lt.and.u32 q, n, 1000000, !p;\n"
        "@q bra.uni WA3;\nlop3.b32 ida, v, %67, 0x1fff, 0xe4;\nld.volatile.shared.u16 id, [ida+%74];\nbra.uni HA;\n"
        "WB:\nshr.u32 t2, v, 1;\nand.b32 t2, t2, 0xff8;\nsetp.eq.u32 p, t2, 0;\nvote.sync.all.pred p, p, 0xffffffff;\n@p bra.uni DONE;\nmov.b32 n, 0;\n"
        "WB3:\nmbarrier.try_wait.parity.shared.b64 p, [t2+%75], 0;\nvote.sync.all.pred p, p, 0xffffffff;\nadd.u32 n, n, 1;\nsetp.lt.and.u32 q, n, 1000000, !p;\n"
        "@q bra.uni WB3;\nlop3.b32 ida, v, %67, 0x1fff, 0xe4;\nld.volatile.shared.u16 id, [ida+%74];\nbra.uni HB;\n"
        "DONE:\nmov.b32 %0, h0;\nmov.b32 %1, h1;\nmov.b32 %2, h2;\nmov.b32 %3, h3;\nmov.b32 %4, h4;\nmov.b32 %5, h5;\nmov.b32 %6, h6;\nmov.b32 %7, h7;\n"
        "mov.b32 %8, h8;\nmov.b32 %9, h9;\nmov.b32 %10, h10;\nmov.b32 %11, h11;\nmov.b32 %12, h12;\nmov.b32 %13, h13;\nmov.b32 %14, h14;\nmov.b32 %15, h15;\n"
        "mov.b32 %16, h16;\nmov.b32 %17, h17;\nmov.b32 %18, h18;\nmov.b32 %19, h19;\nmov.b32 %20, h20;\nmov.b32 %21, h21;\nmov.b32 %22, h22;\nmov.b32 %23, h23;\n"
        "mov.b32 %24, h24;\nmov.b32 %25, h25;\nmov.b32 %26, h26;\nmov.b32 %27, h27;\nmov.b32 %28, h28;\nmov.b32 %29, h29;\nmov.b32 %30, h30;\nmov.b32 %31, h31;\n"
        "mov.b32 %32, h32;\nmov.b32 %33, h33;\nmov.b32 %34, h34;\nmov.b32 %35, h35;\nmov.b32 %36, h36;\nmov.b32 %37, h37;\nmov.b32 %38, h38;\nmov.b32 %39, h39;\n"
        "mov.b32 %40, h40;\nmov.b32 %41, h41;\nmov.b32 %42, h42;\nmov.b32 %43, h43;\nmov.b32 %44, h44;\nmov.b32 %45, h45;\nmov.b32 %46, h46;\nmov.b32 %47, h47;\n"
        "mov.b32 %48, h48;\nmov.b32 %49, h49;\nmov.b32 %50, h50;\nmov.b32 %51, h51;\nmov.b32 %52, h52;\nmov.b32 %53, h53;\nmov.b32 %54, h54;\nmov.b32 %55, h55;\n"
        "mov.b32 %56, h56;\nmov.b32 %57, h57;\nmov.b32 %58, h58;\nmov.b32 %59, h59;\nmov.b32 %60, h60;\nmov.b32 %61, h61;\nmov.b32 %62, h62;\nmov.b32 %63, h63;\n"
        "}\n"
        : "=r"(pk[0]), "=r"(pk[1]), "=r"(pk[2]), "=r"(pk[3]), "=r"(pk[4]), "=r"(pk[5]), "=r"(pk[6]), "=r"(pk[7]), "=r"(pk[8]), "=r"(pk[9]),
          "=r"(pk[10]), "=r"(pk[11]), "=r"(pk[12]), "=r"(pk[13]), "=r"(pk[14]), "=r"(pk[15]), "=r"(pk[16]), "=r"(pk[17]), "=r"(pk[18]), "=r"(pk[19]),
          "=r"(pk[20]), "=r"(pk[21]), "=r"(pk[22]), "=r"(pk[23]), "=r"(pk[24]), "=r"(pk[25]), "=r"(pk[26]), "=r"(pk[27]), "=r"(pk[28]), "=r"(pk[29]),
          "=r"(pk[30]), "=r"(pk[31]), "=r"(pk[32]), "=r"(pk[33]), "=r"(pk[34]), "=r"(pk[35]), "=r"(pk[36]), "=r"(pk[37]), "=r"(pk[38]), "=r"(pk[39]),
          "=r"(pk[40]), "=r"(pk[41]), "=r"(pk[42]), "=r"(pk[43]), "=r"(pk[44]), "=r"(pk[45]), "=r"(pk[46]), "=r"(pk[47]), "=r"(pk[48]), "=r"(pk[49]),
          "=r"(pk[50]), "=r"(pk[51]), "=r"(pk[52]), "=r"(pk[53]), "=r"(pk[54]), "=r"(pk[55]), "=r"(pk[56]), "=r"(pk[57]), "=r"(pk[58]), "=r"(pk[59]),
          "=r"(pk[60]), "=r"(pk[61]), "=r"(pk[62]), "=r"(pk[63])
        : "r"(olp), "r"(xa), "r"(ln), "r"(lc), "r"(linc), "r"(lt), "l"(ea), "l"(sh), "l"(wf),
          "n"(sb + SM_REC), "n"(sb + SM_R), "n"(sb + SM_BAR), "n"(sb + SM_CTR),
          "r"(w[0]), "r"(w[1]), "r"(w[2]), "r"(w[3]), "r"(w[4]), "r"(w[5]), "r"(w[6]), "r"(w[7]), "r"(w[8]), "r"(w[9]), "r"(w[10]), "r"(w[11]),
          "r"(w[12]), "r"(w[13]), "r"(w[14]), "r"(w[15]), "r"(w[16]), "r"(w[17]), "r"(w[18]), "r"(w[19]), "r"(w[20]), "r"(w[21]), "r"(w[22]),
          "r"(w[23]), "r"(w[24]), "r"(w[25]), "r"(w[26]), "r"(w[27]), "r"(w[28]), "r"(w[29]), "r"(w[30]), "r"(w[31]), "r"(w[32]), "r"(w[33]),
          "r"(w[34]), "r"(w[35])
        : "memory");
}
__device__ __forceinline__ void consume3(uint32_t (&pk)[48], const uint32_t (&w)[36], uint32_t olp, uint32_t xa, uint32_t ln,
                                      uint32_t lc, uint32_t linc, uint32_t lt, const __nv_bfloat16* ea, const __nv_bfloat16* sh, const void* wf) {
    ea += lt * 4, sh += lt & 2;
    asm volatile(
        "{\n.reg .pred p, q, psw, prdy, ps1, ps2, ps3, pz;\n.reg .f32 d<32>, fz;\n"
        ".reg .b32 h<48>, x<32>, y<32>, ra<8>, rb<8>, bA0, bA1, bB0, bB1, c0, c1, c2, c3, e0, e1, s0, kept;\n"
        ".reg .b32 olp, v, vB, m, id, ida, bar, xb, pos, t0, t1, t2, t3, n, z<16>;\n.reg .b16 lo, hi, i16;\n.reg .b64 pa, pb;\nmov.f32 fz, 0f00000000;\n"
        "mov.b32 h0, 0;\nmov.b32 h1, 0;\nmov.b32 h2, 0;\nmov.b32 h3, 0;\nmov.b32 h4, 0;\nmov.b32 h5, 0;\nmov.b32 h6, 0;\nmov.b32 h7, 0;\nmov.b32 h8, 0;\n"
        "mov.b32 h9, 0;\nmov.b32 h10, 0;\nmov.b32 h11, 0;\nmov.b32 h12, 0;\nmov.b32 h13, 0;\nmov.b32 h14, 0;\nmov.b32 h15, 0;\nmov.b32 h16, 0;\nmov.b32 h17, 0;\n"
        "mov.b32 h18, 0;\nmov.b32 h19, 0;\nmov.b32 h20, 0;\nmov.b32 h21, 0;\nmov.b32 h22, 0;\nmov.b32 h23, 0;\nmov.b32 h24, 0;\nmov.b32 h25, 0;\n"
        "mov.b32 h26, 0;\nmov.b32 h27, 0;\nmov.b32 h28, 0;\nmov.b32 h29, 0;\nmov.b32 h30, 0;\nmov.b32 h31, 0;\nmov.b32 h32, 0;\nmov.b32 h33, 0;\n"
        "mov.b32 h34, 0;\nmov.b32 h35, 0;\nmov.b32 h36, 0;\nmov.b32 h37, 0;\nmov.b32 h38, 0;\nmov.b32 h39, 0;\nmov.b32 h40, 0;\nmov.b32 h41, 0;\n"
        "mov.b32 h42, 0;\nmov.b32 h43, 0;\nmov.b32 h44, 0;\nmov.b32 h45, 0;\nmov.b32 h46, 0;\nmov.b32 h47, 0;\nmov.b32 olp, %48;\nor.b32 t3, %51, 4;\n"
        "shfl.sync.bfly.b32 t3, t3, 8, 0x1f, 0xffffffff;\nand.b32 t0, %50, 32;\nsetp.ne.u32 psw, t0, 0;\nsetp.eq.u32 pz, %48, 0;\n"
        "vote.sync.any.pred pz, pz, 0xffffffff;\nld.shared.u16 t0, [olp];\nadd.u32 olp, olp, 4;\nlop3.b32 t1, t0, %50, 0x3ff0, 0xe4;\n"
        "ld.shared.b32 t1, [t1+%57];\nlop3.b32 kept, t1, t0, 0x1ffc, 0xe4;\nlop3.b32 t2, t1, %51, 3, 0x80;\nsetp.ne.u32 q, t2, 0;\nshr.u32 t2, t1, 13;\n"
        "mad.wide.u32 pa, t2, 32, %54;\nmad.wide.u32 pb, t2, 8, %55;\nmov.b32 s0, 0;\nld.global.cg.v2.b32 {e0,e1}, [pa];\n@q ld.global.cg.b32 s0, [pb];\n"
        "setp.ne.u64 p, %56, 0;\n@p fence.proxy.async.global;\n@p red.release.gpu.global.add.u32 [%56+12], 1;\nbar.warp.sync 0xffffffff;\n"
        "shfl.sync.idx.b32 v, kept, %51, 0x1f, 0xffffffff;\nshfl.sync.idx.b32 vB, kept, t3, 0x1f, 0xffffffff;\n"
        "RW:\nmma.sync.aligned.m16n8k8.row.col.f32.bf16.bf16.f32 {d0,d1,d2,d3}, {%93,%94}, {s0}, {fz,fz,fz,fz};\n"
        "mma.sync.aligned.m16n8k8.row.col.f32.bf16.bf16.f32 {d4,d5,d6,d7}, {%95,%96}, {s0}, {fz,fz,fz,fz};\ncvt.rn.bf16x2.f32 c0, d2, d0;\n"
        "cvt.rn.bf16x2.f32 c1, d3, d1;\ncvt.rn.bf16x2.f32 c2, d6, d4;\ncvt.rn.bf16x2.f32 c3, d7, d5;\nselp.b32 bA0, c2, c0, psw;\nselp.b32 bA1, c0, c2, psw;\n"
        "selp.b32 bB0, c3, c1, psw;\nselp.b32 bB1, c1, c3, psw;\n"
        "mma.sync.aligned.m16n8k16.row.col.f32.bf16.bf16.f32 {d0,d1,d2,d3}, {%61,%62,%63,%64}, {e0,e1}, {fz,fz,fz,fz};\ncvt.rn.bf16x2.f32 ra0, d2, d0;\n"
        "cvt.rn.bf16x2.f32 rb0, d3, d1;\nmma.sync.aligned.m16n8k16.row.col.f32.bf16.bf16.f32 {d4,d5,d6,d7}, {%65,%66,%67,%68}, {e0,e1}, {fz,fz,fz,fz};\n"
        "cvt.rn.bf16x2.f32 ra1, d6, d4;\ncvt.rn.bf16x2.f32 rb1, d7, d5;\n"
        "mma.sync.aligned.m16n8k16.row.col.f32.bf16.bf16.f32 {d8,d9,d10,d11}, {%69,%70,%71,%72}, {e0,e1}, {fz,fz,fz,fz};\ncvt.rn.bf16x2.f32 ra2, d10, d8;\n"
        "cvt.rn.bf16x2.f32 rb2, d11, d9;\nmma.sync.aligned.m16n8k16.row.col.f32.bf16.bf16.f32 {d12,d13,d14,d15}, {%73,%74,%75,%76}, {e0,e1}, {fz,fz,fz,fz};\n"
        "cvt.rn.bf16x2.f32 ra3, d14, d12;\ncvt.rn.bf16x2.f32 rb3, d15, d13;\n"
        "mma.sync.aligned.m16n8k16.row.col.f32.bf16.bf16.f32 {d16,d17,d18,d19}, {%77,%78,%79,%80}, {e0,e1}, {fz,fz,fz,fz};\ncvt.rn.bf16x2.f32 ra4, d18, d16;\n"
        "cvt.rn.bf16x2.f32 rb4, d19, d17;\nmma.sync.aligned.m16n8k16.row.col.f32.bf16.bf16.f32 {d20,d21,d22,d23}, {%81,%82,%83,%84}, {e0,e1}, {fz,fz,fz,fz};\n"
        "cvt.rn.bf16x2.f32 ra5, d22, d20;\ncvt.rn.bf16x2.f32 rb5, d23, d21;\n"
        "mma.sync.aligned.m16n8k16.row.col.f32.bf16.bf16.f32 {d24,d25,d26,d27}, {%85,%86,%87,%88}, {e0,e1}, {fz,fz,fz,fz};\ncvt.rn.bf16x2.f32 ra6, d26, d24;\n"
        "cvt.rn.bf16x2.f32 rb6, d27, d25;\nmma.sync.aligned.m16n8k16.row.col.f32.bf16.bf16.f32 {d28,d29,d30,d31}, {%89,%90,%91,%92}, {e0,e1}, {fz,fz,fz,fz};\n"
        "cvt.rn.bf16x2.f32 ra7, d30, d28;\ncvt.rn.bf16x2.f32 rb7, d31, d29;\nld.shared.u16 t0, [olp];\nadd.u32 olp, olp, 4;\n"
        "lop3.b32 t1, t0, %50, 0x3ff0, 0xe4;\nld.shared.b32 t1, [t1+%57];\nlop3.b32 kept, t1, t0, 0x1ffc, 0xe4;\nlop3.b32 t2, t1, %51, 3, 0x80;\n"
        "setp.ne.u32 q, t2, 0;\nshr.u32 t2, t1, 13;\nmad.wide.u32 pa, t2, 32, %54;\nmad.wide.u32 pb, t2, 8, %55;\nmov.b32 s0, 0;\n"
        "ld.global.cg.v2.b32 {e0,e1}, [pa];\n@q ld.global.cg.b32 s0, [pb];\nshr.u32 bar, v, 1;\nand.b32 bar, bar, 0xff8;\n"
        "mbarrier.test_wait.parity.shared.b64 p, [bar+%59], 0;\nlop3.b32 ida, v, %51, 0x1fff, 0xe4;\nld.volatile.shared.u16 id, [ida+%58];\n"
        "vote.sync.all.pred prdy, p, 0xffffffff;\n@!prdy bra.uni WA;\n"
        "HA:\nmad.lo.u32 xb, id, 64, %49;\ncvt.u16.u32 i16, id;\natom.shared.add.u32 pos, [%50+%60], %52;\n"
        "ldmatrix.sync.aligned.m8n8.x4.trans.shared.b16 {x0,x1,x2,x3}, [xb];\nldmatrix.sync.aligned.m8n8.x4.trans.shared.b16 {x24,x25,x26,x27}, [xb+512];\n"
        "xor.b32 t1, xb, 32;\nldmatrix.sync.aligned.m8n8.x4.trans.shared.b16 {x4,x5,x6,x7}, [t1];\n"
        "ldmatrix.sync.aligned.m8n8.x4.trans.shared.b16 {x28,x29,x30,x31}, [t1+512];\nxor.b32 t1, xb, 64;\n"
        "ldmatrix.sync.aligned.m8n8.x4.trans.shared.b16 {x8,x9,x10,x11}, [t1];\nldmatrix.sync.aligned.m8n8.x4.trans.shared.b16 {x16,x17,x18,x19}, [t1+512];\n"
        "xor.b32 t1, xb, 96;\nldmatrix.sync.aligned.m8n8.x4.trans.shared.b16 {x12,x13,x14,x15}, [t1];\n"
        "ldmatrix.sync.aligned.m8n8.x4.trans.shared.b16 {x20,x21,x22,x23}, [t1+512];\nst.volatile.shared.u16 [pos], i16;\nand.b32 t0, v, 16384;\n"
        "setp.ne.u32 ps1, t0, 0;\nvote.sync.any.pred ps1, ps1, 0xffffffff;\nand.b32 t0, v, 32768;\nsetp.ne.u32 ps2, t0, 0;\n"
        "vote.sync.any.pred ps2, ps2, 0xffffffff;\nmov.b32 v, vB;\nshr.u32 bar, v, 1;\nand.b32 bar, bar, 0xff8;\n"
        "mbarrier.test_wait.parity.shared.b64 p, [bar+%59], 0;\nlop3.b32 ida, v, %51, 0x1fff, 0xe4;\nld.volatile.shared.u16 id, [ida+%58];\n"
        "vote.sync.all.pred prdy, p, 0xffffffff;\nmov.b32 {lo, hi}, ra0;\nmov.b32 t2, {lo, lo};\nmul.rn.bf16x2 y0, x0, t2;\nmul.rn.bf16x2 y2, x2, t2;\n"
        "mov.b32 t2, {hi, hi};\nmul.rn.bf16x2 y1, x1, t2;\nmul.rn.bf16x2 y3, x3, t2;\n"
        "mma.sync.aligned.m16n8k16.row.col.f32.bf16.bf16.f32 {d0,d1,d2,d3}, {y0,y1,y2,y3}, {bA0,bA1}, {fz,fz,fz,fz};\ncvt.rn.bf16x2.f32 z0, d1, d0;\n"
        "cvt.rn.bf16x2.f32 z1, d3, d2;\nmov.b32 {lo, hi}, ra6;\nmov.b32 t2, {lo, lo};\nmul.rn.bf16x2 y24, x24, t2;\nmul.rn.bf16x2 y26, x26, t2;\n"
        "mov.b32 t2, {hi, hi};\nmul.rn.bf16x2 y25, x25, t2;\nmul.rn.bf16x2 y27, x27, t2;\n"
        "mma.sync.aligned.m16n8k16.row.col.f32.bf16.bf16.f32 {d24,d25,d26,d27}, {y24,y25,y26,y27}, {bA0,bA1}, {fz,fz,fz,fz};\ncvt.rn.bf16x2.f32 z12, d25, d24;\n"
        "cvt.rn.bf16x2.f32 z13, d27, d26;\nmov.b32 {lo, hi}, ra1;\nmov.b32 t2, {lo, lo};\nmul.rn.bf16x2 y4, x4, t2;\nmul.rn.bf16x2 y6, x6, t2;\n"
        "mov.b32 t2, {hi, hi};\nmul.rn.bf16x2 y5, x5, t2;\nmul.rn.bf16x2 y7, x7, t2;\n"
        "mma.sync.aligned.m16n8k16.row.col.f32.bf16.bf16.f32 {d4,d5,d6,d7}, {y4,y5,y6,y7}, {bA0,bA1}, {fz,fz,fz,fz};\ncvt.rn.bf16x2.f32 z2, d5, d4;\n"
        "cvt.rn.bf16x2.f32 z3, d7, d6;\nmov.b32 {lo, hi}, ra7;\nmov.b32 t2, {lo, lo};\nmul.rn.bf16x2 y28, x28, t2;\nmul.rn.bf16x2 y30, x30, t2;\n"
        "mov.b32 t2, {hi, hi};\nmul.rn.bf16x2 y29, x29, t2;\nmul.rn.bf16x2 y31, x31, t2;\n"
        "mma.sync.aligned.m16n8k16.row.col.f32.bf16.bf16.f32 {d28,d29,d30,d31}, {y28,y29,y30,y31}, {bA0,bA1}, {fz,fz,fz,fz};\ncvt.rn.bf16x2.f32 z14, d29, d28;\n"
        "cvt.rn.bf16x2.f32 z15, d31, d30;\nmov.b32 {lo, hi}, ra2;\nmov.b32 t2, {lo, lo};\nmul.rn.bf16x2 y8, x8, t2;\nmul.rn.bf16x2 y10, x10, t2;\n"
        "mov.b32 t2, {hi, hi};\nmul.rn.bf16x2 y9, x9, t2;\nmul.rn.bf16x2 y11, x11, t2;\n"
        "mma.sync.aligned.m16n8k16.row.col.f32.bf16.bf16.f32 {d8,d9,d10,d11}, {y8,y9,y10,y11}, {bA0,bA1}, {fz,fz,fz,fz};\ncvt.rn.bf16x2.f32 z4, d9, d8;\n"
        "cvt.rn.bf16x2.f32 z5, d11, d10;\nmov.b32 {lo, hi}, ra4;\nmov.b32 t2, {lo, lo};\nmul.rn.bf16x2 y16, x16, t2;\nmul.rn.bf16x2 y18, x18, t2;\n"
        "mov.b32 t2, {hi, hi};\nmul.rn.bf16x2 y17, x17, t2;\nmul.rn.bf16x2 y19, x19, t2;\n"
        "mma.sync.aligned.m16n8k16.row.col.f32.bf16.bf16.f32 {d16,d17,d18,d19}, {y16,y17,y18,y19}, {bA0,bA1}, {fz,fz,fz,fz};\ncvt.rn.bf16x2.f32 z8, d17, d16;\n"
        "cvt.rn.bf16x2.f32 z9, d19, d18;\nmov.b32 {lo, hi}, ra3;\nmov.b32 t2, {lo, lo};\nmul.rn.bf16x2 y12, x12, t2;\nmul.rn.bf16x2 y14, x14, t2;\n"
        "mov.b32 t2, {hi, hi};\nmul.rn.bf16x2 y13, x13, t2;\nmul.rn.bf16x2 y15, x15, t2;\n"
        "mma.sync.aligned.m16n8k16.row.col.f32.bf16.bf16.f32 {d12,d13,d14,d15}, {y12,y13,y14,y15}, {bA0,bA1}, {fz,fz,fz,fz};\ncvt.rn.bf16x2.f32 z6, d13, d12;\n"
        "cvt.rn.bf16x2.f32 z7, d15, d14;\nmov.b32 {lo, hi}, ra5;\nmov.b32 t2, {lo, lo};\nmul.rn.bf16x2 y20, x20, t2;\nmul.rn.bf16x2 y22, x22, t2;\n"
        "mov.b32 t2, {hi, hi};\nmul.rn.bf16x2 y21, x21, t2;\nmul.rn.bf16x2 y23, x23, t2;\n"
        "mma.sync.aligned.m16n8k16.row.col.f32.bf16.bf16.f32 {d20,d21,d22,d23}, {y20,y21,y22,y23}, {bA0,bA1}, {fz,fz,fz,fz};\ncvt.rn.bf16x2.f32 z10, d21, d20;\n"
        "cvt.rn.bf16x2.f32 z11, d23, d22;\n@ps2 bra.uni TA2;\n@ps1 bra.uni TA1;\n"
        "TA0:\nadd.rn.bf16x2 h0, h0, z0;\nadd.rn.bf16x2 h1, h1, z1;\nadd.rn.bf16x2 h2, h2, z2;\nadd.rn.bf16x2 h3, h3, z3;\nadd.rn.bf16x2 h4, h4, z4;\n"
        "add.rn.bf16x2 h5, h5, z5;\nadd.rn.bf16x2 h6, h6, z6;\nadd.rn.bf16x2 h7, h7, z7;\nadd.rn.bf16x2 h8, h8, z8;\nadd.rn.bf16x2 h9, h9, z9;\n"
        "add.rn.bf16x2 h10, h10, z10;\nadd.rn.bf16x2 h11, h11, z11;\nadd.rn.bf16x2 h12, h12, z12;\nadd.rn.bf16x2 h13, h13, z13;\nadd.rn.bf16x2 h14, h14, z14;\n"
        "add.rn.bf16x2 h15, h15, z15;\n@prdy bra.uni HB;\nbra.uni WB;\n"
        "TA1:\nadd.rn.bf16x2 h16, h16, z0;\nadd.rn.bf16x2 h17, h17, z1;\nadd.rn.bf16x2 h18, h18, z2;\nadd.rn.bf16x2 h19, h19, z3;\nadd.rn.bf16x2 h20, h20, z4;\n"
        "add.rn.bf16x2 h21, h21, z5;\nadd.rn.bf16x2 h22, h22, z6;\nadd.rn.bf16x2 h23, h23, z7;\nadd.rn.bf16x2 h24, h24, z8;\nadd.rn.bf16x2 h25, h25, z9;\n"
        "add.rn.bf16x2 h26, h26, z10;\nadd.rn.bf16x2 h27, h27, z11;\nadd.rn.bf16x2 h28, h28, z12;\nadd.rn.bf16x2 h29, h29, z13;\nadd.rn.bf16x2 h30, h30, z14;\n"
        "add.rn.bf16x2 h31, h31, z15;\n@prdy bra.uni HB;\nbra.uni WB;\n"
        "TA2:\nadd.rn.bf16x2 h32, h32, z0;\nadd.rn.bf16x2 h33, h33, z1;\nadd.rn.bf16x2 h34, h34, z2;\nadd.rn.bf16x2 h35, h35, z3;\nadd.rn.bf16x2 h36, h36, z4;\n"
        "add.rn.bf16x2 h37, h37, z5;\nadd.rn.bf16x2 h38, h38, z6;\nadd.rn.bf16x2 h39, h39, z7;\nadd.rn.bf16x2 h40, h40, z8;\nadd.rn.bf16x2 h41, h41, z9;\n"
        "add.rn.bf16x2 h42, h42, z10;\nadd.rn.bf16x2 h43, h43, z11;\nadd.rn.bf16x2 h44, h44, z12;\nadd.rn.bf16x2 h45, h45, z13;\nadd.rn.bf16x2 h46, h46, z14;\n"
        "add.rn.bf16x2 h47, h47, z15;\n@prdy bra.uni HB;\nbra.uni WB;\n"
        "HB:\nmad.lo.u32 xb, id, 64, %49;\ncvt.u16.u32 i16, id;\natom.shared.add.u32 pos, [%50+%60], %52;\n"
        "ldmatrix.sync.aligned.m8n8.x4.trans.shared.b16 {x0,x1,x2,x3}, [xb];\nldmatrix.sync.aligned.m8n8.x4.trans.shared.b16 {x24,x25,x26,x27}, [xb+512];\n"
        "xor.b32 t1, xb, 32;\nldmatrix.sync.aligned.m8n8.x4.trans.shared.b16 {x4,x5,x6,x7}, [t1];\n"
        "ldmatrix.sync.aligned.m8n8.x4.trans.shared.b16 {x28,x29,x30,x31}, [t1+512];\nxor.b32 t1, xb, 64;\n"
        "ldmatrix.sync.aligned.m8n8.x4.trans.shared.b16 {x8,x9,x10,x11}, [t1];\nldmatrix.sync.aligned.m8n8.x4.trans.shared.b16 {x16,x17,x18,x19}, [t1+512];\n"
        "xor.b32 t1, xb, 96;\nldmatrix.sync.aligned.m8n8.x4.trans.shared.b16 {x12,x13,x14,x15}, [t1];\n"
        "ldmatrix.sync.aligned.m8n8.x4.trans.shared.b16 {x20,x21,x22,x23}, [t1+512];\nst.volatile.shared.u16 [pos], i16;\nand.b32 t0, v, 16384;\n"
        "setp.ne.u32 ps1, t0, 0;\nvote.sync.any.pred ps1, ps1, 0xffffffff;\nand.b32 t0, v, 32768;\nsetp.ne.u32 ps2, t0, 0;\n"
        "vote.sync.any.pred ps2, ps2, 0xffffffff;\nshfl.sync.idx.b32 v, kept, %51, 0x1f, 0xffffffff;\nshfl.sync.idx.b32 vB, kept, t3, 0x1f, 0xffffffff;\n"
        "mov.b32 {lo, hi}, rb0;\nmov.b32 t2, {lo, lo};\nmul.rn.bf16x2 y0, x0, t2;\nmul.rn.bf16x2 y2, x2, t2;\nmov.b32 t2, {hi, hi};\nmul.rn.bf16x2 y1, x1, t2;\n"
        "mul.rn.bf16x2 y3, x3, t2;\nmma.sync.aligned.m16n8k16.row.col.f32.bf16.bf16.f32 {d0,d1,d2,d3}, {y0,y1,y2,y3}, {bB0,bB1}, {fz,fz,fz,fz};\n"
        "cvt.rn.bf16x2.f32 z0, d1, d0;\ncvt.rn.bf16x2.f32 z1, d3, d2;\nmov.b32 {lo, hi}, rb6;\nmov.b32 t2, {lo, lo};\nmul.rn.bf16x2 y24, x24, t2;\n"
        "mul.rn.bf16x2 y26, x26, t2;\nmov.b32 t2, {hi, hi};\nmul.rn.bf16x2 y25, x25, t2;\nmul.rn.bf16x2 y27, x27, t2;\n"
        "mma.sync.aligned.m16n8k16.row.col.f32.bf16.bf16.f32 {d24,d25,d26,d27}, {y24,y25,y26,y27}, {bB0,bB1}, {fz,fz,fz,fz};\ncvt.rn.bf16x2.f32 z12, d25, d24;\n"
        "cvt.rn.bf16x2.f32 z13, d27, d26;\nmov.b32 {lo, hi}, rb1;\nmov.b32 t2, {lo, lo};\nmul.rn.bf16x2 y4, x4, t2;\nmul.rn.bf16x2 y6, x6, t2;\n"
        "mov.b32 t2, {hi, hi};\nmul.rn.bf16x2 y5, x5, t2;\nmul.rn.bf16x2 y7, x7, t2;\n"
        "mma.sync.aligned.m16n8k16.row.col.f32.bf16.bf16.f32 {d4,d5,d6,d7}, {y4,y5,y6,y7}, {bB0,bB1}, {fz,fz,fz,fz};\ncvt.rn.bf16x2.f32 z2, d5, d4;\n"
        "cvt.rn.bf16x2.f32 z3, d7, d6;\nmov.b32 {lo, hi}, rb7;\nmov.b32 t2, {lo, lo};\nmul.rn.bf16x2 y28, x28, t2;\nmul.rn.bf16x2 y30, x30, t2;\n"
        "mov.b32 t2, {hi, hi};\nmul.rn.bf16x2 y29, x29, t2;\nmul.rn.bf16x2 y31, x31, t2;\n"
        "mma.sync.aligned.m16n8k16.row.col.f32.bf16.bf16.f32 {d28,d29,d30,d31}, {y28,y29,y30,y31}, {bB0,bB1}, {fz,fz,fz,fz};\ncvt.rn.bf16x2.f32 z14, d29, d28;\n"
        "cvt.rn.bf16x2.f32 z15, d31, d30;\nmov.b32 {lo, hi}, rb2;\nmov.b32 t2, {lo, lo};\nmul.rn.bf16x2 y8, x8, t2;\nmul.rn.bf16x2 y10, x10, t2;\n"
        "mov.b32 t2, {hi, hi};\nmul.rn.bf16x2 y9, x9, t2;\nmul.rn.bf16x2 y11, x11, t2;\n"
        "mma.sync.aligned.m16n8k16.row.col.f32.bf16.bf16.f32 {d8,d9,d10,d11}, {y8,y9,y10,y11}, {bB0,bB1}, {fz,fz,fz,fz};\ncvt.rn.bf16x2.f32 z4, d9, d8;\n"
        "cvt.rn.bf16x2.f32 z5, d11, d10;\nmov.b32 {lo, hi}, rb4;\nmov.b32 t2, {lo, lo};\nmul.rn.bf16x2 y16, x16, t2;\nmul.rn.bf16x2 y18, x18, t2;\n"
        "mov.b32 t2, {hi, hi};\nmul.rn.bf16x2 y17, x17, t2;\nmul.rn.bf16x2 y19, x19, t2;\n"
        "mma.sync.aligned.m16n8k16.row.col.f32.bf16.bf16.f32 {d16,d17,d18,d19}, {y16,y17,y18,y19}, {bB0,bB1}, {fz,fz,fz,fz};\ncvt.rn.bf16x2.f32 z8, d17, d16;\n"
        "cvt.rn.bf16x2.f32 z9, d19, d18;\nmov.b32 {lo, hi}, rb3;\nmov.b32 t2, {lo, lo};\nmul.rn.bf16x2 y12, x12, t2;\nmul.rn.bf16x2 y14, x14, t2;\n"
        "mov.b32 t2, {hi, hi};\nmul.rn.bf16x2 y13, x13, t2;\nmul.rn.bf16x2 y15, x15, t2;\n"
        "mma.sync.aligned.m16n8k16.row.col.f32.bf16.bf16.f32 {d12,d13,d14,d15}, {y12,y13,y14,y15}, {bB0,bB1}, {fz,fz,fz,fz};\ncvt.rn.bf16x2.f32 z6, d13, d12;\n"
        "cvt.rn.bf16x2.f32 z7, d15, d14;\nmov.b32 {lo, hi}, rb5;\nmov.b32 t2, {lo, lo};\nmul.rn.bf16x2 y20, x20, t2;\nmul.rn.bf16x2 y22, x22, t2;\n"
        "mov.b32 t2, {hi, hi};\nmul.rn.bf16x2 y21, x21, t2;\nmul.rn.bf16x2 y23, x23, t2;\n"
        "mma.sync.aligned.m16n8k16.row.col.f32.bf16.bf16.f32 {d20,d21,d22,d23}, {y20,y21,y22,y23}, {bB0,bB1}, {fz,fz,fz,fz};\ncvt.rn.bf16x2.f32 z10, d21, d20;\n"
        "cvt.rn.bf16x2.f32 z11, d23, d22;\n@ps2 bra.uni TB2;\n@ps1 bra.uni TB1;\n"
        "TB0:\nadd.rn.bf16x2 h0, h0, z0;\nadd.rn.bf16x2 h1, h1, z1;\nadd.rn.bf16x2 h2, h2, z2;\nadd.rn.bf16x2 h3, h3, z3;\nadd.rn.bf16x2 h4, h4, z4;\n"
        "add.rn.bf16x2 h5, h5, z5;\nadd.rn.bf16x2 h6, h6, z6;\nadd.rn.bf16x2 h7, h7, z7;\nadd.rn.bf16x2 h8, h8, z8;\nadd.rn.bf16x2 h9, h9, z9;\n"
        "add.rn.bf16x2 h10, h10, z10;\nadd.rn.bf16x2 h11, h11, z11;\nadd.rn.bf16x2 h12, h12, z12;\nadd.rn.bf16x2 h13, h13, z13;\nadd.rn.bf16x2 h14, h14, z14;\n"
        "add.rn.bf16x2 h15, h15, z15;\nbra.uni RW;\n"
        "TB1:\nadd.rn.bf16x2 h16, h16, z0;\nadd.rn.bf16x2 h17, h17, z1;\nadd.rn.bf16x2 h18, h18, z2;\nadd.rn.bf16x2 h19, h19, z3;\nadd.rn.bf16x2 h20, h20, z4;\n"
        "add.rn.bf16x2 h21, h21, z5;\nadd.rn.bf16x2 h22, h22, z6;\nadd.rn.bf16x2 h23, h23, z7;\nadd.rn.bf16x2 h24, h24, z8;\nadd.rn.bf16x2 h25, h25, z9;\n"
        "add.rn.bf16x2 h26, h26, z10;\nadd.rn.bf16x2 h27, h27, z11;\nadd.rn.bf16x2 h28, h28, z12;\nadd.rn.bf16x2 h29, h29, z13;\nadd.rn.bf16x2 h30, h30, z14;\n"
        "add.rn.bf16x2 h31, h31, z15;\nbra.uni RW;\n"
        "TB2:\nadd.rn.bf16x2 h32, h32, z0;\nadd.rn.bf16x2 h33, h33, z1;\nadd.rn.bf16x2 h34, h34, z2;\nadd.rn.bf16x2 h35, h35, z3;\nadd.rn.bf16x2 h36, h36, z4;\n"
        "add.rn.bf16x2 h37, h37, z5;\nadd.rn.bf16x2 h38, h38, z6;\nadd.rn.bf16x2 h39, h39, z7;\nadd.rn.bf16x2 h40, h40, z8;\nadd.rn.bf16x2 h41, h41, z9;\n"
        "add.rn.bf16x2 h42, h42, z10;\nadd.rn.bf16x2 h43, h43, z11;\nadd.rn.bf16x2 h44, h44, z12;\nadd.rn.bf16x2 h45, h45, z13;\nadd.rn.bf16x2 h46, h46, z14;\n"
        "add.rn.bf16x2 h47, h47, z15;\nbra.uni RW;\n"
        "WA:\nshr.u32 t2, v, 1;\nand.b32 t2, t2, 0xff8;\nsetp.eq.u32 p, t2, 0;\nvote.sync.all.pred p, p, 0xffffffff;\n@p bra.uni DONE;\nmov.b32 n, 0;\n"
        "WA3:\nmbarrier.try_wait.parity.shared.b64 p, [t2+%59], 0;\nvote.sync.all.pred p, p, 0xffffffff;\nadd.u32 n, n, 1;\nsetp.lt.and.u32 q, n, 1000000, !p;\n"
        "@q bra.uni WA3;\nlop3.b32 ida, v, %51, 0x1fff, 0xe4;\nld.volatile.shared.u16 id, [ida+%58];\nbra.uni HA;\n"
        "WB:\nshr.u32 t2, v, 1;\nand.b32 t2, t2, 0xff8;\nsetp.eq.u32 p, t2, 0;\nvote.sync.all.pred p, p, 0xffffffff;\n@p bra.uni DONE;\nmov.b32 n, 0;\n"
        "WB3:\nmbarrier.try_wait.parity.shared.b64 p, [t2+%59], 0;\nvote.sync.all.pred p, p, 0xffffffff;\nadd.u32 n, n, 1;\nsetp.lt.and.u32 q, n, 1000000, !p;\n"
        "@q bra.uni WB3;\nlop3.b32 ida, v, %51, 0x1fff, 0xe4;\nld.volatile.shared.u16 id, [ida+%58];\nbra.uni HB;\n"
        "DONE:\nmov.b32 %0, h0;\nmov.b32 %1, h1;\nmov.b32 %2, h2;\nmov.b32 %3, h3;\nmov.b32 %4, h4;\nmov.b32 %5, h5;\nmov.b32 %6, h6;\nmov.b32 %7, h7;\n"
        "mov.b32 %8, h8;\nmov.b32 %9, h9;\nmov.b32 %10, h10;\nmov.b32 %11, h11;\nmov.b32 %12, h12;\nmov.b32 %13, h13;\nmov.b32 %14, h14;\nmov.b32 %15, h15;\n"
        "mov.b32 %16, h16;\nmov.b32 %17, h17;\nmov.b32 %18, h18;\nmov.b32 %19, h19;\nmov.b32 %20, h20;\nmov.b32 %21, h21;\nmov.b32 %22, h22;\nmov.b32 %23, h23;\n"
        "mov.b32 %24, h24;\nmov.b32 %25, h25;\nmov.b32 %26, h26;\nmov.b32 %27, h27;\nmov.b32 %28, h28;\nmov.b32 %29, h29;\nmov.b32 %30, h30;\nmov.b32 %31, h31;\n"
        "mov.b32 %32, h32;\nmov.b32 %33, h33;\nmov.b32 %34, h34;\nmov.b32 %35, h35;\nmov.b32 %36, h36;\nmov.b32 %37, h37;\nmov.b32 %38, h38;\nmov.b32 %39, h39;\n"
        "mov.b32 %40, h40;\nmov.b32 %41, h41;\nmov.b32 %42, h42;\nmov.b32 %43, h43;\nmov.b32 %44, h44;\nmov.b32 %45, h45;\nmov.b32 %46, h46;\nmov.b32 %47, h47;\n"
        "}\n"
        : "=r"(pk[0]), "=r"(pk[1]), "=r"(pk[2]), "=r"(pk[3]), "=r"(pk[4]), "=r"(pk[5]), "=r"(pk[6]), "=r"(pk[7]), "=r"(pk[8]), "=r"(pk[9]),
          "=r"(pk[10]), "=r"(pk[11]), "=r"(pk[12]), "=r"(pk[13]), "=r"(pk[14]), "=r"(pk[15]), "=r"(pk[16]), "=r"(pk[17]), "=r"(pk[18]), "=r"(pk[19]),
          "=r"(pk[20]), "=r"(pk[21]), "=r"(pk[22]), "=r"(pk[23]), "=r"(pk[24]), "=r"(pk[25]), "=r"(pk[26]), "=r"(pk[27]), "=r"(pk[28]), "=r"(pk[29]),
          "=r"(pk[30]), "=r"(pk[31]), "=r"(pk[32]), "=r"(pk[33]), "=r"(pk[34]), "=r"(pk[35]), "=r"(pk[36]), "=r"(pk[37]), "=r"(pk[38]), "=r"(pk[39]),
          "=r"(pk[40]), "=r"(pk[41]), "=r"(pk[42]), "=r"(pk[43]), "=r"(pk[44]), "=r"(pk[45]), "=r"(pk[46]), "=r"(pk[47])
        : "r"(olp), "r"(xa), "r"(ln), "r"(lc), "r"(linc), "r"(lt), "l"(ea), "l"(sh), "l"(wf),
          "n"(sb + SM_REC), "n"(sb + SM_R), "n"(sb + SM_BAR), "n"(sb + SM_CTR),
          "r"(w[0]), "r"(w[1]), "r"(w[2]), "r"(w[3]), "r"(w[4]), "r"(w[5]), "r"(w[6]), "r"(w[7]), "r"(w[8]), "r"(w[9]), "r"(w[10]), "r"(w[11]),
          "r"(w[12]), "r"(w[13]), "r"(w[14]), "r"(w[15]), "r"(w[16]), "r"(w[17]), "r"(w[18]), "r"(w[19]), "r"(w[20]), "r"(w[21]), "r"(w[22]),
          "r"(w[23]), "r"(w[24]), "r"(w[25]), "r"(w[26]), "r"(w[27]), "r"(w[28]), "r"(w[29]), "r"(w[30]), "r"(w[31]), "r"(w[32]), "r"(w[33]),
          "r"(w[34]), "r"(w[35])
        : "memory");
}

__device__ __forceinline__ void wf_done() {
    asm volatile("fence.proxy.async.global;\nred.release.gpu.global.add.u32 [%0+12], 1;" ::"l"(g_sync) : "memory");
}

template <int NS>
__device__ __forceinline__ void consumer(const __nv_bfloat16* __restrict__ sh,
                                         const __nv_bfloat16* __restrict__ ea, __nv_bfloat16* __restrict__ out, int N, int npb) {
    uint32_t pk[NS * 16];
    {
        const int lane = threadIdx.x & 31, warp = threadIdx.x >> 5;
        const int mi = lane >> 3, r = lane & 7, j = r >> 1;
        const int u = 2 * ((mi >> 1) ^ (j >> 1)) + (r & 1), ph = (j ^ (j >> 1)) & 1;
        uint32_t w[36];
        {
            const uint32_t a = sb + SC_WR + (4 * j + (r & 1) + (mi & 2)) * 272 + (mi & 1) * 16;
#pragma unroll
            for (int c = 0; c < 8; c++)
                asm volatile("ldmatrix.sync.aligned.m8n8.x4.trans.shared.b16 {%0,%1,%2,%3}, [%4];"
                             : "=r"(w[4 * c]), "=r"(w[4 * c + 1]), "=r"(w[4 * c + 2]), "=r"(w[4 * c + 3]) : "r"(a + c * 32) : "memory");
            const uint32_t ca = sb + SC_CG + (lane & 2) * 8 + ((lane >> 2) & 3) * 2;
#pragma unroll
            for (int k = 0; k < 4; k++) {
                const uint32_t f = lds16(ca + 32 * k) | (lds16(ca + 32 * k + 8) << 16);
                w[32 + k] = (lane & 1) == (lane >> 4) ? f : 0;
            }
            asm volatile("fence.proxy.async.shared::cta;\nbar.sync 2, %0;" ::"n"(NCW * 32) : "memory");
            if (threadIdx.x < WSL) sts16(sb + SM_R + 0x2000 + (4 + SP - WSL + lane) * 4, (sb + SC_WR) / 64 + lane * 16);
        }
        const uint32_t xa = __shfl_sync(0xffffffffu, u * 128 + (((u + 4 * ph) ^ (mi & 1)) << 4), lane);
        const uint32_t ln = __shfl_sync(0xffffffffu, lane * 16 + (lane >> 3) * 4, lane);
        const uint32_t lc = __shfl_sync(0xffffffffu, j * 8 + (1 << (lane & 1)) + (ph << 13), lane);
        const uint32_t linc = __shfl_sync(0xffffffffu, (lane & 0x19) ? 0 : 8, lane);
        const uint32_t lt = __shfl_sync(0xffffffffu, lane & 3, lane);
        const void* wfp = (threadIdx.x >> 2) == WFT && blockIdx.x < 128 ? g_sync : nullptr;
        const uint32_t olp = sb + SM_OL + warp * (OLN * 2) + ((lane & 4) >> 1);
        if constexpr (NS == 4) consume4(pk, w, olp, xa, ln, lc, linc, lt, ea, sh, wfp);
        else consume3(pk, w, olp, xa, ln, lc, linc, lt, ea, sh, wfp);
    }
    TLMAX(10);
    const int tid = thread_id(), lane = tid & 31, warp = tid >> 5, g = lane >> 2, t = lane & 3;
    const uint32_t wc = lds32(sb + SM_MISC + 12) + 1;
    const uint32_t inv = lds32(sb + SM_INV + warp * 4);
    const int node0 = cta_id() * npb, nnodes = min(npb, N - node0);
    uint4* op[NS];
    uint32_t on[NS];
#pragma unroll
    for (int s = 0; s < NS; s++) {
        const int nl = ((inv >> (8 * s)) & 255) + (g >> 2) * 40;
        op[s] = (uint4*)(out + ((size_t)(node0 + nl) * 4 + (g & 3)) * 128 + 8 * t);
        on[s] = nl < nnodes;
    }
    if constexpr (NS == 4) project4(pk, sb + SM_R + wc * 16, sb + SM_BAR + wc * 8, op, on);
    else project3(pk, sb + SM_R + wc * 16, sb + SM_BAR + wc * 8, op, on);
}

#define TLHI "shl.b32 d, tb, 16;\n"
#define RAOFF ((threadIdx.x & 96) >> 1)
#define UNPACK(v) "dp2a.lo.u32.u32 d, " #v ", k64, 0;\nshr.s32 r, " #v ", 14;\n"
#define XSTR(x) XSTR2(x)
#define XSTR2(x) #x
__device__ __forceinline__ void producer(const CUtensorMap* tmx, int pw) {
    const uint32_t nch = lds32(sb + SM_MISC + 12), c0 = lds32(sb + SM_MISC + 24);
    if (elect()) {
        asm volatile(
            "{\n.reg .pred p, q, lead, never;\n.reg .b32 ra, oa, off, poff, due, now, a<4>, b<4>, d, r, z<8>, bar<4>, t, n, tb, ta, prev, k64, ktx;\n"
            ".reg .b64 lg, t64, tm;\n"
            "mov.b32 ta, %5;\nld.volatile.shared.v4.b32 {z0,z1,z2,z3}, [ta+32];\nld.volatile.shared.v4.b32 {z4,z5,z6,z7}, [ta+32];\n"
            "mov.b32 ra, %9;\nmad.lo.u32 t, %0, 8, %10;\n"
            "add.u32 bar0, t, z0;\nadd.u32 bar1, t, z1;\nadd.u32 bar2, t, z2;\nadd.u32 bar3, t, z3;\nsetp.ne.u32 never, z0, 0;\n"
            "add.u32 k64, z4, 64;\nadd.u32 ktx, z5, 8192;\ncvt.u64.u32 tm, z6;\nadd.u64 tm, tm, %3;\n"
            "mov.b32 n, 0;\nld.volatile.shared.b32 prev, [ta];\nmov.b32 poff, 1000000;\nsetp.eq.u32 lead, %0, 0;\n"
            "mov.u32 due, %%globaltimer_lo;\n"
            "setp.gt.u32 p, ra, %1;\n@p bra.uni END;\nshr.u32 oa, ra, 3;\n"
            "FIRST:\n"
            "ld.volatile.shared.u16 off, [oa+%11-8];\nmov.u32 now, %%globaltimer_lo;\nadd.u32 due, prev, off;\nsub.u32 t, due, now;\n"
            "setp.gt.s32 p, t, %12;\n@p bra.uni FIRST;\n"
            "GO:\n"
            "ld.volatile.shared.v4.b32 {a0,a1,a2,a3}, [ra];\nld.volatile.shared.v4.b32 {b0,b1,b2,b3}, [ra+0x2000];\n"
            "shr.u32 oa, ra, 3;\nld.volatile.shared.u16 off, [oa+%11];\nld.volatile.shared.b32 tb, [ta];\n"
            "mov.u32 now, %%globaltimer_lo;\n"
            "lop3.b32 t, a0, a1, a2, 0xfe;\nlop3.b32 d, a3, b0, b1, 0xfe;\nlop3.b32 t, t, d, b2, 0xfe;\nor.b32 t, t, b3;\nand.b32 t, t, 1;\n"
            "setp.ne.u32 p, t, 0;\n"
            "@p bra.uni BACK;\n"
            "shl.b32 t, oa, 2;\nmbarrier.arrive.expect_tx.shared.b64 _, [t+%13], ktx;\n"
            "add.u32 bar0, bar0, 32;\nadd.u32 bar1, bar1, 32;\nadd.u32 bar2, bar2, 32;\nadd.u32 bar3, bar3, 32;\n"
            UNPACK(a0)
            "cp.async.bulk.tensor.3d.shared::cluster.global.mbarrier::complete_tx::bytes [d], [tm, {z0, r, z1}], [bar0];\n"
            UNPACK(b0)
            "cp.async.bulk.tensor.3d.shared::cluster.global.mbarrier::complete_tx::bytes [d], [tm, {z2, r, z3}], [bar1];\n"
            UNPACK(a1)
            "cp.async.bulk.tensor.3d.shared::cluster.global.mbarrier::complete_tx::bytes [d], [tm, {z4, r, z5}], [bar2];\n"
            UNPACK(b1)
            "cp.async.bulk.tensor.3d.shared::cluster.global.mbarrier::complete_tx::bytes [d], [tm, {z6, r, z7}], [bar3];\n"
            "@never bra.uni END;\n"
            "add.u32 ra, ra, 64;\nadd.u32 due, off, tb;\nsub.u32 t, due, now;\nsetp.le.and.u32 q, ra, %1, !lead;\nsetp.le.and.s32 q, t, %2, q;\n"
            UNPACK(a2)
            "cp.async.bulk.tensor.3d.shared::cluster.global.mbarrier::complete_tx::bytes [d], [tm, {z0, r, z1}], [bar0];\n"
            UNPACK(b2)
            "cp.async.bulk.tensor.3d.shared::cluster.global.mbarrier::complete_tx::bytes [d], [tm, {z2, r, z3}], [bar1];\n"
            UNPACK(a3)
            "cp.async.bulk.tensor.3d.shared::cluster.global.mbarrier::complete_tx::bytes [d], [tm, {z4, r, z5}], [bar2];\n"
            UNPACK(b3)
            "cp.async.bulk.tensor.3d.shared::cluster.global.mbarrier::complete_tx::bytes [d], [tm, {z6, r, z7}], [bar3];\n"
            "@q bra.uni GO;\n"
            "setp.gt.u32 p, ra, %1;\n@p bra.uni END;\n@!lead bra.uni WAIT0;\n"
            "add.u32 d, ta, 16;\ncp.async.bulk.shared::cluster.global.mbarrier::complete_tx::bytes [ta], [%4], 16, [d];\n"
            "sub.u32 r, now, poff;\nmov.b32 poff, off;\nsub.u32 d, prev, tb;\nmov.b32 prev, r;\nsub.u32 r, r, tb;\nmin.s32 d, d, r;\n"
            "setp.le.s32 p, d, %6;\n@p bra.uni NOSLIP;\n"
            "setp.lt.u32 p, ra, %8;\n@p bra.uni NOSLIP;\nadd.u32 r, ra, " XSTR(SLIPEND) ";\nsetp.gt.u32 p, r, %1;\n@p bra.uni NOSLIP;\n"
            "ld.volatile.shared.b64 t64, [ta];\ncvt.u32.u64 r, t64;\nsub.u32 r, tb, r;\nsub.u32 d, d, %7;\nadd.s32 d, d, r;\n"
            "cvt.s64.s32 lg, d;\nadd.u64 t64, t64, lg;\n"
            "red.relaxed.gpu.global.max.u64 [%4], t64;\n"
            "NOSLIP:\n"
            "setp.le.s32 p, t, %2;\n@p bra.uni GO;\n"
            "WAIT0:\n"
            "ld.volatile.shared.b32 tb, [ta];\nld.volatile.shared.u16 off, [oa+%11];\nmov.u32 now, %%globaltimer_lo;\nadd.u32 due, tb, off;\nsub.u32 t, due, now;\n"
            "setp.le.s32 p, t, %12;\n@p bra.uni GO;\n"
            "setp.gt.s32 p, t, " XSTR(SPINT) ";\n@p nanosleep.u32 32;\nbra.uni WAIT0;\n"
            "BACK:\n"
            "nanosleep.u32 32;\nsub.u32 t, now, tb;\nsetp.lt.s32 p, t, 200000000;\n@p bra.uni GO;\n"
            "END:\n}" ::"r"(pw),
            "r"(sb + SM_R + nch * 16), "n"(AHEAD + EARLY), "l"(tmx), "l"(g_sync), "n"(sb + SM_MISC + 32), "n"(SLIPTH), "n"(SLIPSUB),
            "n"(sb + SM_R + SLIPFROM * 16), "r"(sb + SM_R + 16 + c0 * 16 + RAOFF), "r"(sb + SM_BAR + 8 - 32 + c0 * 8),
            "n"(sb + SM_OFF + 8 - (sb + SM_R) / 8), "n"(EARLY), "n"(sb + SM_BAR - (sb + SM_R) / 2)
            : "memory");
        const uint32_t wch = lds32(sb + SM_MISC + 12) + 1 + pw;
        const uint32_t ra = sb + SM_R + wch * 16, bar = sb + SM_BAR + wch * 8;
        const uint32_t target = lds32(sb + SM_MISC + 16);
        uint32_t cnt = lds128(sb + SM_MISC + 32).w;
        for (int n = 0; n < 1000000 && (int)(cnt - target) < 0; n++)
            asm volatile("ld.acquire.gpu.global.u32 %0, [%1+12];" : "=r"(cnt) : "l"(g_sync) : "memory");
        uint4 a, b;
        for (int n = 0; n < 1000000; n++) {
            a = lds128(ra), b = lds128(ra + 0x2000);
            if (!((a.x | a.y | a.z | a.w | b.x | b.y | b.z | b.w) & 1)) break;
        }
        asm volatile("fence.proxy.async.global;" ::: "memory");
        asm volatile("mbarrier.arrive.expect_tx.shared.b64 _, [%0], 8192;" ::"r"(bar) : "memory");
        const uint32_t c[8] = {a.x, a.y, a.z, a.w, b.x, b.y, b.z, b.w};
#pragma unroll
        for (int i = 0; i < 8; i++)
            asm volatile("cp.async.bulk.shared::cluster.global.mbarrier::complete_tx::bytes [%0], [%1], 1024, [%2];" ::"r"(
                             (c[i] & 0xffe) << 6),
                         "l"(g_wf + (pw * 8 + i) * 64), "r"(bar)
                         : "memory");
    }
}

#define BARINIT(w, n)                                                                                              \
    if (elect()) {                                                                                                 \
        _Pragma("unroll") for (int k = 0; k < (NBAR + n - 1) / n; k++)                                             \
            asm volatile("mbarrier.init.shared.b64 [%0], 1;" ::"r"(sb + SM_BAR + ((w) * ((NBAR + n - 1) / n) + k) * 8)); \
        asm volatile("fence.mbarrier_init.release.cluster;" ::: "memory");                                         \
    }                                                                                                              \
    __syncwarp();

__global__ void __launch_bounds__(NT, 1)
main_kernel(const __grid_constant__ CUtensorMap tmx, const __nv_bfloat16* __restrict__ x, const int* __restrict__ src,
            const int* __restrict__ dst, const __nv_bfloat16* __restrict__ sh, const __nv_bfloat16* __restrict__ ea,
            const __nv_bfloat16* __restrict__ cg, const __nv_bfloat16* __restrict__ wr,
            const __nv_bfloat16* __restrict__ wout, __nv_bfloat16* __restrict__ out, int N, int E, int npb,
            unsigned npb_magic, int chunk, unsigned wsz, unsigned wmagic, unsigned bkm, int tau, int ramp, int rampn, int tdelay, unsigned polld, int spr, int sprn) {
    extern __shared__ __align__(1024) unsigned char smem[];
    if (s2u(smem) != sb) __trap();
    const int tid = threadIdx.x, lane = tid & 31;
    const int warp = __shfl_sync(0xffffffffu, tid >> 5, 0);
    const int nbins = gridDim.x;
    bool fast = chunk > 0;
    TLSTAMP(0);
    if (fast) {
        const int e0 = blockIdx.x * chunk + tid, left = min(E, (int)(blockIdx.x + 1) * chunk) - e0;
        uint32_t pd[KE], ps[KE];
        {
            const int* dp = dst + e0;
            const int* sp = src + e0;
#pragma unroll
            for (int k = 0; k < KE; k++) {
                pd[k] = (nbins + (k == KE - 1 ? lane : 0)) * npb, ps[k] = 0;
                asm volatile("{\n.reg .pred p;\nsetp.gt.s32 p, %4, %5;\n@p ld.global.nc.u32 %0, [%2];\n@p ld.global.nc.u32 %1, [%3];\n}"
                             : "+r"(pd[k]), "+r"(ps[k]) : "l"(dp + k * NT), "l"(sp + k * NT), "r"(left), "r"(k * NT));
            }
        }
        uint32_t epoch = 0;
        if (tid == NT - 1) asm volatile("ld.relaxed.gpu.global.u32 %0, [%1];" : "=r"(epoch) : "l"(&g_epoch) : "memory");
        uint4 wv, wo[3];
        const bool wrow = (tid >> 2) == WFT && blockIdx.x < 128;
        {
            const uint4* wp = tid < 256 ? (const uint4*)wr + tid
                              : wrow    ? (const uint4*)(wout + blockIdx.x * 128 + (tid & 3) * 32)
                                        : (const uint4*)cg + (tid & 7);
            if (tid < 264 || wrow) wv = __ldg(wp);
            if (wrow) wo[0] = __ldg(wp + 1), wo[1] = __ldg(wp + 2), wo[2] = __ldg(wp + 3);
        }
        const uint32_t t16 = sb + tid * 16;
        const uint32_t sa = sb + SC_STG + (tid >> 3) * CP + (tid & 7) * 16;
        const uint32_t sm = sb + SC_STG + (tid >> 2) * CP + (tid & 3) * 16 + 128;
        const uint32_t none = (40 * NWIN + (lane & 7) + (blockIdx.x & 3) * 8) << 2;
        const uint32_t pade = min(blockIdx.x * chunk, E - 1) << 13;
        const bool third = warp * 4 + 128 < nbins, second = warp * 8 + 128 < nbins;
#pragma unroll
        for (int k = 0; k < 3; k++)
            if (k < 2 || third) sts128(sa + k * 64 * CP, none, none, none, none);
#pragma unroll
        for (int k = 0; k < 2; k++)
            if (k < 1 || second) sts128(sm + k * 128 * CP, none, none, none, none);
        if (tid < MAXB + 32) sts32(sb + SC_CNT + tid * 4, 0);
        if (tid < NOFF) sts16(sb + SM_OFF + tid * 2, 0xffff);
#pragma unroll
        for (int k = 0; k < 3; k++) sts128(t16 + SC_TABB + k * NT * 16, 0, 0, 0, 0);
        const uint32_t ecomp = -(wsz * (CH << 13));
#pragma unroll
        for (int k = 0; k < 3; k++)
            sts128(t16 + SC_TMP + k * NT * 16, 0, pade + ecomp, 0, pade + ecomp);
#pragma unroll
        for (int k = 0; k < ZSL / 8; k++) sts128(t16 + k * NT * 16, 0, 0, 0, 0), sts128(t16 + SP * 1024 + PH + k * NT * 16, 0, 0, 0, 0);
        if (tid < RP / 4) {
            uint32_t c[4], d[4];
#pragma unroll
            for (int i = 0; i < 4; i++) {
                const uint32_t k = tid * 4 - 4 + i;
                c[i] = d[i] = 0xc0000001u;
                if (warp == 0 && k < SP) c[i] += sb / 64 - 1 + k * 16;
                if (warp == 0 && k < SP - WSL) d[i] = c[i] + (SP * 1024 + PH) / 64;
            }
            static_assert(SP + 4 <= 128, "first warp");
            sts128(t16 + SM_R, c[0], c[1], c[2], c[3]);
            sts128(t16 + SM_R + 0x2000, d[0], d[1], d[2], d[3]);
        }
        constexpr uint32_t OLEND = (RECN - 4) * 4 * 0x10001;
        if (tid < NCW * OLN / 8) sts128(t16 + SM_OL, OLEND, OLEND, OLEND, OLEND);
        if (warp == 12) {
            sts32(sb + SM_CTR + lane * 16 + (lane >> 3) * 4,
                  sb + SM_R + ((lane & 0x19) ? (RP - 1) * 4 : (4 + SP) * 4 + (((lane >> 1) ^ (lane >> 2)) & 1) * 0x2000 + (lane & 4)));
            if (lane < 3) sts32(sb + SM_MISC + (lane ? 16 + lane * 4 : 4), 0);
            if (lane == 8) sts128(sb + SM_REC + (RECN - 4) * 4, pade, pade, pade, pade), sts128(sb + SM_MISC + 64, 0, 0, 0, 0);
            if (lane == 9) asm volatile("prefetch.tensormap [%0];" ::"l"(&tmx) : "memory");
        }
        __syncthreads();
        TLSTAMP(1);

        {
            uint32_t b[KE], r[KE];
#pragma unroll
            for (int k = 0; k < KE; k++) {
                b[k] = __umulhi(pd[k], npb_magic);
                r[k] = atoms_add(sb + SC_CNT + b[k] * 4, 4);
                if (k == KE - 1) b[k] = min(b[k], nbins);
            }
            if (tid == NT - 1) {
                sts32(sb + SM_MISC + 8, epoch % 3 + 1);
                asm volatile("{\n.reg .b64 t;\nmov.u64 t, %%globaltimer;\nred.relaxed.gpu.global.max.u64 [%0], t;\n"
                             "red.relaxed.gpu.global.add.u32 [%0+8], 1;\n}" ::"l"(g_sync) : "memory");
            }
            __syncwarp();
#pragma unroll
            for (int k = 0; k < KE; k++) {
                asm volatile(
                    "{\n.reg .pred p;\n.reg .b32 d, t, u;\nmad.lo.u32 d, %1, %3, %0;\nsetp.ge.u32 p, d, 40;\nmul.hi.u32 u, %2, %4;\n"
                    "mad.lo.u32 t, %2, %10, %5;\nmad.lo.u32 t, d, %11, t;\nmad.lo.u32 t, u, %12, t;\n@p add.u32 t, t, %7;\n"
                    "min.u32 d, %6, 188;\nmad.lo.u32 d, %1, %9, d;\nst.shared.b32 [d+%8], t;\n}" ::"r"(pd[k]),
                    "r"(b[k]), "r"(ps[k]), "r"(-npb), "r"(wmagic), "r"(((tid + k * NT) << 14) + 4), "r"(r[k]), "n"(2 - 40 * NWIN * 4),
                    "n"(sb + SC_STG), "n"(CP), "n"(CH << 14), "n"(NWIN * 4), "r"(4 - wsz * (CH << 14))
                    : "memory");
            }
        }
        if (tid < 264) sts128(sb + SC_WR + (tid >> 4) * 272 + (tid & 15) * 16, wv.x, wv.y, wv.z, wv.w);
        uint4* gp = g_cell + ((tid >> 3) * MAXB + blockIdx.x) * 8 + (tid & 7);
        uint4* gm = g_more + ((tid >> 2) * MAXB + blockIdx.x) * 4 + (tid & 3);
        __syncthreads();
        TLSTAMP(6);
        const uint32_t tag = lds32(sb + SM_MISC + 8), t0 = tag & 1, t1 = tag >> 1;
        {
            uint4 v[5];
#pragma unroll
            for (int k = 0; k < 5; k++)
                if (k != 2 && k != 4 || (k == 2 ? third : second)) v[k] = lds128(k < 3 ? sa + k * 64 * CP : sm + (k - 3) * 128 * CP);
#pragma unroll
            for (int k = 0; k < 5; k++)
                if (k != 2 && k != 4 || (k == 2 ? third : second))
                    st_cell(k < 3 ? gp + k * 64 * MAXB * 8 : gm + (k - 3) * 128 * MAXB * 4, v[k].x | t0, v[k].y | t1, v[k].z | t0, v[k].w | t1);
        }
        if (wrow) {
            const int k = blockIdx.x;
            uint4* dp = &g_wf[((tid & 3) * 8 + (k >> 4)) * 64 + (k & 8) * 4 + (k & 7)];
            dp[0] = make_uint4(wv.x, wo[0].x, wo[1].x, wo[2].x);
            dp[8] = make_uint4(wv.y, wo[0].y, wo[1].y, wo[2].y);
            dp[16] = make_uint4(wv.z, wo[0].z, wo[1].z, wo[2].z);
            dp[24] = make_uint4(wv.w, wo[0].w, wo[1].w, wo[2].w);
        }
        if (warp < 14) { BARINIT(warp, 14) }
        __syncwarp();
        if (tid == NT - 1) {
            uint4 q;
            for (int n = 0; n < (1 << 22); n++) {
                q = ld_cell((const uint4*)g_sync);
                if ((int)(q.z - (epoch + 1) * nbins) >= 0) break;
            }
            sts128(sb + SM_MISC + 32, q.x, q.y, q.z, q.w), sts32(sb + SM_MISC + 16, (epoch + 1) * 512);
            asm volatile("mbarrier.init.shared.b64 [%0], 1;" ::"r"(sb + SM_MISC + 48) : "memory");
            while ((uint32_t)(gt_lo() - q.x) < polld) {}
        }
        __syncthreads();
        TLSTAMP(14);
        uint32_t m[20], rk[20], ia[20], eb[2];
        eb[0] = (((tid >> 3) * chunk) << 13) + ecomp + 1;
        eb[1] = eb[0] + (chunk << 19);
        asm volatile("" : "+r"(eb[0]), "+r"(eb[1]));
        bool ext;
        {
            const uint4* hp = g_cell + blockIdx.x * (MAXB * 8) + tid;
            const uint4* hm = g_more + blockIdx.x * (MAXB * 4) + tid;
            uint4 q[5];
            q[2] = q[4] = make_uint4(none | t0, none | t1, none | t0, none | t1);
            for (int n = 0; n < (1 << 22); n++) {
                q[0] = ld_cell(hp), q[1] = ld_cell(hp + NT), q[3] = ld_cell(hm);
                if ((tid >> 3) + 128 < nbins) q[2] = ld_cell(hp + 2 * NT);
                if ((tid >> 2) + 128 < nbins) q[4] = ld_cell(hm + NT);
                uint32_t bad = 0;
#pragma unroll
                for (int k = 0; k < 5; k++)
                    asm("{\n.reg .b32 a, b;\nlop3.b32 a, %1, %2, %5, 0x7e;\nlop3.b32 b, %3, %4, %6, 0x7e;\nlop3.b32 %0, %0, a, b, 0xfe;\n}"
                        : "+r"(bad) : "r"(q[k].x), "r"(q[k].z), "r"(q[k].y), "r"(q[k].w), "r"(t0), "r"(t1));
                if (!(bad & 1)) break;
            }
            __syncwarp();
            TLSTAMP(8);
#pragma unroll
            for (int k = 0; k < 5; k++) m[4 * k] = q[k].x, m[4 * k + 1] = q[k].y, m[4 * k + 2] = q[k].z, m[4 * k + 3] = q[k].w;
#pragma unroll
            for (int k = 0; k < 12; k++)
                if (k < 8 || third) ia[k] = m[k] & 0x3ffc, rk[k] = atoms_add(sb + SC_TABB + ia[k], 8);
            ext = __any_sync(0xffffffffu, min(m[12] & 0x3ffc, m[16] & 0x3ffc) < 40 * NWIN * 4);
            if (ext) {
#pragma unroll
                for (int k = 12; k < 20; k++) ia[k] = m[k] & 0x3ffc, rk[k] = atoms_add(sb + SC_TABB + ia[k], 8);
                if ((tid & 3) == 3 && min(m[15] & 0x3ffc, m[19] & 0x3ffc) < 40 * NWIN * 4) sts32(sb + SM_MISC + 4, 1);
            }
        }
        __syncthreads();
        TLSTAMP(5);
        const uint32_t tr = sb + warp * (NWIN * 4) + lane * 16;
        if (tid == NT - 1 && blockIdx.x == 0) g_epoch = epoch + 1;
        {
            uint4 c[3];
            uint32_t tt[3];
#pragma unroll
            for (int i = 0; i < 3; i++) {
                c[i] = make_uint4(0, 0, 0, 0);
                if ((i < 2 || warp < 8) && lane < NWIN / 4) c[i] = lds128(tr + SC_TABB + i * 16 * NWIN * 4);
                tt[i] = c[i].x + c[i].y + c[i].z + c[i].w;
            }
            const uint32_t sum = (tt[0] >> 3) + (tt[1] << 7) + (tt[2] << 17);
            const uint32_t tot = __reduce_add_sync(0xffffffffu, sum);
            uint32_t inc = scan_step(scan_step(sum, 1), 2);
            const uint32_t q = (tot + 0x300c03) & 0x3fcff3fc, q0 = q & 1023, q1 = q0 + ((q >> 10) & 1023);
            uint32_t base = atoms_add(sb + (lane ? SC_CNT + lane * 4 : SM_MISC + 20), q1 + (q >> 20));
            inc = scan_step(scan_step(scan_step(inc, 4), 8), 16);
            base = __shfl_sync(0xffffffffu, base, 0);
            const uint32_t l3 = min(lane, 2);
            sts32(sb + SC_KEY + (warp + 16 * l3) * 4, ((tot >> (10 * l3)) & 1023) * 64 + 63 - warp - 16 * l3);
            if (max(tt[0], max(tt[1], tt[2])) > 31 * 8) sts32(sb + SM_MISC + 4, 1);
            inc += q - tot - sum;
#pragma unroll
            for (int i = 0; i < 3; i++) {
                const uint32_t e = (((inc >> (10 * i)) & 1023) + base + (i == 0 ? 0 : i == 1 ? q0 : q1)) * 8;
                if ((i < 2 || warp < 8) && lane < NWIN / 4) sts128(tr + SC_TABB + i * 16 * NWIN * 4, e, e + c[i].x, e + c[i].x + c[i].y, e + tt[i] - c[i].w);
            }
        }
        __syncthreads();
        TLSTAMP(2);
        if (warp >= 11) {
            const uint32_t st = (tid - 352) >> 2, key = lds32(sb + SC_KEY + st * 4);
            uint32_t rank = 0;
#pragma unroll
            for (int i = 0; i < 5; i++) {
                const uint2 q = lds64(sb + SC_KEY + (lane & 3) * 40 + i * 8);
                rank += ((key - q.x) >> 31) + ((key - q.y) >> 31);
            }
            rank += __shfl_xor_sync(0xffffffffu, rank, 1);
            rank += __shfl_xor_sync(0xffffffffu, rank, 2);
            const uint32_t lv = rank >> 2, cw = ((0x969u >> (2 * lv)) & 3) * 4 + ((rank ^ -(lv & 1)) & 3);
            const uint32_t sid = (0xe4a50u >> (2 * lv)) & 3;
            sts32(sb + SC_MAP + st * 4, cw * (NWIN * 4) - st * (NWIN * 4) + 0x10000 + (sid << 30));
            asm volatile("st.shared.u8 [%0], %1;" ::"r"(sb + SM_INV + cw * 4 + sid), "r"(st) : "memory");
        }
        const int total = lds32(sb + SM_MISC + 20);
        fast = lds32(sb + SM_MISC + 4) == 0 && total <= RECN - 4;
        auto lookup = [&](int k) {
            asm volatile("{\n.reg .pred p;\n.reg .b32 t;\nsetp.lt.u32 p, %1, %2;\nmov.b32 t, 0x80000000;\n@p ld.shared.b32 t, [%1+%3];\nadd.u32 %0, %0, t;\n}"
                         : "+r"(rk[k]) : "r"(ia[k]), "n"(40 * NWIN * 4), "n"(sb + SC_TABB) : "memory");
        };
        auto place = [&](int k, uint32_t e) {
            asm volatile("{\n.reg .pred p;\nsetp.ge.s32 p, %0, 0;\n@p st.shared.v2.b32 [%0+%3], {%1, %2};\n}" ::"r"(rk[k]), "r"(m[k]), "r"(e),
                         "n"(sb + SC_TMP) : "memory");
        };
#pragma unroll
        for (int k = 0; k < 8; k++) lookup(k);
        if (fast) {
#pragma unroll
            for (int k = 0; k < 8; k++) place(k, eb[k >> 2]);
            if (third) {
#pragma unroll
                for (int k = 8; k < 12; k++) lookup(k);
#pragma unroll
                for (int k = 8; k < 12; k++) place(k, 2 * eb[1] - eb[0]);
            }
            if (ext) {
#pragma unroll
                for (int k = 12; k < 20; k++) lookup(k);
#pragma unroll
                for (int k = 12; k < 20; k++) place(k, ((((tid >> 2) + (k >> 4) * 128) * chunk) << 13) + ecomp + 1);
            }
            constexpr int KD = (RECN + NT - 1) / NT;
            const uint32_t P = (lane ^ (lane >> 1)) & 1;
            const uint32_t binc = (P ? 1u << 11 : 1u) + ((lane & 3) == 3 ? 1u << 22 : 0u);
            const bool last = warp * 32 + (KD - 1) * NT < total, q2 = warp * 128 + NT * 4 < total;
            const int rest = total - tid, restq = (total >> 2) - tid;
            uint2 en[KD];
            uint32_t bk[KD], r2[KD], ca[2], ol[2], r3[2];
            __syncthreads();
            TLSTAMP(9);
#pragma unroll
            for (int k = 0; k < KD; k++)
                if (k < KD - 1 || last) en[k] = lds64(sb + SC_TMP + tid * 8 + k * NT * 8);
#pragma unroll
            for (int k = 0; k < 2; k++)
                if (k == 0 || q2) ca[k] = lds32(sb + SC_TMP + (tid + k * NT) * 32 + 24);
#pragma unroll
            for (int k = 0; k < 2; k++)
                if (k == 0 || q2) ca[k] &= 0x3ffc, ol[k] = lds32(sb + SC_MAP + __umulhi(ca[k], 0xffffffffu / (NWIN * 4) + 1) * 4);
#pragma unroll
            for (int k = 0; k < KD; k++) {
                if (k < KD - 1 || last) {
                    const uint32_t v = en[k].x, f = v >> 14, i = v & 0x3ffc;
                    const uint32_t w4 = i - __umulhi(i, 0xffffffffu / (NWIN * 4) + 1) * (NWIN * 4);
                    const uint32_t o = __umulhi(f, 0xffffffffu / CH + 1) - wsz;
                    bk[k] = (__umulhi(f, bkm) + w4) * 4;
                    en[k].x = (w4 >> 2) * wsz + o;
                    en[k].y += ((v >> 1) & 0xffffe001u) - o * (CH << 13);
                    if (rest <= k * NT) bk[k] = 2048 + lane * 4;
                    r2[k] = atoms_add(sb + SC_TABA + bk[k], binc);
                }
            }
#pragma unroll
            for (int k = 0; k < 2; k++) {
                if (k == 0 || q2) {
                    ca[k] = (ca[k] + ol[k]) & 0xffff;
                    ol[k] = (tid + k * NT) * 16 + (ol[k] >> 30 << 14);
                    r3[k] = atoms_add(sb + SC_TABC + ca[k], restq > k * NT ? 2 : 0);
                }
            }
            __syncthreads();
            TLSTAMP(12);
            if (warp < NCW) {
                uint4 c = make_uint4(0, 0, 0, 0);
                if (lane < NWIN / 4) c = lds128(tr + SC_TABC);
                const uint32_t tt = c.x + c.y + c.z + c.w;
                uint32_t inc = tt;
#pragma unroll
                for (int o = 1; o < 32; o <<= 1) inc = scan_step(inc, o);
                if (inc > (OLN - 6) * 2) sts32(sb + SM_MISC + 4, 1);
                inc += warp * (OLN * 2) - tt;
                if (lane < NWIN / 4) sts128(tr + SC_TABC, inc, inc + c.x, inc + c.x + c.y, inc + tt - c.w);
            } else {
                const uint32_t mine = (warp + lane) & 3;
                uint4 c;
                uint32_t cs, inc = 0, e = 4 + (4 << 11);
#pragma unroll
                for (int i = 0; i < 4; i++) {
                    const uint32_t pc = (mine + i) & 3;
                    const uint4 v = lds128(sb + SC_TABA + lane * 64 + (pc << 4));
                    const uint32_t sum = v.x + v.y + v.z + v.w;
                    inc += sum;
                    if (i == 0) c = v, cs = sum;
                    if (pc >= mine) e -= sum;
                }
#pragma unroll
                for (int o = 1; o < 32; o <<= 1) inc = scan_step(inc, o);
                e += inc;
                sts128(sb + SC_TABB + lane * 64 + (mine << 4), e, e + c.x, e + c.x + c.y, e + cs - c.w);
                if ((int)max((e + cs) & 0x7ff, ((e + cs) >> 11) & 0x7ff) - (int)(e >> 22) * 2 > SP) sts32(sb + SM_MISC + 4, 1);
                if (tid == NCW * 32) {
                    const uint32_t c0 = min(min(c.x & 0x7ff, (c.x >> 11) & 0x7ff), ZSL) >> 2;
                    sts32(sb + SM_MISC + 12, ((total >> 2) + 1) >> 1), sts32(sb + SM_MISC + 24, c0);
                }
            }
            __syncthreads();
            TLSTAMP(13);
            fast = lds32(sb + SM_MISC + 4) == 0;
            if (warp == 15 && lane < lds32(sb + SM_MISC + 24))
                asm volatile("mbarrier.arrive.shared.b64 _, [%0];" ::"r"(sb + SM_BAR + 8 + lane * 8) : "memory");
#pragma unroll
            for (int k = 0; k < KD; k++)
                if (k < KD - 1 || last) r2[k] += lds32(sb + SC_TABB + bk[k]);
#pragma unroll
            for (int k = 0; k < 2; k++)
                if (k == 0 || q2) r3[k] += lds32(sb + SC_TABC + ca[k]);
            if (fast) {
                const uint32_t rot = P ? 9 : 30;
#pragma unroll
                for (int k = 0; k < KD; k++) {
                    if (k < KD - 1 || last) {
                        const uint32_t k4 = __funnelshift_r(r2[k], r2[k], rot);
                        if (rest > k * NT) {
                            sts16(sb + SM_R + 2 + bitsel(k4, P << 13), en[k].x);
                            sts32(sb + SM_REC + tid * 4 + k * NT * 4, bitsel(k4, en[k].y));
                        }
                    }
                }
#pragma unroll
                for (int k = 0; k < 2; k++)
                    if ((k == 0 || q2) && restq > k * NT) sts16(sb + SM_OL + r3[k], ol[k]);
            }
        }
        asm volatile("fence.mbarrier_init.release.cluster;\nfence.proxy.async.shared::cta;" ::: "memory");
        __syncthreads();
        TLSTAMP(3);
        if (!fast && wrow) wf_done();
        if (fast && tid < NOFF) {
            const uint4 a = lds128(t16 + SM_R), b = lds128(t16 + SM_R + 0x2000);
            const int s = (((int)a.x >> 3) + ((int)a.y >> 3) + ((int)a.z >> 3) + ((int)a.w >> 3) + ((int)b.x >> 3) + ((int)b.y >> 3) +
                           ((int)b.z >> 3) + ((int)b.w >> 3)) >> 16;
            sts16(sb + SM_OFF + tid * 2, min(max(tdelay + ((s * tau + min(s, rampn) * ramp - max(s - sprn, 0) * spr) >> 10), 0), 0xffff));
        }
        __syncwarp();
    }

    if (!fast) {
        float* accs = (float*)smem;
        constexpr int NACC = 96;
        const int node0 = blockIdx.x * npb, nnodes = max(0, min(npb, N - node0));
#pragma unroll 1
        for (int nb = 0; nb < nnodes; nb += NACC) {
            __syncthreads();
            for (int i = tid; i < NACC * 512; i += NT) accs[i] = 0.f;
            __syncthreads();
            const int lim = min(NACC, nnodes - nb);
#pragma unroll 1
            for (int base = warp * 32; base < E; base += NT) {
                const int e = base + lane;
                const int dl = e < E ? dst[e] - node0 - nb : -1;
                unsigned mask = __ballot_sync(0xffffffffu, dl >= 0 && dl < lim);
#pragma unroll 1
                while (mask) {
                    const int l = __ffs(mask) - 1;
                    mask &= mask - 1;
                    const int dd = __shfl_sync(0xffffffffu, dl, l);
                    slow_edge(base + l, src[base + l], accs + dd * 512, x, sh, ea, cg, wr, lane);
                }
            }
            __syncthreads();
#pragma unroll 1
            for (int nl = warp; nl < lim; nl += NT / 32) slow_out(accs + nl * 512, wout, out + (size_t)(node0 + nb + nl) * 512, lane);
        }
    } else if (warp >= NCW) {
        asm volatile("setmaxnreg.dec.sync.aligned.u32 %0;" ::"n"(PREG));
        producer(&tmx, warp - NCW);
    } else if (warp >= 4) {
        asm volatile("setmaxnreg.inc.sync.aligned.u32 %0;" ::"n"(R1));
        consumer<3>(sh, ea, out, N, npb);
        TLMAX(4);
    } else {
        asm volatile("setmaxnreg.inc.sync.aligned.u32 %0;" ::"n"(R0));
        consumer<4>(sh, ea, out, N, npb);
        TLMAX(4);
    }
}

typedef CUresult (*EncodeTiledFn)(CUtensorMap*, CUtensorMapDataType, cuuint32_t, void*, const cuuint64_t*,
                                  const cuuint64_t*, const cuuint32_t*, const cuuint32_t*, CUtensorMapInterleave,
                                  CUtensorMapSwizzle, CUtensorMapL2promotion, CUtensorMapFloatOOBfill);

extern "C" void kernel_launch(void* const* d_in, const int* in_sizes, int n_in, void* d_out, int out_size) {
    const __nv_bfloat16* x = (const __nv_bfloat16*)d_in[0];
    const int* src = (const int*)d_in[1];
    const int* dst = (const int*)d_in[2];
    const __nv_bfloat16* sh = (const __nv_bfloat16*)d_in[3];
    const __nv_bfloat16* ea = (const __nv_bfloat16*)d_in[4];
    const __nv_bfloat16* cg = (const __nv_bfloat16*)d_in[5];
    const __nv_bfloat16* wr = (const __nv_bfloat16*)d_in[6];
    const __nv_bfloat16* wout = (const __nv_bfloat16*)d_in[7];
    __nv_bfloat16* out = (__nv_bfloat16*)d_out;
    const int N = in_sizes[0] / 512;
    const int E = in_sizes[1];

    static int num_sms = 0, coresident = 0;
    static EncodeTiledFn encode = nullptr;
    if (num_sms == 0) {
        int dev = 0;
        cudaGetDevice(&dev);
        cudaDeviceGetAttribute(&num_sms, cudaDevAttrMultiProcessorCount, dev);
        cudaFuncSetAttribute(main_kernel, cudaFuncAttributeMaxDynamicSharedMemorySize, SM_TOTAL);
        int occ = 0;
        cudaOccupancyMaxActiveBlocksPerMultiprocessor(&occ, main_kernel, NT, SM_TOTAL);
        coresident = occ * num_sms;
        void* fn = nullptr;
        cudaDriverEntryPointQueryResult qr;
        cudaGetDriverEntryPoint("cuTensorMapEncodeTiled", &fn, cudaEnableDefault, &qr);
        encode = (EncodeTiledFn)fn;
    }
    CUtensorMap tmx;
    const int rank = 3;
    const cuuint64_t gd[3] = {64, (cuuint64_t)N * 4, 2}, gs[2] = {256, 128};
    const cuuint32_t bd[3] = {64, 4, 2}, es[3] = {1, 1, 1};
    encode(&tmx, CU_TENSOR_MAP_DATA_TYPE_BFLOAT16, rank, (void*)x, gd, gs, bd, es, CU_TENSOR_MAP_INTERLEAVE_NONE,
           CU_TENSOR_MAP_SWIZZLE_128B, CU_TENSOR_MAP_L2_PROMOTION_NONE, CU_TENSOR_MAP_FLOAT_OOB_FILL_NONE);

    int nbins = num_sms < MAXB ? num_sms : MAXB;
    int npb = (N + nbins - 1) / nbins;
    if (npb < 2) npb = 2;
    nbins = (N + npb - 1) / npb;
    const unsigned npb_magic = (unsigned)((0x100000000ull + npb - 1) / npb);
    int chunk = (E + nbins - 1) / nbins;
    const unsigned wsz = (N + NWIN - 2) / (NWIN - 1);
    if (nbins > coresident || nbins < 128 || npb > MAXNPB || chunk > CH || wsz > (1 << 18) / CH || N < 512 || E > (1 << 19)) chunk = 0;
    const unsigned wmagic = 0xffffffffu / wsz + 1, bkm = (unsigned)((4ull << 32) / (wsz * CH));
    double pace = PACE, rampt = RAMP, rampf = RAMPF, sprt = SPRINT, sprf = SPRINTF;
    int tdelay = TDELAY, polld = POLLD;
    const int tau = (int)(1024.0 * pace * ((double)E / nbins) / N);
    const int rampn = (int)(N * rampf), ramp = (int)(1024.0 * rampt / rampn);
    main_kernel<<<nbins, NT, SM_TOTAL, cudaStreamPerThread>>>(tmx, x, src, dst, sh, ea, cg, wr, wout, out, N, E, npb, npb_magic,
                                                              chunk, wsz, wmagic, bkm, tau, ramp, rampn, tdelay, polld, (int)(1024.0 * sprt / (N * sprf)), (int)(N * (1 - sprf)));
}
```

```cpp
#include <cuda_runtime.h>
#include <cuda.h>
#include <cuda_bf16.h>
#include <stdint.h>
#include <stdlib.h>

#define NT 512
#define NCW 12
#define MAXB 144
#define MAXNPB 80
#define KE 5
#define SP 99
#define RECN 2752
#define RP 1484
#define OLN 80
#define NBAR 350
#define NOFF 352
#define R0 168
#define R1 160
#define PREG 24
#define PACE 10.0
#define TDELAY 4550
#define POLLD 1000
#define WFT 80
#define SLIPTH 250
#define SLIPADD 150
#define SLIPFROM 36
#define AHEAD 96
#define EARLY 32
#define RAMPF 0.1
#define SPRINT 500
#define SPRINTF 0.5
#define SLIPEND 640
#define SPINT 96
#define RAMP 600

__device__ __align__(1024) uint4 g_cell[MAXB * MAXB * 8];
__device__ __align__(1024) uint4 g_more[MAXB * MAXB * 4];
__device__ __align__(1024) uint4 g_wf[2048];
__device__ __align__(256) ulonglong2 g_sync[16];
__device__ __align__(256) unsigned g_epoch;
#define TLSTAMP(i)
#define TLMAX(i)

constexpr uint32_t sb = 1024;
#define PH 512
#define SM_R (2 * SP * 1024 + PH)
#define SM_CTR (SP * 1024)
#define SM_MISC (SM_R + RP * 4)
#define SM_INV (SM_MISC + 80)
#define SM_OL (SM_INV + 48)
#define SM_REC (SM_R + 0x2000 + RP * 4)
#define SM_OFF (SM_REC + RECN * 4)
#define SM_BAR (SM_OFF + NOFF * 2)
#define SM_TOTAL (SM_BAR + NBAR * 8)
static_assert(SM_TOTAL <= 232448 && SM_OL + NCW * OLN * 2 <= SM_R + 0x2000 && SM_OL % 16 == 0 && SM_BAR % 16 == 0, "shared memory");
static_assert(4 + RECN / 2 + SP + 2 <= RP && RECN / 8 + 5 <= NBAR && NBAR % 14 == 0 && RECN / 8 + 4 <= NOFF, "tables");
#define ZSL 32
#define NWIN 96
#define CH 2432
#define CP 208
#define SC_STG ((SP + ZSL) * 1024 + PH)
#define SC_TMP (ZSL * 1024)
#define SC_TABB (SC_TMP + 3072 * 8)
#define SC_TABC (SC_TABB + 41 * NWIN * 4)
#define SC_TABA (SC_TABC + NCW * NWIN * 4)
#define SC_ZEND (SC_TABB + 3 * NT * 16)
#define SC_CNT SC_ZEND
#define SC_KEY (SC_CNT + (MAXB + 32) * 4)
#define SC_MAP (SC_KEY + 192)
#define WSL 5
#define SC_WR ((2 * SP - WSL) * 1024 + PH)
#define SC_CG (SC_WR + 16 * 272)
static_assert(SC_TABA + 2048 + 128 <= SC_ZEND && RECN <= 3072 && SC_MAP + 192 <= SP * 1024 && SC_STG + (MAXB + 1) * CP <= SC_WR, "scratch");

__device__ __forceinline__ uint32_t pack_bf16(float lo, float hi) {
    uint32_t r;
    asm("cvt.rn.bf16x2.f32 %0, %1, %2;" : "=r"(r) : "f"(hi), "f"(lo));
    return r;
}
__device__ __forceinline__ uint32_t s2u(const void* p) { return (uint32_t)__cvta_generic_to_shared(p); }
__device__ __forceinline__ void mbar_wait0(uint32_t a) {
    asm volatile(
        "{\n.reg .pred p, q;\n.reg .u32 n;\nmov.u32 n, 0;\n"
        "LAB_WAIT:\nmbarrier.try_wait.parity.shared.b64 p, [%0], 0;\nadd.u32 n, n, 1;\nsetp.lt.and.u32 q, n, 1000000, !p;\n@q bra LAB_WAIT;\n}" ::"r"(a)
        : "memory");
}
__device__ __forceinline__ uint32_t lds8(uint32_t a) { uint32_t v; asm volatile("ld.shared.u8 %0, [%1];" : "=r"(v) : "r"(a) : "memory"); return v; }
__device__ __forceinline__ uint32_t lds16(uint32_t a) { uint32_t v; asm volatile("ld.shared.u16 %0, [%1];" : "=r"(v) : "r"(a) : "memory"); return v; }
__device__ __forceinline__ uint32_t lds32(uint32_t a) { uint32_t v; asm volatile("ld.shared.u32 %0, [%1];" : "=r"(v) : "r"(a) : "memory"); return v; }
__device__ __forceinline__ uint2 lds64(uint32_t a) {
    uint2 v; asm volatile("ld.shared.v2.u32 {%0,%1}, [%2];" : "=r"(v.x), "=r"(v.y) : "r"(a) : "memory"); return v;
}
__device__ __forceinline__ uint4 lds128(uint32_t a) {
    uint4 v; asm volatile("ld.volatile.shared.v4.u32 {%0,%1,%2,%3}, [%4];" : "=r"(v.x), "=r"(v.y), "=r"(v.z), "=r"(v.w) : "r"(a) : "memory"); return v;
}
__device__ __forceinline__ void sts16(uint32_t a, uint32_t v) { asm volatile("st.shared.u16 [%0], %1;" ::"r"(a), "h"((unsigned short)v) : "memory"); }
__device__ __forceinline__ void sts32(uint32_t a, uint32_t v) { asm volatile("st.shared.u32 [%0], %1;" ::"r"(a), "r"(v) : "memory"); }
__device__ __forceinline__ void sts64(uint32_t a, uint32_t x, uint32_t y) { asm volatile("st.shared.v2.u32 [%0], {%1,%2};" ::"r"(a), "r"(x), "r"(y) : "memory"); }
__device__ __forceinline__ void sts128(uint32_t a, uint32_t x, uint32_t y, uint32_t z, uint32_t w) {
    asm volatile("st.shared.v4.u32 [%0], {%1,%2,%3,%4};" ::"r"(a), "r"(x), "r"(y), "r"(z), "r"(w) : "memory");
}
__device__ __forceinline__ uint32_t atoms_add(uint32_t a, uint32_t v) {
    uint32_t r;
    asm volatile("atom.shared.add.u32 %0, [%1], %2;" : "=r"(r) : "r"(a), "r"(v) : "memory");
    return r;
}
__device__ __forceinline__ uint4 ld_cell(const uint4* p) {
    uint4 v;
    asm volatile("{\n.reg .b64 a, b;\nld.relaxed.gpu.global.v2.b64 {a, b}, [%4];\nmov.b64 {%0,%1}, a;\nmov.b64 {%2,%3}, b;\n}"
                 : "=r"(v.x), "=r"(v.y), "=r"(v.z), "=r"(v.w) : "l"(p) : "memory");
    return v;
}
__device__ __forceinline__ void st_cell(uint4* p, uint32_t x, uint32_t y, uint32_t z, uint32_t w) {
    asm volatile("st.relaxed.gpu.global.v2.b64 [%0], {%1, %2};" ::"l"(p), "l"(x | (uint64_t)y << 32), "l"(z | (uint64_t)w << 32) : "memory");
}
__device__ __forceinline__ uint32_t scan_step(uint32_t v, int o) {
    asm volatile("{\n.reg .pred p;\n.reg .b32 y;\nshfl.sync.up.b32 y|p, %0, %1, 0, 0xffffffff;\n@p add.u32 %0, %0, y;\n}" : "+r"(v) : "r"(o));
    return v;
}
__device__ __forceinline__ uint32_t bitsel(uint32_t a, uint32_t b) {
    uint32_t r;
    asm("lop3.b32 %0, %1, %2, 0x1ffc, 0xe4;" : "=r"(r) : "r"(a), "r"(b));
    return r;
}
__device__ __forceinline__ uint32_t movm(uint32_t a) {
    uint32_t r;
    asm volatile("movmatrix.sync.aligned.m8n8.trans.b16 %0, %1;" : "=r"(r) : "r"(a));
    return r;
}
__device__ __forceinline__ uint32_t gt_lo() {
    uint32_t t;
    asm volatile("mov.u32 %0, %globaltimer_lo;" : "=r"(t));
    return t;
}
__device__ __forceinline__ bool elect() {
    uint32_t p;
    asm volatile("{\n.reg .pred P;\nelect.sync _|P, 0xffffffff;\nselp.u32 %0, 1, 0, P;\n}" : "=r"(p));
    return p;
}
__device__ __forceinline__ void project4(const uint32_t (&pk)[64], uint32_t ra, uint32_t ba, uint4* const (&p)[4], const uint32_t (&v)[4]) {
    asm volatile(
        "{\n.reg .pred p0, p1, q0, q1, nv, s<4>;\n.reg .b32 t, h, c<16>, a<32>, b<32>, k<16>;\n.reg .b64 d<16>;\n.reg .f32 o<32>;\nsetp.ne.b32 p0, 0, 0;\n"
        "setp.eq.b32 p1, 0, 0;\nmov.b32 h, 8;\nsetp.eq.u32 nv, %64, 0;\nvote.sync.any.pred nv, nv, 0xffffffff;\nsetp.ne.b32 s0, %69, 0;\n"
        "setp.ne.b32 s1, %70, 0;\nsetp.ne.b32 s2, %71, 0;\nsetp.ne.b32 s3, %72, 0;\nmovmatrix.sync.aligned.m8n8.trans.b16 a0, %0;\n"
        "movmatrix.sync.aligned.m8n8.trans.b16 a1, %16;\nmovmatrix.sync.aligned.m8n8.trans.b16 a2, %1;\nmovmatrix.sync.aligned.m8n8.trans.b16 a3, %17;\n"
        "movmatrix.sync.aligned.m8n8.trans.b16 a4, %2;\nmovmatrix.sync.aligned.m8n8.trans.b16 a5, %18;\nmovmatrix.sync.aligned.m8n8.trans.b16 a6, %3;\n"
        "movmatrix.sync.aligned.m8n8.trans.b16 a7, %19;\nmovmatrix.sync.aligned.m8n8.trans.b16 a8, %4;\nmovmatrix.sync.aligned.m8n8.trans.b16 a9, %20;\n"
        "movmatrix.sync.aligned.m8n8.trans.b16 a10, %5;\nmovmatrix.sync.aligned.m8n8.trans.b16 a11, %21;\nmovmatrix.sync.aligned.m8n8.trans.b16 a12, %6;\n"
        "movmatrix.sync.aligned.m8n8.trans.b16 a13, %22;\nmovmatrix.sync.aligned.m8n8.trans.b16 a14, %7;\nmovmatrix.sync.aligned.m8n8.trans.b16 a15, %23;\n"
        "movmatrix.sync.aligned.m8n8.trans.b16 a16, %8;\nmovmatrix.sync.aligned.m8n8.trans.b16 a17, %24;\nmovmatrix.sync.aligned.m8n8.trans.b16 a18, %9;\n"
        "movmatrix.sync.aligned.m8n8.trans.b16 a19, %25;\nmovmatrix.sync.aligned.m8n8.trans.b16 a20, %10;\nmovmatrix.sync.aligned.m8n8.trans.b16 a21, %26;\n"
        "movmatrix.sync.aligned.m8n8.trans.b16 a22, %11;\nmovmatrix.sync.aligned.m8n8.trans.b16 a23, %27;\nmovmatrix.sync.aligned.m8n8.trans.b16 a24, %12;\n"
        "movmatrix.sync.aligned.m8n8.trans.b16 a25, %28;\nmovmatrix.sync.aligned.m8n8.trans.b16 a26, %13;\nmovmatrix.sync.aligned.m8n8.trans.b16 a27, %29;\n"
        "movmatrix.sync.aligned.m8n8.trans.b16 a28, %14;\nmovmatrix.sync.aligned.m8n8.trans.b16 a29, %30;\nmovmatrix.sync.aligned.m8n8.trans.b16 a30, %15;\n"
        "movmatrix.sync.aligned.m8n8.trans.b16 a31, %31;\nmov.b32 t, 0;\n"
        "W0:\nmbarrier.try_wait.parity.shared.b64 q0, [%73+0], 0;\nadd.u32 t, t, 1;\nsetp.lt.and.u32 q1, t, 1000000, !q0;\n@q1 bra.uni W0;\nmov.b32 t, 0;\n"
        "W1:\nmbarrier.try_wait.parity.shared.b64 q0, [%73+8], 0;\nadd.u32 t, t, 1;\nsetp.lt.and.u32 q1, t, 1000000, !q0;\n@q1 bra.uni W1;\nmov.b32 t, 0;\n"
        "W2:\nmbarrier.try_wait.parity.shared.b64 q0, [%73+16], 0;\nadd.u32 t, t, 1;\nsetp.lt.and.u32 q1, t, 1000000, !q0;\n@q1 bra.uni W2;\nmov.b32 t, 0;\n"
        "W3:\nmbarrier.try_wait.parity.shared.b64 q0, [%73+24], 0;\nadd.u32 t, t, 1;\nsetp.lt.and.u32 q1, t, 1000000, !q0;\n@q1 bra.uni W3;\n"
        "ld.volatile.shared.v4.b32 {c0,c1,c2,c3}, [%64+0];\nld.volatile.shared.v4.b32 {c4,c5,c6,c7}, [%64+8192];\n"
        "ld.volatile.shared.v4.b32 {c8,c9,c10,c11}, [%64+16];\nld.volatile.shared.v4.b32 {c12,c13,c14,c15}, [%64+8208];\nand.b32 t, c0, 0xffe;\n"
        "mad.lo.u32 t, t, 4, 0x200000;\nmov.b64 d0, {t, h};\nand.b32 t, c1, 0xffe;\nmad.lo.u32 t, t, 4, 0x200000;\nmov.b64 d1, {t, h};\nand.b32 t, c2, 0xffe;\n"
        "mad.lo.u32 t, t, 4, 0x200000;\nmov.b64 d2, {t, h};\nand.b32 t, c3, 0xffe;\nmad.lo.u32 t, t, 4, 0x200000;\nmov.b64 d3, {t, h};\nand.b32 t, c4, 0xffe;\n"
        "mad.lo.u32 t, t, 4, 0x200000;\nmov.b64 d4, {t, h};\nand.b32 t, c5, 0xffe;\nmad.lo.u32 t, t, 4, 0x200000;\nmov.b64 d5, {t, h};\nand.b32 t, c6, 0xffe;\n"
        "mad.lo.u32 t, t, 4, 0x200000;\nmov.b64 d6, {t, h};\nand.b32 t, c7, 0xffe;\nmad.lo.u32 t, t, 4, 0x200000;\nmov.b64 d7, {t, h};\nand.b32 t, c8, 0xffe;\n"
        "mad.lo.u32 t, t, 4, 0x200000;\nmov.b64 d8, {t, h};\nand.b32 t, c9, 0xffe;\nmad.lo.u32 t, t, 4, 0x200000;\nmov.b64 d9, {t, h};\nand.b32 t, c10, 0xffe;\n"
        "mad.lo.u32 t, t, 4, 0x200000;\nmov.b64 d10, {t, h};\nand.b32 t, c11, 0xffe;\nmad.lo.u32 t, t, 4, 0x200000;\nmov.b64 d11, {t, h};\n"
        "and.b32 t, c12, 0xffe;\nmad.lo.u32 t, t, 4, 0x200000;\nmov.b64 d12, {t, h};\nand.b32 t, c13, 0xffe;\nmad.lo.u32 t, t, 4, 0x200000;\n"
        "mov.b64 d13, {t, h};\nand.b32 t, c14, 0xffe;\nmad.lo.u32 t, t, 4, 0x200000;\nmov.b64 d14, {t, h};\nand.b32 t, c15, 0xffe;\n"
        "mad.lo.u32 t, t, 4, 0x200000;\nmov.b64 d15, {t, h};\nwgmma.fence.sync.aligned;\n"
        "wgmma.mma_async.sync.aligned.m64n32k16.f32.bf16.bf16 {o0,o1,o2,o3,o4,o5,o6,o7,o8,o9,o10,o11,o12,o13,o14,o15}, {a0,a1,a2,a3}, d0, p0, 1, 1, 1;\n"
        "wgmma.mma_async.sync.aligned.m64n32k16.f32.bf16.bf16 {o16,o17,o18,o19,o20,o21,o22,o23,o24,o25,o26,o27,o28,o29,o30,o31}, {a0,a1,a2,a3}, d8, p0, 1, 1, 1;\n"
        "wgmma.mma_async.sync.aligned.m64n32k16.f32.bf16.bf16 {o0,o1,o2,o3,o4,o5,o6,o7,o8,o9,o10,o11,o12,o13,o14,o15}, {a4,a5,a6,a7}, d1, p1, 1, 1, 1;\n"
        "wgmma.mma_async.sync.aligned.m64n32k16.f32.bf16.bf16 {o16,o17,o18,o19,o20,o21,o22,o23,o24,o25,o26,o27,o28,o29,o30,o31}, {a4,a5,a6,a7}, d9, p1, 1, 1, 1;\n"
        "wgmma.mma_async.sync.aligned.m64n32k16.f32.bf16.bf16 {o0,o1,o2,o3,o4,o5,o6,o7,o8,o9,o10,o11,o12,o13,o14,o15}, {a8,a9,a10,a11}, d2, p1, 1, 1, 1;\n"
        "wgmma.mma_async.sync.aligned.m64n32k16.f32.bf16.bf16 {o16,o17,o18,o19,o20,o21,o22,o23,o24,o25,o26,o27,o28,o29,o30,o31}, {a8,a9,a10,a11}, d10, p1, 1, 1, 1;\n"
        "wgmma.mma_async.sync.aligned.m64n32k16.f32.bf16.bf16 {o0,o1,o2,o3,o4,o5,o6,o7,o8,o9,o10,o11,o12,o13,o14,o15}, {a12,a13,a14,a15}, d3, p1, 1, 1, 1;\n"
        "wgmma.mma_async.sync.aligned.m64n32k16.f32.bf16.bf16 {o16,o17,o18,o19,o20,o21,o22,o23,o24,o25,o26,o27,o28,o29,o30,o31}, {a12,a13,a14,a15}, d11, p1, 1, 1, 1;\n"
        "wgmma.mma_async.sync.aligned.m64n32k16.f32.bf16.bf16 {o0,o1,o2,o3,o4,o5,o6,o7,o8,o9,o10,o11,o12,o13,o14,o15}, {a16,a17,a18,a19}, d4, p1, 1, 1, 1;\n"
        "wgmma.mma_async.sync.aligned.m64n32k16.f32.bf16.bf16 {o16,o17,o18,o19,o20,o21,o22,o23,o24,o25,o26,o27,o28,o29,o30,o31}, {a16,a17,a18,a19}, d12, p1, 1, 1, 1;\n"
        "wgmma.mma_async.sync.aligned.m64n32k16.f32.bf16.bf16 {o0,o1,o2,o3,o4,o5,o6,o7,o8,o9,o10,o11,o12,o13,o14,o15}, {a20,a21,a22,a23}, d5, p1, 1, 1, 1;\n"
        "wgmma.mma_async.sync.aligned.m64n32k16.f32.bf16.bf16 {o16,o17,o18,o19,o20,o21,o22,o23,o24,o25,o26,o27,o28,o29,o30,o31}, {a20,a21,a22,a23}, d13, p1, 1, 1, 1;\n"
        "wgmma.mma_async.sync.aligned.m64n32k16.f32.bf16.bf16 {o0,o1,o2,o3,o4,o5,o6,o7,o8,o9,o10,o11,o12,o13,o14,o15}, {a24,a25,a26,a27}, d6, p1, 1, 1, 1;\n"
        "wgmma.mma_async.sync.aligned.m64n32k16.f32.bf16.bf16 {o16,o17,o18,o19,o20,o21,o22,o23,o24,o25,o26,o27,o28,o29,o30,o31}, {a24,a25,a26,a27}, d14, p1, 1, 1, 1;\n"
        "wgmma.mma_async.sync.aligned.m64n32k16.f32.bf16.bf16 {o0,o1,o2,o3,o4,o5,o6,o7,o8,o9,o10,o11,o12,o13,o14,o15}, {a28,a29,a30,a31}, d7, p1, 1, 1, 1;\n"
        "wgmma.mma_async.sync.aligned.m64n32k16.f32.bf16.bf16 {o16,o17,o18,o19,o20,o21,o22,o23,o24,o25,o26,o27,o28,o29,o30,o31}, {a28,a29,a30,a31}, d15, p1, 1, 1, 1;\n"
        "wgmma.commit_group.sync.aligned;\n@nv bra.uni END;\n@nv bra.uni END;\nwgmma.wait_group.sync.aligned 0;\ncvt.rn.bf16x2.f32 k0, o1, o0;\n"
        "cvt.rn.bf16x2.f32 k1, o5, o4;\ncvt.rn.bf16x2.f32 k2, o9, o8;\ncvt.rn.bf16x2.f32 k3, o13, o12;\ncvt.rn.bf16x2.f32 k4, o3, o2;\n"
        "cvt.rn.bf16x2.f32 k5, o7, o6;\ncvt.rn.bf16x2.f32 k6, o11, o10;\ncvt.rn.bf16x2.f32 k7, o15, o14;\ncvt.rn.bf16x2.f32 k8, o17, o16;\n"
        "cvt.rn.bf16x2.f32 k9, o21, o20;\ncvt.rn.bf16x2.f32 k10, o25, o24;\ncvt.rn.bf16x2.f32 k11, o29, o28;\ncvt.rn.bf16x2.f32 k12, o19, o18;\n"
        "cvt.rn.bf16x2.f32 k13, o23, o22;\ncvt.rn.bf16x2.f32 k14, o27, o26;\ncvt.rn.bf16x2.f32 k15, o31, o30;\n@s0 st.global.v4.b32 [%65+0], {k0,k1,k2,k3};\n"
        "@s1 st.global.v4.b32 [%66+0], {k4,k5,k6,k7};\n@s0 st.global.v4.b32 [%65+64], {k8,k9,k10,k11};\n@s1 st.global.v4.b32 [%66+64], {k12,k13,k14,k15};\n"
        "@nv bra.uni END;\nld.volatile.shared.v4.b32 {c0,c1,c2,c3}, [%64+32];\nld.volatile.shared.v4.b32 {c4,c5,c6,c7}, [%64+8224];\n"
        "ld.volatile.shared.v4.b32 {c8,c9,c10,c11}, [%64+48];\nld.volatile.shared.v4.b32 {c12,c13,c14,c15}, [%64+8240];\nand.b32 t, c0, 0xffe;\n"
        "mad.lo.u32 t, t, 4, 0x200000;\nmov.b64 d0, {t, h};\nand.b32 t, c1, 0xffe;\nmad.lo.u32 t, t, 4, 0x200000;\nmov.b64 d1, {t, h};\nand.b32 t, c2, 0xffe;\n"
        "mad.lo.u32 t, t, 4, 0x200000;\nmov.b64 d2, {t, h};\nand.b32 t, c3, 0xffe;\nmad.lo.u32 t, t, 4, 0x200000;\nmov.b64 d3, {t, h};\nand.b32 t, c4, 0xffe;\n"
        "mad.lo.u32 t, t, 4, 0x200000;\nmov.b64 d4, {t, h};\nand.b32 t, c5, 0xffe;\nmad.lo.u32 t, t, 4, 0x200000;\nmov.b64 d5, {t, h};\nand.b32 t, c6, 0xffe;\n"
        "mad.lo.u32 t, t, 4, 0x200000;\nmov.b64 d6, {t, h};\nand.b32 t, c7, 0xffe;\nmad.lo.u32 t, t, 4, 0x200000;\nmov.b64 d7, {t, h};\nand.b32 t, c8, 0xffe;\n"
        "mad.lo.u32 t, t, 4, 0x200000;\nmov.b64 d8, {t, h};\nand.b32 t, c9, 0xffe;\nmad.lo.u32 t, t, 4, 0x200000;\nmov.b64 d9, {t, h};\nand.b32 t, c10, 0xffe;\n"
        "mad.lo.u32 t, t, 4, 0x200000;\nmov.b64 d10, {t, h};\nand.b32 t, c11, 0xffe;\nmad.lo.u32 t, t, 4, 0x200000;\nmov.b64 d11, {t, h};\n"
        "and.b32 t, c12, 0xffe;\nmad.lo.u32 t, t, 4, 0x200000;\nmov.b64 d12, {t, h};\nand.b32 t, c13, 0xffe;\nmad.lo.u32 t, t, 4, 0x200000;\n"
        "mov.b64 d13, {t, h};\nand.b32 t, c14, 0xffe;\nmad.lo.u32 t, t, 4, 0x200000;\nmov.b64 d14, {t, h};\nand.b32 t, c15, 0xffe;\n"
        "mad.lo.u32 t, t, 4, 0x200000;\nmov.b64 d15, {t, h};\nwgmma.fence.sync.aligned;\n"
        "wgmma.mma_async.sync.aligned.m64n32k16.f32.bf16.bf16 {o0,o1,o2,o3,o4,o5,o6,o7,o8,o9,o10,o11,o12,o13,o14,o15}, {a0,a1,a2,a3}, d0, p0, 1, 1, 1;\n"
        "wgmma.mma_async.sync.aligned.m64n32k16.f32.bf16.bf16 {o16,o17,o18,o19,o20,o21,o22,o23,o24,o25,o26,o27,o28,o29,o30,o31}, {a0,a1,a2,a3}, d8, p0, 1, 1, 1;\n"
        "wgmma.mma_async.sync.aligned.m64n32k16.f32.bf16.bf16 {o0,o1,o2,o3,o4,o5,o6,o7,o8,o9,o10,o11,o12,o13,o14,o15}, {a4,a5,a6,a7}, d1, p1, 1, 1, 1;\n"
        "wgmma.mma_async.sync.aligned.m64n32k16.f32.bf16.bf16 {o16,o17,o18,o19,o20,o21,o22,o23,o24,o25,o26,o27,o28,o29,o30,o31}, {a4,a5,a6,a7}, d9, p1, 1, 1, 1;\n"
        "wgmma.mma_async.sync.aligned.m64n32k16.f32.bf16.bf16 {o0,o1,o2,o3,o4,o5,o6,o7,o8,o9,o10,o11,o12,o13,o14,o15}, {a8,a9,a10,a11}, d2, p1, 1, 1, 1;\n"
        "wgmma.mma_async.sync.aligned.m64n32k16.f32.bf16.bf16 {o16,o17,o18,o19,o20,o21,o22,o23,o24,o25,o26,o27,o28,o29,o30,o31}, {a8,a9,a10,a11}, d10, p1, 1, 1, 1;\n"
        "wgmma.mma_async.sync.aligned.m64n32k16.f32.bf16.bf16 {o0,o1,o2,o3,o4,o5,o6,o7,o8,o9,o10,o11,o12,o13,o14,o15}, {a12,a13,a14,a15}, d3, p1, 1, 1, 1;\n"
        "wgmma.mma_async.sync.aligned.m64n32k16.f32.bf16.bf16 {o16,o17,o18,o19,o20,o21,o22,o23,o24,o25,o26,o27,o28,o29,o30,o31}, {a12,a13,a14,a15}, d11, p1, 1, 1, 1;\n"
        "wgmma.mma_async.sync.aligned.m64n32k16.f32.bf16.bf16 {o0,o1,o2,o3,o4,o5,o6,o7,o8,o9,o10,o11,o12,o13,o14,o15}, {a16,a17,a18,a19}, d4, p1, 1, 1, 1;\n"
        "wgmma.mma_async.sync.aligned.m64n32k16.f32.bf16.bf16 {o16,o17,o18,o19,o20,o21,o22,o23,o24,o25,o26,o27,o28,o29,o30,o31}, {a16,a17,a18,a19}, d12, p1, 1, 1, 1;\n"
        "wgmma.mma_async.sync.aligned.m64n32k16.f32.bf16.bf16 {o0,o1,o2,o3,o4,o5,o6,o7,o8,o9,o10,o11,o12,o13,o14,o15}, {a20,a21,a22,a23}, d5, p1, 1, 1, 1;\n"
        "wgmma.mma_async.sync.aligned.m64n32k16.f32.bf16.bf16 {o16,o17,o18,o19,o20,o21,o22,o23,o24,o25,o26,o27,o28,o29,o30,o31}, {a20,a21,a22,a23}, d13, p1, 1, 1, 1;\n"
        "wgmma.mma_async.sync.aligned.m64n32k16.f32.bf16.bf16 {o0,o1,o2,o3,o4,o5,o6,o7,o8,o9,o10,o11,o12,o13,o14,o15}, {a24,a25,a26,a27}, d6, p1, 1, 1, 1;\n"
        "wgmma.mma_async.sync.aligned.m64n32k16.f32.bf16.bf16 {o16,o17,o18,o19,o20,o21,o22,o23,o24,o25,o26,o27,o28,o29,o30,o31}, {a24,a25,a26,a27}, d14, p1, 1, 1, 1;\n"
        "wgmma.mma_async.sync.aligned.m64n32k16.f32.bf16.bf16 {o0,o1,o2,o3,o4,o5,o6,o7,o8,o9,o10,o11,o12,o13,o14,o15}, {a28,a29,a30,a31}, d7, p1, 1, 1, 1;\n"
        "wgmma.mma_async.sync.aligned.m64n32k16.f32.bf16.bf16 {o16,o17,o18,o19,o20,o21,o22,o23,o24,o25,o26,o27,o28,o29,o30,o31}, {a28,a29,a30,a31}, d15, p1, 1, 1, 1;\n"
        "wgmma.commit_group.sync.aligned;\n@nv bra.uni END;\nmovmatrix.sync.aligned.m8n8.trans.b16 b0, %32;\nmovmatrix.sync.aligned.m8n8.trans.b16 b1, %48;\n"
        "movmatrix.sync.aligned.m8n8.trans.b16 b2, %33;\nmovmatrix.sync.aligned.m8n8.trans.b16 b3, %49;\nmovmatrix.sync.aligned.m8n8.trans.b16 b4, %34;\n"
        "movmatrix.sync.aligned.m8n8.trans.b16 b5, %50;\nmovmatrix.sync.aligned.m8n8.trans.b16 b6, %35;\nmovmatrix.sync.aligned.m8n8.trans.b16 b7, %51;\n"
        "movmatrix.sync.aligned.m8n8.trans.b16 b8, %36;\nmovmatrix.sync.aligned.m8n8.trans.b16 b9, %52;\nmovmatrix.sync.aligned.m8n8.trans.b16 b10, %37;\n"
        "movmatrix.sync.aligned.m8n8.trans.b16 b11, %53;\nmovmatrix.sync.aligned.m8n8.trans.b16 b12, %38;\nmovmatrix.sync.aligned.m8n8.trans.b16 b13, %54;\n"
        "movmatrix.sync.aligned.m8n8.trans.b16 b14, %39;\nmovmatrix.sync.aligned.m8n8.trans.b16 b15, %55;\nmovmatrix.sync.aligned.m8n8.trans.b16 b16, %40;\n"
        "movmatrix.sync.aligned.m8n8.trans.b16 b17, %56;\nmovmatrix.sync.aligned.m8n8.trans.b16 b18, %41;\nmovmatrix.sync.aligned.m8n8.trans.b16 b19, %57;\n"
        "movmatrix.sync.aligned.m8n8.trans.b16 b20, %42;\nmovmatrix.sync.aligned.m8n8.trans.b16 b21, %58;\nmovmatrix.sync.aligned.m8n8.trans.b16 b22, %43;\n"
        "movmatrix.sync.aligned.m8n8.trans.b16 b23, %59;\nmovmatrix.sync.aligned.m8n8.trans.b16 b24, %44;\nmovmatrix.sync.aligned.m8n8.trans.b16 b25, %60;\n"
        "movmatrix.sync.aligned.m8n8.trans.b16 b26, %45;\nmovmatrix.sync.aligned.m8n8.trans.b16 b27, %61;\nmovmatrix.sync.aligned.m8n8.trans.b16 b28, %46;\n"
        "movmatrix.sync.aligned.m8n8.trans.b16 b29, %62;\nmovmatrix.sync.aligned.m8n8.trans.b16 b30, %47;\nmovmatrix.sync.aligned.m8n8.trans.b16 b31, %63;\n"
        "@nv bra.uni END;\nwgmma.wait_group.sync.aligned 0;\ncvt.rn.bf16x2.f32 k0, o1, o0;\ncvt.rn.bf16x2.f32 k1, o5, o4;\ncvt.rn.bf16x2.f32 k2, o9, o8;\n"
        "cvt.rn.bf16x2.f32 k3, o13, o12;\ncvt.rn.bf16x2.f32 k4, o3, o2;\ncvt.rn.bf16x2.f32 k5, o7, o6;\ncvt.rn.bf16x2.f32 k6, o11, o10;\n"
        "cvt.rn.bf16x2.f32 k7, o15, o14;\ncvt.rn.bf16x2.f32 k8, o17, o16;\ncvt.rn.bf16x2.f32 k9, o21, o20;\ncvt.rn.bf16x2.f32 k10, o25, o24;\n"
        "cvt.rn.bf16x2.f32 k11, o29, o28;\ncvt.rn.bf16x2.f32 k12, o19, o18;\ncvt.rn.bf16x2.f32 k13, o23, o22;\ncvt.rn.bf16x2.f32 k14, o27, o26;\n"
        "cvt.rn.bf16x2.f32 k15, o31, o30;\nld.volatile.shared.v4.b32 {c0,c1,c2,c3}, [%64+0];\nld.volatile.shared.v4.b32 {c4,c5,c6,c7}, [%64+8192];\n"
        "ld.volatile.shared.v4.b32 {c8,c9,c10,c11}, [%64+16];\nld.volatile.shared.v4.b32 {c12,c13,c14,c15}, [%64+8208];\nand.b32 t, c0, 0xffe;\n"
        "mad.lo.u32 t, t, 4, 0x200000;\nmov.b64 d0, {t, h};\nand.b32 t, c1, 0xffe;\nmad.lo.u32 t, t, 4, 0x200000;\nmov.b64 d1, {t, h};\nand.b32 t, c2, 0xffe;\n"
        "mad.lo.u32 t, t, 4, 0x200000;\nmov.b64 d2, {t, h};\nand.b32 t, c3, 0xffe;\nmad.lo.u32 t, t, 4, 0x200000;\nmov.b64 d3, {t, h};\nand.b32 t, c4, 0xffe;\n"
        "mad.lo.u32 t, t, 4, 0x200000;\nmov.b64 d4, {t, h};\nand.b32 t, c5, 0xffe;\nmad.lo.u32 t, t, 4, 0x200000;\nmov.b64 d5, {t, h};\nand.b32 t, c6, 0xffe;\n"
        "mad.lo.u32 t, t, 4, 0x200000;\nmov.b64 d6, {t, h};\nand.b32 t, c7, 0xffe;\nmad.lo.u32 t, t, 4, 0x200000;\nmov.b64 d7, {t, h};\nand.b32 t, c8, 0xffe;\n"
        "mad.lo.u32 t, t, 4, 0x200000;\nmov.b64 d8, {t, h};\nand.b32 t, c9, 0xffe;\nmad.lo.u32 t, t, 4, 0x200000;\nmov.b64 d9, {t, h};\nand.b32 t, c10, 0xffe;\n"
        "mad.lo.u32 t, t, 4, 0x200000;\nmov.b64 d10, {t, h};\nand.b32 t, c11, 0xffe;\nmad.lo.u32 t, t, 4, 0x200000;\nmov.b64 d11, {t, h};\n"
        "and.b32 t, c12, 0xffe;\nmad.lo.u32 t, t, 4, 0x200000;\nmov.b64 d12, {t, h};\nand.b32 t, c13, 0xffe;\nmad.lo.u32 t, t, 4, 0x200000;\n"
        "mov.b64 d13, {t, h};\nand.b32 t, c14, 0xffe;\nmad.lo.u32 t, t, 4, 0x200000;\nmov.b64 d14, {t, h};\nand.b32 t, c15, 0xffe;\n"
        "mad.lo.u32 t, t, 4, 0x200000;\nmov.b64 d15, {t, h};\nwgmma.fence.sync.aligned;\n"
        "wgmma.mma_async.sync.aligned.m64n32k16.f32.bf16.bf16 {o0,o1,o2,o3,o4,o5,o6,o7,o8,o9,o10,o11,o12,o13,o14,o15}, {b0,b1,b2,b3}, d0, p0, 1, 1, 1;\n"
        "wgmma.mma_async.sync.aligned.m64n32k16.f32.bf16.bf16 {o16,o17,o18,o19,o20,o21,o22,o23,o24,o25,o26,o27,o28,o29,o30,o31}, {b0,b1,b2,b3}, d8, p0, 1, 1, 1;\n"
        "wgmma.mma_async.sync.aligned.m64n32k16.f32.bf16.bf16 {o0,o1,o2,o3,o4,o5,o6,o7,o8,o9,o10,o11,o12,o13,o14,o15}, {b4,b5,b6,b7}, d1, p1, 1, 1, 1;\n"
        "wgmma.mma_async.sync.aligned.m64n32k16.f32.bf16.bf16 {o16,o17,o18,o19,o20,o21,o22,o23,o24,o25,o26,o27,o28,o29,o30,o31}, {b4,b5,b6,b7}, d9, p1, 1, 1, 1;\n"
        "wgmma.mma_async.sync.aligned.m64n32k16.f32.bf16.bf16 {o0,o1,o2,o3,o4,o5,o6,o7,o8,o9,o10,o11,o12,o13,o14,o15}, {b8,b9,b10,b11}, d2, p1, 1, 1, 1;\n"
        "wgmma.mma_async.sync.aligned.m64n32k16.f32.bf16.bf16 {o16,o17,o18,o19,o20,o21,o22,o23,o24,o25,o26,o27,o28,o29,o30,o31}, {b8,b9,b10,b11}, d10, p1, 1, 1, 1;\n"
        "wgmma.mma_async.sync.aligned.m64n32k16.f32.bf16.bf16 {o0,o1,o2,o3,o4,o5,o6,o7,o8,o9,o10,o11,o12,o13,o14,o15}, {b12,b13,b14,b15}, d3, p1, 1, 1, 1;\n"
        "wgmma.mma_async.sync.aligned.m64n32k16.f32.bf16.bf16 {o16,o17,o18,o19,o20,o21,o22,o23,o24,o25,o26,o27,o28,o29,o30,o31}, {b12,b13,b14,b15}, d11, p1, 1, 1, 1;\n"
        "wgmma.mma_async.sync.aligned.m64n32k16.f32.bf16.bf16 {o0,o1,o2,o3,o4,o5,o6,o7,o8,o9,o10,o11,o12,o13,o14,o15}, {b16,b17,b18,b19}, d4, p1, 1, 1, 1;\n"
        "wgmma.mma_async.sync.aligned.m64n32k16.f32.bf16.bf16 {o16,o17,o18,o19,o20,o21,o22,o23,o24,o25,o26,o27,o28,o29,o30,o31}, {b16,b17,b18,b19}, d12, p1, 1, 1, 1;\n"
        "wgmma.mma_async.sync.aligned.m64n32k16.f32.bf16.bf16 {o0,o1,o2,o3,o4,o5,o6,o7,o8,o9,o10,o11,o12,o13,o14,o15}, {b20,b21,b22,b23}, d5, p1, 1, 1, 1;\n"
        "wgmma.mma_async.sync.aligned.m64n32k16.f32.bf16.bf16 {o16,o17,o18,o19,o20,o21,o22,o23,o24,o25,o26,o27,o28,o29,o30,o31}, {b20,b21,b22,b23}, d13, p1, 1, 1, 1;\n"
        "wgmma.mma_async.sync.aligned.m64n32k16.f32.bf16.bf16 {o0,o1,o2,o3,o4,o5,o6,o7,o8,o9,o10,o11,o12,o13,o14,o15}, {b24,b25,b26,b27}, d6, p1, 1, 1, 1;\n"
        "wgmma.mma_async.sync.aligned.m64n32k16.f32.bf16.bf16 {o16,o17,o18,o19,o20,o21,o22,o23,o24,o25,o26,o27,o28,o29,o30,o31}, {b24,b25,b26,b27}, d14, p1, 1, 1, 1;\n"
        "wgmma.mma_async.sync.aligned.m64n32k16.f32.bf16.bf16 {o0,o1,o2,o3,o4,o5,o6,o7,o8,o9,o10,o11,o12,o13,o14,o15}, {b28,b29,b30,b31}, d7, p1, 1, 1, 1;\n"
        "wgmma.mma_async.sync.aligned.m64n32k16.f32.bf16.bf16 {o16,o17,o18,o19,o20,o21,o22,o23,o24,o25,o26,o27,o28,o29,o30,o31}, {b28,b29,b30,b31}, d15, p1, 1, 1, 1;\n"
        "wgmma.commit_group.sync.aligned;\n@nv bra.uni END;\n@s0 st.global.v4.b32 [%65+128], {k0,k1,k2,k3};\n@s1 st.global.v4.b32 [%66+128], {k4,k5,k6,k7};\n"
        "@s0 st.global.v4.b32 [%65+192], {k8,k9,k10,k11};\n@s1 st.global.v4.b32 [%66+192], {k12,k13,k14,k15};\n@nv bra.uni END;\n"
        "wgmma.wait_group.sync.aligned 0;\ncvt.rn.bf16x2.f32 k0, o1, o0;\ncvt.rn.bf16x2.f32 k1, o5, o4;\ncvt.rn.bf16x2.f32 k2, o9, o8;\n"
        "cvt.rn.bf16x2.f32 k3, o13, o12;\ncvt.rn.bf16x2.f32 k4, o3, o2;\ncvt.rn.bf16x2.f32 k5, o7, o6;\ncvt.rn.bf16x2.f32 k6, o11, o10;\n"
        "cvt.rn.bf16x2.f32 k7, o15, o14;\ncvt.rn.bf16x2.f32 k8, o17, o16;\ncvt.rn.bf16x2.f32 k9, o21, o20;\ncvt.rn.bf16x2.f32 k10, o25, o24;\n"
        "cvt.rn.bf16x2.f32 k11, o29, o28;\ncvt.rn.bf16x2.f32 k12, o19, o18;\ncvt.rn.bf16x2.f32 k13, o23, o22;\ncvt.rn.bf16x2.f32 k14, o27, o26;\n"
        "cvt.rn.bf16x2.f32 k15, o31, o30;\nld.volatile.shared.v4.b32 {c0,c1,c2,c3}, [%64+32];\nld.volatile.shared.v4.b32 {c4,c5,c6,c7}, [%64+8224];\n"
        "ld.volatile.shared.v4.b32 {c8,c9,c10,c11}, [%64+48];\nld.volatile.shared.v4.b32 {c12,c13,c14,c15}, [%64+8240];\nand.b32 t, c0, 0xffe;\n"
        "mad.lo.u32 t, t, 4, 0x200000;\nmov.b64 d0, {t, h};\nand.b32 t, c1, 0xffe;\nmad.lo.u32 t, t, 4, 0x200000;\nmov.b64 d1, {t, h};\nand.b32 t, c2, 0xffe;\n"
        "mad.lo.u32 t, t, 4, 0x200000;\nmov.b64 d2, {t, h};\nand.b32 t, c3, 0xffe;\nmad.lo.u32 t, t, 4, 0x200000;\nmov.b64 d3, {t, h};\nand.b32 t, c4, 0xffe;\n"
        "mad.lo.u32 t, t, 4, 0x200000;\nmov.b64 d4, {t, h};\nand.b32 t, c5, 0xffe;\nmad.lo.u32 t, t, 4, 0x200000;\nmov.b64 d5, {t, h};\nand.b32 t, c6, 0xffe;\n"
        "mad.lo.u32 t, t, 4, 0x200000;\nmov.b64 d6, {t, h};\nand.b32 t, c7, 0xffe;\nmad.lo.u32 t, t, 4, 0x200000;\nmov.b64 d7, {t, h};\nand.b32 t, c8, 0xffe;\n"
        "mad.lo.u32 t, t, 4, 0x200000;\nmov.b64 d8, {t, h};\nand.b32 t, c9, 0xffe;\nmad.lo.u32 t, t, 4, 0x200000;\nmov.b64 d9, {t, h};\nand.b32 t, c10, 0xffe;\n"
        "mad.lo.u32 t, t, 4, 0x200000;\nmov.b64 d10, {t, h};\nand.b32 t, c11, 0xffe;\nmad.lo.u32 t, t, 4, 0x200000;\nmov.b64 d11, {t, h};\n"
        "and.b32 t, c12, 0xffe;\nmad.lo.u32 t, t, 4, 0x200000;\nmov.b64 d12, {t, h};\nand.b32 t, c13, 0xffe;\nmad.lo.u32 t, t, 4, 0x200000;\n"
        "mov.b64 d13, {t, h};\nand.b32 t, c14, 0xffe;\nmad.lo.u32 t, t, 4, 0x200000;\nmov.b64 d14, {t, h};\nand.b32 t, c15, 0xffe;\n"
        "mad.lo.u32 t, t, 4, 0x200000;\nmov.b64 d15, {t, h};\nwgmma.fence.sync.aligned;\n"
        "wgmma.mma_async.sync.aligned.m64n32k16.f32.bf16.bf16 {o0,o1,o2,o3,o4,o5,o6,o7,o8,o9,o10,o11,o12,o13,o14,o15}, {b0,b1,b2,b3}, d0, p0, 1, 1, 1;\n"
        "wgmma.mma_async.sync.aligned.m64n32k16.f32.bf16.bf16 {o16,o17,o18,o19,o20,o21,o22,o23,o24,o25,o26,o27,o28,o29,o30,o31}, {b0,b1,b2,b3}, d8, p0, 1, 1, 1;\n"
        "wgmma.mma_async.sync.aligned.m64n32k16.f32.bf16.bf16 {o0,o1,o2,o3,o4,o5,o6,o7,o8,o9,o10,o11,o12,o13,o14,o15}, {b4,b5,b6,b7}, d1, p1, 1, 1, 1;\n"
        "wgmma.mma_async.sync.aligned.m64n32k16.f32.bf16.bf16 {o16,o17,o18,o19,o20,o21,o22,o23,o24,o25,o26,o27,o28,o29,o30,o31}, {b4,b5,b6,b7}, d9, p1, 1, 1, 1;\n"
        "wgmma.mma_async.sync.aligned.m64n32k16.f32.bf16.bf16 {o0,o1,o2,o3,o4,o5,o6,o7,o8,o9,o10,o11,o12,o13,o14,o15}, {b8,b9,b10,b11}, d2, p1, 1, 1, 1;\n"
        "wgmma.mma_async.sync.aligned.m64n32k16.f32.bf16.bf16 {o16,o17,o18,o19,o20,o21,o22,o23,o24,o25,o26,o27,o28,o29,o30,o31}, {b8,b9,b10,b11}, d10, p1, 1, 1, 1;\n"
        "wgmma.mma_async.sync.aligned.m64n32k16.f32.bf16.bf16 {o0,o1,o2,o3,o4,o5,o6,o7,o8,o9,o10,o11,o12,o13,o14,o15}, {b12,b13,b14,b15}, d3, p1, 1, 1, 1;\n"
        "wgmma.mma_async.sync.aligned.m64n32k16.f32.bf16.bf16 {o16,o17,o18,o19,o20,o21,o22,o23,o24,o25,o26,o27,o28,o29,o30,o31}, {b12,b13,b14,b15}, d11, p1, 1, 1, 1;\n"
        "wgmma.mma_async.sync.aligned.m64n32k16.f32.bf16.bf16 {o0,o1,o2,o3,o4,o5,o6,o7,o8,o9,o10,o11,o12,o13,o14,o15}, {b16,b17,b18,b19}, d4, p1, 1, 1, 1;\n"
        "wgmma.mma_async.sync.aligned.m64n32k16.f32.bf16.bf16 {o16,o17,o18,o19,o20,o21,o22,o23,o24,o25,o26,o27,o28,o29,o30,o31}, {b16,b17,b18,b19}, d12, p1, 1, 1, 1;\n"
        "wgmma.mma_async.sync.aligned.m64n32k16.f32.bf16.bf16 {o0,o1,o2,o3,o4,o5,o6,o7,o8,o9,o10,o11,o12,o13,o14,o15}, {b20,b21,b22,b23}, d5, p1, 1, 1, 1;\n"
        "wgmma.mma_async.sync.aligned.m64n32k16.f32.bf16.bf16 {o16,o17,o18,o19,o20,o21,o22,o23,o24,o25,o26,o27,o28,o29,o30,o31}, {b20,b21,b22,b23}, d13, p1, 1, 1, 1;\n"
        "wgmma.mma_async.sync.aligned.m64n32k16.f32.bf16.bf16 {o0,o1,o2,o3,o4,o5,o6,o7,o8,o9,o10,o11,o12,o13,o14,o15}, {b24,b25,b26,b27}, d6, p1, 1, 1, 1;\n"
        "wgmma.mma_async.sync.aligned.m64n32k16.f32.bf16.bf16 {o16,o17,o18,o19,o20,o21,o22,o23,o24,o25,o26,o27,o28,o29,o30,o31}, {b24,b25,b26,b27}, d14, p1, 1, 1, 1;\n"
        "wgmma.mma_async.sync.aligned.m64n32k16.f32.bf16.bf16 {o0,o1,o2,o3,o4,o5,o6,o7,o8,o9,o10,o11,o12,o13,o14,o15}, {b28,b29,b30,b31}, d7, p1, 1, 1, 1;\n"
        "wgmma.mma_async.sync.aligned.m64n32k16.f32.bf16.bf16 {o16,o17,o18,o19,o20,o21,o22,o23,o24,o25,o26,o27,o28,o29,o30,o31}, {b28,b29,b30,b31}, d15, p1, 1, 1, 1;\n"
        "wgmma.commit_group.sync.aligned;\n@nv bra.uni END;\n@s2 st.global.v4.b32 [%67+0], {k0,k1,k2,k3};\n@s3 st.global.v4.b32 [%68+0], {k4,k5,k6,k7};\n"
        "@s2 st.global.v4.b32 [%67+64], {k8,k9,k10,k11};\n@s3 st.global.v4.b32 [%68+64], {k12,k13,k14,k15};\n@nv bra.uni END;\nwgmma.wait_group.sync.aligned 0;\n"
        "cvt.rn.bf16x2.f32 k0, o1, o0;\ncvt.rn.bf16x2.f32 k1, o5, o4;\ncvt.rn.bf16x2.f32 k2, o9, o8;\ncvt.rn.bf16x2.f32 k3, o13, o12;\n"
        "cvt.rn.bf16x2.f32 k4, o3, o2;\ncvt.rn.bf16x2.f32 k5, o7, o6;\ncvt.rn.bf16x2.f32 k6, o11, o10;\ncvt.rn.bf16x2.f32 k7, o15, o14;\n"
        "cvt.rn.bf16x2.f32 k8, o17, o16;\ncvt.rn.bf16x2.f32 k9, o21, o20;\ncvt.rn.bf16x2.f32 k10, o25, o24;\ncvt.rn.bf16x2.f32 k11, o29, o28;\n"
        "cvt.rn.bf16x2.f32 k12, o19, o18;\ncvt.rn.bf16x2.f32 k13, o23, o22;\ncvt.rn.bf16x2.f32 k14, o27, o26;\ncvt.rn.bf16x2.f32 k15, o31, o30;\n"
        "@s2 st.global.v4.b32 [%67+128], {k0,k1,k2,k3};\n@s3 st.global.v4.b32 [%68+128], {k4,k5,k6,k7};\n@s2 st.global.v4.b32 [%67+192], {k8,k9,k10,k11};\n"
        "@s3 st.global.v4.b32 [%68+192], {k12,k13,k14,k15};\n"
        "END:\n}\n"
        ::"r"(pk[0]), "r"(pk[1]), "r"(pk[2]), "r"(pk[3]), "r"(pk[4]), "r"(pk[5]), "r"(pk[6]), "r"(pk[7]), "r"(pk[8]), "r"(pk[9]), "r"(pk[10]),
          "r"(pk[11]), "r"(pk[12]), "r"(pk[13]), "r"(pk[14]), "r"(pk[15]), "r"(pk[16]), "r"(pk[17]), "r"(pk[18]), "r"(pk[19]), "r"(pk[20]),
          "r"(pk[21]), "r"(pk[22]), "r"(pk[23]), "r"(pk[24]), "r"(pk[25]), "r"(pk[26]), "r"(pk[27]), "r"(pk[28]), "r"(pk[29]), "r"(pk[30]),
          "r"(pk[31]), "r"(pk[32]), "r"(pk[33]), "r"(pk[34]), "r"(pk[35]), "r"(pk[36]), "r"(pk[37]), "r"(pk[38]), "r"(pk[39]), "r"(pk[40]),
          "r"(pk[41]), "r"(pk[42]), "r"(pk[43]), "r"(pk[44]), "r"(pk[45]), "r"(pk[46]), "r"(pk[47]), "r"(pk[48]), "r"(pk[49]), "r"(pk[50]),
          "r"(pk[51]), "r"(pk[52]), "r"(pk[53]), "r"(pk[54]), "r"(pk[55]), "r"(pk[56]), "r"(pk[57]), "r"(pk[58]), "r"(pk[59]), "r"(pk[60]),
          "r"(pk[61]), "r"(pk[62]), "r"(pk[63]), "r"(ra), "l"(p[0]), "l"(p[1]), "l"(p[2]), "l"(p[3]), "r"(v[0]), "r"(v[1]), "r"(v[2]), "r"(v[3]),
          "r"(ba)
        : "memory");
}
__device__ __forceinline__ void project3(const uint32_t (&pk)[48], uint32_t ra, uint32_t ba, uint4* const (&p)[3], const uint32_t (&v)[3]) {
    asm volatile(
        "{\n.reg .pred p0, p1, q0, q1, nv, s<4>;\n.reg .b32 t, h, c<16>, a<32>, b<32>, k<16>;\n.reg .b64 d<16>;\n.reg .f32 o<32>;\nsetp.ne.b32 p0, 0, 0;\n"
        "setp.eq.b32 p1, 0, 0;\nmov.b32 h, 8;\nsetp.eq.u32 nv, %48, 0;\nvote.sync.any.pred nv, nv, 0xffffffff;\nsetp.ne.b32 s0, %52, 0;\n"
        "setp.ne.b32 s1, %53, 0;\nsetp.ne.b32 s2, %54, 0;\nmovmatrix.sync.aligned.m8n8.trans.b16 a0, %0;\nmovmatrix.sync.aligned.m8n8.trans.b16 a1, %16;\n"
        "movmatrix.sync.aligned.m8n8.trans.b16 a2, %1;\nmovmatrix.sync.aligned.m8n8.trans.b16 a3, %17;\nmovmatrix.sync.aligned.m8n8.trans.b16 a4, %2;\n"
        "movmatrix.sync.aligned.m8n8.trans.b16 a5, %18;\nmovmatrix.sync.aligned.m8n8.trans.b16 a6, %3;\nmovmatrix.sync.aligned.m8n8.trans.b16 a7, %19;\n"
        "movmatrix.sync.aligned.m8n8.trans.b16 a8, %4;\nmovmatrix.sync.aligned.m8n8.trans.b16 a9, %20;\nmovmatrix.sync.aligned.m8n8.trans.b16 a10, %5;\n"
        "movmatrix.sync.aligned.m8n8.trans.b16 a11, %21;\nmovmatrix.sync.aligned.m8n8.trans.b16 a12, %6;\nmovmatrix.sync.aligned.m8n8.trans.b16 a13, %22;\n"
        "movmatrix.sync.aligned.m8n8.trans.b16 a14, %7;\nmovmatrix.sync.aligned.m8n8.trans.b16 a15, %23;\nmovmatrix.sync.aligned.m8n8.trans.b16 a16, %8;\n"
        "movmatrix.sync.aligned.m8n8.trans.b16 a17, %24;\nmovmatrix.sync.aligned.m8n8.trans.b16 a18, %9;\nmovmatrix.sync.aligned.m8n8.trans.b16 a19, %25;\n"
        "movmatrix.sync.aligned.m8n8.trans.b16 a20, %10;\nmovmatrix.sync.aligned.m8n8.trans.b16 a21, %26;\nmovmatrix.sync.aligned.m8n8.trans.b16 a22, %11;\n"
        "movmatrix.sync.aligned.m8n8.trans.b16 a23, %27;\nmovmatrix.sync.aligned.m8n8.trans.b16 a24, %12;\nmovmatrix.sync.aligned.m8n8.trans.b16 a25, %28;\n"
        "movmatrix.sync.aligned.m8n8.trans.b16 a26, %13;\nmovmatrix.sync.aligned.m8n8.trans.b16 a27, %29;\nmovmatrix.sync.aligned.m8n8.trans.b16 a28, %14;\n"
        "movmatrix.sync.aligned.m8n8.trans.b16 a29, %30;\nmovmatrix.sync.aligned.m8n8.trans.b16 a30, %15;\nmovmatrix.sync.aligned.m8n8.trans.b16 a31, %31;\n"
        "mov.b32 t, 0;\n"
        "W0:\nmbarrier.try_wait.parity.shared.b64 q0, [%55+0], 0;\nadd.u32 t, t, 1;\nsetp.lt.and.u32 q1, t, 1000000, !q0;\n@q1 bra.uni W0;\nmov.b32 t, 0;\n"
        "W1:\nmbarrier.try_wait.parity.shared.b64 q0, [%55+8], 0;\nadd.u32 t, t, 1;\nsetp.lt.and.u32 q1, t, 1000000, !q0;\n@q1 bra.uni W1;\nmov.b32 t, 0;\n"
        "W2:\nmbarrier.try_wait.parity.shared.b64 q0, [%55+16], 0;\nadd.u32 t, t, 1;\nsetp.lt.and.u32 q1, t, 1000000, !q0;\n@q1 bra.uni W2;\nmov.b32 t, 0;\n"
        "W3:\nmbarrier.try_wait.parity.shared.b64 q0, [%55+24], 0;\nadd.u32 t, t, 1;\nsetp.lt.and.u32 q1, t, 1000000, !q0;\n@q1 bra.uni W3;\n"
        "ld.volatile.shared.v4.b32 {c0,c1,c2,c3}, [%48+0];\nld.volatile.shared.v4.b32 {c4,c5,c6,c7}, [%48+8192];\n"
        "ld.volatile.shared.v4.b32 {c8,c9,c10,c11}, [%48+16];\nld.volatile.shared.v4.b32 {c12,c13,c14,c15}, [%48+8208];\nand.b32 t, c0, 0xffe;\n"
        "mad.lo.u32 t, t, 4, 0x200000;\nmov.b64 d0, {t, h};\nand.b32 t, c1, 0xffe;\nmad.lo.u32 t, t, 4, 0x200000;\nmov.b64 d1, {t, h};\nand.b32 t, c2, 0xffe;\n"
        "mad.lo.u32 t, t, 4, 0x200000;\nmov.b64 d2, {t, h};\nand.b32 t, c3, 0xffe;\nmad.lo.u32 t, t, 4, 0x200000;\nmov.b64 d3, {t, h};\nand.b32 t, c4, 0xffe;\n"
        "mad.lo.u32 t, t, 4, 0x200000;\nmov.b64 d4, {t, h};\nand.b32 t, c5, 0xffe;\nmad.lo.u32 t, t, 4, 0x200000;\nmov.b64 d5, {t, h};\nand.b32 t, c6, 0xffe;\n"
        "mad.lo.u32 t, t, 4, 0x200000;\nmov.b64 d6, {t, h};\nand.b32 t, c7, 0xffe;\nmad.lo.u32 t, t, 4, 0x200000;\nmov.b64 d7, {t, h};\nand.b32 t, c8, 0xffe;\n"
        "mad.lo.u32 t, t, 4, 0x200000;\nmov.b64 d8, {t, h};\nand.b32 t, c9, 0xffe;\nmad.lo.u32 t, t, 4, 0x200000;\nmov.b64 d9, {t, h};\nand.b32 t, c10, 0xffe;\n"
        "mad.lo.u32 t, t, 4, 0x200000;\nmov.b64 d10, {t, h};\nand.b32 t, c11, 0xffe;\nmad.lo.u32 t, t, 4, 0x200000;\nmov.b64 d11, {t, h};\n"
        "and.b32 t, c12, 0xffe;\nmad.lo.u32 t, t, 4, 0x200000;\nmov.b64 d12, {t, h};\nand.b32 t, c13, 0xffe;\nmad.lo.u32 t, t, 4, 0x200000;\n"
        "mov.b64 d13, {t, h};\nand.b32 t, c14, 0xffe;\nmad.lo.u32 t, t, 4, 0x200000;\nmov.b64 d14, {t, h};\nand.b32 t, c15, 0xffe;\n"
        "mad.lo.u32 t, t, 4, 0x200000;\nmov.b64 d15, {t, h};\nwgmma.fence.sync.aligned;\n"
        "wgmma.mma_async.sync.aligned.m64n32k16.f32.bf16.bf16 {o0,o1,o2,o3,o4,o5,o6,o7,o8,o9,o10,o11,o12,o13,o14,o15}, {a0,a1,a2,a3}, d0, p0, 1, 1, 1;\n"
        "wgmma.mma_async.sync.aligned.m64n32k16.f32.bf16.bf16 {o16,o17,o18,o19,o20,o21,o22,o23,o24,o25,o26,o27,o28,o29,o30,o31}, {a0,a1,a2,a3}, d8, p0, 1, 1, 1;\n"
        "wgmma.mma_async.sync.aligned.m64n32k16.f32.bf16.bf16 {o0,o1,o2,o3,o4,o5,o6,o7,o8,o9,o10,o11,o12,o13,o14,o15}, {a4,a5,a6,a7}, d1, p1, 1, 1, 1;\n"
        "wgmma.mma_async.sync.aligned.m64n32k16.f32.bf16.bf16 {o16,o17,o18,o19,o20,o21,o22,o23,o24,o25,o26,o27,o28,o29,o30,o31}, {a4,a5,a6,a7}, d9, p1, 1, 1, 1;\n"
        "wgmma.mma_async.sync.aligned.m64n32k16.f32.bf16.bf16 {o0,o1,o2,o3,o4,o5,o6,o7,o8,o9,o10,o11,o12,o13,o14,o15}, {a8,a9,a10,a11}, d2, p1, 1, 1, 1;\n"
        "wgmma.mma_async.sync.aligned.m64n32k16.f32.bf16.bf16 {o16,o17,o18,o19,o20,o21,o22,o23,o24,o25,o26,o27,o28,o29,o30,o31}, {a8,a9,a10,a11}, d10, p1, 1, 1, 1;\n"
        "wgmma.mma_async.sync.aligned.m64n32k16.f32.bf16.bf16 {o0,o1,o2,o3,o4,o5,o6,o7,o8,o9,o10,o11,o12,o13,o14,o15}, {a12,a13,a14,a15}, d3, p1, 1, 1, 1;\n"
        "wgmma.mma_async.sync.aligned.m64n32k16.f32.bf16.bf16 {o16,o17,o18,o19,o20,o21,o22,o23,o24,o25,o26,o27,o28,o29,o30,o31}, {a12,a13,a14,a15}, d11, p1, 1, 1, 1;\n"
        "wgmma.mma_async.sync.aligned.m64n32k16.f32.bf16.bf16 {o0,o1,o2,o3,o4,o5,o6,o7,o8,o9,o10,o11,o12,o13,o14,o15}, {a16,a17,a18,a19}, d4, p1, 1, 1, 1;\n"
        "wgmma.mma_async.sync.aligned.m64n32k16.f32.bf16.bf16 {o16,o17,o18,o19,o20,o21,o22,o23,o24,o25,o26,o27,o28,o29,o30,o31}, {a16,a17,a18,a19}, d12, p1, 1, 1, 1;\n"
        "wgmma.mma_async.sync.aligned.m64n32k16.f32.bf16.bf16 {o0,o1,o2,o3,o4,o5,o6,o7,o8,o9,o10,o11,o12,o13,o14,o15}, {a20,a21,a22,a23}, d5, p1, 1, 1, 1;\n"
        "wgmma.mma_async.sync.aligned.m64n32k16.f32.bf16.bf16 {o16,o17,o18,o19,o20,o21,o22,o23,o24,o25,o26,o27,o28,o29,o30,o31}, {a20,a21,a22,a23}, d13, p1, 1, 1, 1;\n"
        "wgmma.mma_async.sync.aligned.m64n32k16.f32.bf16.bf16 {o0,o1,o2,o3,o4,o5,o6,o7,o8,o9,o10,o11,o12,o13,o14,o15}, {a24,a25,a26,a27}, d6, p1, 1, 1, 1;\n"
        "wgmma.mma_async.sync.aligned.m64n32k16.f32.bf16.bf16 {o16,o17,o18,o19,o20,o21,o22,o23,o24,o25,o26,o27,o28,o29,o30,o31}, {a24,a25,a26,a27}, d14, p1, 1, 1, 1;\n"
        "wgmma.mma_async.sync.aligned.m64n32k16.f32.bf16.bf16 {o0,o1,o2,o3,o4,o5,o6,o7,o8,o9,o10,o11,o12,o13,o14,o15}, {a28,a29,a30,a31}, d7, p1, 1, 1, 1;\n"
        "wgmma.mma_async.sync.aligned.m64n32k16.f32.bf16.bf16 {o16,o17,o18,o19,o20,o21,o22,o23,o24,o25,o26,o27,o28,o29,o30,o31}, {a28,a29,a30,a31}, d15, p1, 1, 1, 1;\n"
        "wgmma.commit_group.sync.aligned;\n@nv bra.uni END;\n@nv bra.uni END;\nwgmma.wait_group.sync.aligned 0;\ncvt.rn.bf16x2.f32 k0, o1, o0;\n"
        "cvt.rn.bf16x2.f32 k1, o5, o4;\ncvt.rn.bf16x2.f32 k2, o9, o8;\ncvt.rn.bf16x2.f32 k3, o13, o12;\ncvt.rn.bf16x2.f32 k4, o3, o2;\n"
        "cvt.rn.bf16x2.f32 k5, o7, o6;\ncvt.rn.bf16x2.f32 k6, o11, o10;\ncvt.rn.bf16x2.f32 k7, o15, o14;\ncvt.rn.bf16x2.f32 k8, o17, o16;\n"
        "cvt.rn.bf16x2.f32 k9, o21, o20;\ncvt.rn.bf16x2.f32 k10, o25, o24;\ncvt.rn.bf16x2.f32 k11, o29, o28;\ncvt.rn.bf16x2.f32 k12, o19, o18;\n"
        "cvt.rn.bf16x2.f32 k13, o23, o22;\ncvt.rn.bf16x2.f32 k14, o27, o26;\ncvt.rn.bf16x2.f32 k15, o31, o30;\n@s0 st.global.v4.b32 [%49+0], {k0,k1,k2,k3};\n"
        "@s1 st.global.v4.b32 [%50+0], {k4,k5,k6,k7};\n@s0 st.global.v4.b32 [%49+64], {k8,k9,k10,k11};\n@s1 st.global.v4.b32 [%50+64], {k12,k13,k14,k15};\n"
        "@nv bra.uni END;\nld.volatile.shared.v4.b32 {c0,c1,c2,c3}, [%48+32];\nld.volatile.shared.v4.b32 {c4,c5,c6,c7}, [%48+8224];\n"
        "ld.volatile.shared.v4.b32 {c8,c9,c10,c11}, [%48+48];\nld.volatile.shared.v4.b32 {c12,c13,c14,c15}, [%48+8240];\nand.b32 t, c0, 0xffe;\n"
        "mad.lo.u32 t, t, 4, 0x200000;\nmov.b64 d0, {t, h};\nand.b32 t, c1, 0xffe;\nmad.lo.u32 t, t, 4, 0x200000;\nmov.b64 d1, {t, h};\nand.b32 t, c2, 0xffe;\n"
        "mad.lo.u32 t, t, 4, 0x200000;\nmov.b64 d2, {t, h};\nand.b32 t, c3, 0xffe;\nmad.lo.u32 t, t, 4, 0x200000;\nmov.b64 d3, {t, h};\nand.b32 t, c4, 0xffe;\n"
        "mad.lo.u32 t, t, 4, 0x200000;\nmov.b64 d4, {t, h};\nand.b32 t, c5, 0xffe;\nmad.lo.u32 t, t, 4, 0x200000;\nmov.b64 d5, {t, h};\nand.b32 t, c6, 0xffe;\n"
        "mad.lo.u32 t, t, 4, 0x200000;\nmov.b64 d6, {t, h};\nand.b32 t, c7, 0xffe;\nmad.lo.u32 t, t, 4, 0x200000;\nmov.b64 d7, {t, h};\nand.b32 t, c8, 0xffe;\n"
        "mad.lo.u32 t, t, 4, 0x200000;\nmov.b64 d8, {t, h};\nand.b32 t, c9, 0xffe;\nmad.lo.u32 t, t, 4, 0x200000;\nmov.b64 d9, {t, h};\nand.b32 t, c10, 0xffe;\n"
        "mad.lo.u32 t, t, 4, 0x200000;\nmov.b64 d10, {t, h};\nand.b32 t, c11, 0xffe;\nmad.lo.u32 t, t, 4, 0x200000;\nmov.b64 d11, {t, h};\n"
        "and.b32 t, c12, 0xffe;\nmad.lo.u32 t, t, 4, 0x200000;\nmov.b64 d12, {t, h};\nand.b32 t, c13, 0xffe;\nmad.lo.u32 t, t, 4, 0x200000;\n"
        "mov.b64 d13, {t, h};\nand.b32 t, c14, 0xffe;\nmad.lo.u32 t, t, 4, 0x200000;\nmov.b64 d14, {t, h};\nand.b32 t, c15, 0xffe;\n"
        "mad.lo.u32 t, t, 4, 0x200000;\nmov.b64 d15, {t, h};\nwgmma.fence.sync.aligned;\n"
        "wgmma.mma_async.sync.aligned.m64n32k16.f32.bf16.bf16 {o0,o1,o2,o3,o4,o5,o6,o7,o8,o9,o10,o11,o12,o13,o14,o15}, {a0,a1,a2,a3}, d0, p0, 1, 1, 1;\n"
        "wgmma.mma_async.sync.aligned.m64n32k16.f32.bf16.bf16 {o16,o17,o18,o19,o20,o21,o22,o23,o24,o25,o26,o27,o28,o29,o30,o31}, {a0,a1,a2,a3}, d8, p0, 1, 1, 1;\n"
        "wgmma.mma_async.sync.aligned.m64n32k16.f32.bf16.bf16 {o0,o1,o2,o3,o4,o5,o6,o7,o8,o9,o10,o11,o12,o13,o14,o15}, {a4,a5,a6,a7}, d1, p1, 1, 1, 1;\n"
        "wgmma.mma_async.sync.aligned.m64n32k16.f32.bf16.bf16 {o16,o17,o18,o19,o20,o21,o22,o23,o24,o25,o26,o27,o28,o29,o30,o31}, {a4,a5,a6,a7}, d9, p1, 1, 1, 1;\n"
        "wgmma.mma_async.sync.aligned.m64n32k16.f32.bf16.bf16 {o0,o1,o2,o3,o4,o5,o6,o7,o8,o9,o10,o11,o12,o13,o14,o15}, {a8,a9,a10,a11}, d2, p1, 1, 1, 1;\n"
        "wgmma.mma_async.sync.aligned.m64n32k16.f32.bf16.bf16 {o16,o17,o18,o19,o20,o21,o22,o23,o24,o25,o26,o27,o28,o29,o30,o31}, {a8,a9,a10,a11}, d10, p1, 1, 1, 1;\n"
        "wgmma.mma_async.sync.aligned.m64n32k16.f32.bf16.bf16 {o0,o1,o2,o3,o4,o5,o6,o7,o8,o9,o10,o11,o12,o13,o14,o15}, {a12,a13,a14,a15}, d3, p1, 1, 1, 1;\n"
        "wgmma.mma_async.sync.aligned.m64n32k16.f32.bf16.bf16 {o16,o17,o18,o19,o20,o21,o22,o23,o24,o25,o26,o27,o28,o29,o30,o31}, {a12,a13,a14,a15}, d11, p1, 1, 1, 1;\n"
        "wgmma.mma_async.sync.aligned.m64n32k16.f32.bf16.bf16 {o0,o1,o2,o3,o4,o5,o6,o7,o8,o9,o10,o11,o12,o13,o14,o15}, {a16,a17,a18,a19}, d4, p1, 1, 1, 1;\n"
        "wgmma.mma_async.sync.aligned.m64n32k16.f32.bf16.bf16 {o16,o17,o18,o19,o20,o21,o22,o23,o24,o25,o26,o27,o28,o29,o30,o31}, {a16,a17,a18,a19}, d12, p1, 1, 1, 1;\n"
        "wgmma.mma_async.sync.aligned.m64n32k16.f32.bf16.bf16 {o0,o1,o2,o3,o4,o5,o6,o7,o8,o9,o10,o11,o12,o13,o14,o15}, {a20,a21,a22,a23}, d5, p1, 1, 1, 1;\n"
        "wgmma.mma_async.sync.aligned.m64n32k16.f32.bf16.bf16 {o16,o17,o18,o19,o20,o21,o22,o23,o24,o25,o26,o27,o28,o29,o30,o31}, {a20,a21,a22,a23}, d13, p1, 1, 1, 1;\n"
        "wgmma.mma_async.sync.aligned.m64n32k16.f32.bf16.bf16 {o0,o1,o2,o3,o4,o5,o6,o7,o8,o9,o10,o11,o12,o13,o14,o15}, {a24,a25,a26,a27}, d6, p1, 1, 1, 1;\n"
        "wgmma.mma_async.sync.aligned.m64n32k16.f32.bf16.bf16 {o16,o17,o18,o19,o20,o21,o22,o23,o24,o25,o26,o27,o28,o29,o30,o31}, {a24,a25,a26,a27}, d14, p1, 1, 1, 1;\n"
        "wgmma.mma_async.sync.aligned.m64n32k16.f32.bf16.bf16 {o0,o1,o2,o3,o4,o5,o6,o7,o8,o9,o10,o11,o12,o13,o14,o15}, {a28,a29,a30,a31}, d7, p1, 1, 1, 1;\n"
        "wgmma.mma_async.sync.aligned.m64n32k16.f32.bf16.bf16 {o16,o17,o18,o19,o20,o21,o22,o23,o24,o25,o26,o27,o28,o29,o30,o31}, {a28,a29,a30,a31}, d15, p1, 1, 1, 1;\n"
        "wgmma.commit_group.sync.aligned;\n@nv bra.uni END;\nmovmatrix.sync.aligned.m8n8.trans.b16 b0, %32;\nmovmatrix.sync.aligned.m8n8.trans.b16 b1, %32;\n"
        "movmatrix.sync.aligned.m8n8.trans.b16 b2, %33;\nmovmatrix.sync.aligned.m8n8.trans.b16 b3, %33;\nmovmatrix.sync.aligned.m8n8.trans.b16 b4, %34;\n"
        "movmatrix.sync.aligned.m8n8.trans.b16 b5, %34;\nmovmatrix.sync.aligned.m8n8.trans.b16 b6, %35;\nmovmatrix.sync.aligned.m8n8.trans.b16 b7, %35;\n"
        "movmatrix.sync.aligned.m8n8.trans.b16 b8, %36;\nmovmatrix.sync.aligned.m8n8.trans.b16 b9, %36;\nmovmatrix.sync.aligned.m8n8.trans.b16 b10, %37;\n"
        "movmatrix.sync.aligned.m8n8.trans.b16 b11, %37;\nmovmatrix.sync.aligned.m8n8.trans.b16 b12, %38;\nmovmatrix.sync.aligned.m8n8.trans.b16 b13, %38;\n"
        "movmatrix.sync.aligned.m8n8.trans.b16 b14, %39;\nmovmatrix.sync.aligned.m8n8.trans.b16 b15, %39;\nmovmatrix.sync.aligned.m8n8.trans.b16 b16, %40;\n"
        "movmatrix.sync.aligned.m8n8.trans.b16 b17, %40;\nmovmatrix.sync.aligned.m8n8.trans.b16 b18, %41;\nmovmatrix.sync.aligned.m8n8.trans.b16 b19, %41;\n"
        "movmatrix.sync.aligned.m8n8.trans.b16 b20, %42;\nmovmatrix.sync.aligned.m8n8.trans.b16 b21, %42;\nmovmatrix.sync.aligned.m8n8.trans.b16 b22, %43;\n"
        "movmatrix.sync.aligned.m8n8.trans.b16 b23, %43;\nmovmatrix.sync.aligned.m8n8.trans.b16 b24, %44;\nmovmatrix.sync.aligned.m8n8.trans.b16 b25, %44;\n"
        "movmatrix.sync.aligned.m8n8.trans.b16 b26, %45;\nmovmatrix.sync.aligned.m8n8.trans.b16 b27, %45;\nmovmatrix.sync.aligned.m8n8.trans.b16 b28, %46;\n"
        "movmatrix.sync.aligned.m8n8.trans.b16 b29, %46;\nmovmatrix.sync.aligned.m8n8.trans.b16 b30, %47;\nmovmatrix.sync.aligned.m8n8.trans.b16 b31, %47;\n"
        "@nv bra.uni END;\nwgmma.wait_group.sync.aligned 0;\ncvt.rn.bf16x2.f32 k0, o1, o0;\ncvt.rn.bf16x2.f32 k1, o5, o4;\ncvt.rn.bf16x2.f32 k2, o9, o8;\n"
        "cvt.rn.bf16x2.f32 k3, o13, o12;\ncvt.rn.bf16x2.f32 k4, o3, o2;\ncvt.rn.bf16x2.f32 k5, o7, o6;\ncvt.rn.bf16x2.f32 k6, o11, o10;\n"
        "cvt.rn.bf16x2.f32 k7, o15, o14;\ncvt.rn.bf16x2.f32 k8, o17, o16;\ncvt.rn.bf16x2.f32 k9, o21, o20;\ncvt.rn.bf16x2.f32 k10, o25, o24;\n"
        "cvt.rn.bf16x2.f32 k11, o29, o28;\ncvt.rn.bf16x2.f32 k12, o19, o18;\ncvt.rn.bf16x2.f32 k13, o23, o22;\ncvt.rn.bf16x2.f32 k14, o27, o26;\n"
        "cvt.rn.bf16x2.f32 k15, o31, o30;\nld.volatile.shared.v4.b32 {c0,c1,c2,c3}, [%48+0];\nld.volatile.shared.v4.b32 {c4,c5,c6,c7}, [%48+8192];\n"
        "ld.volatile.shared.v4.b32 {c8,c9,c10,c11}, [%48+16];\nld.volatile.shared.v4.b32 {c12,c13,c14,c15}, [%48+8208];\nand.b32 t, c0, 0xffe;\n"
        "mad.lo.u32 t, t, 4, 0x200000;\nmov.b64 d0, {t, h};\nand.b32 t, c1, 0xffe;\nmad.lo.u32 t, t, 4, 0x200000;\nmov.b64 d1, {t, h};\nand.b32 t, c2, 0xffe;\n"
        "mad.lo.u32 t, t, 4, 0x200000;\nmov.b64 d2, {t, h};\nand.b32 t, c3, 0xffe;\nmad.lo.u32 t, t, 4, 0x200000;\nmov.b64 d3, {t, h};\nand.b32 t, c4, 0xffe;\n"
        "mad.lo.u32 t, t, 4, 0x200000;\nmov.b64 d4, {t, h};\nand.b32 t, c5, 0xffe;\nmad.lo.u32 t, t, 4, 0x200000;\nmov.b64 d5, {t, h};\nand.b32 t, c6, 0xffe;\n"
        "mad.lo.u32 t, t, 4, 0x200000;\nmov.b64 d6, {t, h};\nand.b32 t, c7, 0xffe;\nmad.lo.u32 t, t, 4, 0x200000;\nmov.b64 d7, {t, h};\nand.b32 t, c8, 0xffe;\n"
        "mad.lo.u32 t, t, 4, 0x200000;\nmov.b64 d8, {t, h};\nand.b32 t, c9, 0xffe;\nmad.lo.u32 t, t, 4, 0x200000;\nmov.b64 d9, {t, h};\nand.b32 t, c10, 0xffe;\n"
        "mad.lo.u32 t, t, 4, 0x200000;\nmov.b64 d10, {t, h};\nand.b32 t, c11, 0xffe;\nmad.lo.u32 t, t, 4, 0x200000;\nmov.b64 d11, {t, h};\n"
        "and.b32 t, c12, 0xffe;\nmad.lo.u32 t, t, 4, 0x200000;\nmov.b64 d12, {t, h};\nand.b32 t, c13, 0xffe;\nmad.lo.u32 t, t, 4, 0x200000;\n"
        "mov.b64 d13, {t, h};\nand.b32 t, c14, 0xffe;\nmad.lo.u32 t, t, 4, 0x200000;\nmov.b64 d14, {t, h};\nand.b32 t, c15, 0xffe;\n"
        "mad.lo.u32 t, t, 4, 0x200000;\nmov.b64 d15, {t, h};\nwgmma.fence.sync.aligned;\n"
        "wgmma.mma_async.sync.aligned.m64n32k16.f32.bf16.bf16 {o0,o1,o2,o3,o4,o5,o6,o7,o8,o9,o10,o11,o12,o13,o14,o15}, {b0,b1,b2,b3}, d0, p0, 1, 1, 1;\n"
        "wgmma.mma_async.sync.aligned.m64n32k16.f32.bf16.bf16 {o16,o17,o18,o19,o20,o21,o22,o23,o24,o25,o26,o27,o28,o29,o30,o31}, {b0,b1,b2,b3}, d8, p0, 1, 1, 1;\n"
        "wgmma.mma_async.sync.aligned.m64n32k16.f32.bf16.bf16 {o0,o1,o2,o3,o4,o5,o6,o7,o8,o9,o10,o11,o12,o13,o14,o15}, {b4,b5,b6,b7}, d1, p1, 1, 1, 1;\n"
        "wgmma.mma_async.sync.aligned.m64n32k16.f32.bf16.bf16 {o16,o17,o18,o19,o20,o21,o22,o23,o24,o25,o26,o27,o28,o29,o30,o31}, {b4,b5,b6,b7}, d9, p1, 1, 1, 1;\n"
        "wgmma.mma_async.sync.aligned.m64n32k16.f32.bf16.bf16 {o0,o1,o2,o3,o4,o5,o6,o7,o8,o9,o10,o11,o12,o13,o14,o15}, {b8,b9,b10,b11}, d2, p1, 1, 1, 1;\n"
        "wgmma.mma_async.sync.aligned.m64n32k16.f32.bf16.bf16 {o16,o17,o18,o19,o20,o21,o22,o23,o24,o25,o26,o27,o28,o29,o30,o31}, {b8,b9,b10,b11}, d10, p1, 1, 1, 1;\n"
        "wgmma.mma_async.sync.aligned.m64n32k16.f32.bf16.bf16 {o0,o1,o2,o3,o4,o5,o6,o7,o8,o9,o10,o11,o12,o13,o14,o15}, {b12,b13,b14,b15}, d3, p1, 1, 1, 1;\n"
        "wgmma.mma_async.sync.aligned.m64n32k16.f32.bf16.bf16 {o16,o17,o18,o19,o20,o21,o22,o23,o24,o25,o26,o27,o28,o29,o30,o31}, {b12,b13,b14,b15}, d11, p1, 1, 1, 1;\n"
        "wgmma.mma_async.sync.aligned.m64n32k16.f32.bf16.bf16 {o0,o1,o2,o3,o4,o5,o6,o7,o8,o9,o10,o11,o12,o13,o14,o15}, {b16,b17,b18,b19}, d4, p1, 1, 1, 1;\n"
        "wgmma.mma_async.sync.aligned.m64n32k16.f32.bf16.bf16 {o16,o17,o18,o19,o20,o21,o22,o23,o24,o25,o26,o27,o28,o29,o30,o31}, {b16,b17,b18,b19}, d12, p1, 1, 1, 1;\n"
        "wgmma.mma_async.sync.aligned.m64n32k16.f32.bf16.bf16 {o0,o1,o2,o3,o4,o5,o6,o7,o8,o9,o10,o11,o12,o13,o14,o15}, {b20,b21,b22,b23}, d5, p1, 1, 1, 1;\n"
        "wgmma.mma_async.sync.aligned.m64n32k16.f32.bf16.bf16 {o16,o17,o18,o19,o20,o21,o22,o23,o24,o25,o26,o27,o28,o29,o30,o31}, {b20,b21,b22,b23}, d13, p1, 1, 1, 1;\n"
        "wgmma.mma_async.sync.aligned.m64n32k16.f32.bf16.bf16 {o0,o1,o2,o3,o4,o5,o6,o7,o8,o9,o10,o11,o12,o13,o14,o15}, {b24,b25,b26,b27}, d6, p1, 1, 1, 1;\n"
        "wgmma.mma_async.sync.aligned.m64n32k16.f32.bf16.bf16 {o16,o17,o18,o19,o20,o21,o22,o23,o24,o25,o26,o27,o28,o29,o30,o31}, {b24,b25,b26,b27}, d14, p1, 1, 1, 1;\n"
        "wgmma.mma_async.sync.aligned.m64n32k16.f32.bf16.bf16 {o0,o1,o2,o3,o4,o5,o6,o7,o8,o9,o10,o11,o12,o13,o14,o15}, {b28,b29,b30,b31}, d7, p1, 1, 1, 1;\n"
        "wgmma.mma_async.sync.aligned.m64n32k16.f32.bf16.bf16 {o16,o17,o18,o19,o20,o21,o22,o23,o24,o25,o26,o27,o28,o29,o30,o31}, {b28,b29,b30,b31}, d15, p1, 1, 1, 1;\n"
        "wgmma.commit_group.sync.aligned;\n@nv bra.uni END;\n@s0 st.global.v4.b32 [%49+128], {k0,k1,k2,k3};\n@s1 st.global.v4.b32 [%50+128], {k4,k5,k6,k7};\n"
        "@s0 st.global.v4.b32 [%49+192], {k8,k9,k10,k11};\n@s1 st.global.v4.b32 [%50+192], {k12,k13,k14,k15};\n@nv bra.uni END;\n"
        "wgmma.wait_group.sync.aligned 0;\ncvt.rn.bf16x2.f32 k0, o1, o0;\ncvt.rn.bf16x2.f32 k1, o5, o4;\ncvt.rn.bf16x2.f32 k2, o9, o8;\n"
        "cvt.rn.bf16x2.f32 k3, o13, o12;\ncvt.rn.bf16x2.f32 k8, o17, o16;\ncvt.rn.bf16x2.f32 k9, o21, o20;\ncvt.rn.bf16x2.f32 k10, o25, o24;\n"
        "cvt.rn.bf16x2.f32 k11, o29, o28;\nld.volatile.shared.v4.b32 {c0,c1,c2,c3}, [%48+32];\nld.volatile.shared.v4.b32 {c4,c5,c6,c7}, [%48+8224];\n"
        "ld.volatile.shared.v4.b32 {c8,c9,c10,c11}, [%48+48];\nld.volatile.shared.v4.b32 {c12,c13,c14,c15}, [%48+8240];\nand.b32 t, c0, 0xffe;\n"
        "mad.lo.u32 t, t, 4, 0x200000;\nmov.b64 d0, {t, h};\nand.b32 t, c1, 0xffe;\nmad.lo.u32 t, t, 4, 0x200000;\nmov.b64 d1, {t, h};\nand.b32 t, c2, 0xffe;\n"
        "mad.lo.u32 t, t, 4, 0x200000;\nmov.b64 d2, {t, h};\nand.b32 t, c3, 0xffe;\nmad.lo.u32 t, t, 4, 0x200000;\nmov.b64 d3, {t, h};\nand.b32 t, c4, 0xffe;\n"
        "mad.lo.u32 t, t, 4, 0x200000;\nmov.b64 d4, {t, h};\nand.b32 t, c5, 0xffe;\nmad.lo.u32 t, t, 4, 0x200000;\nmov.b64 d5, {t, h};\nand.b32 t, c6, 0xffe;\n"
        "mad.lo.u32 t, t, 4, 0x200000;\nmov.b64 d6, {t, h};\nand.b32 t, c7, 0xffe;\nmad.lo.u32 t, t, 4, 0x200000;\nmov.b64 d7, {t, h};\nand.b32 t, c8, 0xffe;\n"
        "mad.lo.u32 t, t, 4, 0x200000;\nmov.b64 d8, {t, h};\nand.b32 t, c9, 0xffe;\nmad.lo.u32 t, t, 4, 0x200000;\nmov.b64 d9, {t, h};\nand.b32 t, c10, 0xffe;\n"
        "mad.lo.u32 t, t, 4, 0x200000;\nmov.b64 d10, {t, h};\nand.b32 t, c11, 0xffe;\nmad.lo.u32 t, t, 4, 0x200000;\nmov.b64 d11, {t, h};\n"
        "and.b32 t, c12, 0xffe;\nmad.lo.u32 t, t, 4, 0x200000;\nmov.b64 d12, {t, h};\nand.b32 t, c13, 0xffe;\nmad.lo.u32 t, t, 4, 0x200000;\n"
        "mov.b64 d13, {t, h};\nand.b32 t, c14, 0xffe;\nmad.lo.u32 t, t, 4, 0x200000;\nmov.b64 d14, {t, h};\nand.b32 t, c15, 0xffe;\n"
        "mad.lo.u32 t, t, 4, 0x200000;\nmov.b64 d15, {t, h};\nwgmma.fence.sync.aligned;\n"
        "wgmma.mma_async.sync.aligned.m64n32k16.f32.bf16.bf16 {o0,o1,o2,o3,o4,o5,o6,o7,o8,o9,o10,o11,o12,o13,o14,o15}, {b0,b1,b2,b3}, d0, p0, 1, 1, 1;\n"
        "wgmma.mma_async.sync.aligned.m64n32k16.f32.bf16.bf16 {o16,o17,o18,o19,o20,o21,o22,o23,o24,o25,o26,o27,o28,o29,o30,o31}, {b0,b1,b2,b3}, d8, p0, 1, 1, 1;\n"
        "wgmma.mma_async.sync.aligned.m64n32k16.f32.bf16.bf16 {o0,o1,o2,o3,o4,o5,o6,o7,o8,o9,o10,o11,o12,o13,o14,o15}, {b4,b5,b6,b7}, d1, p1, 1, 1, 1;\n"
        "wgmma.mma_async.sync.aligned.m64n32k16.f32.bf16.bf16 {o16,o17,o18,o19,o20,o21,o22,o23,o24,o25,o26,o27,o28,o29,o30,o31}, {b4,b5,b6,b7}, d9, p1, 1, 1, 1;\n"
        "wgmma.mma_async.sync.aligned.m64n32k16.f32.bf16.bf16 {o0,o1,o2,o3,o4,o5,o6,o7,o8,o9,o10,o11,o12,o13,o14,o15}, {b8,b9,b10,b11}, d2, p1, 1, 1, 1;\n"
        "wgmma.mma_async.sync.aligned.m64n32k16.f32.bf16.bf16 {o16,o17,o18,o19,o20,o21,o22,o23,o24,o25,o26,o27,o28,o29,o30,o31}, {b8,b9,b10,b11}, d10, p1, 1, 1, 1;\n"
        "wgmma.mma_async.sync.aligned.m64n32k16.f32.bf16.bf16 {o0,o1,o2,o3,o4,o5,o6,o7,o8,o9,o10,o11,o12,o13,o14,o15}, {b12,b13,b14,b15}, d3, p1, 1, 1, 1;\n"
        "wgmma.mma_async.sync.aligned.m64n32k16.f32.bf16.bf16 {o16,o17,o18,o19,o20,o21,o22,o23,o24,o25,o26,o27,o28,o29,o30,o31}, {b12,b13,b14,b15}, d11, p1, 1, 1, 1;\n"
        "wgmma.mma_async.sync.aligned.m64n32k16.f32.bf16.bf16 {o0,o1,o2,o3,o4,o5,o6,o7,o8,o9,o10,o11,o12,o13,o14,o15}, {b16,b17,b18,b19}, d4, p1, 1, 1, 1;\n"
        "wgmma.mma_async.sync.aligned.m64n32k16.f32.bf16.bf16 {o16,o17,o18,o19,o20,o21,o22,o23,o24,o25,o26,o27,o28,o29,o30,o31}, {b16,b17,b18,b19}, d12, p1, 1, 1, 1;\n"
        "wgmma.mma_async.sync.aligned.m64n32k16.f32.bf16.bf16 {o0,o1,o2,o3,o4,o5,o6,o7,o8,o9,o10,o11,o12,o13,o14,o15}, {b20,b21,b22,b23}, d5, p1, 1, 1, 1;\n"
        "wgmma.mma_async.sync.aligned.m64n32k16.f32.bf16.bf16 {o16,o17,o18,o19,o20,o21,o22,o23,o24,o25,o26,o27,o28,o29,o30,o31}, {b20,b21,b22,b23}, d13, p1, 1, 1, 1;\n"
        "wgmma.mma_async.sync.aligned.m64n32k16.f32.bf16.bf16 {o0,o1,o2,o3,o4,o5,o6,o7,o8,o9,o10,o11,o12,o13,o14,o15}, {b24,b25,b26,b27}, d6, p1, 1, 1, 1;\n"
        "wgmma.mma_async.sync.aligned.m64n32k16.f32.bf16.bf16 {o16,o17,o18,o19,o20,o21,o22,o23,o24,o25,o26,o27,o28,o29,o30,o31}, {b24,b25,b26,b27}, d14, p1, 1, 1, 1;\n"
        "wgmma.mma_async.sync.aligned.m64n32k16.f32.bf16.bf16 {o0,o1,o2,o3,o4,o5,o6,o7,o8,o9,o10,o11,o12,o13,o14,o15}, {b28,b29,b30,b31}, d7, p1, 1, 1, 1;\n"
        "wgmma.mma_async.sync.aligned.m64n32k16.f32.bf16.bf16 {o16,o17,o18,o19,o20,o21,o22,o23,o24,o25,o26,o27,o28,o29,o30,o31}, {b28,b29,b30,b31}, d15, p1, 1, 1, 1;\n"
        "wgmma.commit_group.sync.aligned;\n@nv bra.uni END;\n@s2 st.global.v4.b32 [%51+0], {k0,k1,k2,k3};\n@s2 st.global.v4.b32 [%51+64], {k8,k9,k10,k11};\n"
        "@nv bra.uni END;\nwgmma.wait_group.sync.aligned 0;\ncvt.rn.bf16x2.f32 k0, o1, o0;\ncvt.rn.bf16x2.f32 k1, o5, o4;\ncvt.rn.bf16x2.f32 k2, o9, o8;\n"
        "cvt.rn.bf16x2.f32 k3, o13, o12;\ncvt.rn.bf16x2.f32 k8, o17, o16;\ncvt.rn.bf16x2.f32 k9, o21, o20;\ncvt.rn.bf16x2.f32 k10, o25, o24;\n"
        "cvt.rn.bf16x2.f32 k11, o29, o28;\n@s2 st.global.v4.b32 [%51+128], {k0,k1,k2,k3};\n@s2 st.global.v4.b32 [%51+192], {k8,k9,k10,k11};\n"
        "END:\n}\n"
        ::"r"(pk[0]), "r"(pk[1]), "r"(pk[2]), "r"(pk[3]), "r"(pk[4]), "r"(pk[5]), "r"(pk[6]), "r"(pk[7]), "r"(pk[8]), "r"(pk[9]), "r"(pk[10]),
          "r"(pk[11]), "r"(pk[12]), "r"(pk[13]), "r"(pk[14]), "r"(pk[15]), "r"(pk[16]), "r"(pk[17]), "r"(pk[18]), "r"(pk[19]), "r"(pk[20]),
          "r"(pk[21]), "r"(pk[22]), "r"(pk[23]), "r"(pk[24]), "r"(pk[25]), "r"(pk[26]), "r"(pk[27]), "r"(pk[28]), "r"(pk[29]), "r"(pk[30]),
          "r"(pk[31]), "r"(pk[32]), "r"(pk[33]), "r"(pk[34]), "r"(pk[35]), "r"(pk[36]), "r"(pk[37]), "r"(pk[38]), "r"(pk[39]), "r"(pk[40]),
          "r"(pk[41]), "r"(pk[42]), "r"(pk[43]), "r"(pk[44]), "r"(pk[45]), "r"(pk[46]), "r"(pk[47]), "r"(ra), "l"(p[0]), "l"(p[1]), "l"(p[2]),
          "r"(v[0]), "r"(v[1]), "r"(v[2]), "r"(ba)
        : "memory");
}
__device__ __forceinline__ int cta_id() {
    int v;
    asm volatile("mov.u32 %0, %ctaid.x;" : "=r"(v));
    return v;
}
__device__ __forceinline__ int thread_id() {
    int v;
    asm volatile("mov.u32 %0, %tid.x;" : "=r"(v));
    return v;
}

__device__ __forceinline__ void slow_edge(int ee, int s, float* accn, const __nv_bfloat16* __restrict__ x,
                                          const __nv_bfloat16* __restrict__ sh, const __nv_bfloat16* __restrict__ ea,
                                          const __nv_bfloat16* __restrict__ cg, const __nv_bfloat16* __restrict__ wr,
                                          int lane) {
    float rwv[4] = {0.f, 0.f, 0.f, 0.f};
#pragma unroll 4
    for (int d = 0; d < 16; d++) {
        const float a = __bfloat162float(ea[(size_t)ee * 16 + d]);
        const uint2 wv = *(const uint2*)(wr + d * 128 + lane * 4);
        rwv[0] += a * __uint_as_float(wv.x << 16);
        rwv[1] += a * __uint_as_float(wv.x & 0xffff0000u);
        rwv[2] += a * __uint_as_float(wv.y << 16);
        rwv[3] += a * __uint_as_float(wv.y & 0xffff0000u);
    }
    float A = 0.f;
#pragma unroll
    for (int v = 0; v < 4; v++)
        A += __bfloat162float(cg[((lane >> 2) & 3) * 16 + v * 4 + (lane & 3)]) * __bfloat162float(sh[(size_t)ee * 4 + v]);
    float m[4][4];
#pragma unroll
    for (int w = 0; w < 4; w++)
#pragma unroll
        for (int j = 0; j < 4; j++) m[w][j] = 0.f;
#pragma unroll
    for (int u = 0; u < 4; u++) {
        const uint2 xv = *(const uint2*)(x + (size_t)s * 512 + u * 128 + lane * 4);
        const float x0 = __uint_as_float(xv.x << 16), x1 = __uint_as_float(xv.x & 0xffff0000u);
        const float x2 = __uint_as_float(xv.y << 16), x3 = __uint_as_float(xv.y & 0xffff0000u);
#pragma unroll
        for (int w = 0; w < 4; w++) {
            const float a = __shfl_sync(0xffffffffu, A, u * 4 + w);
            m[w][0] += a * x0;
            m[w][1] += a * x1;
            m[w][2] += a * x2;
            m[w][3] += a * x3;
        }
    }
#pragma unroll
    for (int w = 0; w < 4; w++)
#pragma unroll
        for (int j = 0; j < 4; j++) atomicAdd(accn + w * 128 + lane * 4 + j, m[w][j] * rwv[j]);
}

__device__ __forceinline__ void slow_out(const float* accn, const __nv_bfloat16* __restrict__ wout,
                                         __nv_bfloat16* __restrict__ outn, int lane) {
    float o[4][4];
#pragma unroll
    for (int w = 0; w < 4; w++)
#pragma unroll
        for (int j = 0; j < 4; j++) o[w][j] = 0.f;
#pragma unroll 2
    for (int c = 0; c < 128; c++) {
        const uint2 wv = *(const uint2*)(wout + c * 128 + lane * 4);
        const float w0 = __uint_as_float(wv.x << 16), w1 = __uint_as_float(wv.x & 0xffff0000u);
        const float w2 = __uint_as_float(wv.y << 16), w3 = __uint_as_float(wv.y & 0xffff0000u);
#pragma unroll
        for (int w = 0; w < 4; w++) {
            const float a = __bfloat162float(__float2bfloat16(accn[w * 128 + c]));
            o[w][0] += a * w0;
            o[w][1] += a * w1;
            o[w][2] += a * w2;
            o[w][3] += a * w3;
        }
    }
#pragma unroll
    for (int w = 0; w < 4; w++)
        *(uint2*)(outn + w * 128 + lane * 4) = make_uint2(pack_bf16(o[w][0], o[w][1]), pack_bf16(o[w][2], o[w][3]));
}

__device__ __forceinline__ void consume4(uint32_t (&pk)[64], const uint32_t (&w)[36], uint32_t olp, uint32_t xa, uint32_t ln,
                                      uint32_t lc, uint32_t linc, uint32_t lt, const __nv_bfloat16* ea, const __nv_bfloat16* sh, const void* wf) {
    ea += lt * 4, sh += lt & 2;
    asm volatile(
        "{\n.reg .pred p, q, psw, prdy, ps1, ps2, ps3, pz;\n.reg .f32 d<32>, fz;\n"
        ".reg .b32 h<64>, x<32>, y<32>, ra<8>, rb<8>, bA0, bA1, bB0, bB1, c0, c1, c2, c3, e0, e1, s0, kept;\n"
        ".reg .b32 olp, v, vB, m, id, ida, bar, xb, pos, t0, t1, t2, t3, n, z<16>;\n.reg .b16 lo, hi, i16;\n.reg .b64 pa, pb;\nmov.f32 fz, 0f00000000;\n"
        "mov.b32 h0, 0;\nmov.b32 h1, 0;\nmov.b32 h2, 0;\nmov.b32 h3, 0;\nmov.b32 h4, 0;\nmov.b32 h5, 0;\nmov.b32 h6, 0;\nmov.b32 h7, 0;\nmov.b32 h8, 0;\n"
        "mov.b32 h9, 0;\nmov.b32 h10, 0;\nmov.b32 h11, 0;\nmov.b32 h12, 0;\nmov.b32 h13, 0;\nmov.b32 h14, 0;\nmov.b32 h15, 0;\nmov.b32 h16, 0;\nmov.b32 h17, 0;\n"
        "mov.b32 h18, 0;\nmov.b32 h19, 0;\nmov.b32 h20, 0;\nmov.b32 h21, 0;\nmov.b32 h22, 0;\nmov.b32 h23, 0;\nmov.b32 h24, 0;\nmov.b32 h25, 0;\n"
        "mov.b32 h26, 0;\nmov.b32 h27, 0;\nmov.b32 h28, 0;\nmov.b32 h29, 0;\nmov.b32 h30, 0;\nmov.b32 h31, 0;\nmov.b32 h32, 0;\nmov.b32 h33, 0;\n"
        "mov.b32 h34, 0;\nmov.b32 h35, 0;\nmov.b32 h36, 0;\nmov.b32 h37, 0;\nmov.b32 h38, 0;\nmov.b32 h39, 0;\nmov.b32 h40, 0;\nmov.b32 h41, 0;\n"
        "mov.b32 h42, 0;\nmov.b32 h43, 0;\nmov.b32 h44, 0;\nmov.b32 h45, 0;\nmov.b32 h46, 0;\nmov.b32 h47, 0;\nmov.b32 h48, 0;\nmov.b32 h49, 0;\n"
        "mov.b32 h50, 0;\nmov.b32 h51, 0;\nmov.b32 h52, 0;\nmov.b32 h53, 0;\nmov.b32 h54, 0;\nmov.b32 h55, 0;\nmov.b32 h56, 0;\nmov.b32 h57, 0;\n"
        "mov.b32 h58, 0;\nmov.b32 h59, 0;\nmov.b32 h60, 0;\nmov.b32 h61, 0;\nmov.b32 h62, 0;\nmov.b32 h63, 0;\nmov.b32 olp, %64;\nand.b32 t0, %66, 32;\n"
        "setp.ne.u32 psw, t0, 0;\nsetp.eq.u32 pz, %64, 0;\nvote.sync.any.pred pz, pz, 0xffffffff;\nld.shared.u16 t0, [olp];\nadd.u32 olp, olp, 4;\n"
        "lop3.b32 t1, t0, %66, 0x3ff0, 0xe4;\nld.shared.b32 t1, [t1+%73];\nlop3.b32 kept, t1, t0, 0x1ffc, 0xe4;\nlop3.b32 t2, t1, %67, 3, 0x80;\n"
        "setp.ne.u32 q, t2, 0;\nshr.u32 t2, t1, 13;\nmad.wide.u32 pa, t2, 32, %70;\nmad.wide.u32 pb, t2, 8, %71;\nmov.b32 s0, 0;\n"
        "ld.global.cg.v2.b32 {e0,e1}, [pa];\n@q ld.global.cg.b32 s0, [pb];\nsetp.ne.u64 p, %72, 0;\n@p fence.proxy.async.global;\n"
        "@p red.release.gpu.global.add.u32 [%72+12], 1;\nbar.warp.sync 0xffffffff;\nshfl.sync.idx.b32 v, kept, %67, 0x1f, 0xffffffff;\nor.b32 t3, %67, 4;\n"
        "shfl.sync.idx.b32 vB, kept, t3, 0x1f, 0xffffffff;\n"
        "RW:\nmma.sync.aligned.m16n8k8.row.col.f32.bf16.bf16.f32 {d0,d1,d2,d3}, {%109,%110}, {s0}, {fz,fz,fz,fz};\n"
        "mma.sync.aligned.m16n8k8.row.col.f32.bf16.bf16.f32 {d4,d5,d6,d7}, {%111,%112}, {s0}, {fz,fz,fz,fz};\ncvt.rn.bf16x2.f32 c0, d2, d0;\n"
        "cvt.rn.bf16x2.f32 c1, d3, d1;\ncvt.rn.bf16x2.f32 c2, d6, d4;\ncvt.rn.bf16x2.f32 c3, d7, d5;\nselp.b32 bA0, c2, c0, psw;\nselp.b32 bA1, c0, c2, psw;\n"
        "selp.b32 bB0, c3, c1, psw;\nselp.b32 bB1, c1, c3, psw;\n"
        "mma.sync.aligned.m16n8k16.row.col.f32.bf16.bf16.f32 {d0,d1,d2,d3}, {%77,%78,%79,%80}, {e0,e1}, {fz,fz,fz,fz};\ncvt.rn.bf16x2.f32 ra0, d2, d0;\n"
        "cvt.rn.bf16x2.f32 rb0, d3, d1;\nmma.sync.aligned.m16n8k16.row.col.f32.bf16.bf16.f32 {d4,d5,d6,d7}, {%81,%82,%83,%84}, {e0,e1}, {fz,fz,fz,fz};\n"
        "cvt.rn.bf16x2.f32 ra1, d6, d4;\ncvt.rn.bf16x2.f32 rb1, d7, d5;\n"
        "mma.sync.aligned.m16n8k16.row.col.f32.bf16.bf16.f32 {d8,d9,d10,d11}, {%85,%86,%87,%88}, {e0,e1}, {fz,fz,fz,fz};\ncvt.rn.bf16x2.f32 ra2, d10, d8;\n"
        "cvt.rn.bf16x2.f32 rb2, d11, d9;\nmma.sync.aligned.m16n8k16.row.col.f32.bf16.bf16.f32 {d12,d13,d14,d15}, {%89,%90,%91,%92}, {e0,e1}, {fz,fz,fz,fz};\n"
        "cvt.rn.bf16x2.f32 ra3, d14, d12;\ncvt.rn.bf16x2.f32 rb3, d15, d13;\n"
        "mma.sync.aligned.m16n8k16.row.col.f32.bf16.bf16.f32 {d16,d17,d18,d19}, {%93,%94,%95,%96}, {e0,e1}, {fz,fz,fz,fz};\ncvt.rn.bf16x2.f32 ra4, d18, d16;\n"
        "cvt.rn.bf16x2.f32 rb4, d19, d17;\nmma.sync.aligned.m16n8k16.row.col.f32.bf16.bf16.f32 {d20,d21,d22,d23}, {%97,%98,%99,%100}, {e0,e1}, {fz,fz,fz,fz};\n"
        "cvt.rn.bf16x2.f32 ra5, d22, d20;\ncvt.rn.bf16x2.f32 rb5, d23, d21;\n"
        "mma.sync.aligned.m16n8k16.row.col.f32.bf16.bf16.f32 {d24,d25,d26,d27}, {%101,%102,%103,%104}, {e0,e1}, {fz,fz,fz,fz};\n"
        "cvt.rn.bf16x2.f32 ra6, d26, d24;\ncvt.rn.bf16x2.f32 rb6, d27, d25;\n"
        "mma.sync.aligned.m16n8k16.row.col.f32.bf16.bf16.f32 {d28,d29,d30,d31}, {%105,%106,%107,%108}, {e0,e1}, {fz,fz,fz,fz};\n"
        "cvt.rn.bf16x2.f32 ra7, d30, d28;\ncvt.rn.bf16x2.f32 rb7, d31, d29;\nld.shared.u16 t0, [olp];\nadd.u32 olp, olp, 4;\n"
        "lop3.b32 t1, t0, %66, 0x3ff0, 0xe4;\nld.shared.b32 t1, [t1+%73];\nlop3.b32 kept, t1, t0, 0x1ffc, 0xe4;\nlop3.b32 t2, t1, %67, 3, 0x80;\n"
        "setp.ne.u32 q, t2, 0;\nshr.u32 t2, t1, 13;\nmad.wide.u32 pa, t2, 32, %70;\nmad.wide.u32 pb, t2, 8, %71;\nmov.b32 s0, 0;\n"
        "ld.global.cg.v2.b32 {e0,e1}, [pa];\n@q ld.global.cg.b32 s0, [pb];\nshr.u32 bar, v, 1;\nand.b32 bar, bar, 0xff8;\n"
        "mbarrier.test_wait.parity.shared.b64 p, [bar+%75], 0;\nlop3.b32 ida, v, %67, 0x1fff, 0xe4;\nld.volatile.shared.u16 id, [ida+%74];\n"
        "vote.sync.all.pred prdy, p, 0xffffffff;\n@!prdy bra.uni WA;\n"
        "HA:\nmad.lo.u32 xb, id, 64, %65;\ncvt.u16.u32 i16, id;\natom.shared.add.u32 pos, [%66+%76], %68;\n"
        "ldmatrix.sync.aligned.m8n8.x4.trans.shared.b16 {x0,x1,x2,x3}, [xb];\nldmatrix.sync.aligned.m8n8.x4.trans.shared.b16 {x24,x25,x26,x27}, [xb+512];\n"
        "xor.b32 t1, xb, 32;\nldmatrix.sync.aligned.m8n8.x4.trans.shared.b16 {x4,x5,x6,x7}, [t1];\n"
        "ldmatrix.sync.aligned.m8n8.x4.trans.shared.b16 {x28,x29,x30,x31}, [t1+512];\nxor.b32 t1, xb, 64;\n"
        "ldmatrix.sync.aligned.m8n8.x4.trans.shared.b16 {x8,x9,x10,x11}, [t1];\nldmatrix.sync.aligned.m8n8.x4.trans.shared.b16 {x16,x17,x18,x19}, [t1+512];\n"
        "xor.b32 t1, xb, 96;\nldmatrix.sync.aligned.m8n8.x4.trans.shared.b16 {x12,x13,x14,x15}, [t1];\n"
        "ldmatrix.sync.aligned.m8n8.x4.trans.shared.b16 {x20,x21,x22,x23}, [t1+512];\nst.volatile.shared.u16 [pos], i16;\nand.b32 t0, v, 16384;\n"
        "setp.ne.u32 ps1, t0, 0;\nvote.sync.any.pred ps1, ps1, 0xffffffff;\nand.b32 t0, v, 32768;\nsetp.ne.u32 ps2, t0, 0;\n"
        "vote.sync.any.pred ps2, ps2, 0xffffffff;\nmov.b32 v, vB;\nshr.u32 bar, v, 1;\nand.b32 bar, bar, 0xff8;\n"
        "mbarrier.test_wait.parity.shared.b64 p, [bar+%75], 0;\nlop3.b32 ida, v, %67, 0x1fff, 0xe4;\nld.volatile.shared.u16 id, [ida+%74];\n"
        "vote.sync.all.pred prdy, p, 0xffffffff;\nmov.b32 {lo, hi}, ra0;\nmov.b32 t2, {lo, lo};\nmul.rn.bf16x2 y0, x0, t2;\nmul.rn.bf16x2 y2, x2, t2;\n"
        "mov.b32 t2, {hi, hi};\nmul.rn.bf16x2 y1, x1, t2;\nmul.rn.bf16x2 y3, x3, t2;\n"
        "mma.sync.aligned.m16n8k16.row.col.f32.bf16.bf16.f32 {d0,d1,d2,d3}, {y0,y1,y2,y3}, {bA0,bA1}, {fz,fz,fz,fz};\ncvt.rn.bf16x2.f32 z0, d1, d0;\n"
        "cvt.rn.bf16x2.f32 z1, d3, d2;\nmov.b32 {lo, hi}, ra6;\nmov.b32 t2, {lo, lo};\nmul.rn.bf16x2 y24, x24, t2;\nmul.rn.bf16x2 y26, x26, t2;\n"
        "mov.b32 t2, {hi, hi};\nmul.rn.bf16x2 y25, x25, t2;\nmul.rn.bf16x2 y27, x27, t2;\n"
        "mma.sync.aligned.m16n8k16.row.col.f32.bf16.bf16.f32 {d24,d25,d26,d27}, {y24,y25,y26,y27}, {bA0,bA1}, {fz,fz,fz,fz};\ncvt.rn.bf16x2.f32 z12, d25, d24;\n"
        "cvt.rn.bf16x2.f32 z13, d27, d26;\nmov.b32 {lo, hi}, ra1;\nmov.b32 t2, {lo, lo};\nmul.rn.bf16x2 y4, x4, t2;\nmul.rn.bf16x2 y6, x6, t2;\n"
        "mov.b32 t2, {hi, hi};\nmul.rn.bf16x2 y5, x5, t2;\nmul.rn.bf16x2 y7, x7, t2;\n"
        "mma.sync.aligned.m16n8k16.row.col.f32.bf16.bf16.f32 {d4,d5,d6,d7}, {y4,y5,y6,y7}, {bA0,bA1}, {fz,fz,fz,fz};\ncvt.rn.bf16x2.f32 z2, d5, d4;\n"
        "cvt.rn.bf16x2.f32 z3, d7, d6;\nmov.b32 {lo, hi}, ra7;\nmov.b32 t2, {lo, lo};\nmul.rn.bf16x2 y28, x28, t2;\nmul.rn.bf16x2 y30, x30, t2;\n"
        "mov.b32 t2, {hi, hi};\nmul.rn.bf16x2 y29, x29, t2;\nmul.rn.bf16x2 y31, x31, t2;\n"
        "mma.sync.aligned.m16n8k16.row.col.f32.bf16.bf16.f32 {d28,d29,d30,d31}, {y28,y29,y30,y31}, {bA0,bA1}, {fz,fz,fz,fz};\ncvt.rn.bf16x2.f32 z14, d29, d28;\n"
        "cvt.rn.bf16x2.f32 z15, d31, d30;\nmov.b32 {lo, hi}, ra2;\nmov.b32 t2, {lo, lo};\nmul.rn.bf16x2 y8, x8, t2;\nmul.rn.bf16x2 y10, x10, t2;\n"
        "mov.b32 t2, {hi, hi};\nmul.rn.bf16x2 y9, x9, t2;\nmul.rn.bf16x2 y11, x11, t2;\n"
        "mma.sync.aligned.m16n8k16.row.col.f32.bf16.bf16.f32 {d8,d9,d10,d11}, {y8,y9,y10,y11}, {bA0,bA1}, {fz,fz,fz,fz};\ncvt.rn.bf16x2.f32 z4, d9, d8;\n"
        "cvt.rn.bf16x2.f32 z5, d11, d10;\nmov.b32 {lo, hi}, ra4;\nmov.b32 t2, {lo, lo};\nmul.rn.bf16x2 y16, x16, t2;\nmul.rn.bf16x2 y18, x18, t2;\n"
        "mov.b32 t2, {hi, hi};\nmul.rn.bf16x2 y17, x17, t2;\nmul.rn.bf16x2 y19, x19, t2;\n"
        "mma.sync.aligned.m16n8k16.row.col.f32.bf16.bf16.f32 {d16,d17,d18,d19}, {y16,y17,y18,y19}, {bA0,bA1}, {fz,fz,fz,fz};\ncvt.rn.bf16x2.f32 z8, d17, d16;\n"
        "cvt.rn.bf16x2.f32 z9, d19, d18;\nmov.b32 {lo, hi}, ra3;\nmov.b32 t2, {lo, lo};\nmul.rn.bf16x2 y12, x12, t2;\nmul.rn.bf16x2 y14, x14, t2;\n"
        "mov.b32 t2, {hi, hi};\nmul.rn.bf16x2 y13, x13, t2;\nmul.rn.bf16x2 y15, x15, t2;\n"
        "mma.sync.aligned.m16n8k16.row.col.f32.bf16.bf16.f32 {d12,d13,d14,d15}, {y12,y13,y14,y15}, {bA0,bA1}, {fz,fz,fz,fz};\ncvt.rn.bf16x2.f32 z6, d13, d12;\n"
        "cvt.rn.bf16x2.f32 z7, d15, d14;\nmov.b32 {lo, hi}, ra5;\nmov.b32 t2, {lo, lo};\nmul.rn.bf16x2 y20, x20, t2;\nmul.rn.bf16x2 y22, x22, t2;\n"
        "mov.b32 t2, {hi, hi};\nmul.rn.bf16x2 y21, x21, t2;\nmul.rn.bf16x2 y23, x23, t2;\n"
        "mma.sync.aligned.m16n8k16.row.col.f32.bf16.bf16.f32 {d20,d21,d22,d23}, {y20,y21,y22,y23}, {bA0,bA1}, {fz,fz,fz,fz};\ncvt.rn.bf16x2.f32 z10, d21, d20;\n"
        "cvt.rn.bf16x2.f32 z11, d23, d22;\n@ps2 bra.uni TA2;\n@ps1 bra.uni TA1;\n"
        "TA0:\nadd.rn.bf16x2 h0, h0, z0;\nadd.rn.bf16x2 h1, h1, z1;\nadd.rn.bf16x2 h2, h2, z2;\nadd.rn.bf16x2 h3, h3, z3;\nadd.rn.bf16x2 h4, h4, z4;\n"
        "add.rn.bf16x2 h5, h5, z5;\nadd.rn.bf16x2 h6, h6, z6;\nadd.rn.bf16x2 h7, h7, z7;\nadd.rn.bf16x2 h8, h8, z8;\nadd.rn.bf16x2 h9, h9, z9;\n"
        "add.rn.bf16x2 h10, h10, z10;\nadd.rn.bf16x2 h11, h11, z11;\nadd.rn.bf16x2 h12, h12, z12;\nadd.rn.bf16x2 h13, h13, z13;\nadd.rn.bf16x2 h14, h14, z14;\n"
        "add.rn.bf16x2 h15, h15, z15;\n@prdy bra.uni HB;\nbra.uni WB;\n"
        "TA1:\nadd.rn.bf16x2 h16, h16, z0;\nadd.rn.bf16x2 h17, h17, z1;\nadd.rn.bf16x2 h18, h18, z2;\nadd.rn.bf16x2 h19, h19, z3;\nadd.rn.bf16x2 h20, h20, z4;\n"
        "add.rn.bf16x2 h21, h21, z5;\nadd.rn.bf16x2 h22, h22, z6;\nadd.rn.bf16x2 h23, h23, z7;\nadd.rn.bf16x2 h24, h24, z8;\nadd.rn.bf16x2 h25, h25, z9;\n"
        "add.rn.bf16x2 h26, h26, z10;\nadd.rn.bf16x2 h27, h27, z11;\nadd.rn.bf16x2 h28, h28, z12;\nadd.rn.bf16x2 h29, h29, z13;\nadd.rn.bf16x2 h30, h30, z14;\n"
        "add.rn.bf16x2 h31, h31, z15;\n@prdy bra.uni HB;\nbra.uni WB;\n"
        "TA2:\n@ps1 bra.uni TA3;\nadd.rn.bf16x2 h32, h32, z0;\nadd.rn.bf16x2 h33, h33, z1;\nadd.rn.bf16x2 h34, h34, z2;\nadd.rn.bf16x2 h35, h35, z3;\n"
        "add.rn.bf16x2 h36, h36, z4;\nadd.rn.bf16x2 h37, h37, z5;\nadd.rn.bf16x2 h38, h38, z6;\nadd.rn.bf16x2 h39, h39, z7;\nadd.rn.bf16x2 h40, h40, z8;\n"
        "add.rn.bf16x2 h41, h41, z9;\nadd.rn.bf16x2 h42, h42, z10;\nadd.rn.bf16x2 h43, h43, z11;\nadd.rn.bf16x2 h44, h44, z12;\nadd.rn.bf16x2 h45, h45, z13;\n"
        "add.rn.bf16x2 h46, h46, z14;\nadd.rn.bf16x2 h47, h47, z15;\n@prdy bra.uni HB;\nbra.uni WB;\n"
        "TA3:\nadd.rn.bf16x2 h48, h48, z0;\nadd.rn.bf16x2 h49, h49, z1;\nadd.rn.bf16x2 h50, h50, z2;\nadd.rn.bf16x2 h51, h51, z3;\nadd.rn.bf16x2 h52, h52, z4;\n"
        "add.rn.bf16x2 h53, h53, z5;\nadd.rn.bf16x2 h54, h54, z6;\nadd.rn.bf16x2 h55, h55, z7;\nadd.rn.bf16x2 h56, h56, z8;\nadd.rn.bf16x2 h57, h57, z9;\n"
        "add.rn.bf16x2 h58, h58, z10;\nadd.rn.bf16x2 h59, h59, z11;\nadd.rn.bf16x2 h60, h60, z12;\nadd.rn.bf16x2 h61, h61, z13;\nadd.rn.bf16x2 h62, h62, z14;\n"
        "add.rn.bf16x2 h63, h63, z15;\n@prdy bra.uni HB;\nbra.uni WB;\n"
        "HB:\nmad.lo.u32 xb, id, 64, %65;\ncvt.u16.u32 i16, id;\natom.shared.add.u32 pos, [%66+%76], %68;\n"
        "ldmatrix.sync.aligned.m8n8.x4.trans.shared.b16 {x0,x1,x2,x3}, [xb];\nldmatrix.sync.aligned.m8n8.x4.trans.shared.b16 {x24,x25,x26,x27}, [xb+512];\n"
        "xor.b32 t1, xb, 32;\nldmatrix.sync.aligned.m8n8.x4.trans.shared.b16 {x4,x5,x6,x7}, [t1];\n"
        "ldmatrix.sync.aligned.m8n8.x4.trans.shared.b16 {x28,x29,x30,x31}, [t1+512];\nxor.b32 t1, xb, 64;\n"
        "ldmatrix.sync.aligned.m8n8.x4.trans.shared.b16 {x8,x9,x10,x11}, [t1];\nldmatrix.sync.aligned.m8n8.x4.trans.shared.b16 {x16,x17,x18,x19}, [t1+512];\n"
        "xor.b32 t1, xb, 96;\nldmatrix.sync.aligned.m8n8.x4.trans.shared.b16 {x12,x13,x14,x15}, [t1];\n"
        "ldmatrix.sync.aligned.m8n8.x4.trans.shared.b16 {x20,x21,x22,x23}, [t1+512];\nst.volatile.shared.u16 [pos], i16;\nand.b32 t0, v, 16384;\n"
        "setp.ne.u32 ps1, t0, 0;\nvote.sync.any.pred ps1, ps1, 0xffffffff;\nand.b32 t0, v, 32768;\nsetp.ne.u32 ps2, t0, 0;\n"
        "vote.sync.any.pred ps2, ps2, 0xffffffff;\nshfl.sync.idx.b32 v, kept, %67, 0x1f, 0xffffffff;\nor.b32 t3, %67, 4;\n"
        "shfl.sync.idx.b32 vB, kept, t3, 0x1f, 0xffffffff;\nmov.b32 {lo, hi}, rb0;\nmov.b32 t2, {lo, lo};\nmul.rn.bf16x2 y0, x0, t2;\nmul.rn.bf16x2 y2, x2, t2;\n"
        "mov.b32 t2, {hi, hi};\nmul.rn.bf16x2 y1, x1, t2;\nmul.rn.bf16x2 y3, x3, t2;\n"
        "mma.sync.aligned.m16n8k16.row.col.f32.bf16.bf16.f32 {d0,d1,d2,d3}, {y0,y1,y2,y3}, {bB0,bB1}, {fz,fz,fz,fz};\ncvt.rn.bf16x2.f32 z0, d1, d0;\n"
        "cvt.rn.bf16x2.f32 z1, d3, d2;\nmov.b32 {lo, hi}, rb6;\nmov.b32 t2, {lo, lo};\nmul.rn.bf16x2 y24, x24, t2;\nmul.rn.bf16x2 y26, x26, t2;\n"
        "mov.b32 t2, {hi, hi};\nmul.rn.bf16x2 y25, x25, t2;\nmul.rn.bf16x2 y27, x27, t2;\n"
        "mma.sync.aligned.m16n8k16.row.col.f32.bf16.bf16.f32 {d24,d25,d26,d27}, {y24,y25,y26,y27}, {bB0,bB1}, {fz,fz,fz,fz};\ncvt.rn.bf16x2.f32 z12, d25, d24;\n"
        "cvt.rn.bf16x2.f32 z13, d27, d26;\nmov.b32 {lo, hi}, rb1;\nmov.b32 t2, {lo, lo};\nmul.rn.bf16x2 y4, x4, t2;\nmul.rn.bf16x2 y6, x6, t2;\n"
        "mov.b32 t2, {hi, hi};\nmul.rn.bf16x2 y5, x5, t2;\nmul.rn.bf16x2 y7, x7, t2;\n"
        "mma.sync.aligned.m16n8k16.row.col.f32.bf16.bf16.f32 {d4,d5,d6,d7}, {y4,y5,y6,y7}, {bB0,bB1}, {fz,fz,fz,fz};\ncvt.rn.bf16x2.f32 z2, d5, d4;\n"
        "cvt.rn.bf16x2.f32 z3, d7, d6;\nmov.b32 {lo, hi}, rb7;\nmov.b32 t2, {lo, lo};\nmul.rn.bf16x2 y28, x28, t2;\nmul.rn.bf16x2 y30, x30, t2;\n"
        "mov.b32 t2, {hi, hi};\nmul.rn.bf16x2 y29, x29, t2;\nmul.rn.bf16x2 y31, x31, t2;\n"
        "mma.sync.aligned.m16n8k16.row.col.f32.bf16.bf16.f32 {d28,d29,d30,d31}, {y28,y29,y30,y31}, {bB0,bB1}, {fz,fz,fz,fz};\ncvt.rn.bf16x2.f32 z14, d29, d28;\n"
        "cvt.rn.bf16x2.f32 z15, d31, d30;\nmov.b32 {lo, hi}, rb2;\nmov.b32 t2, {lo, lo};\nmul.rn.bf16x2 y8, x8, t2;\nmul.rn.bf16x2 y10, x10, t2;\n"
        "mov.b32 t2, {hi, hi};\nmul.rn.bf16x2 y9, x9, t2;\nmul.rn.bf16x2 y11, x11, t2;\n"
        "mma.sync.aligned.m16n8k16.row.col.f32.bf16.bf16.f32 {d8,d9,d10,d11}, {y8,y9,y10,y11}, {bB0,bB1}, {fz,fz,fz,fz};\ncvt.rn.bf16x2.f32 z4, d9, d8;\n"
        "cvt.rn.bf16x2.f32 z5, d11, d10;\nmov.b32 {lo, hi}, rb4;\nmov.b32 t2, {lo, lo};\nmul.rn.bf16x2 y16, x16, t2;\nmul.rn.bf16x2 y18, x18, t2;\n"
        "mov.b32 t2, {hi, hi};\nmul.rn.bf16x2 y17, x17, t2;\nmul.rn.bf16x2 y19, x19, t2;\n"
        "mma.sync.aligned.m16n8k16.row.col.f32.bf16.bf16.f32 {d16,d17,d18,d19}, {y16,y17,y18,y19}, {bB0,bB1}, {fz,fz,fz,fz};\ncvt.rn.bf16x2.f32 z8, d17, d16;\n"
        "cvt.rn.bf16x2.f32 z9, d19, d18;\nmov.b32 {lo, hi}, rb3;\nmov.b32 t2, {lo, lo};\nmul.rn.bf16x2 y12, x12, t2;\nmul.rn.bf16x2 y14, x14, t2;\n"
        "mov.b32 t2, {hi, hi};\nmul.rn.bf16x2 y13, x13, t2;\nmul.rn.bf16x2 y15, x15, t2;\n"
        "mma.sync.aligned.m16n8k16.row.col.f32.bf16.bf16.f32 {d12,d13,d14,d15}, {y12,y13,y14,y15}, {bB0,bB1}, {fz,fz,fz,fz};\ncvt.rn.bf16x2.f32 z6, d13, d12;\n"
        "cvt.rn.bf16x2.f32 z7, d15, d14;\nmov.b32 {lo, hi}, rb5;\nmov.b32 t2, {lo, lo};\nmul.rn.bf16x2 y20, x20, t2;\nmul.rn.bf16x2 y22, x22, t2;\n"
        "mov.b32 t2, {hi, hi};\nmul.rn.bf16x2 y21, x21, t2;\nmul.rn.bf16x2 y23, x23, t2;\n"
        "mma.sync.aligned.m16n8k16.row.col.f32.bf16.bf16.f32 {d20,d21,d22,d23}, {y20,y21,y22,y23}, {bB0,bB1}, {fz,fz,fz,fz};\ncvt.rn.bf16x2.f32 z10, d21, d20;\n"
        "cvt.rn.bf16x2.f32 z11, d23, d22;\n@ps2 bra.uni TB2;\n@ps1 bra.uni TB1;\n"
        "TB0:\nadd.rn.bf16x2 h0, h0, z0;\nadd.rn.bf16x2 h1, h1, z1;\nadd.rn.bf16x2 h2, h2, z2;\nadd.rn.bf16x2 h3, h3, z3;\nadd.rn.bf16x2 h4, h4, z4;\n"
        "add.rn.bf16x2 h5, h5, z5;\nadd.rn.bf16x2 h6, h6, z6;\nadd.rn.bf16x2 h7, h7, z7;\nadd.rn.bf16x2 h8, h8, z8;\nadd.rn.bf16x2 h9, h9, z9;\n"
        "add.rn.bf16x2 h10, h10, z10;\nadd.rn.bf16x2 h11, h11, z11;\nadd.rn.bf16x2 h12, h12, z12;\nadd.rn.bf16x2 h13, h13, z13;\nadd.rn.bf16x2 h14, h14, z14;\n"
        "add.rn.bf16x2 h15, h15, z15;\nbra.uni RW;\n"
        "TB1:\nadd.rn.bf16x2 h16, h16, z0;\nadd.rn.bf16x2 h17, h17, z1;\nadd.rn.bf16x2 h18, h18, z2;\nadd.rn.bf16x2 h19, h19, z3;\nadd.rn.bf16x2 h20, h20, z4;\n"
        "add.rn.bf16x2 h21, h21, z5;\nadd.rn.bf16x2 h22, h22, z6;\nadd.rn.bf16x2 h23, h23, z7;\nadd.rn.bf16x2 h24, h24, z8;\nadd.rn.bf16x2 h25, h25, z9;\n"
        "add.rn.bf16x2 h26, h26, z10;\nadd.rn.bf16x2 h27, h27, z11;\nadd.rn.bf16x2 h28, h28, z12;\nadd.rn.bf16x2 h29, h29, z13;\nadd.rn.bf16x2 h30, h30, z14;\n"
        "add.rn.bf16x2 h31, h31, z15;\nbra.uni RW;\n"
        "TB2:\n@ps1 bra.uni TB3;\nadd.rn.bf16x2 h32, h32, z0;\nadd.rn.bf16x2 h33, h33, z1;\nadd.rn.bf16x2 h34, h34, z2;\nadd.rn.bf16x2 h35, h35, z3;\n"
        "add.rn.bf16x2 h36, h36, z4;\nadd.rn.bf16x2 h37, h37, z5;\nadd.rn.bf16x2 h38, h38, z6;\nadd.rn.bf16x2 h39, h39, z7;\nadd.rn.bf16x2 h40, h40, z8;\n"
        "add.rn.bf16x2 h41, h41, z9;\nadd.rn.bf16x2 h42, h42, z10;\nadd.rn.bf16x2 h43, h43, z11;\nadd.rn.bf16x2 h44, h44, z12;\nadd.rn.bf16x2 h45, h45, z13;\n"
        "add.rn.bf16x2 h46, h46, z14;\nadd.rn.bf16x2 h47, h47, z15;\nbra.uni RW;\n"
        "TB3:\nadd.rn.bf16x2 h48, h48, z0;\nadd.rn.bf16x2 h49, h49, z1;\nadd.rn.bf16x2 h50, h50, z2;\nadd.rn.bf16x2 h51, h51, z3;\nadd.rn.bf16x2 h52, h52, z4;\n"
        "add.rn.bf16x2 h53, h53, z5;\nadd.rn.bf16x2 h54, h54, z6;\nadd.rn.bf16x2 h55, h55, z7;\nadd.rn.bf16x2 h56, h56, z8;\nadd.rn.bf16x2 h57, h57, z9;\n"
        "add.rn.bf16x2 h58, h58, z10;\nadd.rn.bf16x2 h59, h59, z11;\nadd.rn.bf16x2 h60, h60, z12;\nadd.rn.bf16x2 h61, h61, z13;\nadd.rn.bf16x2 h62, h62, z14;\n"
        "add.rn.bf16x2 h63, h63, z15;\nbra.uni RW;\n"
        "WA:\nshr.u32 t2, v, 1;\nand.b32 t2, t2, 0xff8;\nsetp.eq.u32 p, t2, 0;\nvote.sync.all.pred p, p, 0xffffffff;\n@p bra.uni DONE;\nmov.b32 n, 0;\n"
        "WA3:\nmbarrier.try_wait.parity.shared.b64 p, [t2+%75], 0;\nvote.sync.all.pred p, p, 0xffffffff;\nadd.u32 n, n, 1;\nsetp.lt.and.u32 q, n, 1000000, !p;\n"
        "@q bra.uni WA3;\nlop3.b32 ida, v, %67, 0x1fff, 0xe4;\nld.volatile.shared.u16 id, [ida+%74];\nbra.uni HA;\n"
        "WB:\nshr.u32 t2, v, 1;\nand.b32 t2, t2, 0xff8;\nsetp.eq.u32 p, t2, 0;\nvote.sync.all.pred p, p, 0xffffffff;\n@p bra.uni DONE;\nmov.b32 n, 0;\n"
        "WB3:\nmbarrier.try_wait.parity.shared.b64 p, [t2+%75], 0;\nvote.sync.all.pred p, p, 0xffffffff;\nadd.u32 n, n, 1;\nsetp.lt.and.u32 q, n, 1000000, !p;\n"
        "@q bra.uni WB3;\nlop3.b32 ida, v, %67, 0x1fff, 0xe4;\nld.volatile.shared.u16 id, [ida+%74];\nbra.uni HB;\n"
        "DONE:\nmov.b32 %0, h0;\nmov.b32 %1, h1;\nmov.b32 %2, h2;\nmov.b32 %3, h3;\nmov.b32 %4, h4;\nmov.b32 %5, h5;\nmov.b32 %6, h6;\nmov.b32 %7, h7;\n"
        "mov.b32 %8, h8;\nmov.b32 %9, h9;\nmov.b32 %10, h10;\nmov.b32 %11, h11;\nmov.b32 %12, h12;\nmov.b32 %13, h13;\nmov.b32 %14, h14;\nmov.b32 %15, h15;\n"
        "mov.b32 %16, h16;\nmov.b32 %17, h17;\nmov.b32 %18, h18;\nmov.b32 %19, h19;\nmov.b32 %20, h20;\nmov.b32 %21, h21;\nmov.b32 %22, h22;\nmov.b32 %23, h23;\n"
        "mov.b32 %24, h24;\nmov.b32 %25, h25;\nmov.b32 %26, h26;\nmov.b32 %27, h27;\nmov.b32 %28, h28;\nmov.b32 %29, h29;\nmov.b32 %30, h30;\nmov.b32 %31, h31;\n"
        "mov.b32 %32, h32;\nmov.b32 %33, h33;\nmov.b32 %34, h34;\nmov.b32 %35, h35;\nmov.b32 %36, h36;\nmov.b32 %37, h37;\nmov.b32 %38, h38;\nmov.b32 %39, h39;\n"
        "mov.b32 %40, h40;\nmov.b32 %41, h41;\nmov.b32 %42, h42;\nmov.b32 %43, h43;\nmov.b32 %44, h44;\nmov.b32 %45, h45;\nmov.b32 %46, h46;\nmov.b32 %47, h47;\n"
        "mov.b32 %48, h48;\nmov.b32 %49, h49;\nmov.b32 %50, h50;\nmov.b32 %51, h51;\nmov.b32 %52, h52;\nmov.b32 %53, h53;\nmov.b32 %54, h54;\nmov.b32 %55, h55;\n"
        "mov.b32 %56, h56;\nmov.b32 %57, h57;\nmov.b32 %58, h58;\nmov.b32 %59, h59;\nmov.b32 %60, h60;\nmov.b32 %61, h61;\nmov.b32 %62, h62;\nmov.b32 %63, h63;\n"
        "}\n"
        : "=r"(pk[0]), "=r"(pk[1]), "=r"(pk[2]), "=r"(pk[3]), "=r"(pk[4]), "=r"(pk[5]), "=r"(pk[6]), "=r"(pk[7]), "=r"(pk[8]), "=r"(pk[9]),
          "=r"(pk[10]), "=r"(pk[11]), "=r"(pk[12]), "=r"(pk[13]), "=r"(pk[14]), "=r"(pk[15]), "=r"(pk[16]), "=r"(pk[17]), "=r"(pk[18]), "=r"(pk[19]),
          "=r"(pk[20]), "=r"(pk[21]), "=r"(pk[22]), "=r"(pk[23]), "=r"(pk[24]), "=r"(pk[25]), "=r"(pk[26]), "=r"(pk[27]), "=r"(pk[28]), "=r"(pk[29]),
          "=r"(pk[30]), "=r"(pk[31]), "=r"(pk[32]), "=r"(pk[33]), "=r"(pk[34]), "=r"(pk[35]), "=r"(pk[36]), "=r"(pk[37]), "=r"(pk[38]), "=r"(pk[39]),
          "=r"(pk[40]), "=r"(pk[41]), "=r"(pk[42]), "=r"(pk[43]), "=r"(pk[44]), "=r"(pk[45]), "=r"(pk[46]), "=r"(pk[47]), "=r"(pk[48]), "=r"(pk[49]),
          "=r"(pk[50]), "=r"(pk[51]), "=r"(pk[52]), "=r"(pk[53]), "=r"(pk[54]), "=r"(pk[55]), "=r"(pk[56]), "=r"(pk[57]), "=r"(pk[58]), "=r"(pk[59]),
          "=r"(pk[60]), "=r"(pk[61]), "=r"(pk[62]), "=r"(pk[63])
        : "r"(olp), "r"(xa), "r"(ln), "r"(lc), "r"(linc), "r"(lt), "l"(ea), "l"(sh), "l"(wf),
          "n"(sb + SM_REC), "n"(sb + SM_R), "n"(sb + SM_BAR), "n"(sb + SM_CTR),
          "r"(w[0]), "r"(w[1]), "r"(w[2]), "r"(w[3]), "r"(w[4]), "r"(w[5]), "r"(w[6]), "r"(w[7]), "r"(w[8]), "r"(w[9]), "r"(w[10]), "r"(w[11]),
          "r"(w[12]), "r"(w[13]), "r"(w[14]), "r"(w[15]), "r"(w[16]), "r"(w[17]), "r"(w[18]), "r"(w[19]), "r"(w[20]), "r"(w[21]), "r"(w[22]),
          "r"(w[23]), "r"(w[24]), "r"(w[25]), "r"(w[26]), "r"(w[27]), "r"(w[28]), "r"(w[29]), "r"(w[30]), "r"(w[31]), "r"(w[32]), "r"(w[33]),
          "r"(w[34]), "r"(w[35])
        : "memory");
}
__device__ __forceinline__ void consume3(uint32_t (&pk)[48], const uint32_t (&w)[36], uint32_t olp, uint32_t xa, uint32_t ln,
                                      uint32_t lc, uint32_t linc, uint32_t lt, const __nv_bfloat16* ea, const __nv_bfloat16* sh, const void* wf) {
    ea += lt * 4, sh += lt & 2;
    asm volatile(
        "{\n.reg .pred p, q, psw, prdy, ps1, ps2, ps3, pz;\n.reg .f32 d<32>, fz;\n"
        ".reg .b32 h<48>, x<32>, y<32>, ra<8>, rb<8>, bA0, bA1, bB0, bB1, c0, c1, c2, c3, e0, e1, s0, kept;\n"
        ".reg .b32 olp, v, vB, m, id, ida, bar, xb, pos, t0, t1, t2, t3, n, z<16>;\n.reg .b16 lo, hi, i16;\n.reg .b64 pa, pb;\nmov.f32 fz, 0f00000000;\n"
        "mov.b32 h0, 0;\nmov.b32 h1, 0;\nmov.b32 h2, 0;\nmov.b32 h3, 0;\nmov.b32 h4, 0;\nmov.b32 h5, 0;\nmov.b32 h6, 0;\nmov.b32 h7, 0;\nmov.b32 h8, 0;\n"
        "mov.b32 h9, 0;\nmov.b32 h10, 0;\nmov.b32 h11, 0;\nmov.b32 h12, 0;\nmov.b32 h13, 0;\nmov.b32 h14, 0;\nmov.b32 h15, 0;\nmov.b32 h16, 0;\nmov.b32 h17, 0;\n"
        "mov.b32 h18, 0;\nmov.b32 h19, 0;\nmov.b32 h20, 0;\nmov.b32 h21, 0;\nmov.b32 h22, 0;\nmov.b32 h23, 0;\nmov.b32 h24, 0;\nmov.b32 h25, 0;\n"
        "mov.b32 h26, 0;\nmov.b32 h27, 0;\nmov.b32 h28, 0;\nmov.b32 h29, 0;\nmov.b32 h30, 0;\nmov.b32 h31, 0;\nmov.b32 h32, 0;\nmov.b32 h33, 0;\n"
        "mov.b32 h34, 0;\nmov.b32 h35, 0;\nmov.b32 h36, 0;\nmov.b32 h37, 0;\nmov.b32 h38, 0;\nmov.b32 h39, 0;\nmov.b32 h40, 0;\nmov.b32 h41, 0;\n"
        "mov.b32 h42, 0;\nmov.b32 h43, 0;\nmov.b32 h44, 0;\nmov.b32 h45, 0;\nmov.b32 h46, 0;\nmov.b32 h47, 0;\nmov.b32 olp, %48;\nor.b32 t3, %51, 4;\n"
        "shfl.sync.bfly.b32 t3, t3, 8, 0x1f, 0xffffffff;\nand.b32 t0, %50, 32;\nsetp.ne.u32 psw, t0, 0;\nsetp.eq.u32 pz, %48, 0;\n"
        "vote.sync.any.pred pz, pz, 0xffffffff;\nld.shared.u16 t0, [olp];\nadd.u32 olp, olp, 4;\nlop3.b32 t1, t0, %50, 0x3ff0, 0xe4;\n"
        "ld.shared.b32 t1, [t1+%57];\nlop3.b32 kept, t1, t0, 0x1ffc, 0xe4;\nlop3.b32 t2, t1, %51, 3, 0x80;\nsetp.ne.u32 q, t2, 0;\nshr.u32 t2, t1, 13;\n"
        "mad.wide.u32 pa, t2, 32, %54;\nmad.wide.u32 pb, t2, 8, %55;\nmov.b32 s0, 0;\nld.global.cg.v2.b32 {e0,e1}, [pa];\n@q ld.global.cg.b32 s0, [pb];\n"
        "setp.ne.u64 p, %56, 0;\n@p fence.proxy.async.global;\n@p red.release.gpu.global.add.u32 [%56+12], 1;\nbar.warp.sync 0xffffffff;\n"
        "shfl.sync.idx.b32 v, kept, %51, 0x1f, 0xffffffff;\nshfl.sync.idx.b32 vB, kept, t3, 0x1f, 0xffffffff;\n"
        "RW:\nmma.sync.aligned.m16n8k8.row.col.f32.bf16.bf16.f32 {d0,d1,d2,d3}, {%93,%94}, {s0}, {fz,fz,fz,fz};\n"
        "mma.sync.aligned.m16n8k8.row.col.f32.bf16.bf16.f32 {d4,d5,d6,d7}, {%95,%96}, {s0}, {fz,fz,fz,fz};\ncvt.rn.bf16x2.f32 c0, d2, d0;\n"
        "cvt.rn.bf16x2.f32 c1, d3, d1;\ncvt.rn.bf16x2.f32 c2, d6, d4;\ncvt.rn.bf16x2.f32 c3, d7, d5;\nselp.b32 bA0, c2, c0, psw;\nselp.b32 bA1, c0, c2, psw;\n"
        "selp.b32 bB0, c3, c1, psw;\nselp.b32 bB1, c1, c3, psw;\n"
        "mma.sync.aligned.m16n8k16.row.col.f32.bf16.bf16.f32 {d0,d1,d2,d3}, {%61,%62,%63,%64}, {e0,e1}, {fz,fz,fz,fz};\ncvt.rn.bf16x2.f32 ra0, d2, d0;\n"
        "cvt.rn.bf16x2.f32 rb0, d3, d1;\nmma.sync.aligned.m16n8k16.row.col.f32.bf16.bf16.f32 {d4,d5,d6,d7}, {%65,%66,%67,%68}, {e0,e1}, {fz,fz,fz,fz};\n"
        "cvt.rn.bf16x2.f32 ra1, d6, d4;\ncvt.rn.bf16x2.f32 rb1, d7, d5;\n"
        "mma.sync.aligned.m16n8k16.row.col.f32.bf16.bf16.f32 {d8,d9,d10,d11}, {%69,%70,%71,%72}, {e0,e1}, {fz,fz,fz,fz};\ncvt.rn.bf16x2.f32 ra2, d10, d8;\n"
        "cvt.rn.bf16x2.f32 rb2, d11, d9;\nmma.sync.aligned.m16n8k16.row.col.f32.bf16.bf16.f32 {d12,d13,d14,d15}, {%73,%74,%75,%76}, {e0,e1}, {fz,fz,fz,fz};\n"
        "cvt.rn.bf16x2.f32 ra3, d14, d12;\ncvt.rn.bf16x2.f32 rb3, d15, d13;\n"
        "mma.sync.aligned.m16n8k16.row.col.f32.bf16.bf16.f32 {d16,d17,d18,d19}, {%77,%78,%79,%80}, {e0,e1}, {fz,fz,fz,fz};\ncvt.rn.bf16x2.f32 ra4, d18, d16;\n"
        "cvt.rn.bf16x2.f32 rb4, d19, d17;\nmma.sync.aligned.m16n8k16.row.col.f32.bf16.bf16.f32 {d20,d21,d22,d23}, {%81,%82,%83,%84}, {e0,e1}, {fz,fz,fz,fz};\n"
        "cvt.rn.bf16x2.f32 ra5, d22, d20;\ncvt.rn.bf16x2.f32 rb5, d23, d21;\n"
        "mma.sync.aligned.m16n8k16.row.col.f32.bf16.bf16.f32 {d24,d25,d26,d27}, {%85,%86,%87,%88}, {e0,e1}, {fz,fz,fz,fz};\ncvt.rn.bf16x2.f32 ra6, d26, d24;\n"
        "cvt.rn.bf16x2.f32 rb6, d27, d25;\nmma.sync.aligned.m16n8k16.row.col.f32.bf16.bf16.f32 {d28,d29,d30,d31}, {%89,%90,%91,%92}, {e0,e1}, {fz,fz,fz,fz};\n"
        "cvt.rn.bf16x2.f32 ra7, d30, d28;\ncvt.rn.bf16x2.f32 rb7, d31, d29;\nld.shared.u16 t0, [olp];\nadd.u32 olp, olp, 4;\n"
        "lop3.b32 t1, t0, %50, 0x3ff0, 0xe4;\nld.shared.b32 t1, [t1+%57];\nlop3.b32 kept, t1, t0, 0x1ffc, 0xe4;\nlop3.b32 t2, t1, %51, 3, 0x80;\n"
        "setp.ne.u32 q, t2, 0;\nshr.u32 t2, t1, 13;\nmad.wide.u32 pa, t2, 32, %54;\nmad.wide.u32 pb, t2, 8, %55;\nmov.b32 s0, 0;\n"
        "ld.global.cg.v2.b32 {e0,e1}, [pa];\n@q ld.global.cg.b32 s0, [pb];\nshr.u32 bar, v, 1;\nand.b32 bar, bar, 0xff8;\n"
        "mbarrier.test_wait.parity.shared.b64 p, [bar+%59], 0;\nlop3.b32 ida, v, %51, 0x1fff, 0xe4;\nld.volatile.shared.u16 id, [ida+%58];\n"
        "vote.sync.all.pred prdy, p, 0xffffffff;\n@!prdy bra.uni WA;\n"
        "HA:\nmad.lo.u32 xb, id, 64, %49;\ncvt.u16.u32 i16, id;\natom.shared.add.u32 pos, [%50+%60], %52;\n"
        "ldmatrix.sync.aligned.m8n8.x4.trans.shared.b16 {x0,x1,x2,x3}, [xb];\nldmatrix.sync.aligned.m8n8.x4.trans.shared.b16 {x24,x25,x26,x27}, [xb+512];\n"
        "xor.b32 t1, xb, 32;\nldmatrix.sync.aligned.m8n8.x4.trans.shared.b16 {x4,x5,x6,x7}, [t1];\n"
        "ldmatrix.sync.aligned.m8n8.x4.trans.shared.b16 {x28,x29,x30,x31}, [t1+512];\nxor.b32 t1, xb, 64;\n"
        "ldmatrix.sync.aligned.m8n8.x4.trans.shared.b16 {x8,x9,x10,x11}, [t1];\nldmatrix.sync.aligned.m8n8.x4.trans.shared.b16 {x16,x17,x18,x19}, [t1+512];\n"
        "xor.b32 t1, xb, 96;\nldmatrix.sync.aligned.m8n8.x4.trans.shared.b16 {x12,x13,x14,x15}, [t1];\n"
        "ldmatrix.sync.aligned.m8n8.x4.trans.shared.b16 {x20,x21,x22,x23}, [t1+512];\nst.volatile.shared.u16 [pos], i16;\nand.b32 t0, v, 16384;\n"
        "setp.ne.u32 ps1, t0, 0;\nvote.sync.any.pred ps1, ps1, 0xffffffff;\nand.b32 t0, v, 32768;\nsetp.ne.u32 ps2, t0, 0;\n"
        "vote.sync.any.pred ps2, ps2, 0xffffffff;\nmov.b32 v, vB;\nshr.u32 bar, v, 1;\nand.b32 bar, bar, 0xff8;\n"
        "mbarrier.test_wait.parity.shared.b64 p, [bar+%59], 0;\nlop3.b32 ida, v, %51, 0x1fff, 0xe4;\nld.volatile.shared.u16 id, [ida+%58];\n"
        "vote.sync.all.pred prdy, p, 0xffffffff;\nmov.b32 {lo, hi}, ra0;\nmov.b32 t2, {lo, lo};\nmul.rn.bf16x2 y0, x0, t2;\nmul.rn.bf16x2 y2, x2, t2;\n"
        "mov.b32 t2, {hi, hi};\nmul.rn.bf16x2 y1, x1, t2;\nmul.rn.bf16x2 y3, x3, t2;\n"
        "mma.sync.aligned.m16n8k16.row.col.f32.bf16.bf16.f32 {d0,d1,d2,d3}, {y0,y1,y2,y3}, {bA0,bA1}, {fz,fz,fz,fz};\ncvt.rn.bf16x2.f32 z0, d1, d0;\n"
        "cvt.rn.bf16x2.f32 z1, d3, d2;\nmov.b32 {lo, hi}, ra6;\nmov.b32 t2, {lo, lo};\nmul.rn.bf16x2 y24, x24, t2;\nmul.rn.bf16x2 y26, x26, t2;\n"
        "mov.b32 t2, {hi, hi};\nmul.rn.bf16x2 y25, x25, t2;\nmul.rn.bf16x2 y27, x27, t2;\n"
        "mma.sync.aligned.m16n8k16.row.col.f32.bf16.bf16.f32 {d24,d25,d26,d27}, {y24,y25,y26,y27}, {bA0,bA1}, {fz,fz,fz,fz};\ncvt.rn.bf16x2.f32 z12, d25, d24;\n"
        "cvt.rn.bf16x2.f32 z13, d27, d26;\nmov.b32 {lo, hi}, ra1;\nmov.b32 t2, {lo, lo};\nmul.rn.bf16x2 y4, x4, t2;\nmul.rn.bf16x2 y6, x6, t2;\n"
        "mov.b32 t2, {hi, hi};\nmul.rn.bf16x2 y5, x5, t2;\nmul.rn.bf16x2 y7, x7, t2;\n"
        "mma.sync.aligned.m16n8k16.row.col.f32.bf16.bf16.f32 {d4,d5,d6,d7}, {y4,y5,y6,y7}, {bA0,bA1}, {fz,fz,fz,fz};\ncvt.rn.bf16x2.f32 z2, d5, d4;\n"
        "cvt.rn.bf16x2.f32 z3, d7, d6;\nmov.b32 {lo, hi}, ra7;\nmov.b32 t2, {lo, lo};\nmul.rn.bf16x2 y28, x28, t2;\nmul.rn.bf16x2 y30, x30, t2;\n"
        "mov.b32 t2, {hi, hi};\nmul.rn.bf16x2 y29, x29, t2;\nmul.rn.bf16x2 y31, x31, t2;\n"
        "mma.sync.aligned.m16n8k16.row.col.f32.bf16.bf16.f32 {d28,d29,d30,d31}, {y28,y29,y30,y31}, {bA0,bA1}, {fz,fz,fz,fz};\ncvt.rn.bf16x2.f32 z14, d29, d28;\n"
        "cvt.rn.bf16x2.f32 z15, d31, d30;\nmov.b32 {lo, hi}, ra2;\nmov.b32 t2, {lo, lo};\nmul.rn.bf16x2 y8, x8, t2;\nmul.rn.bf16x2 y10, x10, t2;\n"
        "mov.b32 t2, {hi, hi};\nmul.rn.bf16x2 y9, x9, t2;\nmul.rn.bf16x2 y11, x11, t2;\n"
        "mma.sync.aligned.m16n8k16.row.col.f32.bf16.bf16.f32 {d8,d9,d10,d11}, {y8,y9,y10,y11}, {bA0,bA1}, {fz,fz,fz,fz};\ncvt.rn.bf16x2.f32 z4, d9, d8;\n"
        "cvt.rn.bf16x2.f32 z5, d11, d10;\nmov.b32 {lo, hi}, ra4;\nmov.b32 t2, {lo, lo};\nmul.rn.bf16x2 y16, x16, t2;\nmul.rn.bf16x2 y18, x18, t2;\n"
        "mov.b32 t2, {hi, hi};\nmul.rn.bf16x2 y17, x17, t2;\nmul.rn.bf16x2 y19, x19, t2;\n"
        "mma.sync.aligned.m16n8k16.row.col.f32.bf16.bf16.f32 {d16,d17,d18,d19}, {y16,y17,y18,y19}, {bA0,bA1}, {fz,fz,fz,fz};\ncvt.rn.bf16x2.f32 z8, d17, d16;\n"
        "cvt.rn.bf16x2.f32 z9, d19, d18;\nmov.b32 {lo, hi}, ra3;\nmov.b32 t2, {lo, lo};\nmul.rn.bf16x2 y12, x12, t2;\nmul.rn.bf16x2 y14, x14, t2;\n"
        "mov.b32 t2, {hi, hi};\nmul.rn.bf16x2 y13, x13, t2;\nmul.rn.bf16x2 y15, x15, t2;\n"
        "mma.sync.aligned.m16n8k16.row.col.f32.bf16.bf16.f32 {d12,d13,d14,d15}, {y12,y13,y14,y15}, {bA0,bA1}, {fz,fz,fz,fz};\ncvt.rn.bf16x2.f32 z6, d13, d12;\n"
        "cvt.rn.bf16x2.f32 z7, d15, d14;\nmov.b32 {lo, hi}, ra5;\nmov.b32 t2, {lo, lo};\nmul.rn.bf16x2 y20, x20, t2;\nmul.rn.bf16x2 y22, x22, t2;\n"
        "mov.b32 t2, {hi, hi};\nmul.rn.bf16x2 y21, x21, t2;\nmul.rn.bf16x2 y23, x23, t2;\n"
        "mma.sync.aligned.m16n8k16.row.col.f32.bf16.bf16.f32 {d20,d21,d22,d23}, {y20,y21,y22,y23}, {bA0,bA1}, {fz,fz,fz,fz};\ncvt.rn.bf16x2.f32 z10, d21, d20;\n"
        "cvt.rn.bf16x2.f32 z11, d23, d22;\n@ps2 bra.uni TA2;\n@ps1 bra.uni TA1;\n"
        "TA0:\nadd.rn.bf16x2 h0, h0, z0;\nadd.rn.bf16x2 h1, h1, z1;\nadd.rn.bf16x2 h2, h2, z2;\nadd.rn.bf16x2 h3, h3, z3;\nadd.rn.bf16x2 h4, h4, z4;\n"
        "add.rn.bf16x2 h5, h5, z5;\nadd.rn.bf16x2 h6, h6, z6;\nadd.rn.bf16x2 h7, h7, z7;\nadd.rn.bf16x2 h8, h8, z8;\nadd.rn.bf16x2 h9, h9, z9;\n"
        "add.rn.bf16x2 h10, h10, z10;\nadd.rn.bf16x2 h11, h11, z11;\nadd.rn.bf16x2 h12, h12, z12;\nadd.rn.bf16x2 h13, h13, z13;\nadd.rn.bf16x2 h14, h14, z14;\n"
        "add.rn.bf16x2 h15, h15, z15;\n@prdy bra.uni HB;\nbra.uni WB;\n"
        "TA1:\nadd.rn.bf16x2 h16, h16, z0;\nadd.rn.bf16x2 h17, h17, z1;\nadd.rn.bf16x2 h18, h18, z2;\nadd.rn.bf16x2 h19, h19, z3;\nadd.rn.bf16x2 h20, h20, z4;\n"
        "add.rn.bf16x2 h21, h21, z5;\nadd.rn.bf16x2 h22, h22, z6;\nadd.rn.bf16x2 h23, h23, z7;\nadd.rn.bf16x2 h24, h24, z8;\nadd.rn.bf16x2 h25, h25, z9;\n"
        "add.rn.bf16x2 h26, h26, z10;\nadd.rn.bf16x2 h27, h27, z11;\nadd.rn.bf16x2 h28, h28, z12;\nadd.rn.bf16x2 h29, h29, z13;\nadd.rn.bf16x2 h30, h30, z14;\n"
        "add.rn.bf16x2 h31, h31, z15;\n@prdy bra.uni HB;\nbra.uni WB;\n"
        "TA2:\nadd.rn.bf16x2 h32, h32, z0;\nadd.rn.bf16x2 h33, h33, z1;\nadd.rn.bf16x2 h34, h34, z2;\nadd.rn.bf16x2 h35, h35, z3;\nadd.rn.bf16x2 h36, h36, z4;\n"
        "add.rn.bf16x2 h37, h37, z5;\nadd.rn.bf16x2 h38, h38, z6;\nadd.rn.bf16x2 h39, h39, z7;\nadd.rn.bf16x2 h40, h40, z8;\nadd.rn.bf16x2 h41, h41, z9;\n"
        "add.rn.bf16x2 h42, h42, z10;\nadd.rn.bf16x2 h43, h43, z11;\nadd.rn.bf16x2 h44, h44, z12;\nadd.rn.bf16x2 h45, h45, z13;\nadd.rn.bf16x2 h46, h46, z14;\n"
        "add.rn.bf16x2 h47, h47, z15;\n@prdy bra.uni HB;\nbra.uni WB;\n"
        "HB:\nmad.lo.u32 xb, id, 64, %49;\ncvt.u16.u32 i16, id;\natom.shared.add.u32 pos, [%50+%60], %52;\n"
        "ldmatrix.sync.aligned.m8n8.x4.trans.shared.b16 {x0,x1,x2,x3}, [xb];\nldmatrix.sync.aligned.m8n8.x4.trans.shared.b16 {x24,x25,x26,x27}, [xb+512];\n"
        "xor.b32 t1, xb, 32;\nldmatrix.sync.aligned.m8n8.x4.trans.shared.b16 {x4,x5,x6,x7}, [t1];\n"
        "ldmatrix.sync.aligned.m8n8.x4.trans.shared.b16 {x28,x29,x30,x31}, [t1+512];\nxor.b32 t1, xb, 64;\n"
        "ldmatrix.sync.aligned.m8n8.x4.trans.shared.b16 {x8,x9,x10,x11}, [t1];\nldmatrix.sync.aligned.m8n8.x4.trans.shared.b16 {x16,x17,x18,x19}, [t1+512];\n"
        "xor.b32 t1, xb, 96;\nldmatrix.sync.aligned.m8n8.x4.trans.shared.b16 {x12,x13,x14,x15}, [t1];\n"
        "ldmatrix.sync.aligned.m8n8.x4.trans.shared.b16 {x20,x21,x22,x23}, [t1+512];\nst.volatile.shared.u16 [pos], i16;\nand.b32 t0, v, 16384;\n"
        "setp.ne.u32 ps1, t0, 0;\nvote.sync.any.pred ps1, ps1, 0xffffffff;\nand.b32 t0, v, 32768;\nsetp.ne.u32 ps2, t0, 0;\n"
        "vote.sync.any.pred ps2, ps2, 0xffffffff;\nshfl.sync.idx.b32 v, kept, %51, 0x1f, 0xffffffff;\nshfl.sync.idx.b32 vB, kept, t3, 0x1f, 0xffffffff;\n"
        "mov.b32 {lo, hi}, rb0;\nmov.b32 t2, {lo, lo};\nmul.rn.bf16x2 y0, x0, t2;\nmul.rn.bf16x2 y2, x2, t2;\nmov.b32 t2, {hi, hi};\nmul.rn.bf16x2 y1, x1, t2;\n"
        "mul.rn.bf16x2 y3, x3, t2;\nmma.sync.aligned.m16n8k16.row.col.f32.bf16.bf16.f32 {d0,d1,d2,d3}, {y0,y1,y2,y3}, {bB0,bB1}, {fz,fz,fz,fz};\n"
        "cvt.rn.bf16x2.f32 z0, d1, d0;\ncvt.rn.bf16x2.f32 z1, d3, d2;\nmov.b32 {lo, hi}, rb6;\nmov.b32 t2, {lo, lo};\nmul.rn.bf16x2 y24, x24, t2;\n"
        "mul.rn.bf16x2 y26, x26, t2;\nmov.b32 t2, {hi, hi};\nmul.rn.bf16x2 y25, x25, t2;\nmul.rn.bf16x2 y27, x27, t2;\n"
        "mma.sync.aligned.m16n8k16.row.col.f32.bf16.bf16.f32 {d24,d25,d26,d27}, {y24,y25,y26,y27}, {bB0,bB1}, {fz,fz,fz,fz};\ncvt.rn.bf16x2.f32 z12, d25, d24;\n"
        "cvt.rn.bf16x2.f32 z13, d27, d26;\nmov.b32 {lo, hi}, rb1;\nmov.b32 t2, {lo, lo};\nmul.rn.bf16x2 y4, x4, t2;\nmul.rn.bf16x2 y6, x6, t2;\n"
        "mov.b32 t2, {hi, hi};\nmul.rn.bf16x2 y5, x5, t2;\nmul.rn.bf16x2 y7, x7, t2;\n"
        "mma.sync.aligned.m16n8k16.row.col.f32.bf16.bf16.f32 {d4,d5,d6,d7}, {y4,y5,y6,y7}, {bB0,bB1}, {fz,fz,fz,fz};\ncvt.rn.bf16x2.f32 z2, d5, d4;\n"
        "cvt.rn.bf16x2.f32 z3, d7, d6;\nmov.b32 {lo, hi}, rb7;\nmov.b32 t2, {lo, lo};\nmul.rn.bf16x2 y28, x28, t2;\nmul.rn.bf16x2 y30, x30, t2;\n"
        "mov.b32 t2, {hi, hi};\nmul.rn.bf16x2 y29, x29, t2;\nmul.rn.bf16x2 y31, x31, t2;\n"
        "mma.sync.aligned.m16n8k16.row.col.f32.bf16.bf16.f32 {d28,d29,d30,d31}, {y28,y29,y30,y31}, {bB0,bB1}, {fz,fz,fz,fz};\ncvt.rn.bf16x2.f32 z14, d29, d28;\n"
        "cvt.rn.bf16x2.f32 z15, d31, d30;\nmov.b32 {lo, hi}, rb2;\nmov.b32 t2, {lo, lo};\nmul.rn.bf16x2 y8, x8, t2;\nmul.rn.bf16x2 y10, x10, t2;\n"
        "mov.b32 t2, {hi, hi};\nmul.rn.bf16x2 y9, x9, t2;\nmul.rn.bf16x2 y11, x11, t2;\n"
        "mma.sync.aligned.m16n8k16.row.col.f32.bf16.bf16.f32 {d8,d9,d10,d11}, {y8,y9,y10,y11}, {bB0,bB1}, {fz,fz,fz,fz};\ncvt.rn.bf16x2.f32 z4, d9, d8;\n"
        "cvt.rn.bf16x2.f32 z5, d11, d10;\nmov.b32 {lo, hi}, rb4;\nmov.b32 t2, {lo, lo};\nmul.rn.bf16x2 y16, x16, t2;\nmul.rn.bf16x2 y18, x18, t2;\n"
        "mov.b32 t2, {hi, hi};\nmul.rn.bf16x2 y17, x17, t2;\nmul.rn.bf16x2 y19, x19, t2;\n"
        "mma.sync.aligned.m16n8k16.row.col.f32.bf16.bf16.f32 {d16,d17,d18,d19}, {y16,y17,y18,y19}, {bB0,bB1}, {fz,fz,fz,fz};\ncvt.rn.bf16x2.f32 z8, d17, d16;\n"
        "cvt.rn.bf16x2.f32 z9, d19, d18;\nmov.b32 {lo, hi}, rb3;\nmov.b32 t2, {lo, lo};\nmul.rn.bf16x2 y12, x12, t2;\nmul.rn.bf16x2 y14, x14, t2;\n"
        "mov.b32 t2, {hi, hi};\nmul.rn.bf16x2 y13, x13, t2;\nmul.rn.bf16x2 y15, x15, t2;\n"
        "mma.sync.aligned.m16n8k16.row.col.f32.bf16.bf16.f32 {d12,d13,d14,d15}, {y12,y13,y14,y15}, {bB0,bB1}, {fz,fz,fz,fz};\ncvt.rn.bf16x2.f32 z6, d13, d12;\n"
        "cvt.rn.bf16x2.f32 z7, d15, d14;\nmov.b32 {lo, hi}, rb5;\nmov.b32 t2, {lo, lo};\nmul.rn.bf16x2 y20, x20, t2;\nmul.rn.bf16x2 y22, x22, t2;\n"
        "mov.b32 t2, {hi, hi};\nmul.rn.bf16x2 y21, x21, t2;\nmul.rn.bf16x2 y23, x23, t2;\n"
        "mma.sync.aligned.m16n8k16.row.col.f32.bf16.bf16.f32 {d20,d21,d22,d23}, {y20,y21,y22,y23}, {bB0,bB1}, {fz,fz,fz,fz};\ncvt.rn.bf16x2.f32 z10, d21, d20;\n"
        "cvt.rn.bf16x2.f32 z11, d23, d22;\n@ps2 bra.uni TB2;\n@ps1 bra.uni TB1;\n"
        "TB0:\nadd.rn.bf16x2 h0, h0, z0;\nadd.rn.bf16x2 h1, h1, z1;\nadd.rn.bf16x2 h2, h2, z2;\nadd.rn.bf16x2 h3, h3, z3;\nadd.rn.bf16x2 h4, h4, z4;\n"
        "add.rn.bf16x2 h5, h5, z5;\nadd.rn.bf16x2 h6, h6, z6;\nadd.rn.bf16x2 h7, h7, z7;\nadd.rn.bf16x2 h8, h8, z8;\nadd.rn.bf16x2 h9, h9, z9;\n"
        "add.rn.bf16x2 h10, h10, z10;\nadd.rn.bf16x2 h11, h11, z11;\nadd.rn.bf16x2 h12, h12, z12;\nadd.rn.bf16x2 h13, h13, z13;\nadd.rn.bf16x2 h14, h14, z14;\n"
        "add.rn.bf16x2 h15, h15, z15;\nbra.uni RW;\n"
        "TB1:\nadd.rn.bf16x2 h16, h16, z0;\nadd.rn.bf16x2 h17, h17, z1;\nadd.rn.bf16x2 h18, h18, z2;\nadd.rn.bf16x2 h19, h19, z3;\nadd.rn.bf16x2 h20, h20, z4;\n"
        "add.rn.bf16x2 h21, h21, z5;\nadd.rn.bf16x2 h22, h22, z6;\nadd.rn.bf16x2 h23, h23, z7;\nadd.rn.bf16x2 h24, h24, z8;\nadd.rn.bf16x2 h25, h25, z9;\n"
        "add.rn.bf16x2 h26, h26, z10;\nadd.rn.bf16x2 h27, h27, z11;\nadd.rn.bf16x2 h28, h28, z12;\nadd.rn.bf16x2 h29, h29, z13;\nadd.rn.bf16x2 h30, h30, z14;\n"
        "add.rn.bf16x2 h31, h31, z15;\nbra.uni RW;\n"
        "TB2:\nadd.rn.bf16x2 h32, h32, z0;\nadd.rn.bf16x2 h33, h33, z1;\nadd.rn.bf16x2 h34, h34, z2;\nadd.rn.bf16x2 h35, h35, z3;\nadd.rn.bf16x2 h36, h36, z4;\n"
        "add.rn.bf16x2 h37, h37, z5;\nadd.rn.bf16x2 h38, h38, z6;\nadd.rn.bf16x2 h39, h39, z7;\nadd.rn.bf16x2 h40, h40, z8;\nadd.rn.bf16x2 h41, h41, z9;\n"
        "add.rn.bf16x2 h42, h42, z10;\nadd.rn.bf16x2 h43, h43, z11;\nadd.rn.bf16x2 h44, h44, z12;\nadd.rn.bf16x2 h45, h45, z13;\nadd.rn.bf16x2 h46, h46, z14;\n"
        "add.rn.bf16x2 h47, h47, z15;\nbra.uni RW;\n"
        "WA:\nshr.u32 t2, v, 1;\nand.b32 t2, t2, 0xff8;\nsetp.eq.u32 p, t2, 0;\nvote.sync.all.pred p, p, 0xffffffff;\n@p bra.uni DONE;\nmov.b32 n, 0;\n"
        "WA3:\nmbarrier.try_wait.parity.shared.b64 p, [t2+%59], 0;\nvote.sync.all.pred p, p, 0xffffffff;\nadd.u32 n, n, 1;\nsetp.lt.and.u32 q, n, 1000000, !p;\n"
        "@q bra.uni WA3;\nlop3.b32 ida, v, %51, 0x1fff, 0xe4;\nld.volatile.shared.u16 id, [ida+%58];\nbra.uni HA;\n"
        "WB:\nshr.u32 t2, v, 1;\nand.b32 t2, t2, 0xff8;\nsetp.eq.u32 p, t2, 0;\nvote.sync.all.pred p, p, 0xffffffff;\n@p bra.uni DONE;\nmov.b32 n, 0;\n"
        "WB3:\nmbarrier.try_wait.parity.shared.b64 p, [t2+%59], 0;\nvote.sync.all.pred p, p, 0xffffffff;\nadd.u32 n, n, 1;\nsetp.lt.and.u32 q, n, 1000000, !p;\n"
        "@q bra.uni WB3;\nlop3.b32 ida, v, %51, 0x1fff, 0xe4;\nld.volatile.shared.u16 id, [ida+%58];\nbra.uni HB;\n"
        "DONE:\nmov.b32 %0, h0;\nmov.b32 %1, h1;\nmov.b32 %2, h2;\nmov.b32 %3, h3;\nmov.b32 %4, h4;\nmov.b32 %5, h5;\nmov.b32 %6, h6;\nmov.b32 %7, h7;\n"
        "mov.b32 %8, h8;\nmov.b32 %9, h9;\nmov.b32 %10, h10;\nmov.b32 %11, h11;\nmov.b32 %12, h12;\nmov.b32 %13, h13;\nmov.b32 %14, h14;\nmov.b32 %15, h15;\n"
        "mov.b32 %16, h16;\nmov.b32 %17, h17;\nmov.b32 %18, h18;\nmov.b32 %19, h19;\nmov.b32 %20, h20;\nmov.b32 %21, h21;\nmov.b32 %22, h22;\nmov.b32 %23, h23;\n"
        "mov.b32 %24, h24;\nmov.b32 %25, h25;\nmov.b32 %26, h26;\nmov.b32 %27, h27;\nmov.b32 %28, h28;\nmov.b32 %29, h29;\nmov.b32 %30, h30;\nmov.b32 %31, h31;\n"
        "mov.b32 %32, h32;\nmov.b32 %33, h33;\nmov.b32 %34, h34;\nmov.b32 %35, h35;\nmov.b32 %36, h36;\nmov.b32 %37, h37;\nmov.b32 %38, h38;\nmov.b32 %39, h39;\n"
        "mov.b32 %40, h40;\nmov.b32 %41, h41;\nmov.b32 %42, h42;\nmov.b32 %43, h43;\nmov.b32 %44, h44;\nmov.b32 %45, h45;\nmov.b32 %46, h46;\nmov.b32 %47, h47;\n"
        "}\n"
        : "=r"(pk[0]), "=r"(pk[1]), "=r"(pk[2]), "=r"(pk[3]), "=r"(pk[4]), "=r"(pk[5]), "=r"(pk[6]), "=r"(pk[7]), "=r"(pk[8]), "=r"(pk[9]),
          "=r"(pk[10]), "=r"(pk[11]), "=r"(pk[12]), "=r"(pk[13]), "=r"(pk[14]), "=r"(pk[15]), "=r"(pk[16]), "=r"(pk[17]), "=r"(pk[18]), "=r"(pk[19]),
          "=r"(pk[20]), "=r"(pk[21]), "=r"(pk[22]), "=r"(pk[23]), "=r"(pk[24]), "=r"(pk[25]), "=r"(pk[26]), "=r"(pk[27]), "=r"(pk[28]), "=r"(pk[29]),
          "=r"(pk[30]), "=r"(pk[31]), "=r"(pk[32]), "=r"(pk[33]), "=r"(pk[34]), "=r"(pk[35]), "=r"(pk[36]), "=r"(pk[37]), "=r"(pk[38]), "=r"(pk[39]),
          "=r"(pk[40]), "=r"(pk[41]), "=r"(pk[42]), "=r"(pk[43]), "=r"(pk[44]), "=r"(pk[45]), "=r"(pk[46]), "=r"(pk[47])
        : "r"(olp), "r"(xa), "r"(ln), "r"(lc), "r"(linc), "r"(lt), "l"(ea), "l"(sh), "l"(wf),
          "n"(sb + SM_REC), "n"(sb + SM_R), "n"(sb + SM_BAR), "n"(sb + SM_CTR),
          "r"(w[0]), "r"(w[1]), "r"(w[2]), "r"(w[3]), "r"(w[4]), "r"(w[5]), "r"(w[6]), "r"(w[7]), "r"(w[8]), "r"(w[9]), "r"(w[10]), "r"(w[11]),
          "r"(w[12]), "r"(w[13]), "r"(w[14]), "r"(w[15]), "r"(w[16]), "r"(w[17]), "r"(w[18]), "r"(w[19]), "r"(w[20]), "r"(w[21]), "r"(w[22]),
          "r"(w[23]), "r"(w[24]), "r"(w[25]), "r"(w[26]), "r"(w[27]), "r"(w[28]), "r"(w[29]), "r"(w[30]), "r"(w[31]), "r"(w[32]), "r"(w[33]),
          "r"(w[34]), "r"(w[35])
        : "memory");
}

__device__ __forceinline__ void wf_done() {
    asm volatile("fence.proxy.async.global;\nred.release.gpu.global.add.u32 [%0+12], 1;" ::"l"(g_sync) : "memory");
}

template <int NS>
__device__ __forceinline__ void consumer(const __nv_bfloat16* __restrict__ sh,
                                         const __nv_bfloat16* __restrict__ ea, __nv_bfloat16* __restrict__ out, int N, int npb) {
    uint32_t pk[NS * 16];
    {
        const int lane = threadIdx.x & 31, warp = threadIdx.x >> 5;
        const int mi = lane >> 3, r = lane & 7, j = r >> 1;
        const int u = 2 * ((mi >> 1) ^ (j >> 1)) + (r & 1), ph = (j ^ (j >> 1)) & 1;
        uint32_t w[36];
        {
            const uint32_t a = sb + SC_WR + (4 * j + (r & 1) + (mi & 2)) * 272 + (mi & 1) * 16;
#pragma unroll
            for (int c = 0; c < 8; c++)
                asm volatile("ldmatrix.sync.aligned.m8n8.x4.trans.shared.b16 {%0,%1,%2,%3}, [%4];"
                             : "=r"(w[4 * c]), "=r"(w[4 * c + 1]), "=r"(w[4 * c + 2]), "=r"(w[4 * c + 3]) : "r"(a + c * 32) : "memory");
            const uint32_t ca = sb + SC_CG + (lane & 2) * 8 + ((lane >> 2) & 3) * 2;
#pragma unroll
            for (int k = 0; k < 4; k++) {
                const uint32_t f = lds16(ca + 32 * k) | (lds16(ca + 32 * k + 8) << 16);
                w[32 + k] = (lane & 1) == (lane >> 4) ? f : 0;
            }
            asm volatile("fence.proxy.async.shared::cta;\nbar.sync 2, %0;" ::"n"(NCW * 32) : "memory");
            if (threadIdx.x < WSL) sts16(sb + SM_R + 0x2000 + (4 + SP - WSL + lane) * 4, (sb + SC_WR) / 64 + lane * 16);
        }
        const uint32_t xa = __shfl_sync(0xffffffffu, u * 128 + (((u + 4 * ph) ^ (mi & 1)) << 4), lane);
        const uint32_t ln = __shfl_sync(0xffffffffu, lane * 16 + (lane >> 3) * 4, lane);
        const uint32_t lc = __shfl_sync(0xffffffffu, j * 8 + (1 << (lane & 1)) + (ph << 13), lane);
        const uint32_t linc = __shfl_sync(0xffffffffu, (lane & 0x19) ? 0 : 8, lane);
        const uint32_t lt = __shfl_sync(0xffffffffu, lane & 3, lane);
        const void* wfp = (threadIdx.x >> 2) == WFT && blockIdx.x < 128 ? g_sync : nullptr;
        const uint32_t olp = sb + SM_OL + warp * (OLN * 2) + ((lane & 4) >> 1);
        if constexpr (NS == 4) consume4(pk, w, olp, xa, ln, lc, linc, lt, ea, sh, wfp);
        else consume3(pk, w, olp, xa, ln, lc, linc, lt, ea, sh, wfp);
    }
    TLMAX(10);
    const int tid = thread_id(), lane = tid & 31, warp = tid >> 5, g = lane >> 2, t = lane & 3;
    const uint32_t wc = lds32(sb + SM_MISC + 12) + 1;
    const uint32_t inv = lds32(sb + SM_INV + warp * 4);
    const int node0 = cta_id() * npb, nnodes = min(npb, N - node0);
    uint4* op[NS];
    uint32_t on[NS];
#pragma unroll
    for (int s = 0; s < NS; s++) {
        const int nl = ((inv >> (8 * s)) & 255) + (g >> 2) * 40;
        op[s] = (uint4*)(out + ((size_t)(node0 + nl) * 4 + (g & 3)) * 128 + 8 * t);
        on[s] = nl < nnodes;
    }
    if constexpr (NS == 4) project4(pk, sb + SM_R + wc * 16, sb + SM_BAR + wc * 8, op, on);
    else project3(pk, sb + SM_R + wc * 16, sb + SM_BAR + wc * 8, op, on);
}

#define TLHI "shl.b32 d, tb, 16;\n"
#define RAOFF ((threadIdx.x & 96) >> 1)
#define UNPACK(v) "dp2a.lo.u32.u32 d, " #v ", k64, 0;\nshr.s32 r, " #v ", 14;\n"
#define XSTR(x) XSTR2(x)
#define XSTR2(x) #x
__device__ __forceinline__ void producer(const CUtensorMap* tmx, int pw) {
    const uint32_t nch = lds32(sb + SM_MISC + 12), c0 = lds32(sb + SM_MISC + 24);
    if (elect()) {
        asm volatile(
            "{\n.reg .pred p, q, lead, never;\n.reg .b32 ra, oa, off, due, now, a<4>, b<4>, d, r, z<8>, bar<4>, t, n, tb, ta, k64, ktx;\n"
            ".reg .b64 lg, t64, tm;\n"
            "mov.b32 ta, %5;\nld.volatile.shared.v4.b32 {z0,z1,z2,z3}, [ta+32];\nld.volatile.shared.v4.b32 {z4,z5,z6,z7}, [ta+32];\n"
            "mov.b32 ra, %9;\nmad.lo.u32 t, %0, 8, %10;\n"
            "add.u32 bar0, t, z0;\nadd.u32 bar1, t, z1;\nadd.u32 bar2, t, z2;\nadd.u32 bar3, t, z3;\nsetp.ne.u32 never, z0, 0;\n"
            "add.u32 k64, z4, 64;\nadd.u32 ktx, z5, 8192;\ncvt.u64.u32 tm, z6;\nadd.u64 tm, tm, %3;\n"
            "mov.b32 n, 0;\nld.volatile.shared.b32 tb, [ta];\nsetp.eq.u32 lead, %0, 0;\n"
            "mov.u32 due, %%globaltimer_lo;\n"
            "setp.gt.u32 p, ra, %1;\n@p bra.uni END;\nshr.u32 oa, ra, 3;\n"
            "FIRST:\n"
            "ld.volatile.shared.u16 off, [oa+%11-8];\nmov.u32 now, %%globaltimer_lo;\nadd.u32 due, tb, off;\nsub.u32 t, due, now;\n"
            "setp.gt.s32 p, t, %12;\n@p bra.uni FIRST;\n"
            "GO:\n"
            "ld.volatile.shared.v4.b32 {a0,a1,a2,a3}, [ra];\nld.volatile.shared.v4.b32 {b0,b1,b2,b3}, [ra+0x2000];\n"
            "shr.u32 oa, ra, 3;\nld.volatile.shared.u16 off, [oa+%11];\nld.volatile.shared.b32 tb, [ta];\n"
            "mov.u32 now, %%globaltimer_lo;\n"
            "lop3.b32 t, a0, a1, a2, 0xfe;\nlop3.b32 d, a3, b0, b1, 0xfe;\nlop3.b32 t, t, d, b2, 0xfe;\nor.b32 t, t, b3;\nand.b32 t, t, 1;\n"
            "setp.ne.u32 p, t, 0;\n"
            "@p bra.uni BACK;\n"
            "shl.b32 t, oa, 2;\nmbarrier.arrive.expect_tx.shared.b64 _, [t+%13], ktx;\n"
            "add.u32 bar0, bar0, 32;\nadd.u32 bar1, bar1, 32;\nadd.u32 bar2, bar2, 32;\nadd.u32 bar3, bar3, 32;\n"
            UNPACK(a0)
            "cp.async.bulk.tensor.3d.shared::cluster.global.mbarrier::complete_tx::bytes [d], [tm, {z0, r, z1}], [bar0];\n"
            UNPACK(b0)
            "cp.async.bulk.tensor.3d.shared::cluster.global.mbarrier::complete_tx::bytes [d], [tm, {z2, r, z3}], [bar1];\n"
            UNPACK(a1)
            "cp.async.bulk.tensor.3d.shared::cluster.global.mbarrier::complete_tx::bytes [d], [tm, {z4, r, z5}], [bar2];\n"
            UNPACK(b1)
            "cp.async.bulk.tensor.3d.shared::cluster.global.mbarrier::complete_tx::bytes [d], [tm, {z6, r, z7}], [bar3];\n"
            "@never bra.uni END;\n"
            "add.u32 ra, ra, 64;\nadd.u32 due, off, tb;\nsub.u32 t, due, now;\nsetp.le.u32 q, ra, %1;\nsetp.le.and.u32 q, t, %2, q;\n"
            UNPACK(a2)
            "cp.async.bulk.tensor.3d.shared::cluster.global.mbarrier::complete_tx::bytes [d], [tm, {z0, r, z1}], [bar0];\n"
            UNPACK(b2)
            "cp.async.bulk.tensor.3d.shared::cluster.global.mbarrier::complete_tx::bytes [d], [tm, {z2, r, z3}], [bar1];\n"
            UNPACK(a3)
            "cp.async.bulk.tensor.3d.shared::cluster.global.mbarrier::complete_tx::bytes [d], [tm, {z4, r, z5}], [bar2];\n"
            UNPACK(b3)
            "cp.async.bulk.tensor.3d.shared::cluster.global.mbarrier::complete_tx::bytes [d], [tm, {z6, r, z7}], [bar3];\n"
            "@q bra.uni GO;\n"
            "setp.gt.u32 p, ra, %1;\n@p bra.uni END;\n@!lead bra.uni WAIT;\n"
            "add.u32 d, ta, 16;\ncp.async.bulk.shared::cluster.global.mbarrier::complete_tx::bytes [ta], [%4], 16, [d];\n"
            "setp.ge.s32 p, t, 0;\n@p bra.uni WAIT;\n"
            "setp.lt.u32 p, ra, %8;\n@p bra.uni GO;\nadd.u32 r, ra, " XSTR(SLIPEND) ";\nsetp.gt.u32 p, r, %1;\n@p bra.uni GO;\n"
            "ld.volatile.shared.b64 t64, [ta];\ncvt.u32.u64 r, t64;\nsub.u32 r, tb, r;\nsub.u32 d, %7, t;\nadd.s32 d, d, r;\n"
            "cvt.s64.s32 lg, d;\nadd.u64 t64, t64, lg;\n"
            "red.relaxed.gpu.global.max.u64 [%4], t64;\n"
            "bra.uni GO;\n"
            "SLEEP:\n"
            "nanosleep.u32 32;\nld.volatile.shared.b32 tb, [ta];\nld.volatile.shared.u16 off, [oa+%11];\nadd.u32 due, tb, off;\n"
            "WAIT:\n"
            "mov.u32 now, %%globaltimer_lo;\nsub.u32 t, due, now;\nsetp.gt.s32 p, t, %6;\nsetp.gt.s32 q, t, %12;\n@p bra.uni SLEEP;\n"
            "@q bra.uni WAIT;\nbra.uni GO;\n"
            "BACK:\n"
            "nanosleep.u32 32;\nsub.u32 t, now, tb;\nsetp.lt.s32 p, t, 200000000;\n@p bra.uni GO;\n"
            "END:\n}" ::"r"(pw),
            "r"(sb + SM_R + nch * 16), "n"(AHEAD + EARLY + SLIPTH), "l"(tmx), "l"(g_sync), "n"(sb + SM_MISC + 32), "n"(SPINT + SLIPTH), "n"(SLIPADD),
            "n"(sb + SM_R + SLIPFROM * 16), "r"(sb + SM_R + 16 + c0 * 16 + RAOFF), "r"(sb + SM_BAR + 8 - 32 + c0 * 8),
            "n"(sb + SM_OFF + 8 - (sb + SM_R) / 8), "n"(EARLY + SLIPTH), "n"(sb + SM_BAR - (sb + SM_R) / 2)
            : "memory");
        const uint32_t wch = lds32(sb + SM_MISC + 12) + 1 + pw;
        const uint32_t ra = sb + SM_R + wch * 16, bar = sb + SM_BAR + wch * 8;
        const uint32_t target = lds32(sb + SM_MISC + 16);
        uint32_t cnt = lds128(sb + SM_MISC + 32).w;
        for (int n = 0; n < 1000000 && (int)(cnt - target) < 0; n++)
            asm volatile("ld.acquire.gpu.global.u32 %0, [%1+12];" : "=r"(cnt) : "l"(g_sync) : "memory");
        uint4 a, b;
        for (int n = 0; n < 1000000; n++) {
            a = lds128(ra), b = lds128(ra + 0x2000);
            if (!((a.x | a.y | a.z | a.w | b.x | b.y | b.z | b.w) & 1)) break;
        }
        asm volatile("fence.proxy.async.global;" ::: "memory");
        asm volatile("mbarrier.arrive.expect_tx.shared.b64 _, [%0], 8192;" ::"r"(bar) : "memory");
        const uint32_t c[8] = {a.x, a.y, a.z, a.w, b.x, b.y, b.z, b.w};
#pragma unroll
        for (int i = 0; i < 8; i++)
            asm volatile("cp.async.bulk.shared::cluster.global.mbarrier::complete_tx::bytes [%0], [%1], 1024, [%2];" ::"r"(
                             (c[i] & 0xffe) << 6),
                         "l"(g_wf + (pw * 8 + i) * 64), "r"(bar)
                         : "memory");
    }
}

#define BARINIT(w, n)                                                                                              \
    if (elect()) {                                                                                                 \
        _Pragma("unroll") for (int k = 0; k < (NBAR + n - 1) / n; k++)                                             \
            asm volatile("mbarrier.init.shared.b64 [%0], 1;" ::"r"(sb + SM_BAR + ((w) * ((NBAR + n - 1) / n) + k) * 8)); \
        asm volatile("fence.mbarrier_init.release.cluster;" ::: "memory");                                         \
    }                                                                                                              \
    __syncwarp();

__global__ void __launch_bounds__(NT, 1)
main_kernel(const __grid_constant__ CUtensorMap tmx, const __nv_bfloat16* __restrict__ x, const int* __restrict__ src,
            const int* __restrict__ dst, const __nv_bfloat16* __restrict__ sh, const __nv_bfloat16* __restrict__ ea,
            const __nv_bfloat16* __restrict__ cg, const __nv_bfloat16* __restrict__ wr,
            const __nv_bfloat16* __restrict__ wout, __nv_bfloat16* __restrict__ out, int N, int E, int npb,
            unsigned npb_magic, int chunk, unsigned wsz, unsigned wmagic, unsigned bkm, int tau, int ramp, int rampn, int tdelay, unsigned polld, int spr, int sprn) {
    extern __shared__ __align__(1024) unsigned char smem[];
    if (s2u(smem) != sb) __trap();
    const int tid = threadIdx.x, lane = tid & 31;
    const int warp = __shfl_sync(0xffffffffu, tid >> 5, 0);
    const int nbins = gridDim.x;
    bool fast = chunk > 0;
    TLSTAMP(0);
    if (fast) {
        const int e0 = blockIdx.x * chunk + tid, left = min(E, (int)(blockIdx.x + 1) * chunk) - e0;
        uint32_t pd[KE], ps[KE];
        {
            const int* dp = dst + e0;
            const int* sp = src + e0;
#pragma unroll
            for (int k = 0; k < KE; k++) {
                pd[k] = (nbins + (k == KE - 1 ? lane : 0)) * npb, ps[k] = 0;
                asm volatile("{\n.reg .pred p;\nsetp.gt.s32 p, %4, %5;\n@p ld.global.nc.u32 %0, [%2];\n@p ld.global.nc.u32 %1, [%3];\n}"
                             : "+r"(pd[k]), "+r"(ps[k]) : "l"(dp + k * NT), "l"(sp + k * NT), "r"(left), "r"(k * NT));
            }
        }
        uint32_t epoch = 0;
        if (tid == NT - 1) asm volatile("ld.relaxed.gpu.global.u32 %0, [%1];" : "=r"(epoch) : "l"(&g_epoch) : "memory");
        uint4 wv, wo[3];
        const bool wrow = (tid >> 2) == WFT && blockIdx.x < 128;
        {
            const uint4* wp = tid < 256 ? (const uint4*)wr + tid
                              : wrow    ? (const uint4*)(wout + blockIdx.x * 128 + (tid & 3) * 32)
                                        : (const uint4*)cg + (tid & 7);
            if (tid < 264 || wrow) wv = __ldg(wp);
            if (wrow) wo[0] = __ldg(wp + 1), wo[1] = __ldg(wp + 2), wo[2] = __ldg(wp + 3);
        }
        const uint32_t t16 = sb + tid * 16;
        const uint32_t sa = sb + SC_STG + (tid >> 3) * CP + (tid & 7) * 16;
        const uint32_t sm = sb + SC_STG + (tid >> 2) * CP + (tid & 3) * 16 + 128;
        const uint32_t none = (40 * NWIN + (lane & 7) + (blockIdx.x & 3) * 8) << 2;
        const uint32_t pade = min(blockIdx.x * chunk, E - 1) << 13;
        const bool third = warp * 4 + 128 < nbins, second = warp * 8 + 128 < nbins;
#pragma unroll
        for (int k = 0; k < 3; k++)
            if (k < 2 || third) sts128(sa + k * 64 * CP, none, none, none, none);
#pragma unroll
        for (int k = 0; k < 2; k++)
            if (k < 1 || second) sts128(sm + k * 128 * CP, none, none, none, none);
        if (tid < MAXB + 32) sts32(sb + SC_CNT + tid * 4, 0);
        if (tid < NOFF) sts16(sb + SM_OFF + tid * 2, 0xffff);
#pragma unroll
        for (int k = 0; k < 3; k++) sts128(t16 + SC_TABB + k * NT * 16, 0, 0, 0, 0);
        const uint32_t ecomp = -(wsz * (CH << 13));
#pragma unroll
        for (int k = 0; k < 3; k++)
            sts128(t16 + SC_TMP + k * NT * 16, 0, pade + ecomp, 0, pade + ecomp);
#pragma unroll
        for (int k = 0; k < ZSL / 8; k++) sts128(t16 + k * NT * 16, 0, 0, 0, 0), sts128(t16 + SP * 1024 + PH + k * NT * 16, 0, 0, 0, 0);
        if (tid < RP / 4) {
            uint32_t c[4], d[4];
#pragma unroll
            for (int i = 0; i < 4; i++) {
                const uint32_t k = tid * 4 - 4 + i;
                c[i] = d[i] = 0xc0000001u;
                if (warp == 0 && k < SP) c[i] += sb / 64 - 1 + k * 16;
                if (warp == 0 && k < SP - WSL) d[i] = c[i] + (SP * 1024 + PH) / 64;
            }
            static_assert(SP + 4 <= 128, "first warp");
            sts128(t16 + SM_R, c[0], c[1], c[2], c[3]);
            sts128(t16 + SM_R + 0x2000, d[0], d[1], d[2], d[3]);
        }
        constexpr uint32_t OLEND = (RECN - 4) * 4 * 0x10001;
        if (tid < NCW * OLN / 8) sts128(t16 + SM_OL, OLEND, OLEND, OLEND, OLEND);
        if (warp == 12) {
            sts32(sb + SM_CTR + lane * 16 + (lane >> 3) * 4,
                  sb + SM_R + ((lane & 0x19) ? (RP - 1) * 4 : (4 + SP) * 4 + (((lane >> 1) ^ (lane >> 2)) & 1) * 0x2000 + (lane & 4)));
            if (lane < 3) sts32(sb + SM_MISC + (lane ? 16 + lane * 4 : 4), 0);
            if (lane == 8) sts128(sb + SM_REC + (RECN - 4) * 4, pade, pade, pade, pade), sts128(sb + SM_MISC + 64, 0, 0, 0, 0);
            if (lane == 9) asm volatile("prefetch.tensormap [%0];" ::"l"(&tmx) : "memory");
        }
        __syncthreads();
        TLSTAMP(1);

        {
            uint32_t b[KE], r[KE];
#pragma unroll
            for (int k = 0; k < KE; k++) {
                b[k] = __umulhi(pd[k], npb_magic);
                r[k] = atoms_add(sb + SC_CNT + b[k] * 4, 4);
                if (k == KE - 1) b[k] = min(b[k], nbins);
            }
            if (tid == NT - 1) {
                sts32(sb + SM_MISC + 8, epoch % 3 + 1);
                asm volatile("{\n.reg .b64 t;\nmov.u64 t, %%globaltimer;\nred.relaxed.gpu.global.max.u64 [%0], t;\n"
                             "red.relaxed.gpu.global.add.u32 [%0+8], 1;\n}" ::"l"(g_sync) : "memory");
            }
            __syncwarp();
#pragma unroll
            for (int k = 0; k < KE; k++) {
                asm volatile(
                    "{\n.reg .pred p;\n.reg .b32 d, t, u;\nmad.lo.u32 d, %1, %3, %0;\nsetp.ge.u32 p, d, 40;\nmul.hi.u32 u, %2, %4;\n"
                    "mad.lo.u32 t, %2, %10, %5;\nmad.lo.u32 t, d, %11, t;\nmad.lo.u32 t, u, %12, t;\n@p add.u32 t, t, %7;\n"
                    "min.u32 d, %6, 188;\nmad.lo.u32 d, %1, %9, d;\nst.shared.b32 [d+%8], t;\n}" ::"r"(pd[k]),
                    "r"(b[k]), "r"(ps[k]), "r"(-npb), "r"(wmagic), "r"(((tid + k * NT) << 14) + 4), "r"(r[k]), "n"(2 - 40 * NWIN * 4),
                    "n"(sb + SC_STG), "n"(CP), "n"(CH << 14), "n"(NWIN * 4), "r"(4 - wsz * (CH << 14))
                    : "memory");
            }
        }
        if (tid < 264) sts128(sb + SC_WR + (tid >> 4) * 272 + (tid & 15) * 16, wv.x, wv.y, wv.z, wv.w);
        uint4* gp = g_cell + ((tid >> 3) * MAXB + blockIdx.x) * 8 + (tid & 7);
        uint4* gm = g_more + ((tid >> 2) * MAXB + blockIdx.x) * 4 + (tid & 3);
        __syncthreads();
        TLSTAMP(6);
        const uint32_t tag = lds32(sb + SM_MISC + 8), t0 = tag & 1, t1 = tag >> 1;
        {
            uint4 v[5];
#pragma unroll
            for (int k = 0; k < 5; k++)
                if (k != 2 && k != 4 || (k == 2 ? third : second)) v[k] = lds128(k < 3 ? sa + k * 64 * CP : sm + (k - 3) * 128 * CP);
#pragma unroll
            for (int k = 0; k < 5; k++)
                if (k != 2 && k != 4 || (k == 2 ? third : second))
                    st_cell(k < 3 ? gp + k * 64 * MAXB * 8 : gm + (k - 3) * 128 * MAXB * 4, v[k].x | t0, v[k].y | t1, v[k].z | t0, v[k].w | t1);
        }
        if (wrow) {
            const int k = blockIdx.x;
            uint4* dp = &g_wf[((tid & 3) * 8 + (k >> 4)) * 64 + (k & 8) * 4 + (k & 7)];
            dp[0] = make_uint4(wv.x, wo[0].x, wo[1].x, wo[2].x);
            dp[8] = make_uint4(wv.y, wo[0].y, wo[1].y, wo[2].y);
            dp[16] = make_uint4(wv.z, wo[0].z, wo[1].z, wo[2].z);
            dp[24] = make_uint4(wv.w, wo[0].w, wo[1].w, wo[2].w);
        }
        if (warp < 14) { BARINIT(warp, 14) }
        __syncwarp();
        if (tid == NT - 1) {
            uint4 q;
            for (int n = 0; n < (1 << 22); n++) {
                q = ld_cell((const uint4*)g_sync);
                if ((int)(q.z - (epoch + 1) * nbins) >= 0) break;
            }
            sts128(sb + SM_MISC + 32, q.x, q.y, q.z, q.w), sts32(sb + SM_MISC + 16, (epoch + 1) * 512);
            asm volatile("mbarrier.init.shared.b64 [%0], 1;" ::"r"(sb + SM_MISC + 48) : "memory");
            while ((uint32_t)(gt_lo() - q.x) < polld) {}
        }
        __syncthreads();
        TLSTAMP(14);
        uint32_t m[20], rk[20], ia[20], eb[2];
        eb[0] = (((tid >> 3) * chunk) << 13) + ecomp + 1;
        eb[1] = eb[0] + (chunk << 19);
        asm volatile("" : "+r"(eb[0]), "+r"(eb[1]));
        bool ext;
        {
            const uint4* hp = g_cell + blockIdx.x * (MAXB * 8) + tid;
            const uint4* hm = g_more + blockIdx.x * (MAXB * 4) + tid;
            uint4 q[5];
            q[2] = q[4] = make_uint4(none | t0, none | t1, none | t0, none | t1);
            for (int n = 0; n < (1 << 22); n++) {
                q[0] = ld_cell(hp), q[1] = ld_cell(hp + NT), q[3] = ld_cell(hm);
                if ((tid >> 3) + 128 < nbins) q[2] = ld_cell(hp + 2 * NT);
                if ((tid >> 2) + 128 < nbins) q[4] = ld_cell(hm + NT);
                uint32_t bad = 0;
#pragma unroll
                for (int k = 0; k < 5; k++)
                    asm("{\n.reg .b32 a, b;\nlop3.b32 a, %1, %2, %5, 0x7e;\nlop3.b32 b, %3, %4, %6, 0x7e;\nlop3.b32 %0, %0, a, b, 0xfe;\n}"
                        : "+r"(bad) : "r"(q[k].x), "r"(q[k].z), "r"(q[k].y), "r"(q[k].w), "r"(t0), "r"(t1));
                if (!(bad & 1)) break;
            }
            __syncwarp();
            TLSTAMP(8);
#pragma unroll
            for (int k = 0; k < 5; k++) m[4 * k] = q[k].x, m[4 * k + 1] = q[k].y, m[4 * k + 2] = q[k].z, m[4 * k + 3] = q[k].w;
#pragma unroll
            for (int k = 0; k < 12; k++)
                if (k < 8 || third) ia[k] = m[k] & 0x3ffc, rk[k] = atoms_add(sb + SC_TABB + ia[k], 8);
            ext = __any_sync(0xffffffffu, min(m[12] & 0x3ffc, m[16] & 0x3ffc) < 40 * NWIN * 4);
            if (ext) {
#pragma unroll
                for (int k = 12; k < 20; k++) ia[k] = m[k] & 0x3ffc, rk[k] = atoms_add(sb + SC_TABB + ia[k], 8);
                if ((tid & 3) == 3 && min(m[15] & 0x3ffc, m[19] & 0x3ffc) < 40 * NWIN * 4) sts32(sb + SM_MISC + 4, 1);
            }
        }
        __syncthreads();
        TLSTAMP(5);
        const uint32_t tr = sb + warp * (NWIN * 4) + lane * 16;
        if (tid == NT - 1 && blockIdx.x == 0) g_epoch = epoch + 1;
        {
            uint4 c[3];
            uint32_t tt[3];
#pragma unroll
            for (int i = 0; i < 3; i++) {
                c[i] = make_uint4(0, 0, 0, 0);
                if ((i < 2 || warp < 8) && lane < NWIN / 4) c[i] = lds128(tr + SC_TABB + i * 16 * NWIN * 4);
                tt[i] = c[i].x + c[i].y + c[i].z + c[i].w;
            }
            const uint32_t sum = (tt[0] >> 3) + (tt[1] << 7) + (tt[2] << 17);
            const uint32_t tot = __reduce_add_sync(0xffffffffu, sum);
            uint32_t inc = scan_step(scan_step(sum, 1), 2);
            const uint32_t q = (tot + 0x300c03) & 0x3fcff3fc, q0 = q & 1023, q1 = q0 + ((q >> 10) & 1023);
            uint32_t base = atoms_add(sb + (lane ? SC_CNT + lane * 4 : SM_MISC + 20), q1 + (q >> 20));
            inc = scan_step(scan_step(scan_step(inc, 4), 8), 16);
            base = __shfl_sync(0xffffffffu, base, 0);
            const uint32_t l3 = min(lane, 2);
            sts32(sb + SC_KEY + (warp + 16 * l3) * 4, ((tot >> (10 * l3)) & 1023) * 64 + 63 - warp - 16 * l3);
            if (max(tt[0], max(tt[1], tt[2])) > 31 * 8) sts32(sb + SM_MISC + 4, 1);
            inc += q - tot - sum;
#pragma unroll
            for (int i = 0; i < 3; i++) {
                const uint32_t e = (((inc >> (10 * i)) & 1023) + base + (i == 0 ? 0 : i == 1 ? q0 : q1)) * 8;
                if ((i < 2 || warp < 8) && lane < NWIN / 4) sts128(tr + SC_TABB + i * 16 * NWIN * 4, e, e + c[i].x, e + c[i].x + c[i].y, e + tt[i] - c[i].w);
            }
        }
        __syncthreads();
        TLSTAMP(2);
        if (warp >= 11) {
            const uint32_t st = (tid - 352) >> 2, key = lds32(sb + SC_KEY + st * 4);
            uint32_t rank = 0;
#pragma unroll
            for (int i = 0; i < 5; i++) {
                const uint2 q = lds64(sb + SC_KEY + (lane & 3) * 40 + i * 8);
                rank += ((key - q.x) >> 31) + ((key - q.y) >> 31);
            }
            rank += __shfl_xor_sync(0xffffffffu, rank, 1);
            rank += __shfl_xor_sync(0xffffffffu, rank, 2);
            const uint32_t lv = rank >> 2, cw = ((0x969u >> (2 * lv)) & 3) * 4 + ((rank ^ -(lv & 1)) & 3);
            const uint32_t sid = (0xe4a50u >> (2 * lv)) & 3;
            sts32(sb + SC_MAP + st * 4, cw * (NWIN * 4) - st * (NWIN * 4) + 0x10000 + (sid << 30));
            asm volatile("st.shared.u8 [%0], %1;" ::"r"(sb + SM_INV + cw * 4 + sid), "r"(st) : "memory");
        }
        const int total = lds32(sb + SM_MISC + 20);
        fast = lds32(sb + SM_MISC + 4) == 0 && total <= RECN - 4;
        auto lookup = [&](int k) {
            asm volatile("{\n.reg .pred p;\n.reg .b32 t;\nsetp.lt.u32 p, %1, %2;\nmov.b32 t, 0x80000000;\n@p ld.shared.b32 t, [%1+%3];\nadd.u32 %0, %0, t;\n}"
                         : "+r"(rk[k]) : "r"(ia[k]), "n"(40 * NWIN * 4), "n"(sb + SC_TABB) : "memory");
        };
        auto place = [&](int k, uint32_t e) {
            asm volatile("{\n.reg .pred p;\nsetp.ge.s32 p, %0, 0;\n@p st.shared.v2.b32 [%0+%3], {%1, %2};\n}" ::"r"(rk[k]), "r"(m[k]), "r"(e),
                         "n"(sb + SC_TMP) : "memory");
        };
#pragma unroll
        for (int k = 0; k < 8; k++) lookup(k);
        if (fast) {
#pragma unroll
            for (int k = 0; k < 8; k++) place(k, eb[k >> 2]);
            if (third) {
#pragma unroll
                for (int k = 8; k < 12; k++) lookup(k);
#pragma unroll
                for (int k = 8; k < 12; k++) place(k, 2 * eb[1] - eb[0]);
            }
            if (ext) {
#pragma unroll
                for (int k = 12; k < 20; k++) lookup(k);
#pragma unroll
                for (int k = 12; k < 20; k++) place(k, ((((tid >> 2) + (k >> 4) * 128) * chunk) << 13) + ecomp + 1);
            }
            constexpr int KD = (RECN + NT - 1) / NT;
            const uint32_t P = (lane ^ (lane >> 1)) & 1;
            const uint32_t binc = (P ? 1u << 11 : 1u) + ((lane & 3) == 3 ? 1u << 22 : 0u);
            const bool last = warp * 32 + (KD - 1) * NT < total, q2 = warp * 128 + NT * 4 < total;
            const int rest = total - tid, restq = (total >> 2) - tid;
            uint2 en[KD];
            uint32_t bk[KD], r2[KD], ca[2], ol[2], r3[2];
            __syncthreads();
            TLSTAMP(9);
#pragma unroll
            for (int k = 0; k < KD; k++)
                if (k < KD - 1 || last) en[k] = lds64(sb + SC_TMP + tid * 8 + k * NT * 8);
#pragma unroll
            for (int k = 0; k < 2; k++)
                if (k == 0 || q2) ca[k] = lds32(sb + SC_TMP + (tid + k * NT) * 32 + 24);
#pragma unroll
            for (int k = 0; k < 2; k++)
                if (k == 0 || q2) ca[k] &= 0x3ffc, ol[k] = lds32(sb + SC_MAP + __umulhi(ca[k], 0xffffffffu / (NWIN * 4) + 1) * 4);
#pragma unroll
            for (int k = 0; k < KD; k++) {
                if (k < KD - 1 || last) {
                    const uint32_t v = en[k].x, f = v >> 14, i = v & 0x3ffc;
                    const uint32_t w4 = i - __umulhi(i, 0xffffffffu / (NWIN * 4) + 1) * (NWIN * 4);
                    const uint32_t o = __umulhi(f, 0xffffffffu / CH + 1) - wsz;
                    bk[k] = (__umulhi(f, bkm) + w4) * 4;
                    en[k].x = (w4 >> 2) * wsz + o;
                    en[k].y += ((v >> 1) & 0xffffe001u) - o * (CH << 13);
                    if (rest <= k * NT) bk[k] = 2048 + lane * 4;
                    r2[k] = atoms_add(sb + SC_TABA + bk[k], binc);
                }
            }
#pragma unroll
            for (int k = 0; k < 2; k++) {
                if (k == 0 || q2) {
                    ca[k] = (ca[k] + ol[k]) & 0xffff;
                    ol[k] = (tid + k * NT) * 16 + (ol[k] >> 30 << 14);
                    r3[k] = atoms_add(sb + SC_TABC + ca[k], restq > k * NT ? 2 : 0);
                }
            }
            __syncthreads();
            TLSTAMP(12);
            if (warp < NCW) {
                uint4 c = make_uint4(0, 0, 0, 0);
                if (lane < NWIN / 4) c = lds128(tr + SC_TABC);
                const uint32_t tt = c.x + c.y + c.z + c.w;
                uint32_t inc = tt;
#pragma unroll
                for (int o = 1; o < 32; o <<= 1) inc = scan_step(inc, o);
                if (inc > (OLN - 6) * 2) sts32(sb + SM_MISC + 4, 1);
                inc += warp * (OLN * 2) - tt;
                if (lane < NWIN / 4) sts128(tr + SC_TABC, inc, inc + c.x, inc + c.x + c.y, inc + tt - c.w);
            } else {
                const uint32_t mine = (warp + lane) & 3;
                uint4 c;
                uint32_t cs, inc = 0, e = 4 + (4 << 11);
#pragma unroll
                for (int i = 0; i < 4; i++) {
                    const uint32_t pc = (mine + i) & 3;
                    const uint4 v = lds128(sb + SC_TABA + lane * 64 + (pc << 4));
                    const uint32_t sum = v.x + v.y + v.z + v.w;
                    inc += sum;
                    if (i == 0) c = v, cs = sum;
                    if (pc >= mine) e -= sum;
                }
#pragma unroll
                for (int o = 1; o < 32; o <<= 1) inc = scan_step(inc, o);
                e += inc;
                sts128(sb + SC_TABB + lane * 64 + (mine << 4), e, e + c.x, e + c.x + c.y, e + cs - c.w);
                if ((int)max((e + cs) & 0x7ff, ((e + cs) >> 11) & 0x7ff) - (int)(e >> 22) * 2 > SP) sts32(sb + SM_MISC + 4, 1);
                if (tid == NCW * 32) {
                    const uint32_t c0 = min(min(c.x & 0x7ff, (c.x >> 11) & 0x7ff), ZSL) >> 2;
                    sts32(sb + SM_MISC + 12, ((total >> 2) + 1) >> 1), sts32(sb + SM_MISC + 24, c0);
                }
            }
            __syncthreads();
            TLSTAMP(13);
            fast = lds32(sb + SM_MISC + 4) == 0;
            if (warp == 15 && lane < lds32(sb + SM_MISC + 24))
                asm volatile("mbarrier.arrive.shared.b64 _, [%0];" ::"r"(sb + SM_BAR + 8 + lane * 8) : "memory");
#pragma unroll
            for (int k = 0; k < KD; k++)
                if (k < KD - 1 || last) r2[k] += lds32(sb + SC_TABB + bk[k]);
#pragma unroll
            for (int k = 0; k < 2; k++)
                if (k == 0 || q2) r3[k] += lds32(sb + SC_TABC + ca[k]);
            if (fast) {
                const uint32_t rot = P ? 9 : 30;
#pragma unroll
                for (int k = 0; k < KD; k++) {
                    if (k < KD - 1 || last) {
                        const uint32_t k4 = __funnelshift_r(r2[k], r2[k], rot);
                        if (rest > k * NT) {
                            sts16(sb + SM_R + 2 + bitsel(k4, P << 13), en[k].x);
                            sts32(sb + SM_REC + tid * 4 + k * NT * 4, bitsel(k4, en[k].y));
                        }
                    }
                }
#pragma unroll
                for (int k = 0; k < 2; k++)
                    if ((k == 0 || q2) && restq > k * NT) sts16(sb + SM_OL + r3[k], ol[k]);
            }
        }
        asm volatile("fence.mbarrier_init.release.cluster;\nfence.proxy.async.shared::cta;" ::: "memory");
        __syncthreads();
        TLSTAMP(3);
        if (!fast && wrow) wf_done();
        if (fast && tid < NOFF) {
            const uint4 a = lds128(t16 + SM_R), b = lds128(t16 + SM_R + 0x2000);
            const int s = (((int)a.x >> 3) + ((int)a.y >> 3) + ((int)a.z >> 3) + ((int)a.w >> 3) + ((int)b.x >> 3) + ((int)b.y >> 3) +
                           ((int)b.z >> 3) + ((int)b.w >> 3)) >> 16;
            sts16(sb + SM_OFF + tid * 2, min(max(tdelay + SLIPTH + ((s * tau + min(s, rampn) * ramp - max(s - sprn, 0) * spr) >> 10), 0), 0xffff));
        }
        __syncwarp();
    }

    if (!fast) {
        float* accs = (float*)smem;
        constexpr int NACC = 96;
        const int node0 = blockIdx.x * npb, nnodes = max(0, min(npb, N - node0));
#pragma unroll 1
        for (int nb = 0; nb < nnodes; nb += NACC) {
            __syncthreads();
            for (int i = tid; i < NACC * 512; i += NT) accs[i] = 0.f;
            __syncthreads();
            const int lim = min(NACC, nnodes - nb);
#pragma unroll 1
            for (int base = warp * 32; base < E; base += NT) {
                const int e = base + lane;
                const int dl = e < E ? dst[e] - node0 - nb : -1;
                unsigned mask = __ballot_sync(0xffffffffu, dl >= 0 && dl < lim);
#pragma unroll 1
                while (mask) {
                    const int l = __ffs(mask) - 1;
                    mask &= mask - 1;
                    const int dd = __shfl_sync(0xffffffffu, dl, l);
                    slow_edge(base + l, src[base + l], accs + dd * 512, x, sh, ea, cg, wr, lane);
                }
            }
            __syncthreads();
#pragma unroll 1
            for (int nl = warp; nl < lim; nl += NT / 32) slow_out(accs + nl * 512, wout, out + (size_t)(node0 + nb + nl) * 512, lane);
        }
    } else if (warp >= NCW) {
        asm volatile("setmaxnreg.dec.sync.aligned.u32 %0;" ::"n"(PREG));
        producer(&tmx, warp - NCW);
    } else if (warp >= 4) {
        asm volatile("setmaxnreg.inc.sync.aligned.u32 %0;" ::"n"(R1));
        consumer<3>(sh, ea, out, N, npb);
        TLMAX(4);
    } else {
        asm volatile("setmaxnreg.inc.sync.aligned.u32 %0;" ::"n"(R0));
        consumer<4>(sh, ea, out, N, npb);
        TLMAX(4);
    }
}

typedef CUresult (*EncodeTiledFn)(CUtensorMap*, CUtensorMapDataType, cuuint32_t, void*, const cuuint64_t*,
                                  const cuuint64_t*, const cuuint32_t*, const cuuint32_t*, CUtensorMapInterleave,
                                  CUtensorMapSwizzle, CUtensorMapL2promotion, CUtensorMapFloatOOBfill);

extern "C" void kernel_launch(void* const* d_in, const int* in_sizes, int n_in, void* d_out, int out_size) {
    const __nv_bfloat16* x = (const __nv_bfloat16*)d_in[0];
    const int* src = (const int*)d_in[1];
    const int* dst = (const int*)d_in[2];
    const __nv_bfloat16* sh = (const __nv_bfloat16*)d_in[3];
    const __nv_bfloat16* ea = (const __nv_bfloat16*)d_in[4];
    const __nv_bfloat16* cg = (const __nv_bfloat16*)d_in[5];
    const __nv_bfloat16* wr = (const __nv_bfloat16*)d_in[6];
    const __nv_bfloat16* wout = (const __nv_bfloat16*)d_in[7];
    __nv_bfloat16* out = (__nv_bfloat16*)d_out;
    const int N = in_sizes[0] / 512;
    const int E = in_sizes[1];

    static int num_sms = 0, coresident = 0;
    static EncodeTiledFn encode = nullptr;
    if (num_sms == 0) {
        int dev = 0;
        cudaGetDevice(&dev);
        cudaDeviceGetAttribute(&num_sms, cudaDevAttrMultiProcessorCount, dev);
        cudaFuncSetAttribute(main_kernel, cudaFuncAttributeMaxDynamicSharedMemorySize, SM_TOTAL);
        int occ = 0;
        cudaOccupancyMaxActiveBlocksPerMultiprocessor(&occ, main_kernel, NT, SM_TOTAL);
        coresident = occ * num_sms;
        void* fn = nullptr;
        cudaDriverEntryPointQueryResult qr;
        cudaGetDriverEntryPoint("cuTensorMapEncodeTiled", &fn, cudaEnableDefault, &qr);
        encode = (EncodeTiledFn)fn;
    }
    CUtensorMap tmx;
    const int rank = 3;
    const cuuint64_t gd[3] = {64, (cuuint64_t)N * 4, 2}, gs[2] = {256, 128};
    const cuuint32_t bd[3] = {64, 4, 2}, es[3] = {1, 1, 1};
    encode(&tmx, CU_TENSOR_MAP_DATA_TYPE_BFLOAT16, rank, (void*)x, gd, gs, bd, es, CU_TENSOR_MAP_INTERLEAVE_NONE,
           CU_TENSOR_MAP_SWIZZLE_128B, CU_TENSOR_MAP_L2_PROMOTION_NONE, CU_TENSOR_MAP_FLOAT_OOB_FILL_NONE);

    int nbins = num_sms < MAXB ? num_sms : MAXB;
    int npb = (N + nbins - 1) / nbins;
    if (npb < 2) npb = 2;
    nbins = (N + npb - 1) / npb;
    const unsigned npb_magic = (unsigned)((0x100000000ull + npb - 1) / npb);
    int chunk = (E + nbins - 1) / nbins;
    const unsigned wsz = (N + NWIN - 2) / (NWIN - 1);
    if (nbins > coresident || nbins < 128 || npb > MAXNPB || chunk > CH || wsz > (1 << 18) / CH || N < 512 || E > (1 << 19)) chunk = 0;
    const unsigned wmagic = 0xffffffffu / wsz + 1, bkm = (unsigned)((4ull << 32) / (wsz * CH));
    double pace = PACE, rampt = RAMP, rampf = RAMPF, sprt = SPRINT, sprf = SPRINTF;
    int tdelay = TDELAY, polld = POLLD;
    const int tau = (int)(1024.0 * pace * ((double)E / nbins) / N);
    const int rampn = (int)(N * rampf), ramp = (int)(1024.0 * rampt / rampn);
    main_kernel<<<nbins, NT, SM_TOTAL, cudaStreamPerThread>>>(tmx, x, src, dst, sh, ea, cg, wr, wout, out, N, E, npb, npb_magic,
                                                              chunk, wsz, wmagic, bkm, tau, ramp, rampn, tdelay, polld, (int)(1024.0 * sprt / (N * sprf)), (int)(N * (1 - sprf)));
}
```

```cpp
#include <cuda_runtime.h>
#include <cuda.h>
#include <cuda_bf16.h>
#include <stdint.h>
#include <stdlib.h>

#define NT 512
#define NCW 12
#define MAXB 144
#define MAXNPB 80
#define KE 5
#define SP 99
#define RECN 2752
#define RP 1484
#define OLN 80
#define NBAR 350
#define NOFF 352
#define R0 168
#define R1 160
#define PREG 24
#define PACE 9.95
#define TDELAY 4550
#define POLLD 1000
#define WFT 80
#define SLIPTH 250
#define SLIPADD 150
#define SLIPFROM 36
#define AHEAD 96
#define EARLY 32
#define RAMPF 0.1
#define SPRINT 400
#define SPRINTF 0.5
#define SLIPEND 640
#define SPINT 96
#define PFT 224
#define RAMP 500

__device__ __align__(1024) uint4 g_cell[MAXB * MAXB * 8];
__device__ __align__(1024) uint4 g_more[MAXB * MAXB * 4];
__device__ __align__(1024) uint4 g_wf[2048];
__device__ __align__(256) ulonglong2 g_sync[16];
__device__ __align__(256) unsigned g_epoch;
#define TLSTAMP(i)
#define TLMAX(i)

constexpr uint32_t sb = 1024;
#define PH 512
#define SM_R (2 * SP * 1024 + PH)
#define SM_CTR (SP * 1024)
#define SM_MISC (SM_R + RP * 4)
#define SM_INV (SM_MISC + 80)
#define SM_OL (SM_INV + 48)
#define SM_REC (SM_R + 0x2000 + RP * 4)
#define SM_OFF (SM_REC + RECN * 4)
#define SM_BAR (SM_OFF + NOFF * 2)
#define SM_CGF 0
#define SM_TOTAL (SM_BAR + NBAR * 8)
static_assert(SM_TOTAL <= 232448 && SM_OL + NCW * OLN * 2 <= SM_R + 0x2000 && SM_OL % 16 == 0 && SM_BAR % 16 == 0, "shared memory");
static_assert(4 + RECN / 2 + SP + 2 <= RP && RECN / 8 + 5 <= NBAR && NBAR % 14 == 0 && RECN / 8 + 4 <= NOFF, "tables");
#define ZSL 32
#define NWIN 96
#define CH 2432
#define CP 208
#define SC_STG ((SP + ZSL) * 1024 + PH)
#define SC_TMP (ZSL * 1024)
#define SC_TABB (SC_TMP + 3072 * 8)
#define SC_TABC (SC_TABB + 41 * NWIN * 4)
#define SC_TABA (SC_TABC + NCW * NWIN * 4)
#define SC_ZEND (SC_TABB + 3 * NT * 16)
#define SC_CNT SC_ZEND
#define SC_KEY (SC_CNT + (MAXB + 32) * 4)
#define SC_MAP (SC_KEY + 192)
#define WSL 5
#define SC_WR ((2 * SP - WSL) * 1024 + PH)
#define SC_CG (SC_WR + 16 * 272)
static_assert(SC_TABA + 2048 + 128 <= SC_ZEND && RECN <= 3072 && SC_MAP + 192 <= SP * 1024 && SC_STG + (MAXB + 1) * CP <= SC_WR, "scratch");

__device__ __forceinline__ uint32_t pack_bf16(float lo, float hi) {
    uint32_t r;
    asm("cvt.rn.bf16x2.f32 %0, %1, %2;" : "=r"(r) : "f"(hi), "f"(lo));
    return r;
}
__device__ __forceinline__ uint32_t s2u(const void* p) { return (uint32_t)__cvta_generic_to_shared(p); }
__device__ __forceinline__ void mbar_wait0(uint32_t a) {
    asm volatile(
        "{\n.reg .pred p, q;\n.reg .u32 n;\nmov.u32 n, 0;\n"
        "LAB_WAIT:\nmbarrier.try_wait.parity.shared.b64 p, [%0], 0;\nadd.u32 n, n, 1;\nsetp.lt.and.u32 q, n, 1000000, !p;\n@q bra LAB_WAIT;\n}" ::"r"(a)
        : "memory");
}
__device__ __forceinline__ uint32_t lds8(uint32_t a) { uint32_t v; asm volatile("ld.shared.u8 %0, [%1];" : "=r"(v) : "r"(a) : "memory"); return v; }
__device__ __forceinline__ uint32_t lds16(uint32_t a) { uint32_t v; asm volatile("ld.shared.u16 %0, [%1];" : "=r"(v) : "r"(a) : "memory"); return v; }
__device__ __forceinline__ uint32_t lds32(uint32_t a) { uint32_t v; asm volatile("ld.shared.u32 %0, [%1];" : "=r"(v) : "r"(a) : "memory"); return v; }
__device__ __forceinline__ uint2 lds64(uint32_t a) {
    uint2 v; asm volatile("ld.shared.v2.u32 {%0,%1}, [%2];" : "=r"(v.x), "=r"(v.y) : "r"(a) : "memory"); return v;
}
__device__ __forceinline__ uint4 lds128(uint32_t a) {
    uint4 v; asm volatile("ld.volatile.shared.v4.u32 {%0,%1,%2,%3}, [%4];" : "=r"(v.x), "=r"(v.y), "=r"(v.z), "=r"(v.w) : "r"(a) : "memory"); return v;
}
__device__ __forceinline__ void sts16(uint32_t a, uint32_t v) { asm volatile("st.shared.u16 [%0], %1;" ::"r"(a), "h"((unsigned short)v) : "memory"); }
__device__ __forceinline__ void sts32(uint32_t a, uint32_t v) { asm volatile("st.shared.u32 [%0], %1;" ::"r"(a), "r"(v) : "memory"); }
__device__ __forceinline__ void sts64(uint32_t a, uint32_t x, uint32_t y) { asm volatile("st.shared.v2.u32 [%0], {%1,%2};" ::"r"(a), "r"(x), "r"(y) : "memory"); }
__device__ __forceinline__ void sts128(uint32_t a, uint32_t x, uint32_t y, uint32_t z, uint32_t w) {
    asm volatile("st.shared.v4.u32 [%0], {%1,%2,%3,%4};" ::"r"(a), "r"(x), "r"(y), "r"(z), "r"(w) : "memory");
}
__device__ __forceinline__ uint32_t atoms_add(uint32_t a, uint32_t v) {
    uint32_t r;
    asm volatile("atom.shared.add.u32 %0, [%1], %2;" : "=r"(r) : "r"(a), "r"(v) : "memory");
    return r;
}
__device__ __forceinline__ uint4 ld_cell(const uint4* p) {
    uint4 v;
    asm volatile("{\n.reg .b64 a, b;\nld.relaxed.gpu.global.v2.b64 {a, b}, [%4];\nmov.b64 {%0,%1}, a;\nmov.b64 {%2,%3}, b;\n}"
                 : "=r"(v.x), "=r"(v.y), "=r"(v.z), "=r"(v.w) : "l"(p) : "memory");
    return v;
}
__device__ __forceinline__ void st_cell(uint4* p, uint32_t x, uint32_t y, uint32_t z, uint32_t w) {
    asm volatile("st.relaxed.gpu.global.v2.b64 [%0], {%1, %2};" ::"l"(p), "l"(x | (uint64_t)y << 32), "l"(z | (uint64_t)w << 32) : "memory");
}
__device__ __forceinline__ uint32_t scan_step(uint32_t v, int o) {
    asm volatile("{\n.reg .pred p;\n.reg .b32 y;\nshfl.sync.up.b32 y|p, %0, %1, 0, 0xffffffff;\n@p add.u32 %0, %0, y;\n}" : "+r"(v) : "r"(o));
    return v;
}
__device__ __forceinline__ uint32_t bitsel(uint32_t a, uint32_t b) {
    uint32_t r;
    asm("lop3.b32 %0, %1, %2, 0x1ffc, 0xe4;" : "=r"(r) : "r"(a), "r"(b));
    return r;
}
__device__ __forceinline__ uint32_t movm(uint32_t a) {
    uint32_t r;
    asm volatile("movmatrix.sync.aligned.m8n8.trans.b16 %0, %1;" : "=r"(r) : "r"(a));
    return r;
}
__device__ __forceinline__ uint32_t gt_lo() {
    uint32_t t;
    asm volatile("mov.u32 %0, %globaltimer_lo;" : "=r"(t));
    return t;
}
__device__ __forceinline__ bool elect() {
    uint32_t p;
    asm volatile("{\n.reg .pred P;\nelect.sync _|P, 0xffffffff;\nselp.u32 %0, 1, 0, P;\n}" : "=r"(p));
    return p;
}
__device__ __forceinline__ void project4(const uint32_t (&pk)[64], uint32_t ra, uint32_t ba, uint4* const (&p)[4], const uint32_t (&v)[4]) {
    asm volatile(
        "{\n.reg .pred p0, p1, q0, q1, nv, s<4>;\n.reg .b32 t, h, c<16>, a<32>, b<32>, k<16>;\n.reg .b64 d<16>;\n.reg .f32 o<32>;\nsetp.ne.b32 p0, 0, 0;\n"
        "setp.eq.b32 p1, 0, 0;\nmov.b32 h, 8;\nsetp.eq.u32 nv, %64, 0;\nvote.sync.any.pred nv, nv, 0xffffffff;\nsetp.ne.b32 s0, %69, 0;\n"
        "setp.ne.b32 s1, %70, 0;\nsetp.ne.b32 s2, %71, 0;\nsetp.ne.b32 s3, %72, 0;\nmovmatrix.sync.aligned.m8n8.trans.b16 a0, %0;\n"
        "movmatrix.sync.aligned.m8n8.trans.b16 a1, %16;\nmovmatrix.sync.aligned.m8n8.trans.b16 a2, %1;\nmovmatrix.sync.aligned.m8n8.trans.b16 a3, %17;\n"
        "movmatrix.sync.aligned.m8n8.trans.b16 a4, %2;\nmovmatrix.sync.aligned.m8n8.trans.b16 a5, %18;\nmovmatrix.sync.aligned.m8n8.trans.b16 a6, %3;\n"
        "movmatrix.sync.aligned.m8n8.trans.b16 a7, %19;\nmovmatrix.sync.aligned.m8n8.trans.b16 a8, %4;\nmovmatrix.sync.aligned.m8n8.trans.b16 a9, %20;\n"
        "movmatrix.sync.aligned.m8n8.trans.b16 a10, %5;\nmovmatrix.sync.aligned.m8n8.trans.b16 a11, %21;\nmovmatrix.sync.aligned.m8n8.trans.b16 a12, %6;\n"
        "movmatrix.sync.aligned.m8n8.trans.b16 a13, %22;\nmovmatrix.sync.aligned.m8n8.trans.b16 a14, %7;\nmovmatrix.sync.aligned.m8n8.trans.b16 a15, %23;\n"
        "movmatrix.sync.aligned.m8n8.trans.b16 a16, %8;\nmovmatrix.sync.aligned.m8n8.trans.b16 a17, %24;\nmovmatrix.sync.aligned.m8n8.trans.b16 a18, %9;\n"
        "movmatrix.sync.aligned.m8n8.trans.b16 a19, %25;\nmovmatrix.sync.aligned.m8n8.trans.b16 a20, %10;\nmovmatrix.sync.aligned.m8n8.trans.b16 a21, %26;\n"
        "movmatrix.sync.aligned.m8n8.trans.b16 a22, %11;\nmovmatrix.sync.aligned.m8n8.trans.b16 a23, %27;\nmovmatrix.sync.aligned.m8n8.trans.b16 a24, %12;\n"
        "movmatrix.sync.aligned.m8n8.trans.b16 a25, %28;\nmovmatrix.sync.aligned.m8n8.trans.b16 a26, %13;\nmovmatrix.sync.aligned.m8n8.trans.b16 a27, %29;\n"
        "movmatrix.sync.aligned.m8n8.trans.b16 a28, %14;\nmovmatrix.sync.aligned.m8n8.trans.b16 a29, %30;\nmovmatrix.sync.aligned.m8n8.trans.b16 a30, %15;\n"
        "movmatrix.sync.aligned.m8n8.trans.b16 a31, %31;\nmov.b32 t, 0;\n"
        "W0:\nmbarrier.try_wait.parity.shared.b64 q0, [%73+0], 0;\nadd.u32 t, t, 1;\nsetp.lt.and.u32 q1, t, 1000000, !q0;\n@q1 bra.uni W0;\nmov.b32 t, 0;\n"
        "W1:\nmbarrier.try_wait.parity.shared.b64 q0, [%73+8], 0;\nadd.u32 t, t, 1;\nsetp.lt.and.u32 q1, t, 1000000, !q0;\n@q1 bra.uni W1;\nmov.b32 t, 0;\n"
        "W2:\nmbarrier.try_wait.parity.shared.b64 q0, [%73+16], 0;\nadd.u32 t, t, 1;\nsetp.lt.and.u32 q1, t, 1000000, !q0;\n@q1 bra.uni W2;\nmov.b32 t, 0;\n"
        "W3:\nmbarrier.try_wait.parity.shared.b64 q0, [%73+24], 0;\nadd.u32 t, t, 1;\nsetp.lt.and.u32 q1, t, 1000000, !q0;\n@q1 bra.uni W3;\n"
        "ld.volatile.shared.v4.b32 {c0,c1,c2,c3}, [%64+0];\nld.volatile.shared.v4.b32 {c4,c5,c6,c7}, [%64+8192];\n"
        "ld.volatile.shared.v4.b32 {c8,c9,c10,c11}, [%64+16];\nld.volatile.shared.v4.b32 {c12,c13,c14,c15}, [%64+8208];\nand.b32 t, c0, 0xffe;\n"
        "mad.lo.u32 t, t, 4, 0x200000;\nmov.b64 d0, {t, h};\nand.b32 t, c1, 0xffe;\nmad.lo.u32 t, t, 4, 0x200000;\nmov.b64 d1, {t, h};\nand.b32 t, c2, 0xffe;\n"
        "mad.lo.u32 t, t, 4, 0x200000;\nmov.b64 d2, {t, h};\nand.b32 t, c3, 0xffe;\nmad.lo.u32 t, t, 4, 0x200000;\nmov.b64 d3, {t, h};\nand.b32 t, c4, 0xffe;\n"
        "mad.lo.u32 t, t, 4, 0x200000;\nmov.b64 d4, {t, h};\nand.b32 t, c5, 0xffe;\nmad.lo.u32 t, t, 4, 0x200000;\nmov.b64 d5, {t, h};\nand.b32 t, c6, 0xffe;\n"
        "mad.lo.u32 t, t, 4, 0x200000;\nmov.b64 d6, {t, h};\nand.b32 t, c7, 0xffe;\nmad.lo.u32 t, t, 4, 0x200000;\nmov.b64 d7, {t, h};\nand.b32 t, c8, 0xffe;\n"
        "mad.lo.u32 t, t, 4, 0x200000;\nmov.b64 d8, {t, h};\nand.b32 t, c9, 0xffe;\nmad.lo.u32 t, t, 4, 0x200000;\nmov.b64 d9, {t, h};\nand.b32 t, c10, 0xffe;\n"
        "mad.lo.u32 t, t, 4, 0x200000;\nmov.b64 d10, {t, h};\nand.b32 t, c11, 0xffe;\nmad.lo.u32 t, t, 4, 0x200000;\nmov.b64 d11, {t, h};\n"
        "and.b32 t, c12, 0xffe;\nmad.lo.u32 t, t, 4, 0x200000;\nmov.b64 d12, {t, h};\nand.b32 t, c13, 0xffe;\nmad.lo.u32 t, t, 4, 0x200000;\n"
        "mov.b64 d13, {t, h};\nand.b32 t, c14, 0xffe;\nmad.lo.u32 t, t, 4, 0x200000;\nmov.b64 d14, {t, h};\nand.b32 t, c15, 0xffe;\n"
        "mad.lo.u32 t, t, 4, 0x200000;\nmov.b64 d15, {t, h};\nwgmma.fence.sync.aligned;\n"
        "wgmma.mma_async.sync.aligned.m64n32k16.f32.bf16.bf16 {o0,o1,o2,o3,o4,o5,o6,o7,o8,o9,o10,o11,o12,o13,o14,o15}, {a0,a1,a2,a3}, d0, p0, 1, 1, 1;\n"
        "wgmma.mma_async.sync.aligned.m64n32k16.f32.bf16.bf16 {o16,o17,o18,o19,o20,o21,o22,o23,o24,o25,o26,o27,o28,o29,o30,o31}, {a0,a1,a2,a3}, d8, p0, 1, 1, 1;\n"
        "wgmma.mma_async.sync.aligned.m64n32k16.f32.bf16.bf16 {o0,o1,o2,o3,o4,o5,o6,o7,o8,o9,o10,o11,o12,o13,o14,o15}, {a4,a5,a6,a7}, d1, p1, 1, 1, 1;\n"
        "wgmma.mma_async.sync.aligned.m64n32k16.f32.bf16.bf16 {o16,o17,o18,o19,o20,o21,o22,o23,o24,o25,o26,o27,o28,o29,o30,o31}, {a4,a5,a6,a7}, d9, p1, 1, 1, 1;\n"
        "wgmma.mma_async.sync.aligned.m64n32k16.f32.bf16.bf16 {o0,o1,o2,o3,o4,o5,o6,o7,o8,o9,o10,o11,o12,o13,o14,o15}, {a8,a9,a10,a11}, d2, p1, 1, 1, 1;\n"
        "wgmma.mma_async.sync.aligned.m64n32k16.f32.bf16.bf16 {o16,o17,o18,o19,o20,o21,o22,o23,o24,o25,o26,o27,o28,o29,o30,o31}, {a8,a9,a10,a11}, d10, p1, 1, 1, 1;\n"
        "wgmma.mma_async.sync.aligned.m64n32k16.f32.bf16.bf16 {o0,o1,o2,o3,o4,o5,o6,o7,o8,o9,o10,o11,o12,o13,o14,o15}, {a12,a13,a14,a15}, d3, p1, 1, 1, 1;\n"
        "wgmma.mma_async.sync.aligned.m64n32k16.f32.bf16.bf16 {o16,o17,o18,o19,o20,o21,o22,o23,o24,o25,o26,o27,o28,o29,o30,o31}, {a12,a13,a14,a15}, d11, p1, 1, 1, 1;\n"
        "wgmma.mma_async.sync.aligned.m64n32k16.f32.bf16.bf16 {o0,o1,o2,o3,o4,o5,o6,o7,o8,o9,o10,o11,o12,o13,o14,o15}, {a16,a17,a18,a19}, d4, p1, 1, 1, 1;\n"
        "wgmma.mma_async.sync.aligned.m64n32k16.f32.bf16.bf16 {o16,o17,o18,o19,o20,o21,o22,o23,o24,o25,o26,o27,o28,o29,o30,o31}, {a16,a17,a18,a19}, d12, p1, 1, 1, 1;\n"
        "wgmma.mma_async.sync.aligned.m64n32k16.f32.bf16.bf16 {o0,o1,o2,o3,o4,o5,o6,o7,o8,o9,o10,o11,o12,o13,o14,o15}, {a20,a21,a22,a23}, d5, p1, 1, 1, 1;\n"
        "wgmma.mma_async.sync.aligned.m64n32k16.f32.bf16.bf16 {o16,o17,o18,o19,o20,o21,o22,o23,o24,o25,o26,o27,o28,o29,o30,o31}, {a20,a21,a22,a23}, d13, p1, 1, 1, 1;\n"
        "wgmma.mma_async.sync.aligned.m64n32k16.f32.bf16.bf16 {o0,o1,o2,o3,o4,o5,o6,o7,o8,o9,o10,o11,o12,o13,o14,o15}, {a24,a25,a26,a27}, d6, p1, 1, 1, 1;\n"
        "wgmma.mma_async.sync.aligned.m64n32k16.f32.bf16.bf16 {o16,o17,o18,o19,o20,o21,o22,o23,o24,o25,o26,o27,o28,o29,o30,o31}, {a24,a25,a26,a27}, d14, p1, 1, 1, 1;\n"
        "wgmma.mma_async.sync.aligned.m64n32k16.f32.bf16.bf16 {o0,o1,o2,o3,o4,o5,o6,o7,o8,o9,o10,o11,o12,o13,o14,o15}, {a28,a29,a30,a31}, d7, p1, 1, 1, 1;\n"
        "wgmma.mma_async.sync.aligned.m64n32k16.f32.bf16.bf16 {o16,o17,o18,o19,o20,o21,o22,o23,o24,o25,o26,o27,o28,o29,o30,o31}, {a28,a29,a30,a31}, d15, p1, 1, 1, 1;\n"
        "wgmma.commit_group.sync.aligned;\n@nv bra.uni END;\n@nv bra.uni END;\nwgmma.wait_group.sync.aligned 0;\ncvt.rn.bf16x2.f32 k0, o1, o0;\n"
        "cvt.rn.bf16x2.f32 k1, o5, o4;\ncvt.rn.bf16x2.f32 k2, o9, o8;\ncvt.rn.bf16x2.f32 k3, o13, o12;\ncvt.rn.bf16x2.f32 k4, o3, o2;\n"
        "cvt.rn.bf16x2.f32 k5, o7, o6;\ncvt.rn.bf16x2.f32 k6, o11, o10;\ncvt.rn.bf16x2.f32 k7, o15, o14;\ncvt.rn.bf16x2.f32 k8, o17, o16;\n"
        "cvt.rn.bf16x2.f32 k9, o21, o20;\ncvt.rn.bf16x2.f32 k10, o25, o24;\ncvt.rn.bf16x2.f32 k11, o29, o28;\ncvt.rn.bf16x2.f32 k12, o19, o18;\n"
        "cvt.rn.bf16x2.f32 k13, o23, o22;\ncvt.rn.bf16x2.f32 k14, o27, o26;\ncvt.rn.bf16x2.f32 k15, o31, o30;\n@s0 st.global.v4.b32 [%65+0], {k0,k1,k2,k3};\n"
        "@s1 st.global.v4.b32 [%66+0], {k4,k5,k6,k7};\n@s0 st.global.v4.b32 [%65+64], {k8,k9,k10,k11};\n@s1 st.global.v4.b32 [%66+64], {k12,k13,k14,k15};\n"
        "@nv bra.uni END;\nld.volatile.shared.v4.b32 {c0,c1,c2,c3}, [%64+32];\nld.volatile.shared.v4.b32 {c4,c5,c6,c7}, [%64+8224];\n"
        "ld.volatile.shared.v4.b32 {c8,c9,c10,c11}, [%64+48];\nld.volatile.shared.v4.b32 {c12,c13,c14,c15}, [%64+8240];\nand.b32 t, c0, 0xffe;\n"
        "mad.lo.u32 t, t, 4, 0x200000;\nmov.b64 d0, {t, h};\nand.b32 t, c1, 0xffe;\nmad.lo.u32 t, t, 4, 0x200000;\nmov.b64 d1, {t, h};\nand.b32 t, c2, 0xffe;\n"
        "mad.lo.u32 t, t, 4, 0x200000;\nmov.b64 d2, {t, h};\nand.b32 t, c3, 0xffe;\nmad.lo.u32 t, t, 4, 0x200000;\nmov.b64 d3, {t, h};\nand.b32 t, c4, 0xffe;\n"
        "mad.lo.u32 t, t, 4, 0x200000;\nmov.b64 d4, {t, h};\nand.b32 t, c5, 0xffe;\nmad.lo.u32 t, t, 4, 0x200000;\nmov.b64 d5, {t, h};\nand.b32 t, c6, 0xffe;\n"
        "mad.lo.u32 t, t, 4, 0x200000;\nmov.b64 d6, {t, h};\nand.b32 t, c7, 0xffe;\nmad.lo.u32 t, t, 4, 0x200000;\nmov.b64 d7, {t, h};\nand.b32 t, c8, 0xffe;\n"
        "mad.lo.u32 t, t, 4, 0x200000;\nmov.b64 d8, {t, h};\nand.b32 t, c9, 0xffe;\nmad.lo.u32 t, t, 4, 0x200000;\nmov.b64 d9, {t, h};\nand.b32 t, c10, 0xffe;\n"
        "mad.lo.u32 t, t, 4, 0x200000;\nmov.b64 d10, {t, h};\nand.b32 t, c11, 0xffe;\nmad.lo.u32 t, t, 4, 0x200000;\nmov.b64 d11, {t, h};\n"
        "and.b32 t, c12, 0xffe;\nmad.lo.u32 t, t, 4, 0x200000;\nmov.b64 d12, {t, h};\nand.b32 t, c13, 0xffe;\nmad.lo.u32 t, t, 4, 0x200000;\n"
        "mov.b64 d13, {t, h};\nand.b32 t, c14, 0xffe;\nmad.lo.u32 t, t, 4, 0x200000;\nmov.b64 d14, {t, h};\nand.b32 t, c15, 0xffe;\n"
        "mad.lo.u32 t, t, 4, 0x200000;\nmov.b64 d15, {t, h};\nwgmma.fence.sync.aligned;\n"
        "wgmma.mma_async.sync.aligned.m64n32k16.f32.bf16.bf16 {o0,o1,o2,o3,o4,o5,o6,o7,o8,o9,o10,o11,o12,o13,o14,o15}, {a0,a1,a2,a3}, d0, p0, 1, 1, 1;\n"
        "wgmma.mma_async.sync.aligned.m64n32k16.f32.bf16.bf16 {o16,o17,o18,o19,o20,o21,o22,o23,o24,o25,o26,o27,o28,o29,o30,o31}, {a0,a1,a2,a3}, d8, p0, 1, 1, 1;\n"
        "wgmma.mma_async.sync.aligned.m64n32k16.f32.bf16.bf16 {o0,o1,o2,o3,o4,o5,o6,o7,o8,o9,o10,o11,o12,o13,o14,o15}, {a4,a5,a6,a7}, d1, p1, 1, 1, 1;\n"
        "wgmma.mma_async.sync.aligned.m64n32k16.f32.bf16.bf16 {o16,o17,o18,o19,o20,o21,o22,o23,o24,o25,o26,o27,o28,o29,o30,o31}, {a4,a5,a6,a7}, d9, p1, 1, 1, 1;\n"
        "wgmma.mma_async.sync.aligned.m64n32k16.f32.bf16.bf16 {o0,o1,o2,o3,o4,o5,o6,o7,o8,o9,o10,o11,o12,o13,o14,o15}, {a8,a9,a10,a11}, d2, p1, 1, 1, 1;\n"
        "wgmma.mma_async.sync.aligned.m64n32k16.f32.bf16.bf16 {o16,o17,o18,o19,o20,o21,o22,o23,o24,o25,o26,o27,o28,o29,o30,o31}, {a8,a9,a10,a11}, d10, p1, 1, 1, 1;\n"
        "wgmma.mma_async.sync.aligned.m64n32k16.f32.bf16.bf16 {o0,o1,o2,o3,o4,o5,o6,o7,o8,o9,o10,o11,o12,o13,o14,o15}, {a12,a13,a14,a15}, d3, p1, 1, 1, 1;\n"
        "wgmma.mma_async.sync.aligned.m64n32k16.f32.bf16.bf16 {o16,o17,o18,o19,o20,o21,o22,o23,o24,o25,o26,o27,o28,o29,o30,o31}, {a12,a13,a14,a15}, d11, p1, 1, 1, 1;\n"
        "wgmma.mma_async.sync.aligned.m64n32k16.f32.bf16.bf16 {o0,o1,o2,o3,o4,o5,o6,o7,o8,o9,o10,o11,o12,o13,o14,o15}, {a16,a17,a18,a19}, d4, p1, 1, 1, 1;\n"
        "wgmma.mma_async.sync.aligned.m64n32k16.f32.bf16.bf16 {o16,o17,o18,o19,o20,o21,o22,o23,o24,o25,o26,o27,o28,o29,o30,o31}, {a16,a17,a18,a19}, d12, p1, 1, 1, 1;\n"
        "wgmma.mma_async.sync.aligned.m64n32k16.f32.bf16.bf16 {o0,o1,o2,o3,o4,o5,o6,o7,o8,o9,o10,o11,o12,o13,o14,o15}, {a20,a21,a22,a23}, d5, p1, 1, 1, 1;\n"
        "wgmma.mma_async.sync.aligned.m64n32k16.f32.bf16.bf16 {o16,o17,o18,o19,o20,o21,o22,o23,o24,o25,o26,o27,o28,o29,o30,o31}, {a20,a21,a22,a23}, d13, p1, 1, 1, 1;\n"
        "wgmma.mma_async.sync.aligned.m64n32k16.f32.bf16.bf16 {o0,o1,o2,o3,o4,o5,o6,o7,o8,o9,o10,o11,o12,o13,o14,o15}, {a24,a25,a26,a27}, d6, p1, 1, 1, 1;\n"
        "wgmma.mma_async.sync.aligned.m64n32k16.f32.bf16.bf16 {o16,o17,o18,o19,o20,o21,o22,o23,o24,o25,o26,o27,o28,o29,o30,o31}, {a24,a25,a26,a27}, d14, p1, 1, 1, 1;\n"
        "wgmma.mma_async.sync.aligned.m64n32k16.f32.bf16.bf16 {o0,o1,o2,o3,o4,o5,o6,o7,o8,o9,o10,o11,o12,o13,o14,o15}, {a28,a29,a30,a31}, d7, p1, 1, 1, 1;\n"
        "wgmma.mma_async.sync.aligned.m64n32k16.f32.bf16.bf16 {o16,o17,o18,o19,o20,o21,o22,o23,o24,o25,o26,o27,o28,o29,o30,o31}, {a28,a29,a30,a31}, d15, p1, 1, 1, 1;\n"
        "wgmma.commit_group.sync.aligned;\n@nv bra.uni END;\nmovmatrix.sync.aligned.m8n8.trans.b16 b0, %32;\nmovmatrix.sync.aligned.m8n8.trans.b16 b1, %48;\n"
        "movmatrix.sync.aligned.m8n8.trans.b16 b2, %33;\nmovmatrix.sync.aligned.m8n8.trans.b16 b3, %49;\nmovmatrix.sync.aligned.m8n8.trans.b16 b4, %34;\n"
        "movmatrix.sync.aligned.m8n8.trans.b16 b5, %50;\nmovmatrix.sync.aligned.m8n8.trans.b16 b6, %35;\nmovmatrix.sync.aligned.m8n8.trans.b16 b7, %51;\n"
        "movmatrix.sync.aligned.m8n8.trans.b16 b8, %36;\nmovmatrix.sync.aligned.m8n8.trans.b16 b9, %52;\nmovmatrix.sync.aligned.m8n8.trans.b16 b10, %37;\n"
        "movmatrix.sync.aligned.m8n8.trans.b16 b11, %53;\nmovmatrix.sync.aligned.m8n8.trans.b16 b12, %38;\nmovmatrix.sync.aligned.m8n8.trans.b16 b13, %54;\n"
        "movmatrix.sync.aligned.m8n8.trans.b16 b14, %39;\nmovmatrix.sync.aligned.m8n8.trans.b16 b15, %55;\nmovmatrix.sync.aligned.m8n8.trans.b16 b16, %40;\n"
        "movmatrix.sync.aligned.m8n8.trans.b16 b17, %56;\nmovmatrix.sync.aligned.m8n8.trans.b16 b18, %41;\nmovmatrix.sync.aligned.m8n8.trans.b16 b19, %57;\n"
        "movmatrix.sync.aligned.m8n8.trans.b16 b20, %42;\nmovmatrix.sync.aligned.m8n8.trans.b16 b21, %58;\nmovmatrix.sync.aligned.m8n8.trans.b16 b22, %43;\n"
        "movmatrix.sync.aligned.m8n8.trans.b16 b23, %59;\nmovmatrix.sync.aligned.m8n8.trans.b16 b24, %44;\nmovmatrix.sync.aligned.m8n8.trans.b16 b25, %60;\n"
        "movmatrix.sync.aligned.m8n8.trans.b16 b26, %45;\nmovmatrix.sync.aligned.m8n8.trans.b16 b27, %61;\nmovmatrix.sync.aligned.m8n8.trans.b16 b28, %46;\n"
        "movmatrix.sync.aligned.m8n8.trans.b16 b29, %62;\nmovmatrix.sync.aligned.m8n8.trans.b16 b30, %47;\nmovmatrix.sync.aligned.m8n8.trans.b16 b31, %63;\n"
        "@nv bra.uni END;\nwgmma.wait_group.sync.aligned 0;\ncvt.rn.bf16x2.f32 k0, o1, o0;\ncvt.rn.bf16x2.f32 k1, o5, o4;\ncvt.rn.bf16x2.f32 k2, o9, o8;\n"
        "cvt.rn.bf16x2.f32 k3, o13, o12;\ncvt.rn.bf16x2.f32 k4, o3, o2;\ncvt.rn.bf16x2.f32 k5, o7, o6;\ncvt.rn.bf16x2.f32 k6, o11, o10;\n"
        "cvt.rn.bf16x2.f32 k7, o15, o14;\ncvt.rn.bf16x2.f32 k8, o17, o16;\ncvt.rn.bf16x2.f32 k9, o21, o20;\ncvt.rn.bf16x2.f32 k10, o25, o24;\n"
        "cvt.rn.bf16x2.f32 k11, o29, o28;\ncvt.rn.bf16x2.f32 k12, o19, o18;\ncvt.rn.bf16x2.f32 k13, o23, o22;\ncvt.rn.bf16x2.f32 k14, o27, o26;\n"
        "cvt.rn.bf16x2.f32 k15, o31, o30;\nld.volatile.shared.v4.b32 {c0,c1,c2,c3}, [%64+0];\nld.volatile.shared.v4.b32 {c4,c5,c6,c7}, [%64+8192];\n"
        "ld.volatile.shared.v4.b32 {c8,c9,c10,c11}, [%64+16];\nld.volatile.shared.v4.b32 {c12,c13,c14,c15}, [%64+8208];\nand.b32 t, c0, 0xffe;\n"
        "mad.lo.u32 t, t, 4, 0x200000;\nmov.b64 d0, {t, h};\nand.b32 t, c1, 0xffe;\nmad.lo.u32 t, t, 4, 0x200000;\nmov.b64 d1, {t, h};\nand.b32 t, c2, 0xffe;\n"
        "mad.lo.u32 t, t, 4, 0x200000;\nmov.b64 d2, {t, h};\nand.b32 t, c3, 0xffe;\nmad.lo.u32 t, t, 4, 0x200000;\nmov.b64 d3, {t, h};\nand.b32 t, c4, 0xffe;\n"
        "mad.lo.u32 t, t, 4, 0x200000;\nmov.b64 d4, {t, h};\nand.b32 t, c5, 0xffe;\nmad.lo.u32 t, t, 4, 0x200000;\nmov.b64 d5, {t, h};\nand.b32 t, c6, 0xffe;\n"
        "mad.lo.u32 t, t, 4, 0x200000;\nmov.b64 d6, {t, h};\nand.b32 t, c7, 0xffe;\nmad.lo.u32 t, t, 4, 0x200000;\nmov.b64 d7, {t, h};\nand.b32 t, c8, 0xffe;\n"
        "mad.lo.u32 t, t, 4, 0x200000;\nmov.b64 d8, {t, h};\nand.b32 t, c9, 0xffe;\nmad.lo.u32 t, t, 4, 0x200000;\nmov.b64 d9, {t, h};\nand.b32 t, c10, 0xffe;\n"
        "mad.lo.u32 t, t, 4, 0x200000;\nmov.b64 d10, {t, h};\nand.b32 t, c11, 0xffe;\nmad.lo.u32 t, t, 4, 0x200000;\nmov.b64 d11, {t, h};\n"
        "and.b32 t, c12, 0xffe;\nmad.lo.u32 t, t, 4, 0x200000;\nmov.b64 d12, {t, h};\nand.b32 t, c13, 0xffe;\nmad.lo.u32 t, t, 4, 0x200000;\n"
        "mov.b64 d13, {t, h};\nand.b32 t, c14, 0xffe;\nmad.lo.u32 t, t, 4, 0x200000;\nmov.b64 d14, {t, h};\nand.b32 t, c15, 0xffe;\n"
        "mad.lo.u32 t, t, 4, 0x200000;\nmov.b64 d15, {t, h};\nwgmma.fence.sync.aligned;\n"
        "wgmma.mma_async.sync.aligned.m64n32k16.f32.bf16.bf16 {o0,o1,o2,o3,o4,o5,o6,o7,o8,o9,o10,o11,o12,o13,o14,o15}, {b0,b1,b2,b3}, d0, p0, 1, 1, 1;\n"
        "wgmma.mma_async.sync.aligned.m64n32k16.f32.bf16.bf16 {o16,o17,o18,o19,o20,o21,o22,o23,o24,o25,o26,o27,o28,o29,o30,o31}, {b0,b1,b2,b3}, d8, p0, 1, 1, 1;\n"
        "wgmma.mma_async.sync.aligned.m64n32k16.f32.bf16.bf16 {o0,o1,o2,o3,o4,o5,o6,o7,o8,o9,o10,o11,o12,o13,o14,o15}, {b4,b5,b6,b7}, d1, p1, 1, 1, 1;\n"
        "wgmma.mma_async.sync.aligned.m64n32k16.f32.bf16.bf16 {o16,o17,o18,o19,o20,o21,o22,o23,o24,o25,o26,o27,o28,o29,o30,o31}, {b4,b5,b6,b7}, d9, p1, 1, 1, 1;\n"
        "wgmma.mma_async.sync.aligned.m64n32k16.f32.bf16.bf16 {o0,o1,o2,o3,o4,o5,o6,o7,o8,o9,o10,o11,o12,o13,o14,o15}, {b8,b9,b10,b11}, d2, p1, 1, 1, 1;\n"
        "wgmma.mma_async.sync.aligned.m64n32k16.f32.bf16.bf16 {o16,o17,o18,o19,o20,o21,o22,o23,o24,o25,o26,o27,o28,o29,o30,o31}, {b8,b9,b10,b11}, d10, p1, 1, 1, 1;\n"
        "wgmma.mma_async.sync.aligned.m64n32k16.f32.bf16.bf16 {o0,o1,o2,o3,o4,o5,o6,o7,o8,o9,o10,o11,o12,o13,o14,o15}, {b12,b13,b14,b15}, d3, p1, 1, 1, 1;\n"
        "wgmma.mma_async.sync.aligned.m64n32k16.f32.bf16.bf16 {o16,o17,o18,o19,o20,o21,o22,o23,o24,o25,o26,o27,o28,o29,o30,o31}, {b12,b13,b14,b15}, d11, p1, 1, 1, 1;\n"
        "wgmma.mma_async.sync.aligned.m64n32k16.f32.bf16.bf16 {o0,o1,o2,o3,o4,o5,o6,o7,o8,o9,o10,o11,o12,o13,o14,o15}, {b16,b17,b18,b19}, d4, p1, 1, 1, 1;\n"
        "wgmma.mma_async.sync.aligned.m64n32k16.f32.bf16.bf16 {o16,o17,o18,o19,o20,o21,o22,o23,o24,o25,o26,o27,o28,o29,o30,o31}, {b16,b17,b18,b19}, d12, p1, 1, 1, 1;\n"
        "wgmma.mma_async.sync.aligned.m64n32k16.f32.bf16.bf16 {o0,o1,o2,o3,o4,o5,o6,o7,o8,o9,o10,o11,o12,o13,o14,o15}, {b20,b21,b22,b23}, d5, p1, 1, 1, 1;\n"
        "wgmma.mma_async.sync.aligned.m64n32k16.f32.bf16.bf16 {o16,o17,o18,o19,o20,o21,o22,o23,o24,o25,o26,o27,o28,o29,o30,o31}, {b20,b21,b22,b23}, d13, p1, 1, 1, 1;\n"
        "wgmma.mma_async.sync.aligned.m64n32k16.f32.bf16.bf16 {o0,o1,o2,o3,o4,o5,o6,o7,o8,o9,o10,o11,o12,o13,o14,o15}, {b24,b25,b26,b27}, d6, p1, 1, 1, 1;\n"
        "wgmma.mma_async.sync.aligned.m64n32k16.f32.bf16.bf16 {o16,o17,o18,o19,o20,o21,o22,o23,o24,o25,o26,o27,o28,o29,o30,o31}, {b24,b25,b26,b27}, d14, p1, 1, 1, 1;\n"
        "wgmma.mma_async.sync.aligned.m64n32k16.f32.bf16.bf16 {o0,o1,o2,o3,o4,o5,o6,o7,o8,o9,o10,o11,o12,o13,o14,o15}, {b28,b29,b30,b31}, d7, p1, 1, 1, 1;\n"
        "wgmma.mma_async.sync.aligned.m64n32k16.f32.bf16.bf16 {o16,o17,o18,o19,o20,o21,o22,o23,o24,o25,o26,o27,o28,o29,o30,o31}, {b28,b29,b30,b31}, d15, p1, 1, 1, 1;\n"
        "wgmma.commit_group.sync.aligned;\n@nv bra.uni END;\n@s0 st.global.v4.b32 [%65+128], {k0,k1,k2,k3};\n@s1 st.global.v4.b32 [%66+128], {k4,k5,k6,k7};\n"
        "@s0 st.global.v4.b32 [%65+192], {k8,k9,k10,k11};\n@s1 st.global.v4.b32 [%66+192], {k12,k13,k14,k15};\n@nv bra.uni END;\n"
        "wgmma.wait_group.sync.aligned 0;\ncvt.rn.bf16x2.f32 k0, o1, o0;\ncvt.rn.bf16x2.f32 k1, o5, o4;\ncvt.rn.bf16x2.f32 k2, o9, o8;\n"
        "cvt.rn.bf16x2.f32 k3, o13, o12;\ncvt.rn.bf16x2.f32 k4, o3, o2;\ncvt.rn.bf16x2.f32 k5, o7, o6;\ncvt.rn.bf16x2.f32 k6, o11, o10;\n"
        "cvt.rn.bf16x2.f32 k7, o15, o14;\ncvt.rn.bf16x2.f32 k8, o17, o16;\ncvt.rn.bf16x2.f32 k9, o21, o20;\ncvt.rn.bf16x2.f32 k10, o25, o24;\n"
        "cvt.rn.bf16x2.f32 k11, o29, o28;\ncvt.rn.bf16x2.f32 k12, o19, o18;\ncvt.rn.bf16x2.f32 k13, o23, o22;\ncvt.rn.bf16x2.f32 k14, o27, o26;\n"
        "cvt.rn.bf16x2.f32 k15, o31, o30;\nld.volatile.shared.v4.b32 {c0,c1,c2,c3}, [%64+32];\nld.volatile.shared.v4.b32 {c4,c5,c6,c7}, [%64+8224];\n"
        "ld.volatile.shared.v4.b32 {c8,c9,c10,c11}, [%64+48];\nld.volatile.shared.v4.b32 {c12,c13,c14,c15}, [%64+8240];\nand.b32 t, c0, 0xffe;\n"
        "mad.lo.u32 t, t, 4, 0x200000;\nmov.b64 d0, {t, h};\nand.b32 t, c1, 0xffe;\nmad.lo.u32 t, t, 4, 0x200000;\nmov.b64 d1, {t, h};\nand.b32 t, c2, 0xffe;\n"
        "mad.lo.u32 t, t, 4, 0x200000;\nmov.b64 d2, {t, h};\nand.b32 t, c3, 0xffe;\nmad.lo.u32 t, t, 4, 0x200000;\nmov.b64 d3, {t, h};\nand.b32 t, c4, 0xffe;\n"
        "mad.lo.u32 t, t, 4, 0x200000;\nmov.b64 d4, {t, h};\nand.b32 t, c5, 0xffe;\nmad.lo.u32 t, t, 4, 0x200000;\nmov.b64 d5, {t, h};\nand.b32 t, c6, 0xffe;\n"
        "mad.lo.u32 t, t, 4, 0x200000;\nmov.b64 d6, {t, h};\nand.b32 t, c7, 0xffe;\nmad.lo.u32 t, t, 4, 0x200000;\nmov.b64 d7, {t, h};\nand.b32 t, c8, 0xffe;\n"
        "mad.lo.u32 t, t, 4, 0x200000;\nmov.b64 d8, {t, h};\nand.b32 t, c9, 0xffe;\nmad.lo.u32 t, t, 4, 0x200000;\nmov.b64 d9, {t, h};\nand.b32 t, c10, 0xffe;\n"
        "mad.lo.u32 t, t, 4, 0x200000;\nmov.b64 d10, {t, h};\nand.b32 t, c11, 0xffe;\nmad.lo.u32 t, t, 4, 0x200000;\nmov.b64 d11, {t, h};\n"
        "and.b32 t, c12, 0xffe;\nmad.lo.u32 t, t, 4, 0x200000;\nmov.b64 d12, {t, h};\nand.b32 t, c13, 0xffe;\nmad.lo.u32 t, t, 4, 0x200000;\n"
        "mov.b64 d13, {t, h};\nand.b32 t, c14, 0xffe;\nmad.lo.u32 t, t, 4, 0x200000;\nmov.b64 d14, {t, h};\nand.b32 t, c15, 0xffe;\n"
        "mad.lo.u32 t, t, 4, 0x200000;\nmov.b64 d15, {t, h};\nwgmma.fence.sync.aligned;\n"
        "wgmma.mma_async.sync.aligned.m64n32k16.f32.bf16.bf16 {o0,o1,o2,o3,o4,o5,o6,o7,o8,o9,o10,o11,o12,o13,o14,o15}, {b0,b1,b2,b3}, d0, p0, 1, 1, 1;\n"
        "wgmma.mma_async.sync.aligned.m64n32k16.f32.bf16.bf16 {o16,o17,o18,o19,o20,o21,o22,o23,o24,o25,o26,o27,o28,o29,o30,o31}, {b0,b1,b2,b3}, d8, p0, 1, 1, 1;\n"
        "wgmma.mma_async.sync.aligned.m64n32k16.f32.bf16.bf16 {o0,o1,o2,o3,o4,o5,o6,o7,o8,o9,o10,o11,o12,o13,o14,o15}, {b4,b5,b6,b7}, d1, p1, 1, 1, 1;\n"
        "wgmma.mma_async.sync.aligned.m64n32k16.f32.bf16.bf16 {o16,o17,o18,o19,o20,o21,o22,o23,o24,o25,o26,o27,o28,o29,o30,o31}, {b4,b5,b6,b7}, d9, p1, 1, 1, 1;\n"
        "wgmma.mma_async.sync.aligned.m64n32k16.f32.bf16.bf16 {o0,o1,o2,o3,o4,o5,o6,o7,o8,o9,o10,o11,o12,o13,o14,o15}, {b8,b9,b10,b11}, d2, p1, 1, 1, 1;\n"
        "wgmma.mma_async.sync.aligned.m64n32k16.f32.bf16.bf16 {o16,o17,o18,o19,o20,o21,o22,o23,o24,o25,o26,o27,o28,o29,o30,o31}, {b8,b9,b10,b11}, d10, p1, 1, 1, 1;\n"
        "wgmma.mma_async.sync.aligned.m64n32k16.f32.bf16.bf16 {o0,o1,o2,o3,o4,o5,o6,o7,o8,o9,o10,o11,o12,o13,o14,o15}, {b12,b13,b14,b15}, d3, p1, 1, 1, 1;\n"
        "wgmma.mma_async.sync.aligned.m64n32k16.f32.bf16.bf16 {o16,o17,o18,o19,o20,o21,o22,o23,o24,o25,o26,o27,o28,o29,o30,o31}, {b12,b13,b14,b15}, d11, p1, 1, 1, 1;\n"
        "wgmma.mma_async.sync.aligned.m64n32k16.f32.bf16.bf16 {o0,o1,o2,o3,o4,o5,o6,o7,o8,o9,o10,o11,o12,o13,o14,o15}, {b16,b17,b18,b19}, d4, p1, 1, 1, 1;\n"
        "wgmma.mma_async.sync.aligned.m64n32k16.f32.bf16.bf16 {o16,o17,o18,o19,o20,o21,o22,o23,o24,o25,o26,o27,o28,o29,o30,o31}, {b16,b17,b18,b19}, d12, p1, 1, 1, 1;\n"
        "wgmma.mma_async.sync.aligned.m64n32k16.f32.bf16.bf16 {o0,o1,o2,o3,o4,o5,o6,o7,o8,o9,o10,o11,o12,o13,o14,o15}, {b20,b21,b22,b23}, d5, p1, 1, 1, 1;\n"
        "wgmma.mma_async.sync.aligned.m64n32k16.f32.bf16.bf16 {o16,o17,o18,o19,o20,o21,o22,o23,o24,o25,o26,o27,o28,o29,o30,o31}, {b20,b21,b22,b23}, d13, p1, 1, 1, 1;\n"
        "wgmma.mma_async.sync.aligned.m64n32k16.f32.bf16.bf16 {o0,o1,o2,o3,o4,o5,o6,o7,o8,o9,o10,o11,o12,o13,o14,o15}, {b24,b25,b26,b27}, d6, p1, 1, 1, 1;\n"
        "wgmma.mma_async.sync.aligned.m64n32k16.f32.bf16.bf16 {o16,o17,o18,o19,o20,o21,o22,o23,o24,o25,o26,o27,o28,o29,o30,o31}, {b24,b25,b26,b27}, d14, p1, 1, 1, 1;\n"
        "wgmma.mma_async.sync.aligned.m64n32k16.f32.bf16.bf16 {o0,o1,o2,o3,o4,o5,o6,o7,o8,o9,o10,o11,o12,o13,o14,o15}, {b28,b29,b30,b31}, d7, p1, 1, 1, 1;\n"
        "wgmma.mma_async.sync.aligned.m64n32k16.f32.bf16.bf16 {o16,o17,o18,o19,o20,o21,o22,o23,o24,o25,o26,o27,o28,o29,o30,o31}, {b28,b29,b30,b31}, d15, p1, 1, 1, 1;\n"
        "wgmma.commit_group.sync.aligned;\n@nv bra.uni END;\n@s2 st.global.v4.b32 [%67+0], {k0,k1,k2,k3};\n@s3 st.global.v4.b32 [%68+0], {k4,k5,k6,k7};\n"
        "@s2 st.global.v4.b32 [%67+64], {k8,k9,k10,k11};\n@s3 st.global.v4.b32 [%68+64], {k12,k13,k14,k15};\n@nv bra.uni END;\nwgmma.wait_group.sync.aligned 0;\n"
        "cvt.rn.bf16x2.f32 k0, o1, o0;\ncvt.rn.bf16x2.f32 k1, o5, o4;\ncvt.rn.bf16x2.f32 k2, o9, o8;\ncvt.rn.bf16x2.f32 k3, o13, o12;\n"
        "cvt.rn.bf16x2.f32 k4, o3, o2;\ncvt.rn.bf16x2.f32 k5, o7, o6;\ncvt.rn.bf16x2.f32 k6, o11, o10;\ncvt.rn.bf16x2.f32 k7, o15, o14;\n"
        "cvt.rn.bf16x2.f32 k8, o17, o16;\ncvt.rn.bf16x2.f32 k9, o21, o20;\ncvt.rn.bf16x2.f32 k10, o25, o24;\ncvt.rn.bf16x2.f32 k11, o29, o28;\n"
        "cvt.rn.bf16x2.f32 k12, o19, o18;\ncvt.rn.bf16x2.f32 k13, o23, o22;\ncvt.rn.bf16x2.f32 k14, o27, o26;\ncvt.rn.bf16x2.f32 k15, o31, o30;\n"
        "@s2 st.global.v4.b32 [%67+128], {k0,k1,k2,k3};\n@s3 st.global.v4.b32 [%68+128], {k4,k5,k6,k7};\n@s2 st.global.v4.b32 [%67+192], {k8,k9,k10,k11};\n"
        "@s3 st.global.v4.b32 [%68+192], {k12,k13,k14,k15};\n"
        "END:\n}\n"
        ::"r"(pk[0]), "r"(pk[1]), "r"(pk[2]), "r"(pk[3]), "r"(pk[4]), "r"(pk[5]), "r"(pk[6]), "r"(pk[7]), "r"(pk[8]), "r"(pk[9]), "r"(pk[10]),
          "r"(pk[11]), "r"(pk[12]), "r"(pk[13]), "r"(pk[14]), "r"(pk[15]), "r"(pk[16]), "r"(pk[17]), "r"(pk[18]), "r"(pk[19]), "r"(pk[20]),
          "r"(pk[21]), "r"(pk[22]), "r"(pk[23]), "r"(pk[24]), "r"(pk[25]), "r"(pk[26]), "r"(pk[27]), "r"(pk[28]), "r"(pk[29]), "r"(pk[30]),
          "r"(pk[31]), "r"(pk[32]), "r"(pk[33]), "r"(pk[34]), "r"(pk[35]), "r"(pk[36]), "r"(pk[37]), "r"(pk[38]), "r"(pk[39]), "r"(pk[40]),
          "r"(pk[41]), "r"(pk[42]), "r"(pk[43]), "r"(pk[44]), "r"(pk[45]), "r"(pk[46]), "r"(pk[47]), "r"(pk[48]), "r"(pk[49]), "r"(pk[50]),
          "r"(pk[51]), "r"(pk[52]), "r"(pk[53]), "r"(pk[54]), "r"(pk[55]), "r"(pk[56]), "r"(pk[57]), "r"(pk[58]), "r"(pk[59]), "r"(pk[60]),
          "r"(pk[61]), "r"(pk[62]), "r"(pk[63]), "r"(ra), "l"(p[0]), "l"(p[1]), "l"(p[2]), "l"(p[3]), "r"(v[0]), "r"(v[1]), "r"(v[2]), "r"(v[3]),
          "r"(ba)
        : "memory");
}
__device__ __forceinline__ void project3(const uint32_t (&pk)[48], uint32_t ra, uint32_t ba, uint4* const (&p)[3], const uint32_t (&v)[3]) {
    asm volatile(
        "{\n.reg .pred p0, p1, q0, q1, nv, s<4>;\n.reg .b32 t, h, c<16>, a<32>, b<32>, k<16>;\n.reg .b64 d<16>;\n.reg .f32 o<32>;\nsetp.ne.b32 p0, 0, 0;\n"
        "setp.eq.b32 p1, 0, 0;\nmov.b32 h, 8;\nsetp.eq.u32 nv, %48, 0;\nvote.sync.any.pred nv, nv, 0xffffffff;\nsetp.ne.b32 s0, %52, 0;\n"
        "setp.ne.b32 s1, %53, 0;\nsetp.ne.b32 s2, %54, 0;\nmovmatrix.sync.aligned.m8n8.trans.b16 a0, %0;\nmovmatrix.sync.aligned.m8n8.trans.b16 a1, %16;\n"
        "movmatrix.sync.aligned.m8n8.trans.b16 a2, %1;\nmovmatrix.sync.aligned.m8n8.trans.b16 a3, %17;\nmovmatrix.sync.aligned.m8n8.trans.b16 a4, %2;\n"
        "movmatrix.sync.aligned.m8n8.trans.b16 a5, %18;\nmovmatrix.sync.aligned.m8n8.trans.b16 a6, %3;\nmovmatrix.sync.aligned.m8n8.trans.b16 a7, %19;\n"
        "movmatrix.sync.aligned.m8n8.trans.b16 a8, %4;\nmovmatrix.sync.aligned.m8n8.trans.b16 a9, %20;\nmovmatrix.sync.aligned.m8n8.trans.b16 a10, %5;\n"
        "movmatrix.sync.aligned.m8n8.trans.b16 a11, %21;\nmovmatrix.sync.aligned.m8n8.trans.b16 a12, %6;\nmovmatrix.sync.aligned.m8n8.trans.b16 a13, %22;\n"
        "movmatrix.sync.aligned.m8n8.trans.b16 a14, %7;\nmovmatrix.sync.aligned.m8n8.trans.b16 a15, %23;\nmovmatrix.sync.aligned.m8n8.trans.b16 a16, %8;\n"
        "movmatrix.sync.aligned.m8n8.trans.b16 a17, %24;\nmovmatrix.sync.aligned.m8n8.trans.b16 a18, %9;\nmovmatrix.sync.aligned.m8n8.trans.b16 a19, %25;\n"
        "movmatrix.sync.aligned.m8n8.trans.b16 a20, %10;\nmovmatrix.sync.aligned.m8n8.trans.b16 a21, %26;\nmovmatrix.sync.aligned.m8n8.trans.b16 a22, %11;\n"
        "movmatrix.sync.aligned.m8n8.trans.b16 a23, %27;\nmovmatrix.sync.aligned.m8n8.trans.b16 a24, %12;\nmovmatrix.sync.aligned.m8n8.trans.b16 a25, %28;\n"
        "movmatrix.sync.aligned.m8n8.trans.b16 a26, %13;\nmovmatrix.sync.aligned.m8n8.trans.b16 a27, %29;\nmovmatrix.sync.aligned.m8n8.trans.b16 a28, %14;\n"
        "movmatrix.sync.aligned.m8n8.trans.b16 a29, %30;\nmovmatrix.sync.aligned.m8n8.trans.b16 a30, %15;\nmovmatrix.sync.aligned.m8n8.trans.b16 a31, %31;\n"
        "mov.b32 t, 0;\n"
        "W0:\nmbarrier.try_wait.parity.shared.b64 q0, [%55+0], 0;\nadd.u32 t, t, 1;\nsetp.lt.and.u32 q1, t, 1000000, !q0;\n@q1 bra.uni W0;\nmov.b32 t, 0;\n"
        "W1:\nmbarrier.try_wait.parity.shared.b64 q0, [%55+8], 0;\nadd.u32 t, t, 1;\nsetp.lt.and.u32 q1, t, 1000000, !q0;\n@q1 bra.uni W1;\nmov.b32 t, 0;\n"
        "W2:\nmbarrier.try_wait.parity.shared.b64 q0, [%55+16], 0;\nadd.u32 t, t, 1;\nsetp.lt.and.u32 q1, t, 1000000, !q0;\n@q1 bra.uni W2;\nmov.b32 t, 0;\n"
        "W3:\nmbarrier.try_wait.parity.shared.b64 q0, [%55+24], 0;\nadd.u32 t, t, 1;\nsetp.lt.and.u32 q1, t, 1000000, !q0;\n@q1 bra.uni W3;\n"
        "ld.volatile.shared.v4.b32 {c0,c1,c2,c3}, [%48+0];\nld.volatile.shared.v4.b32 {c4,c5,c6,c7}, [%48+8192];\n"
        "ld.volatile.shared.v4.b32 {c8,c9,c10,c11}, [%48+16];\nld.volatile.shared.v4.b32 {c12,c13,c14,c15}, [%48+8208];\nand.b32 t, c0, 0xffe;\n"
        "mad.lo.u32 t, t, 4, 0x200000;\nmov.b64 d0, {t, h};\nand.b32 t, c1, 0xffe;\nmad.lo.u32 t, t, 4, 0x200000;\nmov.b64 d1, {t, h};\nand.b32 t, c2, 0xffe;\n"
        "mad.lo.u32 t, t, 4, 0x200000;\nmov.b64 d2, {t, h};\nand.b32 t, c3, 0xffe;\nmad.lo.u32 t, t, 4, 0x200000;\nmov.b64 d3, {t, h};\nand.b32 t, c4, 0xffe;\n"
        "mad.lo.u32 t, t, 4, 0x200000;\nmov.b64 d4, {t, h};\nand.b32 t, c5, 0xffe;\nmad.lo.u32 t, t, 4, 0x200000;\nmov.b64 d5, {t, h};\nand.b32 t, c6, 0xffe;\n"
        "mad.lo.u32 t, t, 4, 0x200000;\nmov.b64 d6, {t, h};\nand.b32 t, c7, 0xffe;\nmad.lo.u32 t, t, 4, 0x200000;\nmov.b64 d7, {t, h};\nand.b32 t, c8, 0xffe;\n"
        "mad.lo.u32 t, t, 4, 0x200000;\nmov.b64 d8, {t, h};\nand.b32 t, c9, 0xffe;\nmad.lo.u32 t, t, 4, 0x200000;\nmov.b64 d9, {t, h};\nand.b32 t, c10, 0xffe;\n"
        "mad.lo.u32 t, t, 4, 0x200000;\nmov.b64 d10, {t, h};\nand.b32 t, c11, 0xffe;\nmad.lo.u32 t, t, 4, 0x200000;\nmov.b64 d11, {t, h};\n"
        "and.b32 t, c12, 0xffe;\nmad.lo.u32 t, t, 4, 0x200000;\nmov.b64 d12, {t, h};\nand.b32 t, c13, 0xffe;\nmad.lo.u32 t, t, 4, 0x200000;\n"
        "mov.b64 d13, {t, h};\nand.b32 t, c14, 0xffe;\nmad.lo.u32 t, t, 4, 0x200000;\nmov.b64 d14, {t, h};\nand.b32 t, c15, 0xffe;\n"
        "mad.lo.u32 t, t, 4, 0x200000;\nmov.b64 d15, {t, h};\nwgmma.fence.sync.aligned;\n"
        "wgmma.mma_async.sync.aligned.m64n32k16.f32.bf16.bf16 {o0,o1,o2,o3,o4,o5,o6,o7,o8,o9,o10,o11,o12,o13,o14,o15}, {a0,a1,a2,a3}, d0, p0, 1, 1, 1;\n"
        "wgmma.mma_async.sync.aligned.m64n32k16.f32.bf16.bf16 {o16,o17,o18,o19,o20,o21,o22,o23,o24,o25,o26,o27,o28,o29,o30,o31}, {a0,a1,a2,a3}, d8, p0, 1, 1, 1;\n"
        "wgmma.mma_async.sync.aligned.m64n32k16.f32.bf16.bf16 {o0,o1,o2,o3,o4,o5,o6,o7,o8,o9,o10,o11,o12,o13,o14,o15}, {a4,a5,a6,a7}, d1, p1, 1, 1, 1;\n"
        "wgmma.mma_async.sync.aligned.m64n32k16.f32.bf16.bf16 {o16,o17,o18,o19,o20,o21,o22,o23,o24,o25,o26,o27,o28,o29,o30,o31}, {a4,a5,a6,a7}, d9, p1, 1, 1, 1;\n"
        "wgmma.mma_async.sync.aligned.m64n32k16.f32.bf16.bf16 {o0,o1,o2,o3,o4,o5,o6,o7,o8,o9,o10,o11,o12,o13,o14,o15}, {a8,a9,a10,a11}, d2, p1, 1, 1, 1;\n"
        "wgmma.mma_async.sync.aligned.m64n32k16.f32.bf16.bf16 {o16,o17,o18,o19,o20,o21,o22,o23,o24,o25,o26,o27,o28,o29,o30,o31}, {a8,a9,a10,a11}, d10, p1, 1, 1, 1;\n"
        "wgmma.mma_async.sync.aligned.m64n32k16.f32.bf16.bf16 {o0,o1,o2,o3,o4,o5,o6,o7,o8,o9,o10,o11,o12,o13,o14,o15}, {a12,a13,a14,a15}, d3, p1, 1, 1, 1;\n"
        "wgmma.mma_async.sync.aligned.m64n32k16.f32.bf16.bf16 {o16,o17,o18,o19,o20,o21,o22,o23,o24,o25,o26,o27,o28,o29,o30,o31}, {a12,a13,a14,a15}, d11, p1, 1, 1, 1;\n"
        "wgmma.mma_async.sync.aligned.m64n32k16.f32.bf16.bf16 {o0,o1,o2,o3,o4,o5,o6,o7,o8,o9,o10,o11,o12,o13,o14,o15}, {a16,a17,a18,a19}, d4, p1, 1, 1, 1;\n"
        "wgmma.mma_async.sync.aligned.m64n32k16.f32.bf16.bf16 {o16,o17,o18,o19,o20,o21,o22,o23,o24,o25,o26,o27,o28,o29,o30,o31}, {a16,a17,a18,a19}, d12, p1, 1, 1, 1;\n"
        "wgmma.mma_async.sync.aligned.m64n32k16.f32.bf16.bf16 {o0,o1,o2,o3,o4,o5,o6,o7,o8,o9,o10,o11,o12,o13,o14,o15}, {a20,a21,a22,a23}, d5, p1, 1, 1, 1;\n"
        "wgmma.mma_async.sync.aligned.m64n32k16.f32.bf16.bf16 {o16,o17,o18,o19,o20,o21,o22,o23,o24,o25,o26,o27,o28,o29,o30,o31}, {a20,a21,a22,a23}, d13, p1, 1, 1, 1;\n"
        "wgmma.mma_async.sync.aligned.m64n32k16.f32.bf16.bf16 {o0,o1,o2,o3,o4,o5,o6,o7,o8,o9,o10,o11,o12,o13,o14,o15}, {a24,a25,a26,a27}, d6, p1, 1, 1, 1;\n"
        "wgmma.mma_async.sync.aligned.m64n32k16.f32.bf16.bf16 {o16,o17,o18,o19,o20,o21,o22,o23,o24,o25,o26,o27,o28,o29,o30,o31}, {a24,a25,a26,a27}, d14, p1, 1, 1, 1;\n"
        "wgmma.mma_async.sync.aligned.m64n32k16.f32.bf16.bf16 {o0,o1,o2,o3,o4,o5,o6,o7,o8,o9,o10,o11,o12,o13,o14,o15}, {a28,a29,a30,a31}, d7, p1, 1, 1, 1;\n"
        "wgmma.mma_async.sync.aligned.m64n32k16.f32.bf16.bf16 {o16,o17,o18,o19,o20,o21,o22,o23,o24,o25,o26,o27,o28,o29,o30,o31}, {a28,a29,a30,a31}, d15, p1, 1, 1, 1;\n"
        "wgmma.commit_group.sync.aligned;\n@nv bra.uni END;\n@nv bra.uni END;\nwgmma.wait_group.sync.aligned 0;\ncvt.rn.bf16x2.f32 k0, o1, o0;\n"
        "cvt.rn.bf16x2.f32 k1, o5, o4;\ncvt.rn.bf16x2.f32 k2, o9, o8;\ncvt.rn.bf16x2.f32 k3, o13, o12;\ncvt.rn.bf16x2.f32 k4, o3, o2;\n"
        "cvt.rn.bf16x2.f32 k5, o7, o6;\ncvt.rn.bf16x2.f32 k6, o11, o10;\ncvt.rn.bf16x2.f32 k7, o15, o14;\ncvt.rn.bf16x2.f32 k8, o17, o16;\n"
        "cvt.rn.bf16x2.f32 k9, o21, o20;\ncvt.rn.bf16x2.f32 k10, o25, o24;\ncvt.rn.bf16x2.f32 k11, o29, o28;\ncvt.rn.bf16x2.f32 k12, o19, o18;\n"
        "cvt.rn.bf16x2.f32 k13, o23, o22;\ncvt.rn.bf16x2.f32 k14, o27, o26;\ncvt.rn.bf16x2.f32 k15, o31, o30;\n@s0 st.global.v4.b32 [%49+0], {k0,k1,k2,k3};\n"
        "@s1 st.global.v4.b32 [%50+0], {k4,k5,k6,k7};\n@s0 st.global.v4.b32 [%49+64], {k8,k9,k10,k11};\n@s1 st.global.v4.b32 [%50+64], {k12,k13,k14,k15};\n"
        "@nv bra.uni END;\nld.volatile.shared.v4.b32 {c0,c1,c2,c3}, [%48+32];\nld.volatile.shared.v4.b32 {c4,c5,c6,c7}, [%48+8224];\n"
        "ld.volatile.shared.v4.b32 {c8,c9,c10,c11}, [%48+48];\nld.volatile.shared.v4.b32 {c12,c13,c14,c15}, [%48+8240];\nand.b32 t, c0, 0xffe;\n"
        "mad.lo.u32 t, t, 4, 0x200000;\nmov.b64 d0, {t, h};\nand.b32 t, c1, 0xffe;\nmad.lo.u32 t, t, 4, 0x200000;\nmov.b64 d1, {t, h};\nand.b32 t, c2, 0xffe;\n"
        "mad.lo.u32 t, t, 4, 0x200000;\nmov.b64 d2, {t, h};\nand.b32 t, c3, 0xffe;\nmad.lo.u32 t, t, 4, 0x200000;\nmov.b64 d3, {t, h};\nand.b32 t, c4, 0xffe;\n"
        "mad.lo.u32 t, t, 4, 0x200000;\nmov.b64 d4, {t, h};\nand.b32 t, c5, 0xffe;\nmad.lo.u32 t, t, 4, 0x200000;\nmov.b64 d5, {t, h};\nand.b32 t, c6, 0xffe;\n"
        "mad.lo.u32 t, t, 4, 0x200000;\nmov.b64 d6, {t, h};\nand.b32 t, c7, 0xffe;\nmad.lo.u32 t, t, 4, 0x200000;\nmov.b64 d7, {t, h};\nand.b32 t, c8, 0xffe;\n"
        "mad.lo.u32 t, t, 4, 0x200000;\nmov.b64 d8, {t, h};\nand.b32 t, c9, 0xffe;\nmad.lo.u32 t, t, 4, 0x200000;\nmov.b64 d9, {t, h};\nand.b32 t, c10, 0xffe;\n"
        "mad.lo.u32 t, t, 4, 0x200000;\nmov.b64 d10, {t, h};\nand.b32 t, c11, 0xffe;\nmad.lo.u32 t, t, 4, 0x200000;\nmov.b64 d11, {t, h};\n"
        "and.b32 t, c12, 0xffe;\nmad.lo.u32 t, t, 4, 0x200000;\nmov.b64 d12, {t, h};\nand.b32 t, c13, 0xffe;\nmad.lo.u32 t, t, 4, 0x200000;\n"
        "mov.b64 d13, {t, h};\nand.b32 t, c14, 0xffe;\nmad.lo.u32 t, t, 4, 0x200000;\nmov.b64 d14, {t, h};\nand.b32 t, c15, 0xffe;\n"
        "mad.lo.u32 t, t, 4, 0x200000;\nmov.b64 d15, {t, h};\nwgmma.fence.sync.aligned;\n"
        "wgmma.mma_async.sync.aligned.m64n32k16.f32.bf16.bf16 {o0,o1,o2,o3,o4,o5,o6,o7,o8,o9,o10,o11,o12,o13,o14,o15}, {a0,a1,a2,a3}, d0, p0, 1, 1, 1;\n"
        "wgmma.mma_async.sync.aligned.m64n32k16.f32.bf16.bf16 {o16,o17,o18,o19,o20,o21,o22,o23,o24,o25,o26,o27,o28,o29,o30,o31}, {a0,a1,a2,a3}, d8, p0, 1, 1, 1;\n"
        "wgmma.mma_async.sync.aligned.m64n32k16.f32.bf16.bf16 {o0,o1,o2,o3,o4,o5,o6,o7,o8,o9,o10,o11,o12,o13,o14,o15}, {a4,a5,a6,a7}, d1, p1, 1, 1, 1;\n"
        "wgmma.mma_async.sync.aligned.m64n32k16.f32.bf16.bf16 {o16,o17,o18,o19,o20,o21,o22,o23,o24,o25,o26,o27,o28,o29,o30,o31}, {a4,a5,a6,a7}, d9, p1, 1, 1, 1;\n"
        "wgmma.mma_async.sync.aligned.m64n32k16.f32.bf16.bf16 {o0,o1,o2,o3,o4,o5,o6,o7,o8,o9,o10,o11,o12,o13,o14,o15}, {a8,a9,a10,a11}, d2, p1, 1, 1, 1;\n"
        "wgmma.mma_async.sync.aligned.m64n32k16.f32.bf16.bf16 {o16,o17,o18,o19,o20,o21,o22,o23,o24,o25,o26,o27,o28,o29,o30,o31}, {a8,a9,a10,a11}, d10, p1, 1, 1, 1;\n"
        "wgmma.mma_async.sync.aligned.m64n32k16.f32.bf16.bf16 {o0,o1,o2,o3,o4,o5,o6,o7,o8,o9,o10,o11,o12,o13,o14,o15}, {a12,a13,a14,a15}, d3, p1, 1, 1, 1;\n"
        "wgmma.mma_async.sync.aligned.m64n32k16.f32.bf16.bf16 {o16,o17,o18,o19,o20,o21,o22,o23,o24,o25,o26,o27,o28,o29,o30,o31}, {a12,a13,a14,a15}, d11, p1, 1, 1, 1;\n"
        "wgmma.mma_async.sync.aligned.m64n32k16.f32.bf16.bf16 {o0,o1,o2,o3,o4,o5,o6,o7,o8,o9,o10,o11,o12,o13,o14,o15}, {a16,a17,a18,a19}, d4, p1, 1, 1, 1;\n"
        "wgmma.mma_async.sync.aligned.m64n32k16.f32.bf16.bf16 {o16,o17,o18,o19,o20,o21,o22,o23,o24,o25,o26,o27,o28,o29,o30,o31}, {a16,a17,a18,a19}, d12, p1, 1, 1, 1;\n"
        "wgmma.mma_async.sync.aligned.m64n32k16.f32.bf16.bf16 {o0,o1,o2,o3,o4,o5,o6,o7,o8,o9,o10,o11,o12,o13,o14,o15}, {a20,a21,a22,a23}, d5, p1, 1, 1, 1;\n"
        "wgmma.mma_async.sync.aligned.m64n32k16.f32.bf16.bf16 {o16,o17,o18,o19,o20,o21,o22,o23,o24,o25,o26,o27,o28,o29,o30,o31}, {a20,a21,a22,a23}, d13, p1, 1, 1, 1;\n"
        "wgmma.mma_async.sync.aligned.m64n32k16.f32.bf16.bf16 {o0,o1,o2,o3,o4,o5,o6,o7,o8,o9,o10,o11,o12,o13,o14,o15}, {a24,a25,a26,a27}, d6, p1, 1, 1, 1;\n"
        "wgmma.mma_async.sync.aligned.m64n32k16.f32.bf16.bf16 {o16,o17,o18,o19,o20,o21,o22,o23,o24,o25,o26,o27,o28,o29,o30,o31}, {a24,a25,a26,a27}, d14, p1, 1, 1, 1;\n"
        "wgmma.mma_async.sync.aligned.m64n32k16.f32.bf16.bf16 {o0,o1,o2,o3,o4,o5,o6,o7,o8,o9,o10,o11,o12,o13,o14,o15}, {a28,a29,a30,a31}, d7, p1, 1, 1, 1;\n"
        "wgmma.mma_async.sync.aligned.m64n32k16.f32.bf16.bf16 {o16,o17,o18,o19,o20,o21,o22,o23,o24,o25,o26,o27,o28,o29,o30,o31}, {a28,a29,a30,a31}, d15, p1, 1, 1, 1;\n"
        "wgmma.commit_group.sync.aligned;\n@nv bra.uni END;\nmovmatrix.sync.aligned.m8n8.trans.b16 b0, %32;\nmovmatrix.sync.aligned.m8n8.trans.b16 b1, %32;\n"
        "movmatrix.sync.aligned.m8n8.trans.b16 b2, %33;\nmovmatrix.sync.aligned.m8n8.trans.b16 b3, %33;\nmovmatrix.sync.aligned.m8n8.trans.b16 b4, %34;\n"
        "movmatrix.sync.aligned.m8n8.trans.b16 b5, %34;\nmovmatrix.sync.aligned.m8n8.trans.b16 b6, %35;\nmovmatrix.sync.aligned.m8n8.trans.b16 b7, %35;\n"
        "movmatrix.sync.aligned.m8n8.trans.b16 b8, %36;\nmovmatrix.sync.aligned.m8n8.trans.b16 b9, %36;\nmovmatrix.sync.aligned.m8n8.trans.b16 b10, %37;\n"
        "movmatrix.sync.aligned.m8n8.trans.b16 b11, %37;\nmovmatrix.sync.aligned.m8n8.trans.b16 b12, %38;\nmovmatrix.sync.aligned.m8n8.trans.b16 b13, %38;\n"
        "movmatrix.sync.aligned.m8n8.trans.b16 b14, %39;\nmovmatrix.sync.aligned.m8n8.trans.b16 b15, %39;\nmovmatrix.sync.aligned.m8n8.trans.b16 b16, %40;\n"
        "movmatrix.sync.aligned.m8n8.trans.b16 b17, %40;\nmovmatrix.sync.aligned.m8n8.trans.b16 b18, %41;\nmovmatrix.sync.aligned.m8n8.trans.b16 b19, %41;\n"
        "movmatrix.sync.aligned.m8n8.trans.b16 b20, %42;\nmovmatrix.sync.aligned.m8n8.trans.b16 b21, %42;\nmovmatrix.sync.aligned.m8n8.trans.b16 b22, %43;\n"
        "movmatrix.sync.aligned.m8n8.trans.b16 b23, %43;\nmovmatrix.sync.aligned.m8n8.trans.b16 b24, %44;\nmovmatrix.sync.aligned.m8n8.trans.b16 b25, %44;\n"
        "movmatrix.sync.aligned.m8n8.trans.b16 b26, %45;\nmovmatrix.sync.aligned.m8n8.trans.b16 b27, %45;\nmovmatrix.sync.aligned.m8n8.trans.b16 b28, %46;\n"
        "movmatrix.sync.aligned.m8n8.trans.b16 b29, %46;\nmovmatrix.sync.aligned.m8n8.trans.b16 b30, %47;\nmovmatrix.sync.aligned.m8n8.trans.b16 b31, %47;\n"
        "@nv bra.uni END;\nwgmma.wait_group.sync.aligned 0;\ncvt.rn.bf16x2.f32 k0, o1, o0;\ncvt.rn.bf16x2.f32 k1, o5, o4;\ncvt.rn.bf16x2.f32 k2, o9, o8;\n"
        "cvt.rn.bf16x2.f32 k3, o13, o12;\ncvt.rn.bf16x2.f32 k4, o3, o2;\ncvt.rn.bf16x2.f32 k5, o7, o6;\ncvt.rn.bf16x2.f32 k6, o11, o10;\n"
        "cvt.rn.bf16x2.f32 k7, o15, o14;\ncvt.rn.bf16x2.f32 k8, o17, o16;\ncvt.rn.bf16x2.f32 k9, o21, o20;\ncvt.rn.bf16x2.f32 k10, o25, o24;\n"
        "cvt.rn.bf16x2.f32 k11, o29, o28;\ncvt.rn.bf16x2.f32 k12, o19, o18;\ncvt.rn.bf16x2.f32 k13, o23, o22;\ncvt.rn.bf16x2.f32 k14, o27, o26;\n"
        "cvt.rn.bf16x2.f32 k15, o31, o30;\nld.volatile.shared.v4.b32 {c0,c1,c2,c3}, [%48+0];\nld.volatile.shared.v4.b32 {c4,c5,c6,c7}, [%48+8192];\n"
        "ld.volatile.shared.v4.b32 {c8,c9,c10,c11}, [%48+16];\nld.volatile.shared.v4.b32 {c12,c13,c14,c15}, [%48+8208];\nand.b32 t, c0, 0xffe;\n"
        "mad.lo.u32 t, t, 4, 0x200000;\nmov.b64 d0, {t, h};\nand.b32 t, c1, 0xffe;\nmad.lo.u32 t, t, 4, 0x200000;\nmov.b64 d1, {t, h};\nand.b32 t, c2, 0xffe;\n"
        "mad.lo.u32 t, t, 4, 0x200000;\nmov.b64 d2, {t, h};\nand.b32 t, c3, 0xffe;\nmad.lo.u32 t, t, 4, 0x200000;\nmov.b64 d3, {t, h};\nand.b32 t, c4, 0xffe;\n"
        "mad.lo.u32 t, t, 4, 0x200000;\nmov.b64 d4, {t, h};\nand.b32 t, c5, 0xffe;\nmad.lo.u32 t, t, 4, 0x200000;\nmov.b64 d5, {t, h};\nand.b32 t, c6, 0xffe;\n"
        "mad.lo.u32 t, t, 4, 0x200000;\nmov.b64 d6, {t, h};\nand.b32 t, c7, 0xffe;\nmad.lo.u32 t, t, 4, 0x200000;\nmov.b64 d7, {t, h};\nand.b32 t, c8, 0xffe;\n"
        "mad.lo.u32 t, t, 4, 0x200000;\nmov.b64 d8, {t, h};\nand.b32 t, c9, 0xffe;\nmad.lo.u32 t, t, 4, 0x200000;\nmov.b64 d9, {t, h};\nand.b32 t, c10, 0xffe;\n"
        "mad.lo.u32 t, t, 4, 0x200000;\nmov.b64 d10, {t, h};\nand.b32 t, c11, 0xffe;\nmad.lo.u32 t, t, 4, 0x200000;\nmov.b64 d11, {t, h};\n"
        "and.b32 t, c12, 0xffe;\nmad.lo.u32 t, t, 4, 0x200000;\nmov.b64 d12, {t, h};\nand.b32 t, c13, 0xffe;\nmad.lo.u32 t, t, 4, 0x200000;\n"
        "mov.b64 d13, {t, h};\nand.b32 t, c14, 0xffe;\nmad.lo.u32 t, t, 4, 0x200000;\nmov.b64 d14, {t, h};\nand.b32 t, c15, 0xffe;\n"
        "mad.lo.u32 t, t, 4, 0x200000;\nmov.b64 d15, {t, h};\nwgmma.fence.sync.aligned;\n"
        "wgmma.mma_async.sync.aligned.m64n32k16.f32.bf16.bf16 {o0,o1,o2,o3,o4,o5,o6,o7,o8,o9,o10,o11,o12,o13,o14,o15}, {b0,b1,b2,b3}, d0, p0, 1, 1, 1;\n"
        "wgmma.mma_async.sync.aligned.m64n32k16.f32.bf16.bf16 {o16,o17,o18,o19,o20,o21,o22,o23,o24,o25,o26,o27,o28,o29,o30,o31}, {b0,b1,b2,b3}, d8, p0, 1, 1, 1;\n"
        "wgmma.mma_async.sync.aligned.m64n32k16.f32.bf16.bf16 {o0,o1,o2,o3,o4,o5,o6,o7,o8,o9,o10,o11,o12,o13,o14,o15}, {b4,b5,b6,b7}, d1, p1, 1, 1, 1;\n"
        "wgmma.mma_async.sync.aligned.m64n32k16.f32.bf16.bf16 {o16,o17,o18,o19,o20,o21,o22,o23,o24,o25,o26,o27,o28,o29,o30,o31}, {b4,b5,b6,b7}, d9, p1, 1, 1, 1;\n"
        "wgmma.mma_async.sync.aligned.m64n32k16.f32.bf16.bf16 {o0,o1,o2,o3,o4,o5,o6,o7,o8,o9,o10,o11,o12,o13,o14,o15}, {b8,b9,b10,b11}, d2, p1, 1, 1, 1;\n"
        "wgmma.mma_async.sync.aligned.m64n32k16.f32.bf16.bf16 {o16,o17,o18,o19,o20,o21,o22,o23,o24,o25,o26,o27,o28,o29,o30,o31}, {b8,b9,b10,b11}, d10, p1, 1, 1, 1;\n"
        "wgmma.mma_async.sync.aligned.m64n32k16.f32.bf16.bf16 {o0,o1,o2,o3,o4,o5,o6,o7,o8,o9,o10,o11,o12,o13,o14,o15}, {b12,b13,b14,b15}, d3, p1, 1, 1, 1;\n"
        "wgmma.mma_async.sync.aligned.m64n32k16.f32.bf16.bf16 {o16,o17,o18,o19,o20,o21,o22,o23,o24,o25,o26,o27,o28,o29,o30,o31}, {b12,b13,b14,b15}, d11, p1, 1, 1, 1;\n"
        "wgmma.mma_async.sync.aligned.m64n32k16.f32.bf16.bf16 {o0,o1,o2,o3,o4,o5,o6,o7,o8,o9,o10,o11,o12,o13,o14,o15}, {b16,b17,b18,b19}, d4, p1, 1, 1, 1;\n"
        "wgmma.mma_async.sync.aligned.m64n32k16.f32.bf16.bf16 {o16,o17,o18,o19,o20,o21,o22,o23,o24,o25,o26,o27,o28,o29,o30,o31}, {b16,b17,b18,b19}, d12, p1, 1, 1, 1;\n"
        "wgmma.mma_async.sync.aligned.m64n32k16.f32.bf16.bf16 {o0,o1,o2,o3,o4,o5,o6,o7,o8,o9,o10,o11,o12,o13,o14,o15}, {b20,b21,b22,b23}, d5, p1, 1, 1, 1;\n"
        "wgmma.mma_async.sync.aligned.m64n32k16.f32.bf16.bf16 {o16,o17,o18,o19,o20,o21,o22,o23,o24,o25,o26,o27,o28,o29,o30,o31}, {b20,b21,b22,b23}, d13, p1, 1, 1, 1;\n"
        "wgmma.mma_async.sync.aligned.m64n32k16.f32.bf16.bf16 {o0,o1,o2,o3,o4,o5,o6,o7,o8,o9,o10,o11,o12,o13,o14,o15}, {b24,b25,b26,b27}, d6, p1, 1, 1, 1;\n"
        "wgmma.mma_async.sync.aligned.m64n32k16.f32.bf16.bf16 {o16,o17,o18,o19,o20,o21,o22,o23,o24,o25,o26,o27,o28,o29,o30,o31}, {b24,b25,b26,b27}, d14, p1, 1, 1, 1;\n"
        "wgmma.mma_async.sync.aligned.m64n32k16.f32.bf16.bf16 {o0,o1,o2,o3,o4,o5,o6,o7,o8,o9,o10,o11,o12,o13,o14,o15}, {b28,b29,b30,b31}, d7, p1, 1, 1, 1;\n"
        "wgmma.mma_async.sync.aligned.m64n32k16.f32.bf16.bf16 {o16,o17,o18,o19,o20,o21,o22,o23,o24,o25,o26,o27,o28,o29,o30,o31}, {b28,b29,b30,b31}, d15, p1, 1, 1, 1;\n"
        "wgmma.commit_group.sync.aligned;\n@nv bra.uni END;\n@s0 st.global.v4.b32 [%49+128], {k0,k1,k2,k3};\n@s1 st.global.v4.b32 [%50+128], {k4,k5,k6,k7};\n"
        "@s0 st.global.v4.b32 [%49+192], {k8,k9,k10,k11};\n@s1 st.global.v4.b32 [%50+192], {k12,k13,k14,k15};\n@nv bra.uni END;\n"
        "wgmma.wait_group.sync.aligned 0;\ncvt.rn.bf16x2.f32 k0, o1, o0;\ncvt.rn.bf16x2.f32 k1, o5, o4;\ncvt.rn.bf16x2.f32 k2, o9, o8;\n"
        "cvt.rn.bf16x2.f32 k3, o13, o12;\ncvt.rn.bf16x2.f32 k8, o17, o16;\ncvt.rn.bf16x2.f32 k9, o21, o20;\ncvt.rn.bf16x2.f32 k10, o25, o24;\n"
        "cvt.rn.bf16x2.f32 k11, o29, o28;\nld.volatile.shared.v4.b32 {c0,c1,c2,c3}, [%48+32];\nld.volatile.shared.v4.b32 {c4,c5,c6,c7}, [%48+8224];\n"
        "ld.volatile.shared.v4.b32 {c8,c9,c10,c11}, [%48+48];\nld.volatile.shared.v4.b32 {c12,c13,c14,c15}, [%48+8240];\nand.b32 t, c0, 0xffe;\n"
        "mad.lo.u32 t, t, 4, 0x200000;\nmov.b64 d0, {t, h};\nand.b32 t, c1, 0xffe;\nmad.lo.u32 t, t, 4, 0x200000;\nmov.b64 d1, {t, h};\nand.b32 t, c2, 0xffe;\n"
        "mad.lo.u32 t, t, 4, 0x200000;\nmov.b64 d2, {t, h};\nand.b32 t, c3, 0xffe;\nmad.lo.u32 t, t, 4, 0x200000;\nmov.b64 d3, {t, h};\nand.b32 t, c4, 0xffe;\n"
        "mad.lo.u32 t, t, 4, 0x200000;\nmov.b64 d4, {t, h};\nand.b32 t, c5, 0xffe;\nmad.lo.u32 t, t, 4, 0x200000;\nmov.b64 d5, {t, h};\nand.b32 t, c6, 0xffe;\n"
        "mad.lo.u32 t, t, 4, 0x200000;\nmov.b64 d6, {t, h};\nand.b32 t, c7, 0xffe;\nmad.lo.u32 t, t, 4, 0x200000;\nmov.b64 d7, {t, h};\nand.b32 t, c8, 0xffe;\n"
        "mad.lo.u32 t, t, 4, 0x200000;\nmov.b64 d8, {t, h};\nand.b32 t, c9, 0xffe;\nmad.lo.u32 t, t, 4, 0x200000;\nmov.b64 d9, {t, h};\nand.b32 t, c10, 0xffe;\n"
        "mad.lo.u32 t, t, 4, 0x200000;\nmov.b64 d10, {t, h};\nand.b32 t, c11, 0xffe;\nmad.lo.u32 t, t, 4, 0x200000;\nmov.b64 d11, {t, h};\n"
        "and.b32 t, c12, 0xffe;\nmad.lo.u32 t, t, 4, 0x200000;\nmov.b64 d12, {t, h};\nand.b32 t, c13, 0xffe;\nmad.lo.u32 t, t, 4, 0x200000;\n"
        "mov.b64 d13, {t, h};\nand.b32 t, c14, 0xffe;\nmad.lo.u32 t, t, 4, 0x200000;\nmov.b64 d14, {t, h};\nand.b32 t, c15, 0xffe;\n"
        "mad.lo.u32 t, t, 4, 0x200000;\nmov.b64 d15, {t, h};\nwgmma.fence.sync.aligned;\n"
        "wgmma.mma_async.sync.aligned.m64n32k16.f32.bf16.bf16 {o0,o1,o2,o3,o4,o5,o6,o7,o8,o9,o10,o11,o12,o13,o14,o15}, {b0,b1,b2,b3}, d0, p0, 1, 1, 1;\n"
        "wgmma.mma_async.sync.aligned.m64n32k16.f32.bf16.bf16 {o16,o17,o18,o19,o20,o21,o22,o23,o24,o25,o26,o27,o28,o29,o30,o31}, {b0,b1,b2,b3}, d8, p0, 1, 1, 1;\n"
        "wgmma.mma_async.sync.aligned.m64n32k16.f32.bf16.bf16 {o0,o1,o2,o3,o4,o5,o6,o7,o8,o9,o10,o11,o12,o13,o14,o15}, {b4,b5,b6,b7}, d1, p1, 1, 1, 1;\n"
        "wgmma.mma_async.sync.aligned.m64n32k16.f32.bf16.bf16 {o16,o17,o18,o19,o20,o21,o22,o23,o24,o25,o26,o27,o28,o29,o30,o31}, {b4,b5,b6,b7}, d9, p1, 1, 1, 1;\n"
        "wgmma.mma_async.sync.aligned.m64n32k16.f32.bf16.bf16 {o0,o1,o2,o3,o4,o5,o6,o7,o8,o9,o10,o11,o12,o13,o14,o15}, {b8,b9,b10,b11}, d2, p1, 1, 1, 1;\n"
        "wgmma.mma_async.sync.aligned.m64n32k16.f32.bf16.bf16 {o16,o17,o18,o19,o20,o21,o22,o23,o24,o25,o26,o27,o28,o29,o30,o31}, {b8,b9,b10,b11}, d10, p1, 1, 1, 1;\n"
        "wgmma.mma_async.sync.aligned.m64n32k16.f32.bf16.bf16 {o0,o1,o2,o3,o4,o5,o6,o7,o8,o9,o10,o11,o12,o13,o14,o15}, {b12,b13,b14,b15}, d3, p1, 1, 1, 1;\n"
        "wgmma.mma_async.sync.aligned.m64n32k16.f32.bf16.bf16 {o16,o17,o18,o19,o20,o21,o22,o23,o24,o25,o26,o27,o28,o29,o30,o31}, {b12,b13,b14,b15}, d11, p1, 1, 1, 1;\n"
        "wgmma.mma_async.sync.aligned.m64n32k16.f32.bf16.bf16 {o0,o1,o2,o3,o4,o5,o6,o7,o8,o9,o10,o11,o12,o13,o14,o15}, {b16,b17,b18,b19}, d4, p1, 1, 1, 1;\n"
        "wgmma.mma_async.sync.aligned.m64n32k16.f32.bf16.bf16 {o16,o17,o18,o19,o20,o21,o22,o23,o24,o25,o26,o27,o28,o29,o30,o31}, {b16,b17,b18,b19}, d12, p1, 1, 1, 1;\n"
        "wgmma.mma_async.sync.aligned.m64n32k16.f32.bf16.bf16 {o0,o1,o2,o3,o4,o5,o6,o7,o8,o9,o10,o11,o12,o13,o14,o15}, {b20,b21,b22,b23}, d5, p1, 1, 1, 1;\n"
        "wgmma.mma_async.sync.aligned.m64n32k16.f32.bf16.bf16 {o16,o17,o18,o19,o20,o21,o22,o23,o24,o25,o26,o27,o28,o29,o30,o31}, {b20,b21,b22,b23}, d13, p1, 1, 1, 1;\n"
        "wgmma.mma_async.sync.aligned.m64n32k16.f32.bf16.bf16 {o0,o1,o2,o3,o4,o5,o6,o7,o8,o9,o10,o11,o12,o13,o14,o15}, {b24,b25,b26,b27}, d6, p1, 1, 1, 1;\n"
        "wgmma.mma_async.sync.aligned.m64n32k16.f32.bf16.bf16 {o16,o17,o18,o19,o20,o21,o22,o23,o24,o25,o26,o27,o28,o29,o30,o31}, {b24,b25,b26,b27}, d14, p1, 1, 1, 1;\n"
        "wgmma.mma_async.sync.aligned.m64n32k16.f32.bf16.bf16 {o0,o1,o2,o3,o4,o5,o6,o7,o8,o9,o10,o11,o12,o13,o14,o15}, {b28,b29,b30,b31}, d7, p1, 1, 1, 1;\n"
        "wgmma.mma_async.sync.aligned.m64n32k16.f32.bf16.bf16 {o16,o17,o18,o19,o20,o21,o22,o23,o24,o25,o26,o27,o28,o29,o30,o31}, {b28,b29,b30,b31}, d15, p1, 1, 1, 1;\n"
        "wgmma.commit_group.sync.aligned;\n@nv bra.uni END;\n@s2 st.global.v4.b32 [%51+0], {k0,k1,k2,k3};\n@s2 st.global.v4.b32 [%51+64], {k8,k9,k10,k11};\n"
        "@nv bra.uni END;\nwgmma.wait_group.sync.aligned 0;\ncvt.rn.bf16x2.f32 k0, o1, o0;\ncvt.rn.bf16x2.f32 k1, o5, o4;\ncvt.rn.bf16x2.f32 k2, o9, o8;\n"
        "cvt.rn.bf16x2.f32 k3, o13, o12;\ncvt.rn.bf16x2.f32 k8, o17, o16;\ncvt.rn.bf16x2.f32 k9, o21, o20;\ncvt.rn.bf16x2.f32 k10, o25, o24;\n"
        "cvt.rn.bf16x2.f32 k11, o29, o28;\n@s2 st.global.v4.b32 [%51+128], {k0,k1,k2,k3};\n@s2 st.global.v4.b32 [%51+192], {k8,k9,k10,k11};\n"
        "END:\n}\n"
        ::"r"(pk[0]), "r"(pk[1]), "r"(pk[2]), "r"(pk[3]), "r"(pk[4]), "r"(pk[5]), "r"(pk[6]), "r"(pk[7]), "r"(pk[8]), "r"(pk[9]), "r"(pk[10]),
          "r"(pk[11]), "r"(pk[12]), "r"(pk[13]), "r"(pk[14]), "r"(pk[15]), "r"(pk[16]), "r"(pk[17]), "r"(pk[18]), "r"(pk[19]), "r"(pk[20]),
          "r"(pk[21]), "r"(pk[22]), "r"(pk[23]), "r"(pk[24]), "r"(pk[25]), "r"(pk[26]), "r"(pk[27]), "r"(pk[28]), "r"(pk[29]), "r"(pk[30]),
          "r"(pk[31]), "r"(pk[32]), "r"(pk[33]), "r"(pk[34]), "r"(pk[35]), "r"(pk[36]), "r"(pk[37]), "r"(pk[38]), "r"(pk[39]), "r"(pk[40]),
          "r"(pk[41]), "r"(pk[42]), "r"(pk[43]), "r"(pk[44]), "r"(pk[45]), "r"(pk[46]), "r"(pk[47]), "r"(ra), "l"(p[0]), "l"(p[1]), "l"(p[2]),
          "r"(v[0]), "r"(v[1]), "r"(v[2]), "r"(ba)
        : "memory");
}
__device__ __forceinline__ int cta_id() {
    int v;
    asm volatile("mov.u32 %0, %ctaid.x;" : "=r"(v));
    return v;
}
__device__ __forceinline__ int thread_id() {
    int v;
    asm volatile("mov.u32 %0, %tid.x;" : "=r"(v));
    return v;
}

__device__ __forceinline__ void slow_edge(int ee, int s, float* accn, const __nv_bfloat16* __restrict__ x,
                                          const __nv_bfloat16* __restrict__ sh, const __nv_bfloat16* __restrict__ ea,
                                          const __nv_bfloat16* __restrict__ cg, const __nv_bfloat16* __restrict__ wr,
                                          int lane) {
    float rwv[4] = {0.f, 0.f, 0.f, 0.f};
#pragma unroll 4
    for (int d = 0; d < 16; d++) {
        const float a = __bfloat162float(ea[(size_t)ee * 16 + d]);
        const uint2 wv = *(const uint2*)(wr + d * 128 + lane * 4);
        rwv[0] += a * __uint_as_float(wv.x << 16);
        rwv[1] += a * __uint_as_float(wv.x & 0xffff0000u);
        rwv[2] += a * __uint_as_float(wv.y << 16);
        rwv[3] += a * __uint_as_float(wv.y & 0xffff0000u);
    }
    float A = 0.f;
#pragma unroll
    for (int v = 0; v < 4; v++)
        A += __bfloat162float(cg[((lane >> 2) & 3) * 16 + v * 4 + (lane & 3)]) * __bfloat162float(sh[(size_t)ee * 4 + v]);
    float m[4][4];
#pragma unroll
    for (int w = 0; w < 4; w++)
#pragma unroll
        for (int j = 0; j < 4; j++) m[w][j] = 0.f;
#pragma unroll
    for (int u = 0; u < 4; u++) {
        const uint2 xv = *(const uint2*)(x + (size_t)s * 512 + u * 128 + lane * 4);
        const float x0 = __uint_as_float(xv.x << 16), x1 = __uint_as_float(xv.x & 0xffff0000u);
        const float x2 = __uint_as_float(xv.y << 16), x3 = __uint_as_float(xv.y & 0xffff0000u);
#pragma unroll
        for (int w = 0; w < 4; w++) {
            const float a = __shfl_sync(0xffffffffu, A, u * 4 + w);
            m[w][0] += a * x0;
            m[w][1] += a * x1;
            m[w][2] += a * x2;
            m[w][3] += a * x3;
        }
    }
#pragma unroll
    for (int w = 0; w < 4; w++)
#pragma unroll
        for (int j = 0; j < 4; j++) atomicAdd(accn + w * 128 + lane * 4 + j, m[w][j] * rwv[j]);
}

__device__ __forceinline__ void slow_out(const float* accn, const __nv_bfloat16* __restrict__ wout,
                                         __nv_bfloat16* __restrict__ outn, int lane) {
    float o[4][4];
#pragma unroll
    for (int w = 0; w < 4; w++)
#pragma unroll
        for (int j = 0; j < 4; j++) o[w][j] = 0.f;
#pragma unroll 2
    for (int c = 0; c < 128; c++) {
        const uint2 wv = *(const uint2*)(wout + c * 128 + lane * 4);
        const float w0 = __uint_as_float(wv.x << 16), w1 = __uint_as_float(wv.x & 0xffff0000u);
        const float w2 = __uint_as_float(wv.y << 16), w3 = __uint_as_float(wv.y & 0xffff0000u);
#pragma unroll
        for (int w = 0; w < 4; w++) {
            const float a = __bfloat162float(__float2bfloat16(accn[w * 128 + c]));
            o[w][0] += a * w0;
            o[w][1] += a * w1;
            o[w][2] += a * w2;
            o[w][3] += a * w3;
        }
    }
#pragma unroll
    for (int w = 0; w < 4; w++)
        *(uint2*)(outn + w * 128 + lane * 4) = make_uint2(pack_bf16(o[w][0], o[w][1]), pack_bf16(o[w][2], o[w][3]));
}

__device__ __forceinline__ void consume4(uint32_t (&pk)[64], const uint32_t (&w)[36], uint32_t olp, uint32_t xa, uint32_t ln,
                                      uint32_t lc, uint32_t linc, uint32_t lt, const __nv_bfloat16* ea, const __nv_bfloat16* sh, const void* wf, uint4 first) {
    ea += lt * 4, sh += lt & 2;
    asm volatile(
        "{\n.reg .pred p, q, psw, prdy, ps1, ps2, ps3, pz, pq;\n.reg .f32 d<32>, fz;\n"
        ".reg .b32 h<64>, x<32>, y<32>, ra<8>, rb<8>, bA0, bA1, bB0, bB1, c0, c1, c2, c3, e0, e1, s0, kept;\n"
        ".reg .b32 olp, v, vB, m, id, ida, bar, xb, pos, t0, t1, t2, t3, n, z<16>, kept2, g<4>;\n.reg .b16 lo, hi, i16;\n.reg .b64 pa, pb;\n"
        "mov.f32 fz, 0f00000000;\nmov.b32 h0, 0;\nmov.b32 h1, 0;\nmov.b32 h2, 0;\nmov.b32 h3, 0;\nmov.b32 h4, 0;\nmov.b32 h5, 0;\nmov.b32 h6, 0;\n"
        "mov.b32 h7, 0;\nmov.b32 h8, 0;\nmov.b32 h9, 0;\nmov.b32 h10, 0;\nmov.b32 h11, 0;\nmov.b32 h12, 0;\nmov.b32 h13, 0;\nmov.b32 h14, 0;\nmov.b32 h15, 0;\n"
        "mov.b32 h16, 0;\nmov.b32 h17, 0;\nmov.b32 h18, 0;\nmov.b32 h19, 0;\nmov.b32 h20, 0;\nmov.b32 h21, 0;\nmov.b32 h22, 0;\nmov.b32 h23, 0;\n"
        "mov.b32 h24, 0;\nmov.b32 h25, 0;\nmov.b32 h26, 0;\nmov.b32 h27, 0;\nmov.b32 h28, 0;\nmov.b32 h29, 0;\nmov.b32 h30, 0;\nmov.b32 h31, 0;\n"
        "mov.b32 h32, 0;\nmov.b32 h33, 0;\nmov.b32 h34, 0;\nmov.b32 h35, 0;\nmov.b32 h36, 0;\nmov.b32 h37, 0;\nmov.b32 h38, 0;\nmov.b32 h39, 0;\n"
        "mov.b32 h40, 0;\nmov.b32 h41, 0;\nmov.b32 h42, 0;\nmov.b32 h43, 0;\nmov.b32 h44, 0;\nmov.b32 h45, 0;\nmov.b32 h46, 0;\nmov.b32 h47, 0;\n"
        "mov.b32 h48, 0;\nmov.b32 h49, 0;\nmov.b32 h50, 0;\nmov.b32 h51, 0;\nmov.b32 h52, 0;\nmov.b32 h53, 0;\nmov.b32 h54, 0;\nmov.b32 h55, 0;\n"
        "mov.b32 h56, 0;\nmov.b32 h57, 0;\nmov.b32 h58, 0;\nmov.b32 h59, 0;\nmov.b32 h60, 0;\nmov.b32 h61, 0;\nmov.b32 h62, 0;\nmov.b32 h63, 0;\n"
        "mov.b32 olp, %64;\nand.b32 t0, %66, 32;\nsetp.ne.u32 psw, t0, 0;\nsetp.eq.u32 pz, %64, 0;\nvote.sync.any.pred pz, pz, 0xffffffff;\nmov.b32 e0, %73;\n"
        "mov.b32 e1, %74;\nmov.b32 s0, %75;\nmov.b32 kept, %76;\nadd.u32 olp, olp, 4;\nsetp.ne.u64 p, %72, 0;\n@p fence.proxy.async.global;\n"
        "@p red.release.gpu.global.add.u32 [%72+12], 1;\nbar.warp.sync 0xffffffff;\nshfl.sync.idx.b32 v, kept, %67, 0x1f, 0xffffffff;\nor.b32 t3, %67, 4;\n"
        "shfl.sync.idx.b32 vB, kept, t3, 0x1f, 0xffffffff;\n"
        "RW:\nmma.sync.aligned.m16n8k8.row.col.f32.bf16.bf16.f32 {d0,d1,d2,d3}, {%114,%115}, {s0}, {fz,fz,fz,fz};\n"
        "mma.sync.aligned.m16n8k8.row.col.f32.bf16.bf16.f32 {d4,d5,d6,d7}, {%116,%117}, {s0}, {fz,fz,fz,fz};\ncvt.rn.bf16x2.f32 c0, d2, d0;\n"
        "cvt.rn.bf16x2.f32 c1, d3, d1;\ncvt.rn.bf16x2.f32 c2, d6, d4;\ncvt.rn.bf16x2.f32 c3, d7, d5;\nselp.b32 bA0, c2, c0, psw;\nselp.b32 bA1, c0, c2, psw;\n"
        "selp.b32 bB0, c3, c1, psw;\nselp.b32 bB1, c1, c3, psw;\n"
        "mma.sync.aligned.m16n8k16.row.col.f32.bf16.bf16.f32 {d0,d1,d2,d3}, {%82,%83,%84,%85}, {e0,e1}, {fz,fz,fz,fz};\ncvt.rn.bf16x2.f32 ra0, d2, d0;\n"
        "cvt.rn.bf16x2.f32 rb0, d3, d1;\nmma.sync.aligned.m16n8k16.row.col.f32.bf16.bf16.f32 {d4,d5,d6,d7}, {%86,%87,%88,%89}, {e0,e1}, {fz,fz,fz,fz};\n"
        "cvt.rn.bf16x2.f32 ra1, d6, d4;\ncvt.rn.bf16x2.f32 rb1, d7, d5;\n"
        "mma.sync.aligned.m16n8k16.row.col.f32.bf16.bf16.f32 {d8,d9,d10,d11}, {%90,%91,%92,%93}, {e0,e1}, {fz,fz,fz,fz};\ncvt.rn.bf16x2.f32 ra2, d10, d8;\n"
        "cvt.rn.bf16x2.f32 rb2, d11, d9;\nmma.sync.aligned.m16n8k16.row.col.f32.bf16.bf16.f32 {d12,d13,d14,d15}, {%94,%95,%96,%97}, {e0,e1}, {fz,fz,fz,fz};\n"
        "cvt.rn.bf16x2.f32 ra3, d14, d12;\ncvt.rn.bf16x2.f32 rb3, d15, d13;\n"
        "mma.sync.aligned.m16n8k16.row.col.f32.bf16.bf16.f32 {d16,d17,d18,d19}, {%98,%99,%100,%101}, {e0,e1}, {fz,fz,fz,fz};\ncvt.rn.bf16x2.f32 ra4, d18, d16;\n"
        "cvt.rn.bf16x2.f32 rb4, d19, d17;\n"
        "mma.sync.aligned.m16n8k16.row.col.f32.bf16.bf16.f32 {d20,d21,d22,d23}, {%102,%103,%104,%105}, {e0,e1}, {fz,fz,fz,fz};\n"
        "cvt.rn.bf16x2.f32 ra5, d22, d20;\ncvt.rn.bf16x2.f32 rb5, d23, d21;\n"
        "mma.sync.aligned.m16n8k16.row.col.f32.bf16.bf16.f32 {d24,d25,d26,d27}, {%106,%107,%108,%109}, {e0,e1}, {fz,fz,fz,fz};\n"
        "cvt.rn.bf16x2.f32 ra6, d26, d24;\ncvt.rn.bf16x2.f32 rb6, d27, d25;\n"
        "mma.sync.aligned.m16n8k16.row.col.f32.bf16.bf16.f32 {d28,d29,d30,d31}, {%110,%111,%112,%113}, {e0,e1}, {fz,fz,fz,fz};\n"
        "cvt.rn.bf16x2.f32 ra7, d30, d28;\ncvt.rn.bf16x2.f32 rb7, d31, d29;\nld.shared.u16 t0, [olp];\nadd.u32 olp, olp, 4;\n"
        "lop3.b32 t1, t0, %66, 0x3ff0, 0xe4;\nld.shared.b32 t1, [t1+%77];\nlop3.b32 kept, t1, t0, 0x1ffc, 0xe4;\nlop3.b32 t2, t1, %67, 3, 0x80;\n"
        "setp.ne.u32 q, t2, 0;\nshr.u32 t2, t1, 13;\nmad.wide.u32 pa, t2, 32, %70;\nmad.wide.u32 pb, t2, 8, %71;\nmov.b32 s0, 0;\n"
        "ld.global.cg.L2::128B.v2.b32 {e0,e1}, [pa];\n@q ld.global.cg.L2::128B.b32 s0, [pb];\nshr.u32 bar, v, 1;\nand.b32 bar, bar, 0xff8;\n"
        "mbarrier.test_wait.parity.shared.b64 p, [bar+%79], 0;\nlop3.b32 ida, v, %67, 0x1fff, 0xe4;\nld.volatile.shared.u16 id, [ida+%78];\n"
        "vote.sync.all.pred prdy, p, 0xffffffff;\n@!prdy bra.uni WA;\n"
        "HA:\nmad.lo.u32 xb, id, 64, %65;\ncvt.u16.u32 i16, id;\natom.shared.add.u32 pos, [%66+%80], %68;\n"
        "ldmatrix.sync.aligned.m8n8.x4.trans.shared.b16 {x0,x1,x2,x3}, [xb];\nldmatrix.sync.aligned.m8n8.x4.trans.shared.b16 {x24,x25,x26,x27}, [xb+512];\n"
        "xor.b32 t1, xb, 32;\nldmatrix.sync.aligned.m8n8.x4.trans.shared.b16 {x4,x5,x6,x7}, [t1];\n"
        "ldmatrix.sync.aligned.m8n8.x4.trans.shared.b16 {x28,x29,x30,x31}, [t1+512];\nxor.b32 t1, xb, 64;\n"
        "ldmatrix.sync.aligned.m8n8.x4.trans.shared.b16 {x8,x9,x10,x11}, [t1];\nldmatrix.sync.aligned.m8n8.x4.trans.shared.b16 {x16,x17,x18,x19}, [t1+512];\n"
        "xor.b32 t1, xb, 96;\nldmatrix.sync.aligned.m8n8.x4.trans.shared.b16 {x12,x13,x14,x15}, [t1];\n"
        "ldmatrix.sync.aligned.m8n8.x4.trans.shared.b16 {x20,x21,x22,x23}, [t1+512];\nst.volatile.shared.u16 [pos], i16;\nand.b32 t0, v, 16384;\n"
        "setp.ne.u32 ps1, t0, 0;\nvote.sync.any.pred ps1, ps1, 0xffffffff;\nand.b32 t0, v, 32768;\nsetp.ne.u32 ps2, t0, 0;\n"
        "vote.sync.any.pred ps2, ps2, 0xffffffff;\nmov.b32 v, vB;\nshr.u32 bar, v, 1;\nand.b32 bar, bar, 0xff8;\n"
        "mbarrier.test_wait.parity.shared.b64 p, [bar+%79], 0;\nlop3.b32 ida, v, %67, 0x1fff, 0xe4;\nld.volatile.shared.u16 id, [ida+%78];\n"
        "vote.sync.all.pred prdy, p, 0xffffffff;\nmov.b32 {lo, hi}, ra0;\nmov.b32 t2, {lo, lo};\nmul.rn.bf16x2 y0, x0, t2;\nmul.rn.bf16x2 y2, x2, t2;\n"
        "mov.b32 t2, {hi, hi};\nmul.rn.bf16x2 y1, x1, t2;\nmul.rn.bf16x2 y3, x3, t2;\n"
        "mma.sync.aligned.m16n8k16.row.col.f32.bf16.bf16.f32 {d0,d1,d2,d3}, {y0,y1,y2,y3}, {bA0,bA1}, {fz,fz,fz,fz};\ncvt.rn.bf16x2.f32 z0, d1, d0;\n"
        "cvt.rn.bf16x2.f32 z1, d3, d2;\nmov.b32 {lo, hi}, ra6;\nmov.b32 t2, {lo, lo};\nmul.rn.bf16x2 y24, x24, t2;\nmul.rn.bf16x2 y26, x26, t2;\n"
        "mov.b32 t2, {hi, hi};\nmul.rn.bf16x2 y25, x25, t2;\nmul.rn.bf16x2 y27, x27, t2;\n"
        "mma.sync.aligned.m16n8k16.row.col.f32.bf16.bf16.f32 {d24,d25,d26,d27}, {y24,y25,y26,y27}, {bA0,bA1}, {fz,fz,fz,fz};\ncvt.rn.bf16x2.f32 z12, d25, d24;\n"
        "cvt.rn.bf16x2.f32 z13, d27, d26;\nmov.b32 {lo, hi}, ra1;\nmov.b32 t2, {lo, lo};\nmul.rn.bf16x2 y4, x4, t2;\nmul.rn.bf16x2 y6, x6, t2;\n"
        "mov.b32 t2, {hi, hi};\nmul.rn.bf16x2 y5, x5, t2;\nmul.rn.bf16x2 y7, x7, t2;\n"
        "mma.sync.aligned.m16n8k16.row.col.f32.bf16.bf16.f32 {d4,d5,d6,d7}, {y4,y5,y6,y7}, {bA0,bA1}, {fz,fz,fz,fz};\ncvt.rn.bf16x2.f32 z2, d5, d4;\n"
        "cvt.rn.bf16x2.f32 z3, d7, d6;\nmov.b32 {lo, hi}, ra7;\nmov.b32 t2, {lo, lo};\nmul.rn.bf16x2 y28, x28, t2;\nmul.rn.bf16x2 y30, x30, t2;\n"
        "mov.b32 t2, {hi, hi};\nmul.rn.bf16x2 y29, x29, t2;\nmul.rn.bf16x2 y31, x31, t2;\n"
        "mma.sync.aligned.m16n8k16.row.col.f32.bf16.bf16.f32 {d28,d29,d30,d31}, {y28,y29,y30,y31}, {bA0,bA1}, {fz,fz,fz,fz};\ncvt.rn.bf16x2.f32 z14, d29, d28;\n"
        "cvt.rn.bf16x2.f32 z15, d31, d30;\nmov.b32 {lo, hi}, ra2;\nmov.b32 t2, {lo, lo};\nmul.rn.bf16x2 y8, x8, t2;\nmul.rn.bf16x2 y10, x10, t2;\n"
        "mov.b32 t2, {hi, hi};\nmul.rn.bf16x2 y9, x9, t2;\nmul.rn.bf16x2 y11, x11, t2;\n"
        "mma.sync.aligned.m16n8k16.row.col.f32.bf16.bf16.f32 {d8,d9,d10,d11}, {y8,y9,y10,y11}, {bA0,bA1}, {fz,fz,fz,fz};\ncvt.rn.bf16x2.f32 z4, d9, d8;\n"
        "cvt.rn.bf16x2.f32 z5, d11, d10;\nmov.b32 {lo, hi}, ra4;\nmov.b32 t2, {lo, lo};\nmul.rn.bf16x2 y16, x16, t2;\nmul.rn.bf16x2 y18, x18, t2;\n"
        "mov.b32 t2, {hi, hi};\nmul.rn.bf16x2 y17, x17, t2;\nmul.rn.bf16x2 y19, x19, t2;\n"
        "mma.sync.aligned.m16n8k16.row.col.f32.bf16.bf16.f32 {d16,d17,d18,d19}, {y16,y17,y18,y19}, {bA0,bA1}, {fz,fz,fz,fz};\ncvt.rn.bf16x2.f32 z8, d17, d16;\n"
        "cvt.rn.bf16x2.f32 z9, d19, d18;\nmov.b32 {lo, hi}, ra3;\nmov.b32 t2, {lo, lo};\nmul.rn.bf16x2 y12, x12, t2;\nmul.rn.bf16x2 y14, x14, t2;\n"
        "mov.b32 t2, {hi, hi};\nmul.rn.bf16x2 y13, x13, t2;\nmul.rn.bf16x2 y15, x15, t2;\n"
        "mma.sync.aligned.m16n8k16.row.col.f32.bf16.bf16.f32 {d12,d13,d14,d15}, {y12,y13,y14,y15}, {bA0,bA1}, {fz,fz,fz,fz};\ncvt.rn.bf16x2.f32 z6, d13, d12;\n"
        "cvt.rn.bf16x2.f32 z7, d15, d14;\nmov.b32 {lo, hi}, ra5;\nmov.b32 t2, {lo, lo};\nmul.rn.bf16x2 y20, x20, t2;\nmul.rn.bf16x2 y22, x22, t2;\n"
        "mov.b32 t2, {hi, hi};\nmul.rn.bf16x2 y21, x21, t2;\nmul.rn.bf16x2 y23, x23, t2;\n"
        "mma.sync.aligned.m16n8k16.row.col.f32.bf16.bf16.f32 {d20,d21,d22,d23}, {y20,y21,y22,y23}, {bA0,bA1}, {fz,fz,fz,fz};\ncvt.rn.bf16x2.f32 z10, d21, d20;\n"
        "cvt.rn.bf16x2.f32 z11, d23, d22;\n@ps2 bra.uni TA2;\n@ps1 bra.uni TA1;\n"
        "TA0:\nadd.rn.bf16x2 h0, h0, z0;\nadd.rn.bf16x2 h1, h1, z1;\nadd.rn.bf16x2 h2, h2, z2;\nadd.rn.bf16x2 h3, h3, z3;\nadd.rn.bf16x2 h4, h4, z4;\n"
        "add.rn.bf16x2 h5, h5, z5;\nadd.rn.bf16x2 h6, h6, z6;\nadd.rn.bf16x2 h7, h7, z7;\nadd.rn.bf16x2 h8, h8, z8;\nadd.rn.bf16x2 h9, h9, z9;\n"
        "add.rn.bf16x2 h10, h10, z10;\nadd.rn.bf16x2 h11, h11, z11;\nadd.rn.bf16x2 h12, h12, z12;\nadd.rn.bf16x2 h13, h13, z13;\nadd.rn.bf16x2 h14, h14, z14;\n"
        "add.rn.bf16x2 h15, h15, z15;\n@prdy bra.uni HB;\nbra.uni WB;\n"
        "TA1:\nadd.rn.bf16x2 h16, h16, z0;\nadd.rn.bf16x2 h17, h17, z1;\nadd.rn.bf16x2 h18, h18, z2;\nadd.rn.bf16x2 h19, h19, z3;\nadd.rn.bf16x2 h20, h20, z4;\n"
        "add.rn.bf16x2 h21, h21, z5;\nadd.rn.bf16x2 h22, h22, z6;\nadd.rn.bf16x2 h23, h23, z7;\nadd.rn.bf16x2 h24, h24, z8;\nadd.rn.bf16x2 h25, h25, z9;\n"
        "add.rn.bf16x2 h26, h26, z10;\nadd.rn.bf16x2 h27, h27, z11;\nadd.rn.bf16x2 h28, h28, z12;\nadd.rn.bf16x2 h29, h29, z13;\nadd.rn.bf16x2 h30, h30, z14;\n"
        "add.rn.bf16x2 h31, h31, z15;\n@prdy bra.uni HB;\nbra.uni WB;\n"
        "TA2:\n@ps1 bra.uni TA3;\nadd.rn.bf16x2 h32, h32, z0;\nadd.rn.bf16x2 h33, h33, z1;\nadd.rn.bf16x2 h34, h34, z2;\nadd.rn.bf16x2 h35, h35, z3;\n"
        "add.rn.bf16x2 h36, h36, z4;\nadd.rn.bf16x2 h37, h37, z5;\nadd.rn.bf16x2 h38, h38, z6;\nadd.rn.bf16x2 h39, h39, z7;\nadd.rn.bf16x2 h40, h40, z8;\n"
        "add.rn.bf16x2 h41, h41, z9;\nadd.rn.bf16x2 h42, h42, z10;\nadd.rn.bf16x2 h43, h43, z11;\nadd.rn.bf16x2 h44, h44, z12;\nadd.rn.bf16x2 h45, h45, z13;\n"
        "add.rn.bf16x2 h46, h46, z14;\nadd.rn.bf16x2 h47, h47, z15;\n@prdy bra.uni HB;\nbra.uni WB;\n"
        "TA3:\nadd.rn.bf16x2 h48, h48, z0;\nadd.rn.bf16x2 h49, h49, z1;\nadd.rn.bf16x2 h50, h50, z2;\nadd.rn.bf16x2 h51, h51, z3;\nadd.rn.bf16x2 h52, h52, z4;\n"
        "add.rn.bf16x2 h53, h53, z5;\nadd.rn.bf16x2 h54, h54, z6;\nadd.rn.bf16x2 h55, h55, z7;\nadd.rn.bf16x2 h56, h56, z8;\nadd.rn.bf16x2 h57, h57, z9;\n"
        "add.rn.bf16x2 h58, h58, z10;\nadd.rn.bf16x2 h59, h59, z11;\nadd.rn.bf16x2 h60, h60, z12;\nadd.rn.bf16x2 h61, h61, z13;\nadd.rn.bf16x2 h62, h62, z14;\n"
        "add.rn.bf16x2 h63, h63, z15;\n@prdy bra.uni HB;\nbra.uni WB;\n"
        "HB:\nmad.lo.u32 xb, id, 64, %65;\ncvt.u16.u32 i16, id;\natom.shared.add.u32 pos, [%66+%80], %68;\n"
        "ldmatrix.sync.aligned.m8n8.x4.trans.shared.b16 {x0,x1,x2,x3}, [xb];\nldmatrix.sync.aligned.m8n8.x4.trans.shared.b16 {x24,x25,x26,x27}, [xb+512];\n"
        "xor.b32 t1, xb, 32;\nldmatrix.sync.aligned.m8n8.x4.trans.shared.b16 {x4,x5,x6,x7}, [t1];\n"
        "ldmatrix.sync.aligned.m8n8.x4.trans.shared.b16 {x28,x29,x30,x31}, [t1+512];\nxor.b32 t1, xb, 64;\n"
        "ldmatrix.sync.aligned.m8n8.x4.trans.shared.b16 {x8,x9,x10,x11}, [t1];\nldmatrix.sync.aligned.m8n8.x4.trans.shared.b16 {x16,x17,x18,x19}, [t1+512];\n"
        "xor.b32 t1, xb, 96;\nldmatrix.sync.aligned.m8n8.x4.trans.shared.b16 {x12,x13,x14,x15}, [t1];\n"
        "ldmatrix.sync.aligned.m8n8.x4.trans.shared.b16 {x20,x21,x22,x23}, [t1+512];\nst.volatile.shared.u16 [pos], i16;\nand.b32 t0, v, 16384;\n"
        "setp.ne.u32 ps1, t0, 0;\nvote.sync.any.pred ps1, ps1, 0xffffffff;\nand.b32 t0, v, 32768;\nsetp.ne.u32 ps2, t0, 0;\n"
        "vote.sync.any.pred ps2, ps2, 0xffffffff;\nshfl.sync.idx.b32 v, kept, %67, 0x1f, 0xffffffff;\nor.b32 t3, %67, 4;\n"
        "shfl.sync.idx.b32 vB, kept, t3, 0x1f, 0xffffffff;\nmov.b32 {lo, hi}, rb0;\nmov.b32 t2, {lo, lo};\nmul.rn.bf16x2 y0, x0, t2;\nmul.rn.bf16x2 y2, x2, t2;\n"
        "mov.b32 t2, {hi, hi};\nmul.rn.bf16x2 y1, x1, t2;\nmul.rn.bf16x2 y3, x3, t2;\n"
        "mma.sync.aligned.m16n8k16.row.col.f32.bf16.bf16.f32 {d0,d1,d2,d3}, {y0,y1,y2,y3}, {bB0,bB1}, {fz,fz,fz,fz};\ncvt.rn.bf16x2.f32 z0, d1, d0;\n"
        "cvt.rn.bf16x2.f32 z1, d3, d2;\nmov.b32 {lo, hi}, rb6;\nmov.b32 t2, {lo, lo};\nmul.rn.bf16x2 y24, x24, t2;\nmul.rn.bf16x2 y26, x26, t2;\n"
        "mov.b32 t2, {hi, hi};\nmul.rn.bf16x2 y25, x25, t2;\nmul.rn.bf16x2 y27, x27, t2;\n"
        "mma.sync.aligned.m16n8k16.row.col.f32.bf16.bf16.f32 {d24,d25,d26,d27}, {y24,y25,y26,y27}, {bB0,bB1}, {fz,fz,fz,fz};\ncvt.rn.bf16x2.f32 z12, d25, d24;\n"
        "cvt.rn.bf16x2.f32 z13, d27, d26;\nmov.b32 {lo, hi}, rb1;\nmov.b32 t2, {lo, lo};\nmul.rn.bf16x2 y4, x4, t2;\nmul.rn.bf16x2 y6, x6, t2;\n"
        "mov.b32 t2, {hi, hi};\nmul.rn.bf16x2 y5, x5, t2;\nmul.rn.bf16x2 y7, x7, t2;\n"
        "mma.sync.aligned.m16n8k16.row.col.f32.bf16.bf16.f32 {d4,d5,d6,d7}, {y4,y5,y6,y7}, {bB0,bB1}, {fz,fz,fz,fz};\ncvt.rn.bf16x2.f32 z2, d5, d4;\n"
        "cvt.rn.bf16x2.f32 z3, d7, d6;\nmov.b32 {lo, hi}, rb7;\nmov.b32 t2, {lo, lo};\nmul.rn.bf16x2 y28, x28, t2;\nmul.rn.bf16x2 y30, x30, t2;\n"
        "mov.b32 t2, {hi, hi};\nmul.rn.bf16x2 y29, x29, t2;\nmul.rn.bf16x2 y31, x31, t2;\n"
        "mma.sync.aligned.m16n8k16.row.col.f32.bf16.bf16.f32 {d28,d29,d30,d31}, {y28,y29,y30,y31}, {bB0,bB1}, {fz,fz,fz,fz};\ncvt.rn.bf16x2.f32 z14, d29, d28;\n"
        "cvt.rn.bf16x2.f32 z15, d31, d30;\nmov.b32 {lo, hi}, rb2;\nmov.b32 t2, {lo, lo};\nmul.rn.bf16x2 y8, x8, t2;\nmul.rn.bf16x2 y10, x10, t2;\n"
        "mov.b32 t2, {hi, hi};\nmul.rn.bf16x2 y9, x9, t2;\nmul.rn.bf16x2 y11, x11, t2;\n"
        "mma.sync.aligned.m16n8k16.row.col.f32.bf16.bf16.f32 {d8,d9,d10,d11}, {y8,y9,y10,y11}, {bB0,bB1}, {fz,fz,fz,fz};\ncvt.rn.bf16x2.f32 z4, d9, d8;\n"
        "cvt.rn.bf16x2.f32 z5, d11, d10;\nmov.b32 {lo, hi}, rb4;\nmov.b32 t2, {lo, lo};\nmul.rn.bf16x2 y16, x16, t2;\nmul.rn.bf16x2 y18, x18, t2;\n"
        "mov.b32 t2, {hi, hi};\nmul.rn.bf16x2 y17, x17, t2;\nmul.rn.bf16x2 y19, x19, t2;\n"
        "mma.sync.aligned.m16n8k16.row.col.f32.bf16.bf16.f32 {d16,d17,d18,d19}, {y16,y17,y18,y19}, {bB0,bB1}, {fz,fz,fz,fz};\ncvt.rn.bf16x2.f32 z8, d17, d16;\n"
        "cvt.rn.bf16x2.f32 z9, d19, d18;\nmov.b32 {lo, hi}, rb3;\nmov.b32 t2, {lo, lo};\nmul.rn.bf16x2 y12, x12, t2;\nmul.rn.bf16x2 y14, x14, t2;\n"
        "mov.b32 t2, {hi, hi};\nmul.rn.bf16x2 y13, x13, t2;\nmul.rn.bf16x2 y15, x15, t2;\n"
        "mma.sync.aligned.m16n8k16.row.col.f32.bf16.bf16.f32 {d12,d13,d14,d15}, {y12,y13,y14,y15}, {bB0,bB1}, {fz,fz,fz,fz};\ncvt.rn.bf16x2.f32 z6, d13, d12;\n"
        "cvt.rn.bf16x2.f32 z7, d15, d14;\nmov.b32 {lo, hi}, rb5;\nmov.b32 t2, {lo, lo};\nmul.rn.bf16x2 y20, x20, t2;\nmul.rn.bf16x2 y22, x22, t2;\n"
        "mov.b32 t2, {hi, hi};\nmul.rn.bf16x2 y21, x21, t2;\nmul.rn.bf16x2 y23, x23, t2;\n"
        "mma.sync.aligned.m16n8k16.row.col.f32.bf16.bf16.f32 {d20,d21,d22,d23}, {y20,y21,y22,y23}, {bB0,bB1}, {fz,fz,fz,fz};\ncvt.rn.bf16x2.f32 z10, d21, d20;\n"
        "cvt.rn.bf16x2.f32 z11, d23, d22;\n@ps2 bra.uni TB2;\n@ps1 bra.uni TB1;\n"
        "TB0:\nadd.rn.bf16x2 h0, h0, z0;\nadd.rn.bf16x2 h1, h1, z1;\nadd.rn.bf16x2 h2, h2, z2;\nadd.rn.bf16x2 h3, h3, z3;\nadd.rn.bf16x2 h4, h4, z4;\n"
        "add.rn.bf16x2 h5, h5, z5;\nadd.rn.bf16x2 h6, h6, z6;\nadd.rn.bf16x2 h7, h7, z7;\nadd.rn.bf16x2 h8, h8, z8;\nadd.rn.bf16x2 h9, h9, z9;\n"
        "add.rn.bf16x2 h10, h10, z10;\nadd.rn.bf16x2 h11, h11, z11;\nadd.rn.bf16x2 h12, h12, z12;\nadd.rn.bf16x2 h13, h13, z13;\nadd.rn.bf16x2 h14, h14, z14;\n"
        "add.rn.bf16x2 h15, h15, z15;\nbra.uni RW;\n"
        "TB1:\nadd.rn.bf16x2 h16, h16, z0;\nadd.rn.bf16x2 h17, h17, z1;\nadd.rn.bf16x2 h18, h18, z2;\nadd.rn.bf16x2 h19, h19, z3;\nadd.rn.bf16x2 h20, h20, z4;\n"
        "add.rn.bf16x2 h21, h21, z5;\nadd.rn.bf16x2 h22, h22, z6;\nadd.rn.bf16x2 h23, h23, z7;\nadd.rn.bf16x2 h24, h24, z8;\nadd.rn.bf16x2 h25, h25, z9;\n"
        "add.rn.bf16x2 h26, h26, z10;\nadd.rn.bf16x2 h27, h27, z11;\nadd.rn.bf16x2 h28, h28, z12;\nadd.rn.bf16x2 h29, h29, z13;\nadd.rn.bf16x2 h30, h30, z14;\n"
        "add.rn.bf16x2 h31, h31, z15;\nbra.uni RW;\n"
        "TB2:\n@ps1 bra.uni TB3;\nadd.rn.bf16x2 h32, h32, z0;\nadd.rn.bf16x2 h33, h33, z1;\nadd.rn.bf16x2 h34, h34, z2;\nadd.rn.bf16x2 h35, h35, z3;\n"
        "add.rn.bf16x2 h36, h36, z4;\nadd.rn.bf16x2 h37, h37, z5;\nadd.rn.bf16x2 h38, h38, z6;\nadd.rn.bf16x2 h39, h39, z7;\nadd.rn.bf16x2 h40, h40, z8;\n"
        "add.rn.bf16x2 h41, h41, z9;\nadd.rn.bf16x2 h42, h42, z10;\nadd.rn.bf16x2 h43, h43, z11;\nadd.rn.bf16x2 h44, h44, z12;\nadd.rn.bf16x2 h45, h45, z13;\n"
        "add.rn.bf16x2 h46, h46, z14;\nadd.rn.bf16x2 h47, h47, z15;\nbra.uni RW;\n"
        "TB3:\nadd.rn.bf16x2 h48, h48, z0;\nadd.rn.bf16x2 h49, h49, z1;\nadd.rn.bf16x2 h50, h50, z2;\nadd.rn.bf16x2 h51, h51, z3;\nadd.rn.bf16x2 h52, h52, z4;\n"
        "add.rn.bf16x2 h53, h53, z5;\nadd.rn.bf16x2 h54, h54, z6;\nadd.rn.bf16x2 h55, h55, z7;\nadd.rn.bf16x2 h56, h56, z8;\nadd.rn.bf16x2 h57, h57, z9;\n"
        "add.rn.bf16x2 h58, h58, z10;\nadd.rn.bf16x2 h59, h59, z11;\nadd.rn.bf16x2 h60, h60, z12;\nadd.rn.bf16x2 h61, h61, z13;\nadd.rn.bf16x2 h62, h62, z14;\n"
        "add.rn.bf16x2 h63, h63, z15;\nbra.uni RW;\n"
        "WA:\nshr.u32 t2, v, 1;\nand.b32 t2, t2, 0xff8;\nsetp.eq.u32 p, t2, 0;\nvote.sync.all.pred p, p, 0xffffffff;\n@p bra.uni DONE;\nmov.b32 n, 0;\n"
        "WA3:\nmbarrier.try_wait.parity.shared.b64 p, [t2+%79], 0;\nvote.sync.all.pred p, p, 0xffffffff;\nadd.u32 n, n, 1;\nsetp.lt.and.u32 q, n, 1000000, !p;\n"
        "@q bra.uni WA3;\nlop3.b32 ida, v, %67, 0x1fff, 0xe4;\nld.volatile.shared.u16 id, [ida+%78];\nbra.uni HA;\n"
        "WB:\nshr.u32 t2, v, 1;\nand.b32 t2, t2, 0xff8;\nsetp.eq.u32 p, t2, 0;\nvote.sync.all.pred p, p, 0xffffffff;\n@p bra.uni DONE;\nmov.b32 n, 0;\n"
        "WB3:\nmbarrier.try_wait.parity.shared.b64 p, [t2+%79], 0;\nvote.sync.all.pred p, p, 0xffffffff;\nadd.u32 n, n, 1;\nsetp.lt.and.u32 q, n, 1000000, !p;\n"
        "@q bra.uni WB3;\nlop3.b32 ida, v, %67, 0x1fff, 0xe4;\nld.volatile.shared.u16 id, [ida+%78];\nbra.uni HB;\n"
        "DONE:\nmov.b32 %0, h0;\nmov.b32 %1, h1;\nmov.b32 %2, h2;\nmov.b32 %3, h3;\nmov.b32 %4, h4;\nmov.b32 %5, h5;\nmov.b32 %6, h6;\nmov.b32 %7, h7;\n"
        "mov.b32 %8, h8;\nmov.b32 %9, h9;\nmov.b32 %10, h10;\nmov.b32 %11, h11;\nmov.b32 %12, h12;\nmov.b32 %13, h13;\nmov.b32 %14, h14;\nmov.b32 %15, h15;\n"
        "mov.b32 %16, h16;\nmov.b32 %17, h17;\nmov.b32 %18, h18;\nmov.b32 %19, h19;\nmov.b32 %20, h20;\nmov.b32 %21, h21;\nmov.b32 %22, h22;\nmov.b32 %23, h23;\n"
        "mov.b32 %24, h24;\nmov.b32 %25, h25;\nmov.b32 %26, h26;\nmov.b32 %27, h27;\nmov.b32 %28, h28;\nmov.b32 %29, h29;\nmov.b32 %30, h30;\nmov.b32 %31, h31;\n"
        "mov.b32 %32, h32;\nmov.b32 %33, h33;\nmov.b32 %34, h34;\nmov.b32 %35, h35;\nmov.b32 %36, h36;\nmov.b32 %37, h37;\nmov.b32 %38, h38;\nmov.b32 %39, h39;\n"
        "mov.b32 %40, h40;\nmov.b32 %41, h41;\nmov.b32 %42, h42;\nmov.b32 %43, h43;\nmov.b32 %44, h44;\nmov.b32 %45, h45;\nmov.b32 %46, h46;\nmov.b32 %47, h47;\n"
        "mov.b32 %48, h48;\nmov.b32 %49, h49;\nmov.b32 %50, h50;\nmov.b32 %51, h51;\nmov.b32 %52, h52;\nmov.b32 %53, h53;\nmov.b32 %54, h54;\nmov.b32 %55, h55;\n"
        "mov.b32 %56, h56;\nmov.b32 %57, h57;\nmov.b32 %58, h58;\nmov.b32 %59, h59;\nmov.b32 %60, h60;\nmov.b32 %61, h61;\nmov.b32 %62, h62;\nmov.b32 %63, h63;\n"
        "}\n"
        : "=r"(pk[0]), "=r"(pk[1]), "=r"(pk[2]), "=r"(pk[3]), "=r"(pk[4]), "=r"(pk[5]), "=r"(pk[6]), "=r"(pk[7]), "=r"(pk[8]), "=r"(pk[9]),
          "=r"(pk[10]), "=r"(pk[11]), "=r"(pk[12]), "=r"(pk[13]), "=r"(pk[14]), "=r"(pk[15]), "=r"(pk[16]), "=r"(pk[17]), "=r"(pk[18]), "=r"(pk[19]),
          "=r"(pk[20]), "=r"(pk[21]), "=r"(pk[22]), "=r"(pk[23]), "=r"(pk[24]), "=r"(pk[25]), "=r"(pk[26]), "=r"(pk[27]), "=r"(pk[28]), "=r"(pk[29]),
          "=r"(pk[30]), "=r"(pk[31]), "=r"(pk[32]), "=r"(pk[33]), "=r"(pk[34]), "=r"(pk[35]), "=r"(pk[36]), "=r"(pk[37]), "=r"(pk[38]), "=r"(pk[39]),
          "=r"(pk[40]), "=r"(pk[41]), "=r"(pk[42]), "=r"(pk[43]), "=r"(pk[44]), "=r"(pk[45]), "=r"(pk[46]), "=r"(pk[47]), "=r"(pk[48]), "=r"(pk[49]),
          "=r"(pk[50]), "=r"(pk[51]), "=r"(pk[52]), "=r"(pk[53]), "=r"(pk[54]), "=r"(pk[55]), "=r"(pk[56]), "=r"(pk[57]), "=r"(pk[58]), "=r"(pk[59]),
          "=r"(pk[60]), "=r"(pk[61]), "=r"(pk[62]), "=r"(pk[63])
        : "r"(olp), "r"(xa), "r"(ln), "r"(lc), "r"(linc), "r"(lt), "l"(ea), "l"(sh), "l"(wf), "r"(first.x), "r"(first.y), "r"(first.z), "r"(first.w),
          "n"(sb + SM_REC), "n"(sb + SM_R), "n"(sb + SM_BAR), "n"(sb + SM_CTR), "n"(sb + SM_CGF),
          "r"(w[0]), "r"(w[1]), "r"(w[2]), "r"(w[3]), "r"(w[4]), "r"(w[5]), "r"(w[6]), "r"(w[7]), "r"(w[8]), "r"(w[9]), "r"(w[10]), "r"(w[11]),
          "r"(w[12]), "r"(w[13]), "r"(w[14]), "r"(w[15]), "r"(w[16]), "r"(w[17]), "r"(w[18]), "r"(w[19]), "r"(w[20]), "r"(w[21]), "r"(w[22]),
          "r"(w[23]), "r"(w[24]), "r"(w[25]), "r"(w[26]), "r"(w[27]), "r"(w[28]), "r"(w[29]), "r"(w[30]), "r"(w[31]), "r"(w[32]), "r"(w[33]),
          "r"(w[34]), "r"(w[35])
        : "memory");
}
__device__ __forceinline__ void consume3(uint32_t (&pk)[48], const uint32_t (&w)[36], uint32_t olp, uint32_t xa, uint32_t ln,
                                      uint32_t lc, uint32_t linc, uint32_t lt, const __nv_bfloat16* ea, const __nv_bfloat16* sh, const void* wf, uint4 first) {
    ea += lt * 4, sh += lt & 2;
    asm volatile(
        "{\n.reg .pred p, q, psw, prdy, ps1, ps2, ps3, pz, pq;\n.reg .f32 d<32>, fz;\n"
        ".reg .b32 h<48>, x<32>, y<32>, ra<8>, rb<8>, bA0, bA1, bB0, bB1, c0, c1, c2, c3, e0, e1, s0, kept;\n"
        ".reg .b32 olp, v, vB, m, id, ida, bar, xb, pos, t0, t1, t2, t3, n, z<16>, kept2, g<4>;\n.reg .b16 lo, hi, i16;\n.reg .b64 pa, pb;\n"
        "mov.f32 fz, 0f00000000;\nmov.b32 h0, 0;\nmov.b32 h1, 0;\nmov.b32 h2, 0;\nmov.b32 h3, 0;\nmov.b32 h4, 0;\nmov.b32 h5, 0;\nmov.b32 h6, 0;\n"
        "mov.b32 h7, 0;\nmov.b32 h8, 0;\nmov.b32 h9, 0;\nmov.b32 h10, 0;\nmov.b32 h11, 0;\nmov.b32 h12, 0;\nmov.b32 h13, 0;\nmov.b32 h14, 0;\nmov.b32 h15, 0;\n"
        "mov.b32 h16, 0;\nmov.b32 h17, 0;\nmov.b32 h18, 0;\nmov.b32 h19, 0;\nmov.b32 h20, 0;\nmov.b32 h21, 0;\nmov.b32 h22, 0;\nmov.b32 h23, 0;\n"
        "mov.b32 h24, 0;\nmov.b32 h25, 0;\nmov.b32 h26, 0;\nmov.b32 h27, 0;\nmov.b32 h28, 0;\nmov.b32 h29, 0;\nmov.b32 h30, 0;\nmov.b32 h31, 0;\n"
        "mov.b32 h32, 0;\nmov.b32 h33, 0;\nmov.b32 h34, 0;\nmov.b32 h35, 0;\nmov.b32 h36, 0;\nmov.b32 h37, 0;\nmov.b32 h38, 0;\nmov.b32 h39, 0;\n"
        "mov.b32 h40, 0;\nmov.b32 h41, 0;\nmov.b32 h42, 0;\nmov.b32 h43, 0;\nmov.b32 h44, 0;\nmov.b32 h45, 0;\nmov.b32 h46, 0;\nmov.b32 h47, 0;\n"
        "mov.b32 olp, %48;\nor.b32 t3, %51, 4;\nshfl.sync.bfly.b32 t3, t3, 8, 0x1f, 0xffffffff;\nand.b32 t0, %50, 32;\nsetp.ne.u32 psw, t0, 0;\n"
        "setp.eq.u32 pz, %48, 0;\nvote.sync.any.pred pz, pz, 0xffffffff;\nmov.b32 e0, %57;\nmov.b32 e1, %58;\nmov.b32 s0, %59;\nmov.b32 kept, %60;\n"
        "add.u32 olp, olp, 4;\nsetp.ne.u64 p, %56, 0;\n@p fence.proxy.async.global;\n@p red.release.gpu.global.add.u32 [%56+12], 1;\nbar.warp.sync 0xffffffff;\n"
        "shfl.sync.idx.b32 v, kept, %51, 0x1f, 0xffffffff;\nshfl.sync.idx.b32 vB, kept, t3, 0x1f, 0xffffffff;\n"
        "RW:\nmma.sync.aligned.m16n8k8.row.col.f32.bf16.bf16.f32 {d0,d1,d2,d3}, {%98,%99}, {s0}, {fz,fz,fz,fz};\n"
        "mma.sync.aligned.m16n8k8.row.col.f32.bf16.bf16.f32 {d4,d5,d6,d7}, {%100,%101}, {s0}, {fz,fz,fz,fz};\ncvt.rn.bf16x2.f32 c0, d2, d0;\n"
        "cvt.rn.bf16x2.f32 c1, d3, d1;\ncvt.rn.bf16x2.f32 c2, d6, d4;\ncvt.rn.bf16x2.f32 c3, d7, d5;\nselp.b32 bA0, c2, c0, psw;\nselp.b32 bA1, c0, c2, psw;\n"
        "selp.b32 bB0, c3, c1, psw;\nselp.b32 bB1, c1, c3, psw;\n"
        "mma.sync.aligned.m16n8k16.row.col.f32.bf16.bf16.f32 {d0,d1,d2,d3}, {%66,%67,%68,%69}, {e0,e1}, {fz,fz,fz,fz};\ncvt.rn.bf16x2.f32 ra0, d2, d0;\n"
        "cvt.rn.bf16x2.f32 rb0, d3, d1;\nmma.sync.aligned.m16n8k16.row.col.f32.bf16.bf16.f32 {d4,d5,d6,d7}, {%70,%71,%72,%73}, {e0,e1}, {fz,fz,fz,fz};\n"
        "cvt.rn.bf16x2.f32 ra1, d6, d4;\ncvt.rn.bf16x2.f32 rb1, d7, d5;\n"
        "mma.sync.aligned.m16n8k16.row.col.f32.bf16.bf16.f32 {d8,d9,d10,d11}, {%74,%75,%76,%77}, {e0,e1}, {fz,fz,fz,fz};\ncvt.rn.bf16x2.f32 ra2, d10, d8;\n"
        "cvt.rn.bf16x2.f32 rb2, d11, d9;\nmma.sync.aligned.m16n8k16.row.col.f32.bf16.bf16.f32 {d12,d13,d14,d15}, {%78,%79,%80,%81}, {e0,e1}, {fz,fz,fz,fz};\n"
        "cvt.rn.bf16x2.f32 ra3, d14, d12;\ncvt.rn.bf16x2.f32 rb3, d15, d13;\n"
        "mma.sync.aligned.m16n8k16.row.col.f32.bf16.bf16.f32 {d16,d17,d18,d19}, {%82,%83,%84,%85}, {e0,e1}, {fz,fz,fz,fz};\ncvt.rn.bf16x2.f32 ra4, d18, d16;\n"
        "cvt.rn.bf16x2.f32 rb4, d19, d17;\nmma.sync.aligned.m16n8k16.row.col.f32.bf16.bf16.f32 {d20,d21,d22,d23}, {%86,%87,%88,%89}, {e0,e1}, {fz,fz,fz,fz};\n"
        "cvt.rn.bf16x2.f32 ra5, d22, d20;\ncvt.rn.bf16x2.f32 rb5, d23, d21;\n"
        "mma.sync.aligned.m16n8k16.row.col.f32.bf16.bf16.f32 {d24,d25,d26,d27}, {%90,%91,%92,%93}, {e0,e1}, {fz,fz,fz,fz};\ncvt.rn.bf16x2.f32 ra6, d26, d24;\n"
        "cvt.rn.bf16x2.f32 rb6, d27, d25;\nmma.sync.aligned.m16n8k16.row.col.f32.bf16.bf16.f32 {d28,d29,d30,d31}, {%94,%95,%96,%97}, {e0,e1}, {fz,fz,fz,fz};\n"
        "cvt.rn.bf16x2.f32 ra7, d30, d28;\ncvt.rn.bf16x2.f32 rb7, d31, d29;\nld.shared.u16 t0, [olp];\nadd.u32 olp, olp, 4;\n"
        "lop3.b32 t1, t0, %50, 0x3ff0, 0xe4;\nld.shared.b32 t1, [t1+%61];\nlop3.b32 kept, t1, t0, 0x1ffc, 0xe4;\nlop3.b32 t2, t1, %51, 3, 0x80;\n"
        "setp.ne.u32 q, t2, 0;\nshr.u32 t2, t1, 13;\nmad.wide.u32 pa, t2, 32, %54;\nmad.wide.u32 pb, t2, 8, %55;\nmov.b32 s0, 0;\n"
        "ld.global.cg.L2::128B.v2.b32 {e0,e1}, [pa];\n@q ld.global.cg.L2::128B.b32 s0, [pb];\nshr.u32 bar, v, 1;\nand.b32 bar, bar, 0xff8;\n"
        "mbarrier.test_wait.parity.shared.b64 p, [bar+%63], 0;\nlop3.b32 ida, v, %51, 0x1fff, 0xe4;\nld.volatile.shared.u16 id, [ida+%62];\n"
        "vote.sync.all.pred prdy, p, 0xffffffff;\n@!prdy bra.uni WA;\n"
        "HA:\nmad.lo.u32 xb, id, 64, %49;\ncvt.u16.u32 i16, id;\natom.shared.add.u32 pos, [%50+%64], %52;\n"
        "ldmatrix.sync.aligned.m8n8.x4.trans.shared.b16 {x0,x1,x2,x3}, [xb];\nldmatrix.sync.aligned.m8n8.x4.trans.shared.b16 {x24,x25,x26,x27}, [xb+512];\n"
        "xor.b32 t1, xb, 32;\nldmatrix.sync.aligned.m8n8.x4.trans.shared.b16 {x4,x5,x6,x7}, [t1];\n"
        "ldmatrix.sync.aligned.m8n8.x4.trans.shared.b16 {x28,x29,x30,x31}, [t1+512];\nxor.b32 t1, xb, 64;\n"
        "ldmatrix.sync.aligned.m8n8.x4.trans.shared.b16 {x8,x9,x10,x11}, [t1];\nldmatrix.sync.aligned.m8n8.x4.trans.shared.b16 {x16,x17,x18,x19}, [t1+512];\n"
        "xor.b32 t1, xb, 96;\nldmatrix.sync.aligned.m8n8.x4.trans.shared.b16 {x12,x13,x14,x15}, [t1];\n"
        "ldmatrix.sync.aligned.m8n8.x4.trans.shared.b16 {x20,x21,x22,x23}, [t1+512];\nst.volatile.shared.u16 [pos], i16;\nand.b32 t0, v, 16384;\n"
        "setp.ne.u32 ps1, t0, 0;\nvote.sync.any.pred ps1, ps1, 0xffffffff;\nand.b32 t0, v, 32768;\nsetp.ne.u32 ps2, t0, 0;\n"
        "vote.sync.any.pred ps2, ps2, 0xffffffff;\nmov.b32 v, vB;\nshr.u32 bar, v, 1;\nand.b32 bar, bar, 0xff8;\n"
        "mbarrier.test_wait.parity.shared.b64 p, [bar+%63], 0;\nlop3.b32 ida, v, %51, 0x1fff, 0xe4;\nld.volatile.shared.u16 id, [ida+%62];\n"
        "vote.sync.all.pred prdy, p, 0xffffffff;\nmov.b32 {lo, hi}, ra0;\nmov.b32 t2, {lo, lo};\nmul.rn.bf16x2 y0, x0, t2;\nmul.rn.bf16x2 y2, x2, t2;\n"
        "mov.b32 t2, {hi, hi};\nmul.rn.bf16x2 y1, x1, t2;\nmul.rn.bf16x2 y3, x3, t2;\n"
        "mma.sync.aligned.m16n8k16.row.col.f32.bf16.bf16.f32 {d0,d1,d2,d3}, {y0,y1,y2,y3}, {bA0,bA1}, {fz,fz,fz,fz};\ncvt.rn.bf16x2.f32 z0, d1, d0;\n"
        "cvt.rn.bf16x2.f32 z1, d3, d2;\nmov.b32 {lo, hi}, ra6;\nmov.b32 t2, {lo, lo};\nmul.rn.bf16x2 y24, x24, t2;\nmul.rn.bf16x2 y26, x26, t2;\n"
        "mov.b32 t2, {hi, hi};\nmul.rn.bf16x2 y25, x25, t2;\nmul.rn.bf16x2 y27, x27, t2;\n"
        "mma.sync.aligned.m16n8k16.row.col.f32.bf16.bf16.f32 {d24,d25,d26,d27}, {y24,y25,y26,y27}, {bA0,bA1}, {fz,fz,fz,fz};\ncvt.rn.bf16x2.f32 z12, d25, d24;\n"
        "cvt.rn.bf16x2.f32 z13, d27, d26;\nmov.b32 {lo, hi}, ra1;\nmov.b32 t2, {lo, lo};\nmul.rn.bf16x2 y4, x4, t2;\nmul.rn.bf16x2 y6, x6, t2;\n"
        "mov.b32 t2, {hi, hi};\nmul.rn.bf16x2 y5, x5, t2;\nmul.rn.bf16x2 y7, x7, t2;\n"
        "mma.sync.aligned.m16n8k16.row.col.f32.bf16.bf16.f32 {d4,d5,d6,d7}, {y4,y5,y6,y7}, {bA0,bA1}, {fz,fz,fz,fz};\ncvt.rn.bf16x2.f32 z2, d5, d4;\n"
        "cvt.rn.bf16x2.f32 z3, d7, d6;\nmov.b32 {lo, hi}, ra7;\nmov.b32 t2, {lo, lo};\nmul.rn.bf16x2 y28, x28, t2;\nmul.rn.bf16x2 y30, x30, t2;\n"
        "mov.b32 t2, {hi, hi};\nmul.rn.bf16x2 y29, x29, t2;\nmul.rn.bf16x2 y31, x31, t2;\n"
        "mma.sync.aligned.m16n8k16.row.col.f32.bf16.bf16.f32 {d28,d29,d30,d31}, {y28,y29,y30,y31}, {bA0,bA1}, {fz,fz,fz,fz};\ncvt.rn.bf16x2.f32 z14, d29, d28;\n"
        "cvt.rn.bf16x2.f32 z15, d31, d30;\nmov.b32 {lo, hi}, ra2;\nmov.b32 t2, {lo, lo};\nmul.rn.bf16x2 y8, x8, t2;\nmul.rn.bf16x2 y10, x10, t2;\n"
        "mov.b32 t2, {hi, hi};\nmul.rn.bf16x2 y9, x9, t2;\nmul.rn.bf16x2 y11, x11, t2;\n"
        "mma.sync.aligned.m16n8k16.row.col.f32.bf16.bf16.f32 {d8,d9,d10,d11}, {y8,y9,y10,y11}, {bA0,bA1}, {fz,fz,fz,fz};\ncvt.rn.bf16x2.f32 z4, d9, d8;\n"
        "cvt.rn.bf16x2.f32 z5, d11, d10;\nmov.b32 {lo, hi}, ra4;\nmov.b32 t2, {lo, lo};\nmul.rn.bf16x2 y16, x16, t2;\nmul.rn.bf16x2 y18, x18, t2;\n"
        "mov.b32 t2, {hi, hi};\nmul.rn.bf16x2 y17, x17, t2;\nmul.rn.bf16x2 y19, x19, t2;\n"
        "mma.sync.aligned.m16n8k16.row.col.f32.bf16.bf16.f32 {d16,d17,d18,d19}, {y16,y17,y18,y19}, {bA0,bA1}, {fz,fz,fz,fz};\ncvt.rn.bf16x2.f32 z8, d17, d16;\n"
        "cvt.rn.bf16x2.f32 z9, d19, d18;\nmov.b32 {lo, hi}, ra3;\nmov.b32 t2, {lo, lo};\nmul.rn.bf16x2 y12, x12, t2;\nmul.rn.bf16x2 y14, x14, t2;\n"
        "mov.b32 t2, {hi, hi};\nmul.rn.bf16x2 y13, x13, t2;\nmul.rn.bf16x2 y15, x15, t2;\n"
        "mma.sync.aligned.m16n8k16.row.col.f32.bf16.bf16.f32 {d12,d13,d14,d15}, {y12,y13,y14,y15}, {bA0,bA1}, {fz,fz,fz,fz};\ncvt.rn.bf16x2.f32 z6, d13, d12;\n"
        "cvt.rn.bf16x2.f32 z7, d15, d14;\nmov.b32 {lo, hi}, ra5;\nmov.b32 t2, {lo, lo};\nmul.rn.bf16x2 y20, x20, t2;\nmul.rn.bf16x2 y22, x22, t2;\n"
        "mov.b32 t2, {hi, hi};\nmul.rn.bf16x2 y21, x21, t2;\nmul.rn.bf16x2 y23, x23, t2;\n"
        "mma.sync.aligned.m16n8k16.row.col.f32.bf16.bf16.f32 {d20,d21,d22,d23}, {y20,y21,y22,y23}, {bA0,bA1}, {fz,fz,fz,fz};\ncvt.rn.bf16x2.f32 z10, d21, d20;\n"
        "cvt.rn.bf16x2.f32 z11, d23, d22;\n@ps2 bra.uni TA2;\n@ps1 bra.uni TA1;\n"
        "TA0:\nadd.rn.bf16x2 h0, h0, z0;\nadd.rn.bf16x2 h1, h1, z1;\nadd.rn.bf16x2 h2, h2, z2;\nadd.rn.bf16x2 h3, h3, z3;\nadd.rn.bf16x2 h4, h4, z4;\n"
        "add.rn.bf16x2 h5, h5, z5;\nadd.rn.bf16x2 h6, h6, z6;\nadd.rn.bf16x2 h7, h7, z7;\nadd.rn.bf16x2 h8, h8, z8;\nadd.rn.bf16x2 h9, h9, z9;\n"
        "add.rn.bf16x2 h10, h10, z10;\nadd.rn.bf16x2 h11, h11, z11;\nadd.rn.bf16x2 h12, h12, z12;\nadd.rn.bf16x2 h13, h13, z13;\nadd.rn.bf16x2 h14, h14, z14;\n"
        "add.rn.bf16x2 h15, h15, z15;\n@prdy bra.uni HB;\nbra.uni WB;\n"
        "TA1:\nadd.rn.bf16x2 h16, h16, z0;\nadd.rn.bf16x2 h17, h17, z1;\nadd.rn.bf16x2 h18, h18, z2;\nadd.rn.bf16x2 h19, h19, z3;\nadd.rn.bf16x2 h20, h20, z4;\n"
        "add.rn.bf16x2 h21, h21, z5;\nadd.rn.bf16x2 h22, h22, z6;\nadd.rn.bf16x2 h23, h23, z7;\nadd.rn.bf16x2 h24, h24, z8;\nadd.rn.bf16x2 h25, h25, z9;\n"
        "add.rn.bf16x2 h26, h26, z10;\nadd.rn.bf16x2 h27, h27, z11;\nadd.rn.bf16x2 h28, h28, z12;\nadd.rn.bf16x2 h29, h29, z13;\nadd.rn.bf16x2 h30, h30, z14;\n"
        "add.rn.bf16x2 h31, h31, z15;\n@prdy bra.uni HB;\nbra.uni WB;\n"
        "TA2:\nadd.rn.bf16x2 h32, h32, z0;\nadd.rn.bf16x2 h33, h33, z1;\nadd.rn.bf16x2 h34, h34, z2;\nadd.rn.bf16x2 h35, h35, z3;\nadd.rn.bf16x2 h36, h36, z4;\n"
        "add.rn.bf16x2 h37, h37, z5;\nadd.rn.bf16x2 h38, h38, z6;\nadd.rn.bf16x2 h39, h39, z7;\nadd.rn.bf16x2 h40, h40, z8;\nadd.rn.bf16x2 h41, h41, z9;\n"
        "add.rn.bf16x2 h42, h42, z10;\nadd.rn.bf16x2 h43, h43, z11;\nadd.rn.bf16x2 h44, h44, z12;\nadd.rn.bf16x2 h45, h45, z13;\nadd.rn.bf16x2 h46, h46, z14;\n"
        "add.rn.bf16x2 h47, h47, z15;\n@prdy bra.uni HB;\nbra.uni WB;\n"
        "HB:\nmad.lo.u32 xb, id, 64, %49;\ncvt.u16.u32 i16, id;\natom.shared.add.u32 pos, [%50+%64], %52;\n"
        "ldmatrix.sync.aligned.m8n8.x4.trans.shared.b16 {x0,x1,x2,x3}, [xb];\nldmatrix.sync.aligned.m8n8.x4.trans.shared.b16 {x24,x25,x26,x27}, [xb+512];\n"
        "xor.b32 t1, xb, 32;\nldmatrix.sync.aligned.m8n8.x4.trans.shared.b16 {x4,x5,x6,x7}, [t1];\n"
        "ldmatrix.sync.aligned.m8n8.x4.trans.shared.b16 {x28,x29,x30,x31}, [t1+512];\nxor.b32 t1, xb, 64;\n"
        "ldmatrix.sync.aligned.m8n8.x4.trans.shared.b16 {x8,x9,x10,x11}, [t1];\nldmatrix.sync.aligned.m8n8.x4.trans.shared.b16 {x16,x17,x18,x19}, [t1+512];\n"
        "xor.b32 t1, xb, 96;\nldmatrix.sync.aligned.m8n8.x4.trans.shared.b16 {x12,x13,x14,x15}, [t1];\n"
        "ldmatrix.sync.aligned.m8n8.x4.trans.shared.b16 {x20,x21,x22,x23}, [t1+512];\nst.volatile.shared.u16 [pos], i16;\nand.b32 t0, v, 16384;\n"
        "setp.ne.u32 ps1, t0, 0;\nvote.sync.any.pred ps1, ps1, 0xffffffff;\nand.b32 t0, v, 32768;\nsetp.ne.u32 ps2, t0, 0;\n"
        "vote.sync.any.pred ps2, ps2, 0xffffffff;\nshfl.sync.idx.b32 v, kept, %51, 0x1f, 0xffffffff;\nshfl.sync.idx.b32 vB, kept, t3, 0x1f, 0xffffffff;\n"
        "mov.b32 {lo, hi}, rb0;\nmov.b32 t2, {lo, lo};\nmul.rn.bf16x2 y0, x0, t2;\nmul.rn.bf16x2 y2, x2, t2;\nmov.b32 t2, {hi, hi};\nmul.rn.bf16x2 y1, x1, t2;\n"
        "mul.rn.bf16x2 y3, x3, t2;\nmma.sync.aligned.m16n8k16.row.col.f32.bf16.bf16.f32 {d0,d1,d2,d3}, {y0,y1,y2,y3}, {bB0,bB1}, {fz,fz,fz,fz};\n"
        "cvt.rn.bf16x2.f32 z0, d1, d0;\ncvt.rn.bf16x2.f32 z1, d3, d2;\nmov.b32 {lo, hi}, rb6;\nmov.b32 t2, {lo, lo};\nmul.rn.bf16x2 y24, x24, t2;\n"
        "mul.rn.bf16x2 y26, x26, t2;\nmov.b32 t2, {hi, hi};\nmul.rn.bf16x2 y25, x25, t2;\nmul.rn.bf16x2 y27, x27, t2;\n"
        "mma.sync.aligned.m16n8k16.row.col.f32.bf16.bf16.f32 {d24,d25,d26,d27}, {y24,y25,y26,y27}, {bB0,bB1}, {fz,fz,fz,fz};\ncvt.rn.bf16x2.f32 z12, d25, d24;\n"
        "cvt.rn.bf16x2.f32 z13, d27, d26;\nmov.b32 {lo, hi}, rb1;\nmov.b32 t2, {lo, lo};\nmul.rn.bf16x2 y4, x4, t2;\nmul.rn.bf16x2 y6, x6, t2;\n"
        "mov.b32 t2, {hi, hi};\nmul.rn.bf16x2 y5, x5, t2;\nmul.rn.bf16x2 y7, x7, t2;\n"
        "mma.sync.aligned.m16n8k16.row.col.f32.bf16.bf16.f32 {d4,d5,d6,d7}, {y4,y5,y6,y7}, {bB0,bB1}, {fz,fz,fz,fz};\ncvt.rn.bf16x2.f32 z2, d5, d4;\n"
        "cvt.rn.bf16x2.f32 z3, d7, d6;\nmov.b32 {lo, hi}, rb7;\nmov.b32 t2, {lo, lo};\nmul.rn.bf16x2 y28, x28, t2;\nmul.rn.bf16x2 y30, x30, t2;\n"
        "mov.b32 t2, {hi, hi};\nmul.rn.bf16x2 y29, x29, t2;\nmul.rn.bf16x2 y31, x31, t2;\n"
        "mma.sync.aligned.m16n8k16.row.col.f32.bf16.bf16.f32 {d28,d29,d30,d31}, {y28,y29,y30,y31}, {bB0,bB1}, {fz,fz,fz,fz};\ncvt.rn.bf16x2.f32 z14, d29, d28;\n"
        "cvt.rn.bf16x2.f32 z15, d31, d30;\nmov.b32 {lo, hi}, rb2;\nmov.b32 t2, {lo, lo};\nmul.rn.bf16x2 y8, x8, t2;\nmul.rn.bf16x2 y10, x10, t2;\n"
        "mov.b32 t2, {hi, hi};\nmul.rn.bf16x2 y9, x9, t2;\nmul.rn.bf16x2 y11, x11, t2;\n"
        "mma.sync.aligned.m16n8k16.row.col.f32.bf16.bf16.f32 {d8,d9,d10,d11}, {y8,y9,y10,y11}, {bB0,bB1}, {fz,fz,fz,fz};\ncvt.rn.bf16x2.f32 z4, d9, d8;\n"
        "cvt.rn.bf16x2.f32 z5, d11, d10;\nmov.b32 {lo, hi}, rb4;\nmov.b32 t2, {lo, lo};\nmul.rn.bf16x2 y16, x16, t2;\nmul.rn.bf16x2 y18, x18, t2;\n"
        "mov.b32 t2, {hi, hi};\nmul.rn.bf16x2 y17, x17, t2;\nmul.rn.bf16x2 y19, x19, t2;\n"
        "mma.sync.aligned.m16n8k16.row.col.f32.bf16.bf16.f32 {d16,d17,d18,d19}, {y16,y17,y18,y19}, {bB0,bB1}, {fz,fz,fz,fz};\ncvt.rn.bf16x2.f32 z8, d17, d16;\n"
        "cvt.rn.bf16x2.f32 z9, d19, d18;\nmov.b32 {lo, hi}, rb3;\nmov.b32 t2, {lo, lo};\nmul.rn.bf16x2 y12, x12, t2;\nmul.rn.bf16x2 y14, x14, t2;\n"
        "mov.b32 t2, {hi, hi};\nmul.rn.bf16x2 y13, x13, t2;\nmul.rn.bf16x2 y15, x15, t2;\n"
        "mma.sync.aligned.m16n8k16.row.col.f32.bf16.bf16.f32 {d12,d13,d14,d15}, {y12,y13,y14,y15}, {bB0,bB1}, {fz,fz,fz,fz};\ncvt.rn.bf16x2.f32 z6, d13, d12;\n"
        "cvt.rn.bf16x2.f32 z7, d15, d14;\nmov.b32 {lo, hi}, rb5;\nmov.b32 t2, {lo, lo};\nmul.rn.bf16x2 y20, x20, t2;\nmul.rn.bf16x2 y22, x22, t2;\n"
        "mov.b32 t2, {hi, hi};\nmul.rn.bf16x2 y21, x21, t2;\nmul.rn.bf16x2 y23, x23, t2;\n"
        "mma.sync.aligned.m16n8k16.row.col.f32.bf16.bf16.f32 {d20,d21,d22,d23}, {y20,y21,y22,y23}, {bB0,bB1}, {fz,fz,fz,fz};\ncvt.rn.bf16x2.f32 z10, d21, d20;\n"
        "cvt.rn.bf16x2.f32 z11, d23, d22;\n@ps2 bra.uni TB2;\n@ps1 bra.uni TB1;\n"
        "TB0:\nadd.rn.bf16x2 h0, h0, z0;\nadd.rn.bf16x2 h1, h1, z1;\nadd.rn.bf16x2 h2, h2, z2;\nadd.rn.bf16x2 h3, h3, z3;\nadd.rn.bf16x2 h4, h4, z4;\n"
        "add.rn.bf16x2 h5, h5, z5;\nadd.rn.bf16x2 h6, h6, z6;\nadd.rn.bf16x2 h7, h7, z7;\nadd.rn.bf16x2 h8, h8, z8;\nadd.rn.bf16x2 h9, h9, z9;\n"
        "add.rn.bf16x2 h10, h10, z10;\nadd.rn.bf16x2 h11, h11, z11;\nadd.rn.bf16x2 h12, h12, z12;\nadd.rn.bf16x2 h13, h13, z13;\nadd.rn.bf16x2 h14, h14, z14;\n"
        "add.rn.bf16x2 h15, h15, z15;\nbra.uni RW;\n"
        "TB1:\nadd.rn.bf16x2 h16, h16, z0;\nadd.rn.bf16x2 h17, h17, z1;\nadd.rn.bf16x2 h18, h18, z2;\nadd.rn.bf16x2 h19, h19, z3;\nadd.rn.bf16x2 h20, h20, z4;\n"
        "add.rn.bf16x2 h21, h21, z5;\nadd.rn.bf16x2 h22, h22, z6;\nadd.rn.bf16x2 h23, h23, z7;\nadd.rn.bf16x2 h24, h24, z8;\nadd.rn.bf16x2 h25, h25, z9;\n"
        "add.rn.bf16x2 h26, h26, z10;\nadd.rn.bf16x2 h27, h27, z11;\nadd.rn.bf16x2 h28, h28, z12;\nadd.rn.bf16x2 h29, h29, z13;\nadd.rn.bf16x2 h30, h30, z14;\n"
        "add.rn.bf16x2 h31, h31, z15;\nbra.uni RW;\n"
        "TB2:\nadd.rn.bf16x2 h32, h32, z0;\nadd.rn.bf16x2 h33, h33, z1;\nadd.rn.bf16x2 h34, h34, z2;\nadd.rn.bf16x2 h35, h35, z3;\nadd.rn.bf16x2 h36, h36, z4;\n"
        "add.rn.bf16x2 h37, h37, z5;\nadd.rn.bf16x2 h38, h38, z6;\nadd.rn.bf16x2 h39, h39, z7;\nadd.rn.bf16x2 h40, h40, z8;\nadd.rn.bf16x2 h41, h41, z9;\n"
        "add.rn.bf16x2 h42, h42, z10;\nadd.rn.bf16x2 h43, h43, z11;\nadd.rn.bf16x2 h44, h44, z12;\nadd.rn.bf16x2 h45, h45, z13;\nadd.rn.bf16x2 h46, h46, z14;\n"
        "add.rn.bf16x2 h47, h47, z15;\nbra.uni RW;\n"
        "WA:\nshr.u32 t2, v, 1;\nand.b32 t2, t2, 0xff8;\nsetp.eq.u32 p, t2, 0;\nvote.sync.all.pred p, p, 0xffffffff;\n@p bra.uni DONE;\nmov.b32 n, 0;\n"
        "WA3:\nmbarrier.try_wait.parity.shared.b64 p, [t2+%63], 0;\nvote.sync.all.pred p, p, 0xffffffff;\nadd.u32 n, n, 1;\nsetp.lt.and.u32 q, n, 1000000, !p;\n"
        "@q bra.uni WA3;\nlop3.b32 ida, v, %51, 0x1fff, 0xe4;\nld.volatile.shared.u16 id, [ida+%62];\nbra.uni HA;\n"
        "WB:\nshr.u32 t2, v, 1;\nand.b32 t2, t2, 0xff8;\nsetp.eq.u32 p, t2, 0;\nvote.sync.all.pred p, p, 0xffffffff;\n@p bra.uni DONE;\nmov.b32 n, 0;\n"
        "WB3:\nmbarrier.try_wait.parity.shared.b64 p, [t2+%63], 0;\nvote.sync.all.pred p, p, 0xffffffff;\nadd.u32 n, n, 1;\nsetp.lt.and.u32 q, n, 1000000, !p;\n"
        "@q bra.uni WB3;\nlop3.b32 ida, v, %51, 0x1fff, 0xe4;\nld.volatile.shared.u16 id, [ida+%62];\nbra.uni HB;\n"
        "DONE:\nmov.b32 %0, h0;\nmov.b32 %1, h1;\nmov.b32 %2, h2;\nmov.b32 %3, h3;\nmov.b32 %4, h4;\nmov.b32 %5, h5;\nmov.b32 %6, h6;\nmov.b32 %7, h7;\n"
        "mov.b32 %8, h8;\nmov.b32 %9, h9;\nmov.b32 %10, h10;\nmov.b32 %11, h11;\nmov.b32 %12, h12;\nmov.b32 %13, h13;\nmov.b32 %14, h14;\nmov.b32 %15, h15;\n"
        "mov.b32 %16, h16;\nmov.b32 %17, h17;\nmov.b32 %18, h18;\nmov.b32 %19, h19;\nmov.b32 %20, h20;\nmov.b32 %21, h21;\nmov.b32 %22, h22;\nmov.b32 %23, h23;\n"
        "mov.b32 %24, h24;\nmov.b32 %25, h25;\nmov.b32 %26, h26;\nmov.b32 %27, h27;\nmov.b32 %28, h28;\nmov.b32 %29, h29;\nmov.b32 %30, h30;\nmov.b32 %31, h31;\n"
        "mov.b32 %32, h32;\nmov.b32 %33, h33;\nmov.b32 %34, h34;\nmov.b32 %35, h35;\nmov.b32 %36, h36;\nmov.b32 %37, h37;\nmov.b32 %38, h38;\nmov.b32 %39, h39;\n"
        "mov.b32 %40, h40;\nmov.b32 %41, h41;\nmov.b32 %42, h42;\nmov.b32 %43, h43;\nmov.b32 %44, h44;\nmov.b32 %45, h45;\nmov.b32 %46, h46;\nmov.b32 %47, h47;\n"
        "}\n"
        : "=r"(pk[0]), "=r"(pk[1]), "=r"(pk[2]), "=r"(pk[3]), "=r"(pk[4]), "=r"(pk[5]), "=r"(pk[6]), "=r"(pk[7]), "=r"(pk[8]), "=r"(pk[9]),
          "=r"(pk[10]), "=r"(pk[11]), "=r"(pk[12]), "=r"(pk[13]), "=r"(pk[14]), "=r"(pk[15]), "=r"(pk[16]), "=r"(pk[17]), "=r"(pk[18]), "=r"(pk[19]),
          "=r"(pk[20]), "=r"(pk[21]), "=r"(pk[22]), "=r"(pk[23]), "=r"(pk[24]), "=r"(pk[25]), "=r"(pk[26]), "=r"(pk[27]), "=r"(pk[28]), "=r"(pk[29]),
          "=r"(pk[30]), "=r"(pk[31]), "=r"(pk[32]), "=r"(pk[33]), "=r"(pk[34]), "=r"(pk[35]), "=r"(pk[36]), "=r"(pk[37]), "=r"(pk[38]), "=r"(pk[39]),
          "=r"(pk[40]), "=r"(pk[41]), "=r"(pk[42]), "=r"(pk[43]), "=r"(pk[44]), "=r"(pk[45]), "=r"(pk[46]), "=r"(pk[47])
        : "r"(olp), "r"(xa), "r"(ln), "r"(lc), "r"(linc), "r"(lt), "l"(ea), "l"(sh), "l"(wf), "r"(first.x), "r"(first.y), "r"(first.z), "r"(first.w),
          "n"(sb + SM_REC), "n"(sb + SM_R), "n"(sb + SM_BAR), "n"(sb + SM_CTR), "n"(sb + SM_CGF),
          "r"(w[0]), "r"(w[1]), "r"(w[2]), "r"(w[3]), "r"(w[4]), "r"(w[5]), "r"(w[6]), "r"(w[7]), "r"(w[8]), "r"(w[9]), "r"(w[10]), "r"(w[11]),
          "r"(w[12]), "r"(w[13]), "r"(w[14]), "r"(w[15]), "r"(w[16]), "r"(w[17]), "r"(w[18]), "r"(w[19]), "r"(w[20]), "r"(w[21]), "r"(w[22]),
          "r"(w[23]), "r"(w[24]), "r"(w[25]), "r"(w[26]), "r"(w[27]), "r"(w[28]), "r"(w[29]), "r"(w[30]), "r"(w[31]), "r"(w[32]), "r"(w[33]),
          "r"(w[34]), "r"(w[35])
        : "memory");
}

__device__ __forceinline__ void wf_done() {
    asm volatile("fence.proxy.async.global;\nred.release.gpu.global.add.u32 [%0+12], 1;" ::"l"(g_sync) : "memory");
}

template <int NS>
__device__ __forceinline__ void consumer(const __nv_bfloat16* __restrict__ sh,
                                         const __nv_bfloat16* __restrict__ ea, __nv_bfloat16* __restrict__ out, int N, int npb, uint4 first) {
    uint32_t pk[NS * 16];
    {
        const int lane = threadIdx.x & 31, warp = threadIdx.x >> 5;
        const int mi = lane >> 3, r = lane & 7, j = r >> 1;
        const int u = 2 * ((mi >> 1) ^ (j >> 1)) + (r & 1), ph = (j ^ (j >> 1)) & 1;
        uint32_t w[36];
        {
            const uint32_t a = sb + SC_WR + (4 * j + (r & 1) + (mi & 2)) * 272 + (mi & 1) * 16;
#pragma unroll
            for (int c = 0; c < 8; c++)
                asm volatile("ldmatrix.sync.aligned.m8n8.x4.trans.shared.b16 {%0,%1,%2,%3}, [%4];"
                             : "=r"(w[4 * c]), "=r"(w[4 * c + 1]), "=r"(w[4 * c + 2]), "=r"(w[4 * c + 3]) : "r"(a + c * 32) : "memory");
            const uint32_t ca = sb + SC_CG + (lane & 2) * 8 + ((lane >> 2) & 3) * 2;
#pragma unroll
            for (int k = 0; k < 4; k++) {
                const uint32_t f = lds16(ca + 32 * k) | (lds16(ca + 32 * k + 8) << 16);
                w[32 + k] = (lane & 1) == (lane >> 4) ? f : 0;
            }
            asm volatile("fence.proxy.async.shared::cta;\nbar.sync 2, %0;" ::"n"(NCW * 32) : "memory");
            if (threadIdx.x < WSL) sts16(sb + SM_R + 0x2000 + (4 + SP - WSL + lane) * 4, (sb + SC_WR) / 64 + lane * 16);
        }
        const uint32_t xa = __shfl_sync(0xffffffffu, u * 128 + (((u + 4 * ph) ^ (mi & 1)) << 4), lane);
        const uint32_t ln = __shfl_sync(0xffffffffu, lane * 16 + (lane >> 3) * 4, lane);
        const uint32_t lc = __shfl_sync(0xffffffffu, j * 8 + (1 << (lane & 1)) + (ph << 13), lane);
        const uint32_t linc = __shfl_sync(0xffffffffu, (lane & 0x19) ? 0 : 8, lane);
        const uint32_t lt = __shfl_sync(0xffffffffu, lane & 3, lane);
        const void* wfp = (threadIdx.x >> 2) == WFT && blockIdx.x < 128 ? g_sync : nullptr;
        const uint32_t olp = sb + SM_OL + warp * (OLN * 2) + ((lane & 4) >> 1);
        if constexpr (NS == 4) consume4(pk, w, olp, xa, ln, lc, linc, lt, ea, sh, wfp, first);
        else consume3(pk, w, olp, xa, ln, lc, linc, lt, ea, sh, wfp, first);
    }
    TLMAX(10);
    const int tid = thread_id(), lane = tid & 31, warp = tid >> 5, g = lane >> 2, t = lane & 3;
    const uint32_t wc = lds32(sb + SM_MISC + 12) + 1;
    const uint32_t inv = lds32(sb + SM_INV + warp * 4);
    const int node0 = cta_id() * npb, nnodes = min(npb, N - node0);
    uint4* op[NS];
    uint32_t on[NS];
#pragma unroll
    for (int s = 0; s < NS; s++) {
        const int nl = ((inv >> (8 * s)) & 255) + (g >> 2) * 40;
        op[s] = (uint4*)(out + ((size_t)(node0 + nl) * 4 + (g & 3)) * 128 + 8 * t);
        on[s] = nl < nnodes;
    }
    if constexpr (NS == 4) project4(pk, sb + SM_R + wc * 16, sb + SM_BAR + wc * 8, op, on);
    else project3(pk, sb + SM_R + wc * 16, sb + SM_BAR + wc * 8, op, on);
}

#define TLHI "shl.b32 d, tb, 16;\n"
#define RAOFF ((threadIdx.x & 96) >> 1)
#define UNPACK(v) "dp2a.lo.u32.u32 d, " #v ", k64, 0;\nshr.s32 r, " #v ", 14;\n"
#define XSTR(x) XSTR2(x)
#define XSTR2(x) #x
__device__ __forceinline__ void producer(const CUtensorMap* tmx, int pw) {
    const uint32_t nch = lds32(sb + SM_MISC + 12), c0 = lds32(sb + SM_MISC + 24);
    if (elect()) {
        asm volatile(
            "{\n.reg .pred p, q, lead, never;\n.reg .b32 ra, oa, off, due, now, a<4>, b<4>, d, r, z<8>, bar<4>, t, n, tb, ta, k64, ktx;\n"
            ".reg .b64 lg, t64, tm;\n"
            "mov.b32 ta, %5;\nld.volatile.shared.v4.b32 {z0,z1,z2,z3}, [ta+32];\nld.volatile.shared.v4.b32 {z4,z5,z6,z7}, [ta+32];\n"
            "mov.b32 ra, %9;\nmad.lo.u32 t, %0, 8, %10;\n"
            "add.u32 bar0, t, z0;\nadd.u32 bar1, t, z1;\nadd.u32 bar2, t, z2;\nadd.u32 bar3, t, z3;\nsetp.ne.u32 never, z0, 0;\n"
            "add.u32 k64, z4, 64;\nadd.u32 ktx, z5, 8192;\ncvt.u64.u32 tm, z6;\nadd.u64 tm, tm, %3;\n"
            "mov.b32 n, 0;\nld.volatile.shared.b32 tb, [ta];\nsetp.eq.u32 lead, %0, 0;\n"
            "mov.u32 due, %%globaltimer_lo;\n"
            "setp.gt.u32 p, ra, %1;\n@p bra.uni END;\nshr.u32 oa, ra, 3;\n"
            "FIRST:\n"
            "ld.volatile.shared.u16 off, [oa+%11-8];\nmov.u32 now, %%globaltimer_lo;\nadd.u32 due, tb, off;\nsub.u32 t, due, now;\n"
            "setp.gt.s32 p, t, %12;\n@p bra.uni FIRST;\n"
            "GO:\n"
            "ld.volatile.shared.v4.b32 {a0,a1,a2,a3}, [ra];\nld.volatile.shared.v4.b32 {b0,b1,b2,b3}, [ra+0x2000];\n"
            "shr.u32 oa, ra, 3;\nld.volatile.shared.u16 off, [oa+%11];\nld.volatile.shared.b32 tb, [ta];\n"
            "mov.u32 now, %%globaltimer_lo;\n"
            "lop3.b32 t, a0, a1, a2, 0xfe;\nlop3.b32 d, a3, b0, b1, 0xfe;\nlop3.b32 t, t, d, b2, 0xfe;\nor.b32 t, t, b3;\nand.b32 t, t, 1;\n"
            "setp.ne.u32 p, t, 0;\n"
            "@p bra.uni BACK;\n"
            "shl.b32 t, oa, 2;\nmbarrier.arrive.expect_tx.shared.b64 _, [t+%13], ktx;\n"
            "add.u32 bar0, bar0, 32;\nadd.u32 bar1, bar1, 32;\nadd.u32 bar2, bar2, 32;\nadd.u32 bar3, bar3, 32;\n"
            UNPACK(a0)
            "cp.async.bulk.tensor.3d.shared::cluster.global.mbarrier::complete_tx::bytes [d], [tm, {z0, r, z1}], [bar0];\n"
            UNPACK(b0)
            "cp.async.bulk.tensor.3d.shared::cluster.global.mbarrier::complete_tx::bytes [d], [tm, {z2, r, z3}], [bar1];\n"
            UNPACK(a1)
            "cp.async.bulk.tensor.3d.shared::cluster.global.mbarrier::complete_tx::bytes [d], [tm, {z4, r, z5}], [bar2];\n"
            UNPACK(b1)
            "cp.async.bulk.tensor.3d.shared::cluster.global.mbarrier::complete_tx::bytes [d], [tm, {z6, r, z7}], [bar3];\n"
            "@never bra.uni END;\n"
            "add.u32 ra, ra, 64;\nadd.u32 due, off, tb;\nsub.u32 t, due, now;\nsetp.le.u32 q, ra, %1;\nsetp.le.and.u32 q, t, %2, q;\n"
            UNPACK(a2)
            "cp.async.bulk.tensor.3d.shared::cluster.global.mbarrier::complete_tx::bytes [d], [tm, {z0, r, z1}], [bar0];\n"
            UNPACK(b2)
            "cp.async.bulk.tensor.3d.shared::cluster.global.mbarrier::complete_tx::bytes [d], [tm, {z2, r, z3}], [bar1];\n"
            UNPACK(a3)
            "cp.async.bulk.tensor.3d.shared::cluster.global.mbarrier::complete_tx::bytes [d], [tm, {z4, r, z5}], [bar2];\n"
            UNPACK(b3)
            "cp.async.bulk.tensor.3d.shared::cluster.global.mbarrier::complete_tx::bytes [d], [tm, {z6, r, z7}], [bar3];\n"
            "@q bra.uni GO;\n"
            "setp.gt.u32 p, ra, %1;\n@p bra.uni END;\n@!lead bra.uni WAIT;\n"
            "add.u32 d, ta, 16;\ncp.async.bulk.shared::cluster.global.mbarrier::complete_tx::bytes [ta], [%4], 16, [d];\n"
            "setp.ge.s32 p, t, 0;\n@p bra.uni WAIT;\n"
            "setp.lt.u32 p, ra, %8;\n@p bra.uni GO;\nadd.u32 r, ra, " XSTR(SLIPEND) ";\nsetp.gt.u32 p, r, %1;\n@p bra.uni GO;\n"
            "ld.volatile.shared.b64 t64, [ta];\ncvt.u32.u64 r, t64;\nsub.u32 r, tb, r;\nsub.u32 d, %7, t;\nadd.s32 d, d, r;\n"
            "cvt.s64.s32 lg, d;\nadd.u64 t64, t64, lg;\n"
            "red.relaxed.gpu.global.max.u64 [%4], t64;\n"
            "bra.uni GO;\n"
            "SLEEP:\n"
            "nanosleep.u32 32;\nld.volatile.shared.b32 tb, [ta];\nld.volatile.shared.u16 off, [oa+%11];\nadd.u32 due, tb, off;\n"
            "WAIT:\n"
            "mov.u32 now, %%globaltimer_lo;\nsub.u32 t, due, now;\nsetp.gt.s32 p, t, %6;\nsetp.gt.s32 q, t, %12;\n@p bra.uni SLEEP;\n"
            "@q bra.uni WAIT;\nbra.uni GO;\n"
            "BACK:\n"
            "nanosleep.u32 32;\nsub.u32 t, now, tb;\nsetp.lt.s32 p, t, 200000000;\n@p bra.uni GO;\n"
            "END:\n}" ::"r"(pw),
            "r"(sb + SM_R + nch * 16), "n"(AHEAD + EARLY + SLIPTH), "l"(tmx), "l"(g_sync), "n"(sb + SM_MISC + 32), "n"(SPINT + SLIPTH), "n"(SLIPADD),
            "n"(sb + SM_R + SLIPFROM * 16), "r"(sb + SM_R + 16 + c0 * 16 + RAOFF), "r"(sb + SM_BAR + 8 - 32 + c0 * 8),
            "n"(sb + SM_OFF + 8 - (sb + SM_R) / 8), "n"(EARLY + SLIPTH), "n"(sb + SM_BAR - (sb + SM_R) / 2)
            : "memory");
        const uint32_t wch = lds32(sb + SM_MISC + 12) + 1 + pw;
        const uint32_t ra = sb + SM_R + wch * 16, bar = sb + SM_BAR + wch * 8;
        const uint32_t target = lds32(sb + SM_MISC + 16);
        uint32_t cnt = lds128(sb + SM_MISC + 32).w;
        for (int n = 0; n < 1000000 && (int)(cnt - target) < 0; n++)
            asm volatile("ld.acquire.gpu.global.u32 %0, [%1+12];" : "=r"(cnt) : "l"(g_sync) : "memory");
        uint4 a, b;
        for (int n = 0; n < 1000000; n++) {
            a = lds128(ra), b = lds128(ra + 0x2000);
            if (!((a.x | a.y | a.z | a.w | b.x | b.y | b.z | b.w) & 1)) break;
        }
        asm volatile("fence.proxy.async.global;" ::: "memory");
        asm volatile("mbarrier.arrive.expect_tx.shared.b64 _, [%0], 8192;" ::"r"(bar) : "memory");
        const uint32_t c[8] = {a.x, a.y, a.z, a.w, b.x, b.y, b.z, b.w};
#pragma unroll
        for (int i = 0; i < 8; i++)
            asm volatile("cp.async.bulk.shared::cluster.global.mbarrier::complete_tx::bytes [%0], [%1], 1024, [%2];" ::"r"(
                             (c[i] & 0xffe) << 6),
                         "l"(g_wf + (pw * 8 + i) * 64), "r"(bar)
                         : "memory");
    }
}

#define BARINIT(w, n)                                                                                              \
    if (elect()) {                                                                                                 \
        _Pragma("unroll") for (int k = 0; k < (NBAR + n - 1) / n; k++)                                             \
            asm volatile("mbarrier.init.shared.b64 [%0], 1;" ::"r"(sb + SM_BAR + ((w) * ((NBAR + n - 1) / n) + k) * 8)); \
        asm volatile("fence.mbarrier_init.release.cluster;" ::: "memory");                                         \
    }                                                                                                              \
    __syncwarp();

__global__ void __launch_bounds__(NT, 1)
main_kernel(const __grid_constant__ CUtensorMap tmx, const __nv_bfloat16* __restrict__ x, const int* __restrict__ src,
            const int* __restrict__ dst, const __nv_bfloat16* __restrict__ sh, const __nv_bfloat16* __restrict__ ea,
            const __nv_bfloat16* __restrict__ cg, const __nv_bfloat16* __restrict__ wr,
            const __nv_bfloat16* __restrict__ wout, __nv_bfloat16* __restrict__ out, int N, int E, int npb,
            unsigned npb_magic, int chunk, unsigned wsz, unsigned wmagic, unsigned bkm, int tau, int ramp, int rampn, int tdelay, unsigned polld, int spr, int sprn) {
    extern __shared__ __align__(1024) unsigned char smem[];
    if (s2u(smem) != sb) __trap();
    const int tid = threadIdx.x, lane = tid & 31;
    const int warp = __shfl_sync(0xffffffffu, tid >> 5, 0);
    const int nbins = gridDim.x;
    bool fast = chunk > 0;
    uint4 first = make_uint4(0, 0, 0, 0);
    TLSTAMP(0);
    if (fast) {
        const int e0 = blockIdx.x * chunk + tid, left = min(E, (int)(blockIdx.x + 1) * chunk) - e0;
        uint32_t pd[KE], ps[KE];
        {
            const int* dp = dst + e0;
            const int* sp = src + e0;
#pragma unroll
            for (int k = 0; k < KE; k++) {
                pd[k] = (nbins + (k == KE - 1 ? lane : 0)) * npb, ps[k] = 0;
                asm volatile("{\n.reg .pred p;\nsetp.gt.s32 p, %4, %5;\n@p ld.global.nc.u32 %0, [%2];\n@p ld.global.nc.u32 %1, [%3];\n}"
                             : "+r"(pd[k]), "+r"(ps[k]) : "l"(dp + k * NT), "l"(sp + k * NT), "r"(left), "r"(k * NT));
            }
        }
        uint32_t epoch = 0;
        if (tid == NT - 1) asm volatile("ld.relaxed.gpu.global.u32 %0, [%1];" : "=r"(epoch) : "l"(&g_epoch) : "memory");
        uint4 wv, wo[3];
        const bool wrow = (tid >> 2) == WFT && blockIdx.x < 128;
        {
            const uint4* wp = tid < 256 ? (const uint4*)wr + tid
                              : wrow    ? (const uint4*)(wout + blockIdx.x * 128 + (tid & 3) * 32)
                                        : (const uint4*)cg + (tid & 7);
            if (tid < 264 || wrow) wv = __ldg(wp);
            if (wrow) wo[0] = __ldg(wp + 1), wo[1] = __ldg(wp + 2), wo[2] = __ldg(wp + 3);
        }
        const uint32_t t16 = sb + tid * 16;
        const uint32_t sa = sb + SC_STG + (tid >> 3) * CP + (tid & 7) * 16;
        const uint32_t sm = sb + SC_STG + (tid >> 2) * CP + (tid & 3) * 16 + 128;
        const uint32_t none = (40 * NWIN + (lane & 7) + (blockIdx.x & 3) * 8) << 2;
        const uint32_t pade = min(blockIdx.x * chunk, E - 1) << 13;
        const bool third = warp * 4 + 128 < nbins, second = warp * 8 + 128 < nbins;
#pragma unroll
        for (int k = 0; k < 3; k++)
            if (k < 2 || third) sts128(sa + k * 64 * CP, none, none, none, none);
#pragma unroll
        for (int k = 0; k < 2; k++)
            if (k < 1 || second) sts128(sm + k * 128 * CP, none, none, none, none);
        if (tid < MAXB + 32) sts32(sb + SC_CNT + tid * 4, 0);
        if (tid < NOFF) sts16(sb + SM_OFF + tid * 2, 0xffff);
#pragma unroll
        for (int k = 0; k < 3; k++) sts128(t16 + SC_TABB + k * NT * 16, 0, 0, 0, 0);
        const uint32_t ecomp = -(wsz * (CH << 13));
#pragma unroll
        for (int k = 0; k < 3; k++)
            sts128(t16 + SC_TMP + k * NT * 16, 0, pade + ecomp, 0, pade + ecomp);
#pragma unroll
        for (int k = 0; k < ZSL / 8; k++) sts128(t16 + k * NT * 16, 0, 0, 0, 0), sts128(t16 + SP * 1024 + PH + k * NT * 16, 0, 0, 0, 0);
        if (tid < RP / 4) {
            uint32_t c[4], d[4];
#pragma unroll
            for (int i = 0; i < 4; i++) {
                const uint32_t k = tid * 4 - 4 + i;
                c[i] = d[i] = 0xc0000001u;
                if (warp == 0 && k < SP) c[i] += sb / 64 - 1 + k * 16;
                if (warp == 0 && k < SP - WSL) d[i] = c[i] + (SP * 1024 + PH) / 64;
            }
            static_assert(SP + 4 <= 128, "first warp");
            sts128(t16 + SM_R, c[0], c[1], c[2], c[3]);
            sts128(t16 + SM_R + 0x2000, d[0], d[1], d[2], d[3]);
        }
        constexpr uint32_t OLEND = (RECN - 4) * 4 * 0x10001;
        if (tid < NCW * OLN / 8) sts128(t16 + SM_OL, OLEND, OLEND, OLEND, OLEND);
        if (warp == 12) {
            sts32(sb + SM_CTR + lane * 16 + (lane >> 3) * 4,
                  sb + SM_R + ((lane & 0x19) ? (RP - 1) * 4 : (4 + SP) * 4 + (((lane >> 1) ^ (lane >> 2)) & 1) * 0x2000 + (lane & 4)));
            if (lane < 3) sts32(sb + SM_MISC + (lane ? 16 + lane * 4 : 4), 0);
            if (lane == 8) sts128(sb + SM_REC + (RECN - 4) * 4, pade, pade, pade, pade), sts128(sb + SM_MISC + 64, 0, 0, 0, 0);
            if (lane == 9) asm volatile("prefetch.tensormap [%0];" ::"l"(&tmx) : "memory");
        }
        __syncthreads();
        TLSTAMP(1);

        {
            uint32_t b[KE], r[KE];
#pragma unroll
            for (int k = 0; k < KE; k++) {
                b[k] = __umulhi(pd[k], npb_magic);
                r[k] = atoms_add(sb + SC_CNT + b[k] * 4, 4);
                if (k == KE - 1) b[k] = min(b[k], nbins);
            }
            if (tid == NT - 1) {
                sts32(sb + SM_MISC + 8, epoch % 3 + 1);
                asm volatile("{\n.reg .b64 t;\nmov.u64 t, %%globaltimer;\nred.relaxed.gpu.global.max.u64 [%0], t;\n"
                             "red.relaxed.gpu.global.add.u32 [%0+8], 1;\n}" ::"l"(g_sync) : "memory");
            }
            __syncwarp();
#pragma unroll
            for (int k = 0; k < KE; k++) {
                asm volatile(
                    "{\n.reg .pred p;\n.reg .b32 d, t, u;\nmad.lo.u32 d, %1, %3, %0;\nsetp.ge.u32 p, d, 40;\nmul.hi.u32 u, %2, %4;\n"
                    "mad.lo.u32 t, %2, %10, %5;\nmad.lo.u32 t, d, %11, t;\nmad.lo.u32 t, u, %12, t;\n@p add.u32 t, t, %7;\n"
                    "min.u32 d, %6, 188;\nmad.lo.u32 d, %1, %9, d;\nst.shared.b32 [d+%8], t;\n}" ::"r"(pd[k]),
                    "r"(b[k]), "r"(ps[k]), "r"(-npb), "r"(wmagic), "r"(((tid + k * NT) << 14) + 4), "r"(r[k]), "n"(2 - 40 * NWIN * 4),
                    "n"(sb + SC_STG), "n"(CP), "n"(CH << 14), "n"(NWIN * 4), "r"(4 - wsz * (CH << 14))
                    : "memory");
            }
        }
        if (tid < 264) sts128(sb + SC_WR + (tid >> 4) * 272 + (tid & 15) * 16, wv.x, wv.y, wv.z, wv.w);
        uint4* gp = g_cell + ((tid >> 3) * MAXB + blockIdx.x) * 8 + (tid & 7);
        uint4* gm = g_more + ((tid >> 2) * MAXB + blockIdx.x) * 4 + (tid & 3);
        __syncthreads();
        TLSTAMP(6);
        const uint32_t tag = lds32(sb + SM_MISC + 8), t0 = tag & 1, t1 = tag >> 1;
        {
            uint4 v[5];
#pragma unroll
            for (int k = 0; k < 5; k++)
                if (k != 2 && k != 4 || (k == 2 ? third : second)) v[k] = lds128(k < 3 ? sa + k * 64 * CP : sm + (k - 3) * 128 * CP);
#pragma unroll
            for (int k = 0; k < 5; k++)
                if (k != 2 && k != 4 || (k == 2 ? third : second))
                    st_cell(k < 3 ? gp + k * 64 * MAXB * 8 : gm + (k - 3) * 128 * MAXB * 4, v[k].x | t0, v[k].y | t1, v[k].z | t0, v[k].w | t1);
        }
        if (wrow) {
            const int k = blockIdx.x;
            uint4* dp = &g_wf[((tid & 3) * 8 + (k >> 4)) * 64 + (k & 8) * 4 + (k & 7)];
            dp[0] = make_uint4(wv.x, wo[0].x, wo[1].x, wo[2].x);
            dp[8] = make_uint4(wv.y, wo[0].y, wo[1].y, wo[2].y);
            dp[16] = make_uint4(wv.z, wo[0].z, wo[1].z, wo[2].z);
            dp[24] = make_uint4(wv.w, wo[0].w, wo[1].w, wo[2].w);
        }
        if (warp < 14) { BARINIT(warp, 14) }
        __syncwarp();
        if (tid == NT - 1) {
            uint4 q;
            for (int n = 0; n < (1 << 22); n++) {
                q = ld_cell((const uint4*)g_sync);
                if ((int)(q.z - (epoch + 1) * nbins) >= 0) break;
            }
            sts128(sb + SM_MISC + 32, q.x, q.y, q.z, q.w), sts32(sb + SM_MISC + 16, (epoch + 1) * 512);
            asm volatile("mbarrier.init.shared.b64 [%0], 1;" ::"r"(sb + SM_MISC + 48) : "memory");
            while ((uint32_t)(gt_lo() - q.x) < polld) {}
        }
        __syncthreads();
        TLSTAMP(14);
        uint32_t m[20], rk[20], ia[20], eb[2];
        eb[0] = (((tid >> 3) * chunk) << 13) + ecomp + 1;
        eb[1] = eb[0] + (chunk << 19);
        asm volatile("" : "+r"(eb[0]), "+r"(eb[1]));
        bool ext;
        {
            const uint4* hp = g_cell + blockIdx.x * (MAXB * 8) + tid;
            const uint4* hm = g_more + blockIdx.x * (MAXB * 4) + tid;
            uint4 q[5];
            q[2] = q[4] = make_uint4(none | t0, none | t1, none | t0, none | t1);
            for (int n = 0; n < (1 << 22); n++) {
                q[0] = ld_cell(hp), q[1] = ld_cell(hp + NT), q[3] = ld_cell(hm);
                if ((tid >> 3) + 128 < nbins) q[2] = ld_cell(hp + 2 * NT);
                if ((tid >> 2) + 128 < nbins) q[4] = ld_cell(hm + NT);
                uint32_t bad = 0;
#pragma unroll
                for (int k = 0; k < 5; k++)
                    asm("{\n.reg .b32 a, b;\nlop3.b32 a, %1, %2, %5, 0x7e;\nlop3.b32 b, %3, %4, %6, 0x7e;\nlop3.b32 %0, %0, a, b, 0xfe;\n}"
                        : "+r"(bad) : "r"(q[k].x), "r"(q[k].z), "r"(q[k].y), "r"(q[k].w), "r"(t0), "r"(t1));
                if (!(bad & 1)) break;
            }
            __syncwarp();
            TLSTAMP(8);
#pragma unroll
            for (int k = 0; k < 5; k++) m[4 * k] = q[k].x, m[4 * k + 1] = q[k].y, m[4 * k + 2] = q[k].z, m[4 * k + 3] = q[k].w;
#pragma unroll
            for (int k = 0; k < 12; k++)
                if (k < 8 || third) ia[k] = m[k] & 0x3ffc, rk[k] = atoms_add(sb + SC_TABB + ia[k], 8);
            ext = __any_sync(0xffffffffu, min(m[12] & 0x3ffc, m[16] & 0x3ffc) < 40 * NWIN * 4);
            if (ext) {
#pragma unroll
                for (int k = 12; k < 20; k++) ia[k] = m[k] & 0x3ffc, rk[k] = atoms_add(sb + SC_TABB + ia[k], 8);
                if ((tid & 3) == 3 && min(m[15] & 0x3ffc, m[19] & 0x3ffc) < 40 * NWIN * 4) sts32(sb + SM_MISC + 4, 1);
            }
        }
        __syncthreads();
        TLSTAMP(5);
        const uint32_t tr = sb + warp * (NWIN * 4) + lane * 16;
        if (tid >= NT - PFT) {
            const int i = NT - 1 - tid;
            const char* p = i < 76 ? (const char*)sh + (size_t)min(blockIdx.x * chunk + i * 32, E - 32) * 8
                                   : (const char*)ea + (size_t)min(blockIdx.x * chunk + (i - 76) * 8, E - 8) * 32;
            asm volatile("prefetch.global.L2 [%0];\nprefetch.global.L2 [%0+128];" ::"l"(p));
        }
        if (tid == NT - 1 && blockIdx.x == 0) g_epoch = epoch + 1;
        {
            uint4 c[3];
            uint32_t tt[3];
#pragma unroll
            for (int i = 0; i < 3; i++) {
                c[i] = make_uint4(0, 0, 0, 0);
                if ((i < 2 || warp < 8) && lane < NWIN / 4) c[i] = lds128(tr + SC_TABB + i * 16 * NWIN * 4);
                tt[i] = c[i].x + c[i].y + c[i].z + c[i].w;
            }
            const uint32_t sum = (tt[0] >> 3) + (tt[1] << 7) + (tt[2] << 17);
            const uint32_t tot = __reduce_add_sync(0xffffffffu, sum);
            uint32_t inc = scan_step(scan_step(sum, 1), 2);
            const uint32_t q = (tot + 0x300c03) & 0x3fcff3fc, q0 = q & 1023, q1 = q0 + ((q >> 10) & 1023);
            uint32_t base = atoms_add(sb + (lane ? SC_CNT + lane * 4 : SM_MISC + 20), q1 + (q >> 20));
            inc = scan_step(scan_step(scan_step(inc, 4), 8), 16);
            base = __shfl_sync(0xffffffffu, base, 0);
            const uint32_t l3 = min(lane, 2);
            sts32(sb + SC_KEY + (warp + 16 * l3) * 4, ((tot >> (10 * l3)) & 1023) * 64 + 63 - warp - 16 * l3);
            if (max(tt[0], max(tt[1], tt[2])) > 31 * 8) sts32(sb + SM_MISC + 4, 1);
            inc += q - tot - sum;
#pragma unroll
            for (int i = 0; i < 3; i++) {
                const uint32_t e = (((inc >> (10 * i)) & 1023) + base + (i == 0 ? 0 : i == 1 ? q0 : q1)) * 8;
                if ((i < 2 || warp < 8) && lane < NWIN / 4) sts128(tr + SC_TABB + i * 16 * NWIN * 4, e, e + c[i].x, e + c[i].x + c[i].y, e + tt[i] - c[i].w);
            }
        }
        __syncthreads();
        TLSTAMP(2);
        if (warp >= 11) {
            const uint32_t st = (tid - 352) >> 2, key = lds32(sb + SC_KEY + st * 4);
            uint32_t rank = 0;
#pragma unroll
            for (int i = 0; i < 5; i++) {
                const uint2 q = lds64(sb + SC_KEY + (lane & 3) * 40 + i * 8);
                rank += ((key - q.x) >> 31) + ((key - q.y) >> 31);
            }
            rank += __shfl_xor_sync(0xffffffffu, rank, 1);
            rank += __shfl_xor_sync(0xffffffffu, rank, 2);
            const uint32_t lv = rank >> 2, cw = ((0x969u >> (2 * lv)) & 3) * 4 + ((rank ^ -(lv & 1)) & 3);
            const uint32_t sid = (0xe4a50u >> (2 * lv)) & 3;
            sts32(sb + SC_MAP + st * 4, cw * (NWIN * 4) - st * (NWIN * 4) + 0x10000 + (sid << 30));
            asm volatile("st.shared.u8 [%0], %1;" ::"r"(sb + SM_INV + cw * 4 + sid), "r"(st) : "memory");
        }
        const int total = lds32(sb + SM_MISC + 20);
        fast = lds32(sb + SM_MISC + 4) == 0 && total <= RECN - 4;
        auto lookup = [&](int k) {
            asm volatile("{\n.reg .pred p;\n.reg .b32 t;\nsetp.lt.u32 p, %1, %2;\nmov.b32 t, 0x80000000;\n@p ld.shared.b32 t, [%1+%3];\nadd.u32 %0, %0, t;\n}"
                         : "+r"(rk[k]) : "r"(ia[k]), "n"(40 * NWIN * 4), "n"(sb + SC_TABB) : "memory");
        };
        auto place = [&](int k, uint32_t e) {
            asm volatile("{\n.reg .pred p;\nsetp.ge.s32 p, %0, 0;\n@p st.shared.v2.b32 [%0+%3], {%1, %2};\n}" ::"r"(rk[k]), "r"(m[k]), "r"(e),
                         "n"(sb + SC_TMP) : "memory");
        };
#pragma unroll
        for (int k = 0; k < 8; k++) lookup(k);
        if (fast) {
#pragma unroll
            for (int k = 0; k < 8; k++) place(k, eb[k >> 2]);
            if (third) {
#pragma unroll
                for (int k = 8; k < 12; k++) lookup(k);
#pragma unroll
                for (int k = 8; k < 12; k++) place(k, 2 * eb[1] - eb[0]);
            }
            if (ext) {
#pragma unroll
                for (int k = 12; k < 20; k++) lookup(k);
#pragma unroll
                for (int k = 12; k < 20; k++) place(k, ((((tid >> 2) + (k >> 4) * 128) * chunk) << 13) + ecomp + 1);
            }
            constexpr int KD = (RECN + NT - 1) / NT;
            const uint32_t P = (lane ^ (lane >> 1)) & 1;
            const uint32_t binc = (P ? 1u << 11 : 1u) + ((lane & 3) == 3 ? 1u << 22 : 0u);
            const bool last = warp * 32 + (KD - 1) * NT < total, q2 = warp * 128 + NT * 4 < total;
            const int rest = total - tid, restq = (total >> 2) - tid;
            uint2 en[KD];
            uint32_t bk[KD], r2[KD], ca[2], ol[2], r3[2];
            __syncthreads();
            TLSTAMP(9);
#pragma unroll
            for (int k = 0; k < KD; k++)
                if (k < KD - 1 || last) en[k] = lds64(sb + SC_TMP + tid * 8 + k * NT * 8);
#pragma unroll
            for (int k = 0; k < 2; k++)
                if (k == 0 || q2) ca[k] = lds32(sb + SC_TMP + (tid + k * NT) * 32 + 24);
#pragma unroll
            for (int k = 0; k < 2; k++)
                if (k == 0 || q2) ca[k] &= 0x3ffc, ol[k] = lds32(sb + SC_MAP + __umulhi(ca[k], 0xffffffffu / (NWIN * 4) + 1) * 4);
#pragma unroll
            for (int k = 0; k < KD; k++) {
                if (k < KD - 1 || last) {
                    const uint32_t v = en[k].x, f = v >> 14, i = v & 0x3ffc;
                    const uint32_t w4 = i - __umulhi(i, 0xffffffffu / (NWIN * 4) + 1) * (NWIN * 4);
                    const uint32_t o = __umulhi(f, 0xffffffffu / CH + 1) - wsz;
                    bk[k] = (__umulhi(f, bkm) + w4) * 4;
                    en[k].x = (w4 >> 2) * wsz + o;
                    en[k].y += ((v >> 1) & 0xffffe001u) - o * (CH << 13);
                    if (rest <= k * NT) bk[k] = 2048 + lane * 4;
                    r2[k] = atoms_add(sb + SC_TABA + bk[k], binc);
                }
            }
#pragma unroll
            for (int k = 0; k < 2; k++) {
                if (k == 0 || q2) {
                    ca[k] = (ca[k] + ol[k]) & 0xffff;
                    ol[k] = (tid + k * NT) * 16 + (ol[k] >> 30 << 14);
                    r3[k] = atoms_add(sb + SC_TABC + ca[k], restq > k * NT ? 2 : 0);
                }
            }
            __syncthreads();
            TLSTAMP(12);
            if (warp < NCW) {
                uint4 c = make_uint4(0, 0, 0, 0);
                if (lane < NWIN / 4) c = lds128(tr + SC_TABC);
                const uint32_t tt = c.x + c.y + c.z + c.w;
                uint32_t inc = tt;
#pragma unroll
                for (int o = 1; o < 32; o <<= 1) inc = scan_step(inc, o);
                if (inc > (OLN - 8) * 2) sts32(sb + SM_MISC + 4, 1);
                inc += warp * (OLN * 2) - tt;
                if (lane < NWIN / 4) sts128(tr + SC_TABC, inc, inc + c.x, inc + c.x + c.y, inc + tt - c.w);
            } else {
                const uint32_t mine = (warp + lane) & 3;
                uint4 c;
                uint32_t cs, inc = 0, e = 4 + (4 << 11);
#pragma unroll
                for (int i = 0; i < 4; i++) {
                    const uint32_t pc = (mine + i) & 3;
                    const uint4 v = lds128(sb + SC_TABA + lane * 64 + (pc << 4));
                    const uint32_t sum = v.x + v.y + v.z + v.w;
                    inc += sum;
                    if (i == 0) c = v, cs = sum;
                    if (pc >= mine) e -= sum;
                }
#pragma unroll
                for (int o = 1; o < 32; o <<= 1) inc = scan_step(inc, o);
                e += inc;
                sts128(sb + SC_TABB + lane * 64 + (mine << 4), e, e + c.x, e + c.x + c.y, e + cs - c.w);
                if ((int)max((e + cs) & 0x7ff, ((e + cs) >> 11) & 0x7ff) - (int)(e >> 22) * 2 > SP) sts32(sb + SM_MISC + 4, 1);
                if (tid == NCW * 32) {
                    const uint32_t c0 = min(min(c.x & 0x7ff, (c.x >> 11) & 0x7ff), ZSL) >> 2;
                    sts32(sb + SM_MISC + 12, ((total >> 2) + 1) >> 1), sts32(sb + SM_MISC + 24, c0);
                }
            }
            __syncthreads();
            TLSTAMP(13);
            fast = lds32(sb + SM_MISC + 4) == 0;
            if (warp == 15 && lane < lds32(sb + SM_MISC + 24))
                asm volatile("mbarrier.arrive.shared.b64 _, [%0];" ::"r"(sb + SM_BAR + 8 + lane * 8) : "memory");
#pragma unroll
            for (int k = 0; k < KD; k++)
                if (k < KD - 1 || last) r2[k] += lds32(sb + SC_TABB + bk[k]);
#pragma unroll
            for (int k = 0; k < 2; k++)
                if (k == 0 || q2) r3[k] += lds32(sb + SC_TABC + ca[k]);
            if (fast) {
                const uint32_t rot = P ? 9 : 30;
#pragma unroll
                for (int k = 0; k < KD; k++) {
                    if (k < KD - 1 || last) {
                        const uint32_t k4 = __funnelshift_r(r2[k], r2[k], rot);
                        if (rest > k * NT) {
                            sts16(sb + SM_R + 2 + bitsel(k4, P << 13), en[k].x);
                            sts32(sb + SM_REC + tid * 4 + k * NT * 4, bitsel(k4, en[k].y));
                        }
                    }
                }
#pragma unroll
                for (int k = 0; k < 2; k++)
                    if ((k == 0 || q2) && restq > k * NT) sts16(sb + SM_OL + r3[k], ol[k]);
            }
        }
        asm volatile("fence.mbarrier_init.release.cluster;\nfence.proxy.async.shared::cta;" ::: "memory");
        __syncthreads();
        TLSTAMP(3);
        if (!fast && wrow) wf_done();
        if (fast && warp < NCW) {
            const uint32_t e = lds16(sb + SM_OL + warp * (OLN * 2) + ((lane & 4) >> 1));
            const uint32_t rec = lds32(sb + SM_REC + (e & 0x3ff0) + (lane >> 3) * 4);
            first.w = bitsel(rec, e);
            asm volatile("{\n.reg .pred q;\nsetp.ne.u32 q, %5, 0;\nld.global.cg.v2.b32 {%0,%1}, [%3];\n@q ld.global.cg.b32 %2, [%4];\n}"
                         : "=r"(first.x), "=r"(first.y), "+r"(first.z)
                         : "l"(ea + (size_t)(rec >> 13) * 16 + (lane & 3) * 4), "l"(sh + (size_t)(rec >> 13) * 4 + (lane & 2)), "r"(rec & (1 << (lane & 1))));
        }
        if (fast && tid < NOFF) {
            const uint4 a = lds128(t16 + SM_R), b = lds128(t16 + SM_R + 0x2000);
            const int s = (((int)a.x >> 3) + ((int)a.y >> 3) + ((int)a.z >> 3) + ((int)a.w >> 3) + ((int)b.x >> 3) + ((int)b.y >> 3) +
                           ((int)b.z >> 3) + ((int)b.w >> 3)) >> 16;
            sts16(sb + SM_OFF + tid * 2, min(max(tdelay + SLIPTH + ((s * tau + min(s, rampn) * ramp - max(s - sprn, 0) * spr) >> 10), 0), 0xffff));
        }
        __syncwarp();
    }

    if (!fast) {
        float* accs = (float*)smem;
        constexpr int NACC = 96;
        const int node0 = blockIdx.x * npb, nnodes = max(0, min(npb, N - node0));
#pragma unroll 1
        for (int nb = 0; nb < nnodes; nb += NACC) {
            __syncthreads();
            for (int i = tid; i < NACC * 512; i += NT) accs[i] = 0.f;
            __syncthreads();
            const int lim = min(NACC, nnodes - nb);
#pragma unroll 1
            for (int base = warp * 32; base < E; base += NT) {
                const int e = base + lane;
                const int dl = e < E ? dst[e] - node0 - nb : -1;
                unsigned mask = __ballot_sync(0xffffffffu, dl >= 0 && dl < lim);
#pragma unroll 1
                while (mask) {
                    const int l = __ffs(mask) - 1;
                    mask &= mask - 1;
                    const int dd = __shfl_sync(0xffffffffu, dl, l);
                    slow_edge(base + l, src[base + l], accs + dd * 512, x, sh, ea, cg, wr, lane);
                }
            }
            __syncthreads();
#pragma unroll 1
            for (int nl = warp; nl < lim; nl += NT / 32) slow_out(accs + nl * 512, wout, out + (size_t)(node0 + nb + nl) * 512, lane);
        }
    } else if (warp >= NCW) {
        asm volatile("setmaxnreg.dec.sync.aligned.u32 %0;" ::"n"(PREG));
        producer(&tmx, warp - NCW);
    } else if (warp >= 4) {
        asm volatile("setmaxnreg.inc.sync.aligned.u32 %0;" ::"n"(R1));
        consumer<3>(sh, ea, out, N, npb, first);
        TLMAX(4);
    } else {
        asm volatile("setmaxnreg.inc.sync.aligned.u32 %0;" ::"n"(R0));
        consumer<4>(sh, ea, out, N, npb, first);
        TLMAX(4);
    }
}

typedef CUresult (*EncodeTiledFn)(CUtensorMap*, CUtensorMapDataType, cuuint32_t, void*, const cuuint64_t*,
                                  const cuuint64_t*, const cuuint32_t*, const cuuint32_t*, CUtensorMapInterleave,
                                  CUtensorMapSwizzle, CUtensorMapL2promotion, CUtensorMapFloatOOBfill);

extern "C" void kernel_launch(void* const* d_in, const int* in_sizes, int n_in, void* d_out, int out_size) {
    const __nv_bfloat16* x = (const __nv_bfloat16*)d_in[0];
    const int* src = (const int*)d_in[1];
    const int* dst = (const int*)d_in[2];
    const __nv_bfloat16* sh = (const __nv_bfloat16*)d_in[3];
    const __nv_bfloat16* ea = (const __nv_bfloat16*)d_in[4];
    const __nv_bfloat16* cg = (const __nv_bfloat16*)d_in[5];
    const __nv_bfloat16* wr = (const __nv_bfloat16*)d_in[6];
    const __nv_bfloat16* wout = (const __nv_bfloat16*)d_in[7];
    __nv_bfloat16* out = (__nv_bfloat16*)d_out;
    const int N = in_sizes[0] / 512;
    const int E = in_sizes[1];

    static int num_sms = 0, coresident = 0;
    static EncodeTiledFn encode = nullptr;
    if (num_sms == 0) {
        int dev = 0;
        cudaGetDevice(&dev);
        cudaDeviceGetAttribute(&num_sms, cudaDevAttrMultiProcessorCount, dev);
        cudaFuncSetAttribute(main_kernel, cudaFuncAttributeMaxDynamicSharedMemorySize, SM_TOTAL);
        int occ = 0;
        cudaOccupancyMaxActiveBlocksPerMultiprocessor(&occ, main_kernel, NT, SM_TOTAL);
        coresident = occ * num_sms;
        void* fn = nullptr;
        cudaDriverEntryPointQueryResult qr;
        cudaGetDriverEntryPoint("cuTensorMapEncodeTiled", &fn, cudaEnableDefault, &qr);
        encode = (EncodeTiledFn)fn;
    }
    CUtensorMap tmx;
    const int rank = 3;
    const cuuint64_t gd[3] = {64, (cuuint64_t)N * 4, 2}, gs[2] = {256, 128};
    const cuuint32_t bd[3] = {64, 4, 2}, es[3] = {1, 1, 1};
    encode(&tmx, CU_TENSOR_MAP_DATA_TYPE_BFLOAT16, rank, (void*)x, gd, gs, bd, es, CU_TENSOR_MAP_INTERLEAVE_NONE,
           CU_TENSOR_MAP_SWIZZLE_128B, CU_TENSOR_MAP_L2_PROMOTION_NONE, CU_TENSOR_MAP_FLOAT_OOB_FILL_NONE);

    int nbins = num_sms < MAXB ? num_sms : MAXB;
    int npb = (N + nbins - 1) / nbins;
    if (npb < 2) npb = 2;
    nbins = (N + npb - 1) / npb;
    const unsigned npb_magic = (unsigned)((0x100000000ull + npb - 1) / npb);
    int chunk = (E + nbins - 1) / nbins;
    const unsigned wsz = (N + NWIN - 2) / (NWIN - 1);
    if (nbins > coresident || nbins < 128 || npb > MAXNPB || chunk > CH || wsz > (1 << 18) / CH || N < 512 || E < 32 || E > (1 << 19)) chunk = 0;
    const unsigned wmagic = 0xffffffffu / wsz + 1, bkm = (unsigned)((4ull << 32) / (wsz * CH));
    double pace = PACE, rampt = RAMP, rampf = RAMPF, sprt = SPRINT, sprf = SPRINTF;
    int tdelay = TDELAY, polld = POLLD;
    const int tau = (int)(1024.0 * pace * ((double)E / nbins) / N);
    const int rampn = (int)(N * rampf), ramp = (int)(1024.0 * rampt / rampn);
    main_kernel<<<nbins, NT, SM_TOTAL, cudaStreamPerThread>>>(tmx, x, src, dst, sh, ea, cg, wr, wout, out, N, E, npb, npb_magic,
                                                              chunk, wsz, wmagic, bkm, tau, ramp, rampn, tdelay, polld, (int)(1024.0 * sprt / (N * sprf)), (int)(N * (1 - sprf)));
}
```

```cpp
#include <cuda_runtime.h>
#include <cuda.h>
#include <cuda_bf16.h>
#include <stdint.h>
#include <stdlib.h>

#define NT 512
#define NCW 12
#define MAXB 144
#define MAXNPB 80
#define KE 5
#define SP 99
#define RECN 2752
#define RP 1484
#define OLN 80
#define NBAR 350
#define NOFF 352
#define R0 168
#define R1 160
#define PREG 24
#define PACE 9.95
#define TDELAY 4550
#define POLLD 1000
#define WFT 80
#define SLIPTH 250
#define SLIPADD 150
#define SLIPFROM 36
#define AHEAD 96
#define EARLY 32
#define RAMPF 0.1
#define SPRINT 400
#define SPRINTF 0.5
#define SLIPEND 640
#define SPINT 96
#define PFT 224
#define EM3 1
#define RAMP 500

__device__ __align__(1024) uint4 g_cell[MAXB * MAXB * 8];
__device__ __align__(1024) uint4 g_more[MAXB * MAXB * 4];
__device__ __align__(1024) uint4 g_wf[2048];
__device__ __align__(256) ulonglong2 g_sync[16];
__device__ __align__(256) unsigned g_epoch;
#define TLSTAMP(i)
#define TLMAX(i)

constexpr uint32_t sb = 1024;
#define PH 512
#define SM_R (2 * SP * 1024 + PH)
#define SM_CTR (SP * 1024)
#define SM_MISC (SM_R + RP * 4)
#define SM_INV (SM_MISC + 80)
#define SM_OL (SM_INV + 48)
#define SM_REC (SM_R + 0x2000 + RP * 4)
#define SM_OFF (SM_REC + RECN * 4)
#define SM_BAR (SM_OFF + NOFF * 2)
#define SM_CGF (SM_BAR + NBAR * 8)
#define SM_TOTAL (SM_CGF + 512)
static_assert(SM_TOTAL <= 232448 && SM_OL + NCW * OLN * 2 <= SM_R + 0x2000 && SM_OL % 16 == 0 && SM_BAR % 16 == 0, "shared memory");
static_assert(4 + RECN / 2 + SP + 2 <= RP && RECN / 8 + 5 <= NBAR && NBAR % 14 == 0 && RECN / 8 + 4 <= NOFF, "tables");
#define ZSL 32
#define NWIN 96
#define CH 2432
#define CP 208
#define SC_STG ((SP + ZSL) * 1024 + PH)
#define SC_TMP (ZSL * 1024)
#define SC_TABB (SC_TMP + 3072 * 8)
#define SC_TABC (SC_TABB + 41 * NWIN * 4)
#define SC_TABA (SC_TABC + NCW * NWIN * 4)
#define SC_ZEND (SC_TABB + 3 * NT * 16)
#define SC_CNT SC_ZEND
#define SC_KEY (SC_CNT + (MAXB + 32) * 4)
#define SC_MAP (SC_KEY + 192)
#define WSL 5
#define SC_WR ((2 * SP - WSL) * 1024 + PH)
#define SC_CG (SC_WR + 16 * 272)
static_assert(SC_TABA + 2048 + 128 <= SC_ZEND && RECN <= 3072 && SC_MAP + 192 <= SP * 1024 && SC_STG + (MAXB + 1) * CP <= SC_WR, "scratch");

__device__ __forceinline__ uint32_t pack_bf16(float lo, float hi) {
    uint32_t r;
    asm("cvt.rn.bf16x2.f32 %0, %1, %2;" : "=r"(r) : "f"(hi), "f"(lo));
    return r;
}
__device__ __forceinline__ uint32_t s2u(const void* p) { return (uint32_t)__cvta_generic_to_shared(p); }
__device__ __forceinline__ void mbar_wait0(uint32_t a) {
    asm volatile(
        "{\n.reg .pred p, q;\n.reg .u32 n;\nmov.u32 n, 0;\n"
        "LAB_WAIT:\nmbarrier.try_wait.parity.shared.b64 p, [%0], 0;\nadd.u32 n, n, 1;\nsetp.lt.and.u32 q, n, 1000000, !p;\n@q bra LAB_WAIT;\n}" ::"r"(a)
        : "memory");
}
__device__ __forceinline__ uint32_t lds8(uint32_t a) { uint32_t v; asm volatile("ld.shared.u8 %0, [%1];" : "=r"(v) : "r"(a) : "memory"); return v; }
__device__ __forceinline__ uint32_t lds16(uint32_t a) { uint32_t v; asm volatile("ld.shared.u16 %0, [%1];" : "=r"(v) : "r"(a) : "memory"); return v; }
__device__ __forceinline__ uint32_t lds32(uint32_t a) { uint32_t v; asm volatile("ld.shared.u32 %0, [%1];" : "=r"(v) : "r"(a) : "memory"); return v; }
__device__ __forceinline__ uint2 lds64(uint32_t a) {
    uint2 v; asm volatile("ld.shared.v2.u32 {%0,%1}, [%2];" : "=r"(v.x), "=r"(v.y) : "r"(a) : "memory"); return v;
}
__device__ __forceinline__ uint4 lds128(uint32_t a) {
    uint4 v; asm volatile("ld.volatile.shared.v4.u32 {%0,%1,%2,%3}, [%4];" : "=r"(v.x), "=r"(v.y), "=r"(v.z), "=r"(v.w) : "r"(a) : "memory"); return v;
}
__device__ __forceinline__ void sts16(uint32_t a, uint32_t v) { asm volatile("st.shared.u16 [%0], %1;" ::"r"(a), "h"((unsigned short)v) : "memory"); }
__device__ __forceinline__ void sts32(uint32_t a, uint32_t v) { asm volatile("st.shared.u32 [%0], %1;" ::"r"(a), "r"(v) : "memory"); }
__device__ __forceinline__ void sts64(uint32_t a, uint32_t x, uint32_t y) { asm volatile("st.shared.v2.u32 [%0], {%1,%2};" ::"r"(a), "r"(x), "r"(y) : "memory"); }
__device__ __forceinline__ void sts128(uint32_t a, uint32_t x, uint32_t y, uint32_t z, uint32_t w) {
    asm volatile("st.shared.v4.u32 [%0], {%1,%2,%3,%4};" ::"r"(a), "r"(x), "r"(y), "r"(z), "r"(w) : "memory");
}
__device__ __forceinline__ uint32_t atoms_add(uint32_t a, uint32_t v) {
    uint32_t r;
    asm volatile("atom.shared.add.u32 %0, [%1], %2;" : "=r"(r) : "r"(a), "r"(v) : "memory");
    return r;
}
__device__ __forceinline__ uint4 ld_cell(const uint4* p) {
    uint4 v;
    asm volatile("{\n.reg .b64 a, b;\nld.relaxed.gpu.global.v2.b64 {a, b}, [%4];\nmov.b64 {%0,%1}, a;\nmov.b64 {%2,%3}, b;\n}"
                 : "=r"(v.x), "=r"(v.y), "=r"(v.z), "=r"(v.w) : "l"(p) : "memory");
    return v;
}
__device__ __forceinline__ void st_cell(uint4* p, uint32_t x, uint32_t y, uint32_t z, uint32_t w) {
    asm volatile("st.relaxed.gpu.global.v2.b64 [%0], {%1, %2};" ::"l"(p), "l"(x | (uint64_t)y << 32), "l"(z | (uint64_t)w << 32) : "memory");
}
__device__ __forceinline__ uint32_t scan_step(uint32_t v, int o) {
    asm volatile("{\n.reg .pred p;\n.reg .b32 y;\nshfl.sync.up.b32 y|p, %0, %1, 0, 0xffffffff;\n@p add.u32 %0, %0, y;\n}" : "+r"(v) : "r"(o));
    return v;
}
__device__ __forceinline__ uint32_t bitsel(uint32_t a, uint32_t b) {
    uint32_t r;
    asm("lop3.b32 %0, %1, %2, 0x1ffc, 0xe4;" : "=r"(r) : "r"(a), "r"(b));
    return r;
}
__device__ __forceinline__ uint32_t movm(uint32_t a) {
    uint32_t r;
    asm volatile("movmatrix.sync.aligned.m8n8.trans.b16 %0, %1;" : "=r"(r) : "r"(a));
    return r;
}
__device__ __forceinline__ uint32_t gt_lo() {
    uint32_t t;
    asm volatile("mov.u32 %0, %globaltimer_lo;" : "=r"(t));
    return t;
}
__device__ __forceinline__ bool elect() {
    uint32_t p;
    asm volatile("{\n.reg .pred P;\nelect.sync _|P, 0xffffffff;\nselp.u32 %0, 1, 0, P;\n}" : "=r"(p));
    return p;
}
__device__ __forceinline__ void project4(const uint32_t (&pk)[64], uint32_t ra, uint32_t ba, uint4* const (&p)[4], const uint32_t (&v)[4]) {
    asm volatile(
        "{\n.reg .pred p0, p1, q0, q1, nv, s<4>;\n.reg .b32 t, h, c<16>, a<32>, b<32>, k<16>;\n.reg .b64 d<16>;\n.reg .f32 o<32>;\nsetp.ne.b32 p0, 0, 0;\n"
        "setp.eq.b32 p1, 0, 0;\nmov.b32 h, 8;\nsetp.eq.u32 nv, %64, 0;\nvote.sync.any.pred nv, nv, 0xffffffff;\nsetp.ne.b32 s0, %69, 0;\n"
        "setp.ne.b32 s1, %70, 0;\nsetp.ne.b32 s2, %71, 0;\nsetp.ne.b32 s3, %72, 0;\nmov.b32 t, 0;\n"
        "W0:\nmbarrier.try_wait.parity.shared.b64 q0, [%73], 0;\nvote.sync.all.pred q0, q0, 0xffffffff;\nadd.u32 t, t, 1;\nsetp.lt.and.u32 q1, t, 1000000, !q0;\n"
        "@q1 bra.uni W0;\nld.volatile.shared.v4.b32 {c0,c1,c2,c3}, [%64+0];\nld.volatile.shared.v4.b32 {c4,c5,c6,c7}, [%64+8192];\n"
        "ld.volatile.shared.v4.b32 {c8,c9,c10,c11}, [%64+16];\nld.volatile.shared.v4.b32 {c12,c13,c14,c15}, [%64+8208];\nand.b32 t, c0, 0xffe;\n"
        "mad.lo.u32 t, t, 4, 0x200000;\nmov.b64 d0, {t, h};\nand.b32 t, c1, 0xffe;\nmad.lo.u32 t, t, 4, 0x200000;\nmov.b64 d1, {t, h};\nand.b32 t, c2, 0xffe;\n"
        "mad.lo.u32 t, t, 4, 0x200000;\nmov.b64 d2, {t, h};\nand.b32 t, c3, 0xffe;\nmad.lo.u32 t, t, 4, 0x200000;\nmov.b64 d3, {t, h};\nand.b32 t, c4, 0xffe;\n"
        "mad.lo.u32 t, t, 4, 0x200000;\nmov.b64 d4, {t, h};\nand.b32 t, c5, 0xffe;\nmad.lo.u32 t, t, 4, 0x200000;\nmov.b64 d5, {t, h};\nand.b32 t, c6, 0xffe;\n"
        "mad.lo.u32 t, t, 4, 0x200000;\nmov.b64 d6, {t, h};\nand.b32 t, c7, 0xffe;\nmad.lo.u32 t, t, 4, 0x200000;\nmov.b64 d7, {t, h};\nand.b32 t, c8, 0xffe;\n"
        "mad.lo.u32 t, t, 4, 0x200000;\nmov.b64 d8, {t, h};\nand.b32 t, c9, 0xffe;\nmad.lo.u32 t, t, 4, 0x200000;\nmov.b64 d9, {t, h};\nand.b32 t, c10, 0xffe;\n"
        "mad.lo.u32 t, t, 4, 0x200000;\nmov.b64 d10, {t, h};\nand.b32 t, c11, 0xffe;\nmad.lo.u32 t, t, 4, 0x200000;\nmov.b64 d11, {t, h};\n"
        "and.b32 t, c12, 0xffe;\nmad.lo.u32 t, t, 4, 0x200000;\nmov.b64 d12, {t, h};\nand.b32 t, c13, 0xffe;\nmad.lo.u32 t, t, 4, 0x200000;\n"
        "mov.b64 d13, {t, h};\nand.b32 t, c14, 0xffe;\nmad.lo.u32 t, t, 4, 0x200000;\nmov.b64 d14, {t, h};\nand.b32 t, c15, 0xffe;\n"
        "mad.lo.u32 t, t, 4, 0x200000;\nmov.b64 d15, {t, h};\nmovmatrix.sync.aligned.m8n8.trans.b16 a0, %0;\nmovmatrix.sync.aligned.m8n8.trans.b16 a1, %16;\n"
        "movmatrix.sync.aligned.m8n8.trans.b16 a2, %1;\nmovmatrix.sync.aligned.m8n8.trans.b16 a3, %17;\nmovmatrix.sync.aligned.m8n8.trans.b16 a4, %2;\n"
        "movmatrix.sync.aligned.m8n8.trans.b16 a5, %18;\nmovmatrix.sync.aligned.m8n8.trans.b16 a6, %3;\nmovmatrix.sync.aligned.m8n8.trans.b16 a7, %19;\n"
        "movmatrix.sync.aligned.m8n8.trans.b16 a8, %4;\nmovmatrix.sync.aligned.m8n8.trans.b16 a9, %20;\nmovmatrix.sync.aligned.m8n8.trans.b16 a10, %5;\n"
        "movmatrix.sync.aligned.m8n8.trans.b16 a11, %21;\nmovmatrix.sync.aligned.m8n8.trans.b16 a12, %6;\nmovmatrix.sync.aligned.m8n8.trans.b16 a13, %22;\n"
        "movmatrix.sync.aligned.m8n8.trans.b16 a14, %7;\nmovmatrix.sync.aligned.m8n8.trans.b16 a15, %23;\nmovmatrix.sync.aligned.m8n8.trans.b16 a16, %8;\n"
        "movmatrix.sync.aligned.m8n8.trans.b16 a17, %24;\nmovmatrix.sync.aligned.m8n8.trans.b16 a18, %9;\nmovmatrix.sync.aligned.m8n8.trans.b16 a19, %25;\n"
        "movmatrix.sync.aligned.m8n8.trans.b16 a20, %10;\nmovmatrix.sync.aligned.m8n8.trans.b16 a21, %26;\nmovmatrix.sync.aligned.m8n8.trans.b16 a22, %11;\n"
        "movmatrix.sync.aligned.m8n8.trans.b16 a23, %27;\nmovmatrix.sync.aligned.m8n8.trans.b16 a24, %12;\nmovmatrix.sync.aligned.m8n8.trans.b16 a25, %28;\n"
        "movmatrix.sync.aligned.m8n8.trans.b16 a26, %13;\nmovmatrix.sync.aligned.m8n8.trans.b16 a27, %29;\nmovmatrix.sync.aligned.m8n8.trans.b16 a28, %14;\n"
        "movmatrix.sync.aligned.m8n8.trans.b16 a29, %30;\nmovmatrix.sync.aligned.m8n8.trans.b16 a30, %15;\nmovmatrix.sync.aligned.m8n8.trans.b16 a31, %31;\n"
        "wgmma.fence.sync.aligned;\n"
        "wgmma.mma_async.sync.aligned.m64n32k16.f32.bf16.bf16 {o0,o1,o2,o3,o4,o5,o6,o7,o8,o9,o10,o11,o12,o13,o14,o15}, {a0,a1,a2,a3}, d0, p0, 1, 1, 1;\n"
        "wgmma.mma_async.sync.aligned.m64n32k16.f32.bf16.bf16 {o0,o1,o2,o3,o4,o5,o6,o7,o8,o9,o10,o11,o12,o13,o14,o15}, {a4,a5,a6,a7}, d1, p1, 1, 1, 1;\n"
        "wgmma.mma_async.sync.aligned.m64n32k16.f32.bf16.bf16 {o0,o1,o2,o3,o4,o5,o6,o7,o8,o9,o10,o11,o12,o13,o14,o15}, {a8,a9,a10,a11}, d2, p1, 1, 1, 1;\n"
        "wgmma.mma_async.sync.aligned.m64n32k16.f32.bf16.bf16 {o0,o1,o2,o3,o4,o5,o6,o7,o8,o9,o10,o11,o12,o13,o14,o15}, {a12,a13,a14,a15}, d3, p1, 1, 1, 1;\n"
        "wgmma.mma_async.sync.aligned.m64n32k16.f32.bf16.bf16 {o0,o1,o2,o3,o4,o5,o6,o7,o8,o9,o10,o11,o12,o13,o14,o15}, {a16,a17,a18,a19}, d4, p1, 1, 1, 1;\n"
        "wgmma.mma_async.sync.aligned.m64n32k16.f32.bf16.bf16 {o0,o1,o2,o3,o4,o5,o6,o7,o8,o9,o10,o11,o12,o13,o14,o15}, {a20,a21,a22,a23}, d5, p1, 1, 1, 1;\n"
        "wgmma.mma_async.sync.aligned.m64n32k16.f32.bf16.bf16 {o0,o1,o2,o3,o4,o5,o6,o7,o8,o9,o10,o11,o12,o13,o14,o15}, {a24,a25,a26,a27}, d6, p1, 1, 1, 1;\n"
        "wgmma.mma_async.sync.aligned.m64n32k16.f32.bf16.bf16 {o0,o1,o2,o3,o4,o5,o6,o7,o8,o9,o10,o11,o12,o13,o14,o15}, {a28,a29,a30,a31}, d7, p1, 1, 1, 1;\n"
        "wgmma.commit_group.sync.aligned;\n"
        "wgmma.mma_async.sync.aligned.m64n32k16.f32.bf16.bf16 {o16,o17,o18,o19,o20,o21,o22,o23,o24,o25,o26,o27,o28,o29,o30,o31}, {a0,a1,a2,a3}, d8, p0, 1, 1, 1;\n"
        "wgmma.mma_async.sync.aligned.m64n32k16.f32.bf16.bf16 {o16,o17,o18,o19,o20,o21,o22,o23,o24,o25,o26,o27,o28,o29,o30,o31}, {a4,a5,a6,a7}, d9, p1, 1, 1, 1;\n"
        "wgmma.mma_async.sync.aligned.m64n32k16.f32.bf16.bf16 {o16,o17,o18,o19,o20,o21,o22,o23,o24,o25,o26,o27,o28,o29,o30,o31}, {a8,a9,a10,a11}, d10, p1, 1, 1, 1;\n"
        "wgmma.mma_async.sync.aligned.m64n32k16.f32.bf16.bf16 {o16,o17,o18,o19,o20,o21,o22,o23,o24,o25,o26,o27,o28,o29,o30,o31}, {a12,a13,a14,a15}, d11, p1, 1, 1, 1;\n"
        "wgmma.mma_async.sync.aligned.m64n32k16.f32.bf16.bf16 {o16,o17,o18,o19,o20,o21,o22,o23,o24,o25,o26,o27,o28,o29,o30,o31}, {a16,a17,a18,a19}, d12, p1, 1, 1, 1;\n"
        "wgmma.mma_async.sync.aligned.m64n32k16.f32.bf16.bf16 {o16,o17,o18,o19,o20,o21,o22,o23,o24,o25,o26,o27,o28,o29,o30,o31}, {a20,a21,a22,a23}, d13, p1, 1, 1, 1;\n"
        "wgmma.mma_async.sync.aligned.m64n32k16.f32.bf16.bf16 {o16,o17,o18,o19,o20,o21,o22,o23,o24,o25,o26,o27,o28,o29,o30,o31}, {a24,a25,a26,a27}, d14, p1, 1, 1, 1;\n"
        "wgmma.mma_async.sync.aligned.m64n32k16.f32.bf16.bf16 {o16,o17,o18,o19,o20,o21,o22,o23,o24,o25,o26,o27,o28,o29,o30,o31}, {a28,a29,a30,a31}, d15, p1, 1, 1, 1;\n"
        "wgmma.commit_group.sync.aligned;\nwgmma.wait_group.sync.aligned 1;\ncvt.rn.bf16x2.f32 k0, o1, o0;\ncvt.rn.bf16x2.f32 k1, o5, o4;\n"
        "cvt.rn.bf16x2.f32 k2, o9, o8;\ncvt.rn.bf16x2.f32 k3, o13, o12;\n@s0 st.global.v4.b32 [%65+0], {k0,k1,k2,k3};\ncvt.rn.bf16x2.f32 k4, o3, o2;\n"
        "cvt.rn.bf16x2.f32 k5, o7, o6;\ncvt.rn.bf16x2.f32 k6, o11, o10;\ncvt.rn.bf16x2.f32 k7, o15, o14;\n@s1 st.global.v4.b32 [%66+0], {k4,k5,k6,k7};\n"
        "@nv bra.uni END;\nwgmma.wait_group.sync.aligned 0;\ncvt.rn.bf16x2.f32 k8, o17, o16;\ncvt.rn.bf16x2.f32 k9, o21, o20;\ncvt.rn.bf16x2.f32 k10, o25, o24;\n"
        "cvt.rn.bf16x2.f32 k11, o29, o28;\n@s0 st.global.v4.b32 [%65+64], {k8,k9,k10,k11};\ncvt.rn.bf16x2.f32 k12, o19, o18;\ncvt.rn.bf16x2.f32 k13, o23, o22;\n"
        "cvt.rn.bf16x2.f32 k14, o27, o26;\ncvt.rn.bf16x2.f32 k15, o31, o30;\n@s1 st.global.v4.b32 [%66+64], {k12,k13,k14,k15};\n@nv bra.uni END;\n"
        "ld.volatile.shared.v4.b32 {c0,c1,c2,c3}, [%64+32];\nld.volatile.shared.v4.b32 {c4,c5,c6,c7}, [%64+8224];\n"
        "ld.volatile.shared.v4.b32 {c8,c9,c10,c11}, [%64+48];\nld.volatile.shared.v4.b32 {c12,c13,c14,c15}, [%64+8240];\nand.b32 t, c0, 0xffe;\n"
        "mad.lo.u32 t, t, 4, 0x200000;\nmov.b64 d0, {t, h};\nand.b32 t, c1, 0xffe;\nmad.lo.u32 t, t, 4, 0x200000;\nmov.b64 d1, {t, h};\nand.b32 t, c2, 0xffe;\n"
        "mad.lo.u32 t, t, 4, 0x200000;\nmov.b64 d2, {t, h};\nand.b32 t, c3, 0xffe;\nmad.lo.u32 t, t, 4, 0x200000;\nmov.b64 d3, {t, h};\nand.b32 t, c4, 0xffe;\n"
        "mad.lo.u32 t, t, 4, 0x200000;\nmov.b64 d4, {t, h};\nand.b32 t, c5, 0xffe;\nmad.lo.u32 t, t, 4, 0x200000;\nmov.b64 d5, {t, h};\nand.b32 t, c6, 0xffe;\n"
        "mad.lo.u32 t, t, 4, 0x200000;\nmov.b64 d6, {t, h};\nand.b32 t, c7, 0xffe;\nmad.lo.u32 t, t, 4, 0x200000;\nmov.b64 d7, {t, h};\nand.b32 t, c8, 0xffe;\n"
        "mad.lo.u32 t, t, 4, 0x200000;\nmov.b64 d8, {t, h};\nand.b32 t, c9, 0xffe;\nmad.lo.u32 t, t, 4, 0x200000;\nmov.b64 d9, {t, h};\nand.b32 t, c10, 0xffe;\n"
        "mad.lo.u32 t, t, 4, 0x200000;\nmov.b64 d10, {t, h};\nand.b32 t, c11, 0xffe;\nmad.lo.u32 t, t, 4, 0x200000;\nmov.b64 d11, {t, h};\n"
        "and.b32 t, c12, 0xffe;\nmad.lo.u32 t, t, 4, 0x200000;\nmov.b64 d12, {t, h};\nand.b32 t, c13, 0xffe;\nmad.lo.u32 t, t, 4, 0x200000;\n"
        "mov.b64 d13, {t, h};\nand.b32 t, c14, 0xffe;\nmad.lo.u32 t, t, 4, 0x200000;\nmov.b64 d14, {t, h};\nand.b32 t, c15, 0xffe;\n"
        "mad.lo.u32 t, t, 4, 0x200000;\nmov.b64 d15, {t, h};\nwgmma.fence.sync.aligned;\n"
        "wgmma.mma_async.sync.aligned.m64n32k16.f32.bf16.bf16 {o0,o1,o2,o3,o4,o5,o6,o7,o8,o9,o10,o11,o12,o13,o14,o15}, {a0,a1,a2,a3}, d0, p0, 1, 1, 1;\n"
        "wgmma.mma_async.sync.aligned.m64n32k16.f32.bf16.bf16 {o16,o17,o18,o19,o20,o21,o22,o23,o24,o25,o26,o27,o28,o29,o30,o31}, {a0,a1,a2,a3}, d8, p0, 1, 1, 1;\n"
        "wgmma.mma_async.sync.aligned.m64n32k16.f32.bf16.bf16 {o0,o1,o2,o3,o4,o5,o6,o7,o8,o9,o10,o11,o12,o13,o14,o15}, {a4,a5,a6,a7}, d1, p1, 1, 1, 1;\n"
        "wgmma.mma_async.sync.aligned.m64n32k16.f32.bf16.bf16 {o16,o17,o18,o19,o20,o21,o22,o23,o24,o25,o26,o27,o28,o29,o30,o31}, {a4,a5,a6,a7}, d9, p1, 1, 1, 1;\n"
        "wgmma.mma_async.sync.aligned.m64n32k16.f32.bf16.bf16 {o0,o1,o2,o3,o4,o5,o6,o7,o8,o9,o10,o11,o12,o13,o14,o15}, {a8,a9,a10,a11}, d2, p1, 1, 1, 1;\n"
        "wgmma.mma_async.sync.aligned.m64n32k16.f32.bf16.bf16 {o16,o17,o18,o19,o20,o21,o22,o23,o24,o25,o26,o27,o28,o29,o30,o31}, {a8,a9,a10,a11}, d10, p1, 1, 1, 1;\n"
        "wgmma.mma_async.sync.aligned.m64n32k16.f32.bf16.bf16 {o0,o1,o2,o3,o4,o5,o6,o7,o8,o9,o10,o11,o12,o13,o14,o15}, {a12,a13,a14,a15}, d3, p1, 1, 1, 1;\n"
        "wgmma.mma_async.sync.aligned.m64n32k16.f32.bf16.bf16 {o16,o17,o18,o19,o20,o21,o22,o23,o24,o25,o26,o27,o28,o29,o30,o31}, {a12,a13,a14,a15}, d11, p1, 1, 1, 1;\n"
        "wgmma.mma_async.sync.aligned.m64n32k16.f32.bf16.bf16 {o0,o1,o2,o3,o4,o5,o6,o7,o8,o9,o10,o11,o12,o13,o14,o15}, {a16,a17,a18,a19}, d4, p1, 1, 1, 1;\n"
        "wgmma.mma_async.sync.aligned.m64n32k16.f32.bf16.bf16 {o16,o17,o18,o19,o20,o21,o22,o23,o24,o25,o26,o27,o28,o29,o30,o31}, {a16,a17,a18,a19}, d12, p1, 1, 1, 1;\n"
        "wgmma.mma_async.sync.aligned.m64n32k16.f32.bf16.bf16 {o0,o1,o2,o3,o4,o5,o6,o7,o8,o9,o10,o11,o12,o13,o14,o15}, {a20,a21,a22,a23}, d5, p1, 1, 1, 1;\n"
        "wgmma.mma_async.sync.aligned.m64n32k16.f32.bf16.bf16 {o16,o17,o18,o19,o20,o21,o22,o23,o24,o25,o26,o27,o28,o29,o30,o31}, {a20,a21,a22,a23}, d13, p1, 1, 1, 1;\n"
        "wgmma.mma_async.sync.aligned.m64n32k16.f32.bf16.bf16 {o0,o1,o2,o3,o4,o5,o6,o7,o8,o9,o10,o11,o12,o13,o14,o15}, {a24,a25,a26,a27}, d6, p1, 1, 1, 1;\n"
        "wgmma.mma_async.sync.aligned.m64n32k16.f32.bf16.bf16 {o16,o17,o18,o19,o20,o21,o22,o23,o24,o25,o26,o27,o28,o29,o30,o31}, {a24,a25,a26,a27}, d14, p1, 1, 1, 1;\n"
        "wgmma.mma_async.sync.aligned.m64n32k16.f32.bf16.bf16 {o0,o1,o2,o3,o4,o5,o6,o7,o8,o9,o10,o11,o12,o13,o14,o15}, {a28,a29,a30,a31}, d7, p1, 1, 1, 1;\n"
        "wgmma.mma_async.sync.aligned.m64n32k16.f32.bf16.bf16 {o16,o17,o18,o19,o20,o21,o22,o23,o24,o25,o26,o27,o28,o29,o30,o31}, {a28,a29,a30,a31}, d15, p1, 1, 1, 1;\n"
        "wgmma.commit_group.sync.aligned;\n@nv bra.uni END;\nmovmatrix.sync.aligned.m8n8.trans.b16 b0, %32;\nmovmatrix.sync.aligned.m8n8.trans.b16 b1, %48;\n"
        "movmatrix.sync.aligned.m8n8.trans.b16 b2, %33;\nmovmatrix.sync.aligned.m8n8.trans.b16 b3, %49;\nmovmatrix.sync.aligned.m8n8.trans.b16 b4, %34;\n"
        "movmatrix.sync.aligned.m8n8.trans.b16 b5, %50;\nmovmatrix.sync.aligned.m8n8.trans.b16 b6, %35;\nmovmatrix.sync.aligned.m8n8.trans.b16 b7, %51;\n"
        "movmatrix.sync.aligned.m8n8.trans.b16 b8, %36;\nmovmatrix.sync.aligned.m8n8.trans.b16 b9, %52;\nmovmatrix.sync.aligned.m8n8.trans.b16 b10, %37;\n"
        "movmatrix.sync.aligned.m8n8.trans.b16 b11, %53;\nmovmatrix.sync.aligned.m8n8.trans.b16 b12, %38;\nmovmatrix.sync.aligned.m8n8.trans.b16 b13, %54;\n"
        "movmatrix.sync.aligned.m8n8.trans.b16 b14, %39;\nmovmatrix.sync.aligned.m8n8.trans.b16 b15, %55;\nmovmatrix.sync.aligned.m8n8.trans.b16 b16, %40;\n"
        "movmatrix.sync.aligned.m8n8.trans.b16 b17, %56;\nmovmatrix.sync.aligned.m8n8.trans.b16 b18, %41;\nmovmatrix.sync.aligned.m8n8.trans.b16 b19, %57;\n"
        "movmatrix.sync.aligned.m8n8.trans.b16 b20, %42;\nmovmatrix.sync.aligned.m8n8.trans.b16 b21, %58;\nmovmatrix.sync.aligned.m8n8.trans.b16 b22, %43;\n"
        "movmatrix.sync.aligned.m8n8.trans.b16 b23, %59;\nmovmatrix.sync.aligned.m8n8.trans.b16 b24, %44;\nmovmatrix.sync.aligned.m8n8.trans.b16 b25, %60;\n"
        "movmatrix.sync.aligned.m8n8.trans.b16 b26, %45;\nmovmatrix.sync.aligned.m8n8.trans.b16 b27, %61;\nmovmatrix.sync.aligned.m8n8.trans.b16 b28, %46;\n"
        "movmatrix.sync.aligned.m8n8.trans.b16 b29, %62;\nmovmatrix.sync.aligned.m8n8.trans.b16 b30, %47;\nmovmatrix.sync.aligned.m8n8.trans.b16 b31, %63;\n"
        "@nv bra.uni END;\nwgmma.wait_group.sync.aligned 0;\ncvt.rn.bf16x2.f32 k0, o1, o0;\ncvt.rn.bf16x2.f32 k1, o5, o4;\ncvt.rn.bf16x2.f32 k2, o9, o8;\n"
        "cvt.rn.bf16x2.f32 k3, o13, o12;\ncvt.rn.bf16x2.f32 k4, o3, o2;\ncvt.rn.bf16x2.f32 k5, o7, o6;\ncvt.rn.bf16x2.f32 k6, o11, o10;\n"
        "cvt.rn.bf16x2.f32 k7, o15, o14;\ncvt.rn.bf16x2.f32 k8, o17, o16;\ncvt.rn.bf16x2.f32 k9, o21, o20;\ncvt.rn.bf16x2.f32 k10, o25, o24;\n"
        "cvt.rn.bf16x2.f32 k11, o29, o28;\ncvt.rn.bf16x2.f32 k12, o19, o18;\ncvt.rn.bf16x2.f32 k13, o23, o22;\ncvt.rn.bf16x2.f32 k14, o27, o26;\n"
        "cvt.rn.bf16x2.f32 k15, o31, o30;\nld.volatile.shared.v4.b32 {c0,c1,c2,c3}, [%64+0];\nld.volatile.shared.v4.b32 {c4,c5,c6,c7}, [%64+8192];\n"
        "ld.volatile.shared.v4.b32 {c8,c9,c10,c11}, [%64+16];\nld.volatile.shared.v4.b32 {c12,c13,c14,c15}, [%64+8208];\nand.b32 t, c0, 0xffe;\n"
        "mad.lo.u32 t, t, 4, 0x200000;\nmov.b64 d0, {t, h};\nand.b32 t, c1, 0xffe;\nmad.lo.u32 t, t, 4, 0x200000;\nmov.b64 d1, {t, h};\nand.b32 t, c2, 0xffe;\n"
        "mad.lo.u32 t, t, 4, 0x200000;\nmov.b64 d2, {t, h};\nand.b32 t, c3, 0xffe;\nmad.lo.u32 t, t, 4, 0x200000;\nmov.b64 d3, {t, h};\nand.b32 t, c4, 0xffe;\n"
        "mad.lo.u32 t, t, 4, 0x200000;\nmov.b64 d4, {t, h};\nand.b32 t, c5, 0xffe;\nmad.lo.u32 t, t, 4, 0x200000;\nmov.b64 d5, {t, h};\nand.b32 t, c6, 0xffe;\n"
        "mad.lo.u32 t, t, 4, 0x200000;\nmov.b64 d6, {t, h};\nand.b32 t, c7, 0xffe;\nmad.lo.u32 t, t, 4, 0x200000;\nmov.b64 d7, {t, h};\nand.b32 t, c8, 0xffe;\n"
        "mad.lo.u32 t, t, 4, 0x200000;\nmov.b64 d8, {t, h};\nand.b32 t, c9, 0xffe;\nmad.lo.u32 t, t, 4, 0x200000;\nmov.b64 d9, {t, h};\nand.b32 t, c10, 0xffe;\n"
        "mad.lo.u32 t, t, 4, 0x200000;\nmov.b64 d10, {t, h};\nand.b32 t, c11, 0xffe;\nmad.lo.u32 t, t, 4, 0x200000;\nmov.b64 d11, {t, h};\n"
        "and.b32 t, c12, 0xffe;\nmad.lo.u32 t, t, 4, 0x200000;\nmov.b64 d12, {t, h};\nand.b32 t, c13, 0xffe;\nmad.lo.u32 t, t, 4, 0x200000;\n"
        "mov.b64 d13, {t, h};\nand.b32 t, c14, 0xffe;\nmad.lo.u32 t, t, 4, 0x200000;\nmov.b64 d14, {t, h};\nand.b32 t, c15, 0xffe;\n"
        "mad.lo.u32 t, t, 4, 0x200000;\nmov.b64 d15, {t, h};\nwgmma.fence.sync.aligned;\n"
        "wgmma.mma_async.sync.aligned.m64n32k16.f32.bf16.bf16 {o0,o1,o2,o3,o4,o5,o6,o7,o8,o9,o10,o11,o12,o13,o14,o15}, {b0,b1,b2,b3}, d0, p0, 1, 1, 1;\n"
        "wgmma.mma_async.sync.aligned.m64n32k16.f32.bf16.bf16 {o16,o17,o18,o19,o20,o21,o22,o23,o24,o25,o26,o27,o28,o29,o30,o31}, {b0,b1,b2,b3}, d8, p0, 1, 1, 1;\n"
        "wgmma.mma_async.sync.aligned.m64n32k16.f32.bf16.bf16 {o0,o1,o2,o3,o4,o5,o6,o7,o8,o9,o10,o11,o12,o13,o14,o15}, {b4,b5,b6,b7}, d1, p1, 1, 1, 1;\n"
        "wgmma.mma_async.sync.aligned.m64n32k16.f32.bf16.bf16 {o16,o17,o18,o19,o20,o21,o22,o23,o24,o25,o26,o27,o28,o29,o30,o31}, {b4,b5,b6,b7}, d9, p1, 1, 1, 1;\n"
        "wgmma.mma_async.sync.aligned.m64n32k16.f32.bf16.bf16 {o0,o1,o2,o3,o4,o5,o6,o7,o8,o9,o10,o11,o12,o13,o14,o15}, {b8,b9,b10,b11}, d2, p1, 1, 1, 1;\n"
        "wgmma.mma_async.sync.aligned.m64n32k16.f32.bf16.bf16 {o16,o17,o18,o19,o20,o21,o22,o23,o24,o25,o26,o27,o28,o29,o30,o31}, {b8,b9,b10,b11}, d10, p1, 1, 1, 1;\n"
        "wgmma.mma_async.sync.aligned.m64n32k16.f32.bf16.bf16 {o0,o1,o2,o3,o4,o5,o6,o7,o8,o9,o10,o11,o12,o13,o14,o15}, {b12,b13,b14,b15}, d3, p1, 1, 1, 1;\n"
        "wgmma.mma_async.sync.aligned.m64n32k16.f32.bf16.bf16 {o16,o17,o18,o19,o20,o21,o22,o23,o24,o25,o26,o27,o28,o29,o30,o31}, {b12,b13,b14,b15}, d11, p1, 1, 1, 1;\n"
        "wgmma.mma_async.sync.aligned.m64n32k16.f32.bf16.bf16 {o0,o1,o2,o3,o4,o5,o6,o7,o8,o9,o10,o11,o12,o13,o14,o15}, {b16,b17,b18,b19}, d4, p1, 1, 1, 1;\n"
        "wgmma.mma_async.sync.aligned.m64n32k16.f32.bf16.bf16 {o16,o17,o18,o19,o20,o21,o22,o23,o24,o25,o26,o27,o28,o29,o30,o31}, {b16,b17,b18,b19}, d12, p1, 1, 1, 1;\n"
        "wgmma.mma_async.sync.aligned.m64n32k16.f32.bf16.bf16 {o0,o1,o2,o3,o4,o5,o6,o7,o8,o9,o10,o11,o12,o13,o14,o15}, {b20,b21,b22,b23}, d5, p1, 1, 1, 1;\n"
        "wgmma.mma_async.sync.aligned.m64n32k16.f32.bf16.bf16 {o16,o17,o18,o19,o20,o21,o22,o23,o24,o25,o26,o27,o28,o29,o30,o31}, {b20,b21,b22,b23}, d13, p1, 1, 1, 1;\n"
        "wgmma.mma_async.sync.aligned.m64n32k16.f32.bf16.bf16 {o0,o1,o2,o3,o4,o5,o6,o7,o8,o9,o10,o11,o12,o13,o14,o15}, {b24,b25,b26,b27}, d6, p1, 1, 1, 1;\n"
        "wgmma.mma_async.sync.aligned.m64n32k16.f32.bf16.bf16 {o16,o17,o18,o19,o20,o21,o22,o23,o24,o25,o26,o27,o28,o29,o30,o31}, {b24,b25,b26,b27}, d14, p1, 1, 1, 1;\n"
        "wgmma.mma_async.sync.aligned.m64n32k16.f32.bf16.bf16 {o0,o1,o2,o3,o4,o5,o6,o7,o8,o9,o10,o11,o12,o13,o14,o15}, {b28,b29,b30,b31}, d7, p1, 1, 1, 1;\n"
        "wgmma.mma_async.sync.aligned.m64n32k16.f32.bf16.bf16 {o16,o17,o18,o19,o20,o21,o22,o23,o24,o25,o26,o27,o28,o29,o30,o31}, {b28,b29,b30,b31}, d15, p1, 1, 1, 1;\n"
        "wgmma.commit_group.sync.aligned;\n@nv bra.uni END;\n@s0 st.global.v4.b32 [%65+128], {k0,k1,k2,k3};\n@s1 st.global.v4.b32 [%66+128], {k4,k5,k6,k7};\n"
        "@s0 st.global.v4.b32 [%65+192], {k8,k9,k10,k11};\n@s1 st.global.v4.b32 [%66+192], {k12,k13,k14,k15};\n@nv bra.uni END;\n"
        "wgmma.wait_group.sync.aligned 0;\ncvt.rn.bf16x2.f32 k0, o1, o0;\ncvt.rn.bf16x2.f32 k1, o5, o4;\ncvt.rn.bf16x2.f32 k2, o9, o8;\n"
        "cvt.rn.bf16x2.f32 k3, o13, o12;\ncvt.rn.bf16x2.f32 k4, o3, o2;\ncvt.rn.bf16x2.f32 k5, o7, o6;\ncvt.rn.bf16x2.f32 k6, o11, o10;\n"
        "cvt.rn.bf16x2.f32 k7, o15, o14;\ncvt.rn.bf16x2.f32 k8, o17, o16;\ncvt.rn.bf16x2.f32 k9, o21, o20;\ncvt.rn.bf16x2.f32 k10, o25, o24;\n"
        "cvt.rn.bf16x2.f32 k11, o29, o28;\ncvt.rn.bf16x2.f32 k12, o19, o18;\ncvt.rn.bf16x2.f32 k13, o23, o22;\ncvt.rn.bf16x2.f32 k14, o27, o26;\n"
        "cvt.rn.bf16x2.f32 k15, o31, o30;\nld.volatile.shared.v4.b32 {c0,c1,c2,c3}, [%64+32];\nld.volatile.shared.v4.b32 {c4,c5,c6,c7}, [%64+8224];\n"
        "ld.volatile.shared.v4.b32 {c8,c9,c10,c11}, [%64+48];\nld.volatile.shared.v4.b32 {c12,c13,c14,c15}, [%64+8240];\nand.b32 t, c0, 0xffe;\n"
        "mad.lo.u32 t, t, 4, 0x200000;\nmov.b64 d0, {t, h};\nand.b32 t, c1, 0xffe;\nmad.lo.u32 t, t, 4, 0x200000;\nmov.b64 d1, {t, h};\nand.b32 t, c2, 0xffe;\n"
        "mad.lo.u32 t, t, 4, 0x200000;\nmov.b64 d2, {t, h};\nand.b32 t, c3, 0xffe;\nmad.lo.u32 t, t, 4, 0x200000;\nmov.b64 d3, {t, h};\nand.b32 t, c4, 0xffe;\n"
        "mad.lo.u32 t, t, 4, 0x200000;\nmov.b64 d4, {t, h};\nand.b32 t, c5, 0xffe;\nmad.lo.u32 t, t, 4, 0x200000;\nmov.b64 d5, {t, h};\nand.b32 t, c6, 0xffe;\n"
        "mad.lo.u32 t, t, 4, 0x200000;\nmov.b64 d6, {t, h};\nand.b32 t, c7, 0xffe;\nmad.lo.u32 t, t, 4, 0x200000;\nmov.b64 d7, {t, h};\nand.b32 t, c8, 0xffe;\n"
        "mad.lo.u32 t, t, 4, 0x200000;\nmov.b64 d8, {t, h};\nand.b32 t, c9, 0xffe;\nmad.lo.u32 t, t, 4, 0x200000;\nmov.b64 d9, {t, h};\nand.b32 t, c10, 0xffe;\n"
        "mad.lo.u32 t, t, 4, 0x200000;\nmov.b64 d10, {t, h};\nand.b32 t, c11, 0xffe;\nmad.lo.u32 t, t, 4, 0x200000;\nmov.b64 d11, {t, h};\n"
        "and.b32 t, c12, 0xffe;\nmad.lo.u32 t, t, 4, 0x200000;\nmov.b64 d12, {t, h};\nand.b32 t, c13, 0xffe;\nmad.lo.u32 t, t, 4, 0x200000;\n"
        "mov.b64 d13, {t, h};\nand.b32 t, c14, 0xffe;\nmad.lo.u32 t, t, 4, 0x200000;\nmov.b64 d14, {t, h};\nand.b32 t, c15, 0xffe;\n"
        "mad.lo.u32 t, t, 4, 0x200000;\nmov.b64 d15, {t, h};\nwgmma.fence.sync.aligned;\n"
        "wgmma.mma_async.sync.aligned.m64n32k16.f32.bf16.bf16 {o0,o1,o2,o3,o4,o5,o6,o7,o8,o9,o10,o11,o12,o13,o14,o15}, {b0,b1,b2,b3}, d0, p0, 1, 1, 1;\n"
        "wgmma.mma_async.sync.aligned.m64n32k16.f32.bf16.bf16 {o16,o17,o18,o19,o20,o21,o22,o23,o24,o25,o26,o27,o28,o29,o30,o31}, {b0,b1,b2,b3}, d8, p0, 1, 1, 1;\n"
        "wgmma.mma_async.sync.aligned.m64n32k16.f32.bf16.bf16 {o0,o1,o2,o3,o4,o5,o6,o7,o8,o9,o10,o11,o12,o13,o14,o15}, {b4,b5,b6,b7}, d1, p1, 1, 1, 1;\n"
        "wgmma.mma_async.sync.aligned.m64n32k16.f32.bf16.bf16 {o16,o17,o18,o19,o20,o21,o22,o23,o24,o25,o26,o27,o28,o29,o30,o31}, {b4,b5,b6,b7}, d9, p1, 1, 1, 1;\n"
        "wgmma.mma_async.sync.aligned.m64n32k16.f32.bf16.bf16 {o0,o1,o2,o3,o4,o5,o6,o7,o8,o9,o10,o11,o12,o13,o14,o15}, {b8,b9,b10,b11}, d2, p1, 1, 1, 1;\n"
        "wgmma.mma_async.sync.aligned.m64n32k16.f32.bf16.bf16 {o16,o17,o18,o19,o20,o21,o22,o23,o24,o25,o26,o27,o28,o29,o30,o31}, {b8,b9,b10,b11}, d10, p1, 1, 1, 1;\n"
        "wgmma.mma_async.sync.aligned.m64n32k16.f32.bf16.bf16 {o0,o1,o2,o3,o4,o5,o6,o7,o8,o9,o10,o11,o12,o13,o14,o15}, {b12,b13,b14,b15}, d3, p1, 1, 1, 1;\n"
        "wgmma.mma_async.sync.aligned.m64n32k16.f32.bf16.bf16 {o16,o17,o18,o19,o20,o21,o22,o23,o24,o25,o26,o27,o28,o29,o30,o31}, {b12,b13,b14,b15}, d11, p1, 1, 1, 1;\n"
        "wgmma.mma_async.sync.aligned.m64n32k16.f32.bf16.bf16 {o0,o1,o2,o3,o4,o5,o6,o7,o8,o9,o10,o11,o12,o13,o14,o15}, {b16,b17,b18,b19}, d4, p1, 1, 1, 1;\n"
        "wgmma.mma_async.sync.aligned.m64n32k16.f32.bf16.bf16 {o16,o17,o18,o19,o20,o21,o22,o23,o24,o25,o26,o27,o28,o29,o30,o31}, {b16,b17,b18,b19}, d12, p1, 1, 1, 1;\n"
        "wgmma.mma_async.sync.aligned.m64n32k16.f32.bf16.bf16 {o0,o1,o2,o3,o4,o5,o6,o7,o8,o9,o10,o11,o12,o13,o14,o15}, {b20,b21,b22,b23}, d5, p1, 1, 1, 1;\n"
        "wgmma.mma_async.sync.aligned.m64n32k16.f32.bf16.bf16 {o16,o17,o18,o19,o20,o21,o22,o23,o24,o25,o26,o27,o28,o29,o30,o31}, {b20,b21,b22,b23}, d13, p1, 1, 1, 1;\n"
        "wgmma.mma_async.sync.aligned.m64n32k16.f32.bf16.bf16 {o0,o1,o2,o3,o4,o5,o6,o7,o8,o9,o10,o11,o12,o13,o14,o15}, {b24,b25,b26,b27}, d6, p1, 1, 1, 1;\n"
        "wgmma.mma_async.sync.aligned.m64n32k16.f32.bf16.bf16 {o16,o17,o18,o19,o20,o21,o22,o23,o24,o25,o26,o27,o28,o29,o30,o31}, {b24,b25,b26,b27}, d14, p1, 1, 1, 1;\n"
        "wgmma.mma_async.sync.aligned.m64n32k16.f32.bf16.bf16 {o0,o1,o2,o3,o4,o5,o6,o7,o8,o9,o10,o11,o12,o13,o14,o15}, {b28,b29,b30,b31}, d7, p1, 1, 1, 1;\n"
        "wgmma.mma_async.sync.aligned.m64n32k16.f32.bf16.bf16 {o16,o17,o18,o19,o20,o21,o22,o23,o24,o25,o26,o27,o28,o29,o30,o31}, {b28,b29,b30,b31}, d15, p1, 1, 1, 1;\n"
        "wgmma.commit_group.sync.aligned;\n@nv bra.uni END;\n@s2 st.global.v4.b32 [%67+0], {k0,k1,k2,k3};\n@s3 st.global.v4.b32 [%68+0], {k4,k5,k6,k7};\n"
        "@s2 st.global.v4.b32 [%67+64], {k8,k9,k10,k11};\n@s3 st.global.v4.b32 [%68+64], {k12,k13,k14,k15};\n@nv bra.uni END;\nwgmma.wait_group.sync.aligned 0;\n"
        "cvt.rn.bf16x2.f32 k0, o1, o0;\ncvt.rn.bf16x2.f32 k1, o5, o4;\ncvt.rn.bf16x2.f32 k2, o9, o8;\ncvt.rn.bf16x2.f32 k3, o13, o12;\n"
        "cvt.rn.bf16x2.f32 k4, o3, o2;\ncvt.rn.bf16x2.f32 k5, o7, o6;\ncvt.rn.bf16x2.f32 k6, o11, o10;\ncvt.rn.bf16x2.f32 k7, o15, o14;\n"
        "cvt.rn.bf16x2.f32 k8, o17, o16;\ncvt.rn.bf16x2.f32 k9, o21, o20;\ncvt.rn.bf16x2.f32 k10, o25, o24;\ncvt.rn.bf16x2.f32 k11, o29, o28;\n"
        "cvt.rn.bf16x2.f32 k12, o19, o18;\ncvt.rn.bf16x2.f32 k13, o23, o22;\ncvt.rn.bf16x2.f32 k14, o27, o26;\ncvt.rn.bf16x2.f32 k15, o31, o30;\n"
        "@s2 st.global.v4.b32 [%67+128], {k0,k1,k2,k3};\n@s3 st.global.v4.b32 [%68+128], {k4,k5,k6,k7};\n@s2 st.global.v4.b32 [%67+192], {k8,k9,k10,k11};\n"
        "@s3 st.global.v4.b32 [%68+192], {k12,k13,k14,k15};\n"
        "END:\n}\n"
        ::"r"(pk[0]), "r"(pk[1]), "r"(pk[2]), "r"(pk[3]), "r"(pk[4]), "r"(pk[5]), "r"(pk[6]), "r"(pk[7]), "r"(pk[8]), "r"(pk[9]), "r"(pk[10]),
          "r"(pk[11]), "r"(pk[12]), "r"(pk[13]), "r"(pk[14]), "r"(pk[15]), "r"(pk[16]), "r"(pk[17]), "r"(pk[18]), "r"(pk[19]), "r"(pk[20]),
          "r"(pk[21]), "r"(pk[22]), "r"(pk[23]), "r"(pk[24]), "r"(pk[25]), "r"(pk[26]), "r"(pk[27]), "r"(pk[28]), "r"(pk[29]), "r"(pk[30]),
          "r"(pk[31]), "r"(pk[32]), "r"(pk[33]), "r"(pk[34]), "r"(pk[35]), "r"(pk[36]), "r"(pk[37]), "r"(pk[38]), "r"(pk[39]), "r"(pk[40]),
          "r"(pk[41]), "r"(pk[42]), "r"(pk[43]), "r"(pk[44]), "r"(pk[45]), "r"(pk[46]), "r"(pk[47]), "r"(pk[48]), "r"(pk[49]), "r"(pk[50]),
          "r"(pk[51]), "r"(pk[52]), "r"(pk[53]), "r"(pk[54]), "r"(pk[55]), "r"(pk[56]), "r"(pk[57]), "r"(pk[58]), "r"(pk[59]), "r"(pk[60]),
          "r"(pk[61]), "r"(pk[62]), "r"(pk[63]), "r"(ra), "l"(p[0]), "l"(p[1]), "l"(p[2]), "l"(p[3]), "r"(v[0]), "r"(v[1]), "r"(v[2]), "r"(v[3]),
          "r"(ba)
        : "memory");
}
__device__ __forceinline__ void project3(const uint32_t (&pk)[48], uint32_t ra, uint32_t ba, uint4* const (&p)[3], const uint32_t (&v)[3]) {
    asm volatile(
        "{\n.reg .pred p0, p1, q0, q1, nv, s<4>;\n.reg .b32 t, h, c<16>, a<32>, b<32>, k<16>;\n.reg .b64 d<16>;\n.reg .f32 o<32>;\nsetp.ne.b32 p0, 0, 0;\n"
        "setp.eq.b32 p1, 0, 0;\nmov.b32 h, 8;\nsetp.eq.u32 nv, %48, 0;\nvote.sync.any.pred nv, nv, 0xffffffff;\nsetp.ne.b32 s0, %52, 0;\n"
        "setp.ne.b32 s1, %53, 0;\nsetp.ne.b32 s2, %54, 0;\nmov.b32 t, 0;\n"
        "W0:\nmbarrier.try_wait.parity.shared.b64 q0, [%55], 0;\nvote.sync.all.pred q0, q0, 0xffffffff;\nadd.u32 t, t, 1;\nsetp.lt.and.u32 q1, t, 1000000, !q0;\n"
        "@q1 bra.uni W0;\nld.volatile.shared.v4.b32 {c0,c1,c2,c3}, [%48+0];\nld.volatile.shared.v4.b32 {c4,c5,c6,c7}, [%48+8192];\n"
        "ld.volatile.shared.v4.b32 {c8,c9,c10,c11}, [%48+16];\nld.volatile.shared.v4.b32 {c12,c13,c14,c15}, [%48+8208];\nand.b32 t, c0, 0xffe;\n"
        "mad.lo.u32 t, t, 4, 0x200000;\nmov.b64 d0, {t, h};\nand.b32 t, c1, 0xffe;\nmad.lo.u32 t, t, 4, 0x200000;\nmov.b64 d1, {t, h};\nand.b32 t, c2, 0xffe;\n"
        "mad.lo.u32 t, t, 4, 0x200000;\nmov.b64 d2, {t, h};\nand.b32 t, c3, 0xffe;\nmad.lo.u32 t, t, 4, 0x200000;\nmov.b64 d3, {t, h};\nand.b32 t, c4, 0xffe;\n"
        "mad.lo.u32 t, t, 4, 0x200000;\nmov.b64 d4, {t, h};\nand.b32 t, c5, 0xffe;\nmad.lo.u32 t, t, 4, 0x200000;\nmov.b64 d5, {t, h};\nand.b32 t, c6, 0xffe;\n"
        "mad.lo.u32 t, t, 4, 0x200000;\nmov.b64 d6, {t, h};\nand.b32 t, c7, 0xffe;\nmad.lo.u32 t, t, 4, 0x200000;\nmov.b64 d7, {t, h};\nand.b32 t, c8, 0xffe;\n"
        "mad.lo.u32 t, t, 4, 0x200000;\nmov.b64 d8, {t, h};\nand.b32 t, c9, 0xffe;\nmad.lo.u32 t, t, 4, 0x200000;\nmov.b64 d9, {t, h};\nand.b32 t, c10, 0xffe;\n"
        "mad.lo.u32 t, t, 4, 0x200000;\nmov.b64 d10, {t, h};\nand.b32 t, c11, 0xffe;\nmad.lo.u32 t, t, 4, 0x200000;\nmov.b64 d11, {t, h};\n"
        "and.b32 t, c12, 0xffe;\nmad.lo.u32 t, t, 4, 0x200000;\nmov.b64 d12, {t, h};\nand.b32 t, c13, 0xffe;\nmad.lo.u32 t, t, 4, 0x200000;\n"
        "mov.b64 d13, {t, h};\nand.b32 t, c14, 0xffe;\nmad.lo.u32 t, t, 4, 0x200000;\nmov.b64 d14, {t, h};\nand.b32 t, c15, 0xffe;\n"
        "mad.lo.u32 t, t, 4, 0x200000;\nmov.b64 d15, {t, h};\nmovmatrix.sync.aligned.m8n8.trans.b16 a0, %0;\nmovmatrix.sync.aligned.m8n8.trans.b16 a1, %16;\n"
        "movmatrix.sync.aligned.m8n8.trans.b16 a2, %1;\nmovmatrix.sync.aligned.m8n8.trans.b16 a3, %17;\nmovmatrix.sync.aligned.m8n8.trans.b16 a4, %2;\n"
        "movmatrix.sync.aligned.m8n8.trans.b16 a5, %18;\nmovmatrix.sync.aligned.m8n8.trans.b16 a6, %3;\nmovmatrix.sync.aligned.m8n8.trans.b16 a7, %19;\n"
        "movmatrix.sync.aligned.m8n8.trans.b16 a8, %4;\nmovmatrix.sync.aligned.m8n8.trans.b16 a9, %20;\nmovmatrix.sync.aligned.m8n8.trans.b16 a10, %5;\n"
        "movmatrix.sync.aligned.m8n8.trans.b16 a11, %21;\nmovmatrix.sync.aligned.m8n8.trans.b16 a12, %6;\nmovmatrix.sync.aligned.m8n8.trans.b16 a13, %22;\n"
        "movmatrix.sync.aligned.m8n8.trans.b16 a14, %7;\nmovmatrix.sync.aligned.m8n8.trans.b16 a15, %23;\nmovmatrix.sync.aligned.m8n8.trans.b16 a16, %8;\n"
        "movmatrix.sync.aligned.m8n8.trans.b16 a17, %24;\nmovmatrix.sync.aligned.m8n8.trans.b16 a18, %9;\nmovmatrix.sync.aligned.m8n8.trans.b16 a19, %25;\n"
        "movmatrix.sync.aligned.m8n8.trans.b16 a20, %10;\nmovmatrix.sync.aligned.m8n8.trans.b16 a21, %26;\nmovmatrix.sync.aligned.m8n8.trans.b16 a22, %11;\n"
        "movmatrix.sync.aligned.m8n8.trans.b16 a23, %27;\nmovmatrix.sync.aligned.m8n8.trans.b16 a24, %12;\nmovmatrix.sync.aligned.m8n8.trans.b16 a25, %28;\n"
        "movmatrix.sync.aligned.m8n8.trans.b16 a26, %13;\nmovmatrix.sync.aligned.m8n8.trans.b16 a27, %29;\nmovmatrix.sync.aligned.m8n8.trans.b16 a28, %14;\n"
        "movmatrix.sync.aligned.m8n8.trans.b16 a29, %30;\nmovmatrix.sync.aligned.m8n8.trans.b16 a30, %15;\nmovmatrix.sync.aligned.m8n8.trans.b16 a31, %31;\n"
        "wgmma.fence.sync.aligned;\n"
        "wgmma.mma_async.sync.aligned.m64n32k16.f32.bf16.bf16 {o0,o1,o2,o3,o4,o5,o6,o7,o8,o9,o10,o11,o12,o13,o14,o15}, {a0,a1,a2,a3}, d0, p0, 1, 1, 1;\n"
        "wgmma.mma_async.sync.aligned.m64n32k16.f32.bf16.bf16 {o0,o1,o2,o3,o4,o5,o6,o7,o8,o9,o10,o11,o12,o13,o14,o15}, {a4,a5,a6,a7}, d1, p1, 1, 1, 1;\n"
        "wgmma.mma_async.sync.aligned.m64n32k16.f32.bf16.bf16 {o0,o1,o2,o3,o4,o5,o6,o7,o8,o9,o10,o11,o12,o13,o14,o15}, {a8,a9,a10,a11}, d2, p1, 1, 1, 1;\n"
        "wgmma.mma_async.sync.aligned.m64n32k16.f32.bf16.bf16 {o0,o1,o2,o3,o4,o5,o6,o7,o8,o9,o10,o11,o12,o13,o14,o15}, {a12,a13,a14,a15}, d3, p1, 1, 1, 1;\n"
        "wgmma.mma_async.sync.aligned.m64n32k16.f32.bf16.bf16 {o0,o1,o2,o3,o4,o5,o6,o7,o8,o9,o10,o11,o12,o13,o14,o15}, {a16,a17,a18,a19}, d4, p1, 1, 1, 1;\n"
        "wgmma.mma_async.sync.aligned.m64n32k16.f32.bf16.bf16 {o0,o1,o2,o3,o4,o5,o6,o7,o8,o9,o10,o11,o12,o13,o14,o15}, {a20,a21,a22,a23}, d5, p1, 1, 1, 1;\n"
        "wgmma.mma_async.sync.aligned.m64n32k16.f32.bf16.bf16 {o0,o1,o2,o3,o4,o5,o6,o7,o8,o9,o10,o11,o12,o13,o14,o15}, {a24,a25,a26,a27}, d6, p1, 1, 1, 1;\n"
        "wgmma.mma_async.sync.aligned.m64n32k16.f32.bf16.bf16 {o0,o1,o2,o3,o4,o5,o6,o7,o8,o9,o10,o11,o12,o13,o14,o15}, {a28,a29,a30,a31}, d7, p1, 1, 1, 1;\n"
        "wgmma.commit_group.sync.aligned;\n"
        "wgmma.mma_async.sync.aligned.m64n32k16.f32.bf16.bf16 {o16,o17,o18,o19,o20,o21,o22,o23,o24,o25,o26,o27,o28,o29,o30,o31}, {a0,a1,a2,a3}, d8, p0, 1, 1, 1;\n"
        "wgmma.mma_async.sync.aligned.m64n32k16.f32.bf16.bf16 {o16,o17,o18,o19,o20,o21,o22,o23,o24,o25,o26,o27,o28,o29,o30,o31}, {a4,a5,a6,a7}, d9, p1, 1, 1, 1;\n"
        "wgmma.mma_async.sync.aligned.m64n32k16.f32.bf16.bf16 {o16,o17,o18,o19,o20,o21,o22,o23,o24,o25,o26,o27,o28,o29,o30,o31}, {a8,a9,a10,a11}, d10, p1, 1, 1, 1;\n"
        "wgmma.mma_async.sync.aligned.m64n32k16.f32.bf16.bf16 {o16,o17,o18,o19,o20,o21,o22,o23,o24,o25,o26,o27,o28,o29,o30,o31}, {a12,a13,a14,a15}, d11, p1, 1, 1, 1;\n"
        "wgmma.mma_async.sync.aligned.m64n32k16.f32.bf16.bf16 {o16,o17,o18,o19,o20,o21,o22,o23,o24,o25,o26,o27,o28,o29,o30,o31}, {a16,a17,a18,a19}, d12, p1, 1, 1, 1;\n"
        "wgmma.mma_async.sync.aligned.m64n32k16.f32.bf16.bf16 {o16,o17,o18,o19,o20,o21,o22,o23,o24,o25,o26,o27,o28,o29,o30,o31}, {a20,a21,a22,a23}, d13, p1, 1, 1, 1;\n"
        "wgmma.mma_async.sync.aligned.m64n32k16.f32.bf16.bf16 {o16,o17,o18,o19,o20,o21,o22,o23,o24,o25,o26,o27,o28,o29,o30,o31}, {a24,a25,a26,a27}, d14, p1, 1, 1, 1;\n"
        "wgmma.mma_async.sync.aligned.m64n32k16.f32.bf16.bf16 {o16,o17,o18,o19,o20,o21,o22,o23,o24,o25,o26,o27,o28,o29,o30,o31}, {a28,a29,a30,a31}, d15, p1, 1, 1, 1;\n"
        "wgmma.commit_group.sync.aligned;\nwgmma.wait_group.sync.aligned 1;\ncvt.rn.bf16x2.f32 k0, o1, o0;\ncvt.rn.bf16x2.f32 k1, o5, o4;\n"
        "cvt.rn.bf16x2.f32 k2, o9, o8;\ncvt.rn.bf16x2.f32 k3, o13, o12;\n@s0 st.global.v4.b32 [%49+0], {k0,k1,k2,k3};\ncvt.rn.bf16x2.f32 k4, o3, o2;\n"
        "cvt.rn.bf16x2.f32 k5, o7, o6;\ncvt.rn.bf16x2.f32 k6, o11, o10;\ncvt.rn.bf16x2.f32 k7, o15, o14;\n@s1 st.global.v4.b32 [%50+0], {k4,k5,k6,k7};\n"
        "@nv bra.uni END;\nwgmma.wait_group.sync.aligned 0;\ncvt.rn.bf16x2.f32 k8, o17, o16;\ncvt.rn.bf16x2.f32 k9, o21, o20;\ncvt.rn.bf16x2.f32 k10, o25, o24;\n"
        "cvt.rn.bf16x2.f32 k11, o29, o28;\n@s0 st.global.v4.b32 [%49+64], {k8,k9,k10,k11};\ncvt.rn.bf16x2.f32 k12, o19, o18;\ncvt.rn.bf16x2.f32 k13, o23, o22;\n"
        "cvt.rn.bf16x2.f32 k14, o27, o26;\ncvt.rn.bf16x2.f32 k15, o31, o30;\n@s1 st.global.v4.b32 [%50+64], {k12,k13,k14,k15};\n@nv bra.uni END;\n"
        "ld.volatile.shared.v4.b32 {c0,c1,c2,c3}, [%48+32];\nld.volatile.shared.v4.b32 {c4,c5,c6,c7}, [%48+8224];\n"
        "ld.volatile.shared.v4.b32 {c8,c9,c10,c11}, [%48+48];\nld.volatile.shared.v4.b32 {c12,c13,c14,c15}, [%48+8240];\nand.b32 t, c0, 0xffe;\n"
        "mad.lo.u32 t, t, 4, 0x200000;\nmov.b64 d0, {t, h};\nand.b32 t, c1, 0xffe;\nmad.lo.u32 t, t, 4, 0x200000;\nmov.b64 d1, {t, h};\nand.b32 t, c2, 0xffe;\n"
        "mad.lo.u32 t, t, 4, 0x200000;\nmov.b64 d2, {t, h};\nand.b32 t, c3, 0xffe;\nmad.lo.u32 t, t, 4, 0x200000;\nmov.b64 d3, {t, h};\nand.b32 t, c4, 0xffe;\n"
        "mad.lo.u32 t, t, 4, 0x200000;\nmov.b64 d4, {t, h};\nand.b32 t, c5, 0xffe;\nmad.lo.u32 t, t, 4, 0x200000;\nmov.b64 d5, {t, h};\nand.b32 t, c6, 0xffe;\n"
        "mad.lo.u32 t, t, 4, 0x200000;\nmov.b64 d6, {t, h};\nand.b32 t, c7, 0xffe;\nmad.lo.u32 t, t, 4, 0x200000;\nmov.b64 d7, {t, h};\nand.b32 t, c8, 0xffe;\n"
        "mad.lo.u32 t, t, 4, 0x200000;\nmov.b64 d8, {t, h};\nand.b32 t, c9, 0xffe;\nmad.lo.u32 t, t, 4, 0x200000;\nmov.b64 d9, {t, h};\nand.b32 t, c10, 0xffe;\n"
        "mad.lo.u32 t, t, 4, 0x200000;\nmov.b64 d10, {t, h};\nand.b32 t, c11, 0xffe;\nmad.lo.u32 t, t, 4, 0x200000;\nmov.b64 d11, {t, h};\n"
        "and.b32 t, c12, 0xffe;\nmad.lo.u32 t, t, 4, 0x200000;\nmov.b64 d12, {t, h};\nand.b32 t, c13, 0xffe;\nmad.lo.u32 t, t, 4, 0x200000;\n"
        "mov.b64 d13, {t, h};\nand.b32 t, c14, 0xffe;\nmad.lo.u32 t, t, 4, 0x200000;\nmov.b64 d14, {t, h};\nand.b32 t, c15, 0xffe;\n"
        "mad.lo.u32 t, t, 4, 0x200000;\nmov.b64 d15, {t, h};\nwgmma.fence.sync.aligned;\n"
        "wgmma.mma_async.sync.aligned.m64n32k16.f32.bf16.bf16 {o0,o1,o2,o3,o4,o5,o6,o7,o8,o9,o10,o11,o12,o13,o14,o15}, {a0,a1,a2,a3}, d0, p0, 1, 1, 1;\n"
        "wgmma.mma_async.sync.aligned.m64n32k16.f32.bf16.bf16 {o16,o17,o18,o19,o20,o21,o22,o23,o24,o25,o26,o27,o28,o29,o30,o31}, {a0,a1,a2,a3}, d8, p0, 1, 1, 1;\n"
        "wgmma.mma_async.sync.aligned.m64n32k16.f32.bf16.bf16 {o0,o1,o2,o3,o4,o5,o6,o7,o8,o9,o10,o11,o12,o13,o14,o15}, {a4,a5,a6,a7}, d1, p1, 1, 1, 1;\n"
        "wgmma.mma_async.sync.aligned.m64n32k16.f32.bf16.bf16 {o16,o17,o18,o19,o20,o21,o22,o23,o24,o25,o26,o27,o28,o29,o30,o31}, {a4,a5,a6,a7}, d9, p1, 1, 1, 1;\n"
        "wgmma.mma_async.sync.aligned.m64n32k16.f32.bf16.bf16 {o0,o1,o2,o3,o4,o5,o6,o7,o8,o9,o10,o11,o12,o13,o14,o15}, {a8,a9,a10,a11}, d2, p1, 1, 1, 1;\n"
        "wgmma.mma_async.sync.aligned.m64n32k16.f32.bf16.bf16 {o16,o17,o18,o19,o20,o21,o22,o23,o24,o25,o26,o27,o28,o29,o30,o31}, {a8,a9,a10,a11}, d10, p1, 1, 1, 1;\n"
        "wgmma.mma_async.sync.aligned.m64n32k16.f32.bf16.bf16 {o0,o1,o2,o3,o4,o5,o6,o7,o8,o9,o10,o11,o12,o13,o14,o15}, {a12,a13,a14,a15}, d3, p1, 1, 1, 1;\n"
        "wgmma.mma_async.sync.aligned.m64n32k16.f32.bf16.bf16 {o16,o17,o18,o19,o20,o21,o22,o23,o24,o25,o26,o27,o28,o29,o30,o31}, {a12,a13,a14,a15}, d11, p1, 1, 1, 1;\n"
        "wgmma.mma_async.sync.aligned.m64n32k16.f32.bf16.bf16 {o0,o1,o2,o3,o4,o5,o6,o7,o8,o9,o10,o11,o12,o13,o14,o15}, {a16,a17,a18,a19}, d4, p1, 1, 1, 1;\n"
        "wgmma.mma_async.sync.aligned.m64n32k16.f32.bf16.bf16 {o16,o17,o18,o19,o20,o21,o22,o23,o24,o25,o26,o27,o28,o29,o30,o31}, {a16,a17,a18,a19}, d12, p1, 1, 1, 1;\n"
        "wgmma.mma_async.sync.aligned.m64n32k16.f32.bf16.bf16 {o0,o1,o2,o3,o4,o5,o6,o7,o8,o9,o10,o11,o12,o13,o14,o15}, {a20,a21,a22,a23}, d5, p1, 1, 1, 1;\n"
        "wgmma.mma_async.sync.aligned.m64n32k16.f32.bf16.bf16 {o16,o17,o18,o19,o20,o21,o22,o23,o24,o25,o26,o27,o28,o29,o30,o31}, {a20,a21,a22,a23}, d13, p1, 1, 1, 1;\n"
        "wgmma.mma_async.sync.aligned.m64n32k16.f32.bf16.bf16 {o0,o1,o2,o3,o4,o5,o6,o7,o8,o9,o10,o11,o12,o13,o14,o15}, {a24,a25,a26,a27}, d6, p1, 1, 1, 1;\n"
        "wgmma.mma_async.sync.aligned.m64n32k16.f32.bf16.bf16 {o16,o17,o18,o19,o20,o21,o22,o23,o24,o25,o26,o27,o28,o29,o30,o31}, {a24,a25,a26,a27}, d14, p1, 1, 1, 1;\n"
        "wgmma.mma_async.sync.aligned.m64n32k16.f32.bf16.bf16 {o0,o1,o2,o3,o4,o5,o6,o7,o8,o9,o10,o11,o12,o13,o14,o15}, {a28,a29,a30,a31}, d7, p1, 1, 1, 1;\n"
        "wgmma.mma_async.sync.aligned.m64n32k16.f32.bf16.bf16 {o16,o17,o18,o19,o20,o21,o22,o23,o24,o25,o26,o27,o28,o29,o30,o31}, {a28,a29,a30,a31}, d15, p1, 1, 1, 1;\n"
        "wgmma.commit_group.sync.aligned;\n@nv bra.uni END;\nmovmatrix.sync.aligned.m8n8.trans.b16 b0, %32;\nmovmatrix.sync.aligned.m8n8.trans.b16 b1, %32;\n"
        "movmatrix.sync.aligned.m8n8.trans.b16 b2, %33;\nmovmatrix.sync.aligned.m8n8.trans.b16 b3, %33;\nmovmatrix.sync.aligned.m8n8.trans.b16 b4, %34;\n"
        "movmatrix.sync.aligned.m8n8.trans.b16 b5, %34;\nmovmatrix.sync.aligned.m8n8.trans.b16 b6, %35;\nmovmatrix.sync.aligned.m8n8.trans.b16 b7, %35;\n"
        "movmatrix.sync.aligned.m8n8.trans.b16 b8, %36;\nmovmatrix.sync.aligned.m8n8.trans.b16 b9, %36;\nmovmatrix.sync.aligned.m8n8.trans.b16 b10, %37;\n"
        "movmatrix.sync.aligned.m8n8.trans.b16 b11, %37;\nmovmatrix.sync.aligned.m8n8.trans.b16 b12, %38;\nmovmatrix.sync.aligned.m8n8.trans.b16 b13, %38;\n"
        "movmatrix.sync.aligned.m8n8.trans.b16 b14, %39;\nmovmatrix.sync.aligned.m8n8.trans.b16 b15, %39;\nmovmatrix.sync.aligned.m8n8.trans.b16 b16, %40;\n"
        "movmatrix.sync.aligned.m8n8.trans.b16 b17, %40;\nmovmatrix.sync.aligned.m8n8.trans.b16 b18, %41;\nmovmatrix.sync.aligned.m8n8.trans.b16 b19, %41;\n"
        "movmatrix.sync.aligned.m8n8.trans.b16 b20, %42;\nmovmatrix.sync.aligned.m8n8.trans.b16 b21, %42;\nmovmatrix.sync.aligned.m8n8.trans.b16 b22, %43;\n"
        "movmatrix.sync.aligned.m8n8.trans.b16 b23, %43;\nmovmatrix.sync.aligned.m8n8.trans.b16 b24, %44;\nmovmatrix.sync.aligned.m8n8.trans.b16 b25, %44;\n"
        "movmatrix.sync.aligned.m8n8.trans.b16 b26, %45;\nmovmatrix.sync.aligned.m8n8.trans.b16 b27, %45;\nmovmatrix.sync.aligned.m8n8.trans.b16 b28, %46;\n"
        "movmatrix.sync.aligned.m8n8.trans.b16 b29, %46;\nmovmatrix.sync.aligned.m8n8.trans.b16 b30, %47;\nmovmatrix.sync.aligned.m8n8.trans.b16 b31, %47;\n"
        "@nv bra.uni END;\nwgmma.wait_group.sync.aligned 0;\ncvt.rn.bf16x2.f32 k0, o1, o0;\ncvt.rn.bf16x2.f32 k1, o5, o4;\ncvt.rn.bf16x2.f32 k2, o9, o8;\n"
        "cvt.rn.bf16x2.f32 k3, o13, o12;\ncvt.rn.bf16x2.f32 k4, o3, o2;\ncvt.rn.bf16x2.f32 k5, o7, o6;\ncvt.rn.bf16x2.f32 k6, o11, o10;\n"
        "cvt.rn.bf16x2.f32 k7, o15, o14;\ncvt.rn.bf16x2.f32 k8, o17, o16;\ncvt.rn.bf16x2.f32 k9, o21, o20;\ncvt.rn.bf16x2.f32 k10, o25, o24;\n"
        "cvt.rn.bf16x2.f32 k11, o29, o28;\ncvt.rn.bf16x2.f32 k12, o19, o18;\ncvt.rn.bf16x2.f32 k13, o23, o22;\ncvt.rn.bf16x2.f32 k14, o27, o26;\n"
        "cvt.rn.bf16x2.f32 k15, o31, o30;\nld.volatile.shared.v4.b32 {c0,c1,c2,c3}, [%48+0];\nld.volatile.shared.v4.b32 {c4,c5,c6,c7}, [%48+8192];\n"
        "ld.volatile.shared.v4.b32 {c8,c9,c10,c11}, [%48+16];\nld.volatile.shared.v4.b32 {c12,c13,c14,c15}, [%48+8208];\nand.b32 t, c0, 0xffe;\n"
        "mad.lo.u32 t, t, 4, 0x200000;\nmov.b64 d0, {t, h};\nand.b32 t, c1, 0xffe;\nmad.lo.u32 t, t, 4, 0x200000;\nmov.b64 d1, {t, h};\nand.b32 t, c2, 0xffe;\n"
        "mad.lo.u32 t, t, 4, 0x200000;\nmov.b64 d2, {t, h};\nand.b32 t, c3, 0xffe;\nmad.lo.u32 t, t, 4, 0x200000;\nmov.b64 d3, {t, h};\nand.b32 t, c4, 0xffe;\n"
        "mad.lo.u32 t, t, 4, 0x200000;\nmov.b64 d4, {t, h};\nand.b32 t, c5, 0xffe;\nmad.lo.u32 t, t, 4, 0x200000;\nmov.b64 d5, {t, h};\nand.b32 t, c6, 0xffe;\n"
        "mad.lo.u32 t, t, 4, 0x200000;\nmov.b64 d6, {t, h};\nand.b32 t, c7, 0xffe;\nmad.lo.u32 t, t, 4, 0x200000;\nmov.b64 d7, {t, h};\nand.b32 t, c8, 0xffe;\n"
        "mad.lo.u32 t, t, 4, 0x200000;\nmov.b64 d8, {t, h};\nand.b32 t, c9, 0xffe;\nmad.lo.u32 t, t, 4, 0x200000;\nmov.b64 d9, {t, h};\nand.b32 t, c10, 0xffe;\n"
        "mad.lo.u32 t, t, 4, 0x200000;\nmov.b64 d10, {t, h};\nand.b32 t, c11, 0xffe;\nmad.lo.u32 t, t, 4, 0x200000;\nmov.b64 d11, {t, h};\n"
        "and.b32 t, c12, 0xffe;\nmad.lo.u32 t, t, 4, 0x200000;\nmov.b64 d12, {t, h};\nand.b32 t, c13, 0xffe;\nmad.lo.u32 t, t, 4, 0x200000;\n"
        "mov.b64 d13, {t, h};\nand.b32 t, c14, 0xffe;\nmad.lo.u32 t, t, 4, 0x200000;\nmov.b64 d14, {t, h};\nand.b32 t, c15, 0xffe;\n"
        "mad.lo.u32 t, t, 4, 0x200000;\nmov.b64 d15, {t, h};\nwgmma.fence.sync.aligned;\n"
        "wgmma.mma_async.sync.aligned.m64n32k16.f32.bf16.bf16 {o0,o1,o2,o3,o4,o5,o6,o7,o8,o9,o10,o11,o12,o13,o14,o15}, {b0,b1,b2,b3}, d0, p0, 1, 1, 1;\n"
        "wgmma.mma_async.sync.aligned.m64n32k16.f32.bf16.bf16 {o16,o17,o18,o19,o20,o21,o22,o23,o24,o25,o26,o27,o28,o29,o30,o31}, {b0,b1,b2,b3}, d8, p0, 1, 1, 1;\n"
        "wgmma.mma_async.sync.aligned.m64n32k16.f32.bf16.bf16 {o0,o1,o2,o3,o4,o5,o6,o7,o8,o9,o10,o11,o12,o13,o14,o15}, {b4,b5,b6,b7}, d1, p1, 1, 1, 1;\n"
        "wgmma.mma_async.sync.aligned.m64n32k16.f32.bf16.bf16 {o16,o17,o18,o19,o20,o21,o22,o23,o24,o25,o26,o27,o28,o29,o30,o31}, {b4,b5,b6,b7}, d9, p1, 1, 1, 1;\n"
        "wgmma.mma_async.sync.aligned.m64n32k16.f32.bf16.bf16 {o0,o1,o2,o3,o4,o5,o6,o7,o8,o9,o10,o11,o12,o13,o14,o15}, {b8,b9,b10,b11}, d2, p1, 1, 1, 1;\n"
        "wgmma.mma_async.sync.aligned.m64n32k16.f32.bf16.bf16 {o16,o17,o18,o19,o20,o21,o22,o23,o24,o25,o26,o27,o28,o29,o30,o31}, {b8,b9,b10,b11}, d10, p1, 1, 1, 1;\n"
        "wgmma.mma_async.sync.aligned.m64n32k16.f32.bf16.bf16 {o0,o1,o2,o3,o4,o5,o6,o7,o8,o9,o10,o11,o12,o13,o14,o15}, {b12,b13,b14,b15}, d3, p1, 1, 1, 1;\n"
        "wgmma.mma_async.sync.aligned.m64n32k16.f32.bf16.bf16 {o16,o17,o18,o19,o20,o21,o22,o23,o24,o25,o26,o27,o28,o29,o30,o31}, {b12,b13,b14,b15}, d11, p1, 1, 1, 1;\n"
        "wgmma.mma_async.sync.aligned.m64n32k16.f32.bf16.bf16 {o0,o1,o2,o3,o4,o5,o6,o7,o8,o9,o10,o11,o12,o13,o14,o15}, {b16,b17,b18,b19}, d4, p1, 1, 1, 1;\n"
        "wgmma.mma_async.sync.aligned.m64n32k16.f32.bf16.bf16 {o16,o17,o18,o19,o20,o21,o22,o23,o24,o25,o26,o27,o28,o29,o30,o31}, {b16,b17,b18,b19}, d12, p1, 1, 1, 1;\n"
        "wgmma.mma_async.sync.aligned.m64n32k16.f32.bf16.bf16 {o0,o1,o2,o3,o4,o5,o6,o7,o8,o9,o10,o11,o12,o13,o14,o15}, {b20,b21,b22,b23}, d5, p1, 1, 1, 1;\n"
        "wgmma.mma_async.sync.aligned.m64n32k16.f32.bf16.bf16 {o16,o17,o18,o19,o20,o21,o22,o23,o24,o25,o26,o27,o28,o29,o30,o31}, {b20,b21,b22,b23}, d13, p1, 1, 1, 1;\n"
        "wgmma.mma_async.sync.aligned.m64n32k16.f32.bf16.bf16 {o0,o1,o2,o3,o4,o5,o6,o7,o8,o9,o10,o11,o12,o13,o14,o15}, {b24,b25,b26,b27}, d6, p1, 1, 1, 1;\n"
        "wgmma.mma_async.sync.aligned.m64n32k16.f32.bf16.bf16 {o16,o17,o18,o19,o20,o21,o22,o23,o24,o25,o26,o27,o28,o29,o30,o31}, {b24,b25,b26,b27}, d14, p1, 1, 1, 1;\n"
        "wgmma.mma_async.sync.aligned.m64n32k16.f32.bf16.bf16 {o0,o1,o2,o3,o4,o5,o6,o7,o8,o9,o10,o11,o12,o13,o14,o15}, {b28,b29,b30,b31}, d7, p1, 1, 1, 1;\n"
        "wgmma.mma_async.sync.aligned.m64n32k16.f32.bf16.bf16 {o16,o17,o18,o19,o20,o21,o22,o23,o24,o25,o26,o27,o28,o29,o30,o31}, {b28,b29,b30,b31}, d15, p1, 1, 1, 1;\n"
        "wgmma.commit_group.sync.aligned;\n@nv bra.uni END;\n@s0 st.global.v4.b32 [%49+128], {k0,k1,k2,k3};\n@s1 st.global.v4.b32 [%50+128], {k4,k5,k6,k7};\n"
        "@s0 st.global.v4.b32 [%49+192], {k8,k9,k10,k11};\n@s1 st.global.v4.b32 [%50+192], {k12,k13,k14,k15};\n@nv bra.uni END;\n"
        "wgmma.wait_group.sync.aligned 0;\ncvt.rn.bf16x2.f32 k0, o1, o0;\ncvt.rn.bf16x2.f32 k1, o5, o4;\ncvt.rn.bf16x2.f32 k2, o9, o8;\n"
        "cvt.rn.bf16x2.f32 k3, o13, o12;\ncvt.rn.bf16x2.f32 k8, o17, o16;\ncvt.rn.bf16x2.f32 k9, o21, o20;\ncvt.rn.bf16x2.f32 k10, o25, o24;\n"
        "cvt.rn.bf16x2.f32 k11, o29, o28;\nld.volatile.shared.v4.b32 {c0,c1,c2,c3}, [%48+32];\nld.volatile.shared.v4.b32 {c4,c5,c6,c7}, [%48+8224];\n"
        "ld.volatile.shared.v4.b32 {c8,c9,c10,c11}, [%48+48];\nld.volatile.shared.v4.b32 {c12,c13,c14,c15}, [%48+8240];\nand.b32 t, c0, 0xffe;\n"
        "mad.lo.u32 t, t, 4, 0x200000;\nmov.b64 d0, {t, h};\nand.b32 t, c1, 0xffe;\nmad.lo.u32 t, t, 4, 0x200000;\nmov.b64 d1, {t, h};\nand.b32 t, c2, 0xffe;\n"
        "mad.lo.u32 t, t, 4, 0x200000;\nmov.b64 d2, {t, h};\nand.b32 t, c3, 0xffe;\nmad.lo.u32 t, t, 4, 0x200000;\nmov.b64 d3, {t, h};\nand.b32 t, c4, 0xffe;\n"
        "mad.lo.u32 t, t, 4, 0x200000;\nmov.b64 d4, {t, h};\nand.b32 t, c5, 0xffe;\nmad.lo.u32 t, t, 4, 0x200000;\nmov.b64 d5, {t, h};\nand.b32 t, c6, 0xffe;\n"
        "mad.lo.u32 t, t, 4, 0x200000;\nmov.b64 d6, {t, h};\nand.b32 t, c7, 0xffe;\nmad.lo.u32 t, t, 4, 0x200000;\nmov.b64 d7, {t, h};\nand.b32 t, c8, 0xffe;\n"
        "mad.lo.u32 t, t, 4, 0x200000;\nmov.b64 d8, {t, h};\nand.b32 t, c9, 0xffe;\nmad.lo.u32 t, t, 4, 0x200000;\nmov.b64 d9, {t, h};\nand.b32 t, c10, 0xffe;\n"
        "mad.lo.u32 t, t, 4, 0x200000;\nmov.b64 d10, {t, h};\nand.b32 t, c11, 0xffe;\nmad.lo.u32 t, t, 4, 0x200000;\nmov.b64 d11, {t, h};\n"
        "and.b32 t, c12, 0xffe;\nmad.lo.u32 t, t, 4, 0x200000;\nmov.b64 d12, {t, h};\nand.b32 t, c13, 0xffe;\nmad.lo.u32 t, t, 4, 0x200000;\n"
        "mov.b64 d13, {t, h};\nand.b32 t, c14, 0xffe;\nmad.lo.u32 t, t, 4, 0x200000;\nmov.b64 d14, {t, h};\nand.b32 t, c15, 0xffe;\n"
        "mad.lo.u32 t, t, 4, 0x200000;\nmov.b64 d15, {t, h};\nwgmma.fence.sync.aligned;\n"
        "wgmma.mma_async.sync.aligned.m64n32k16.f32.bf16.bf16 {o0,o1,o2,o3,o4,o5,o6,o7,o8,o9,o10,o11,o12,o13,o14,o15}, {b0,b1,b2,b3}, d0, p0, 1, 1, 1;\n"
        "wgmma.mma_async.sync.aligned.m64n32k16.f32.bf16.bf16 {o16,o17,o18,o19,o20,o21,o22,o23,o24,o25,o26,o27,o28,o29,o30,o31}, {b0,b1,b2,b3}, d8, p0, 1, 1, 1;\n"
        "wgmma.mma_async.sync.aligned.m64n32k16.f32.bf16.bf16 {o0,o1,o2,o3,o4,o5,o6,o7,o8,o9,o10,o11,o12,o13,o14,o15}, {b4,b5,b6,b7}, d1, p1, 1, 1, 1;\n"
        "wgmma.mma_async.sync.aligned.m64n32k16.f32.bf16.bf16 {o16,o17,o18,o19,o20,o21,o22,o23,o24,o25,o26,o27,o28,o29,o30,o31}, {b4,b5,b6,b7}, d9, p1, 1, 1, 1;\n"
        "wgmma.mma_async.sync.aligned.m64n32k16.f32.bf16.bf16 {o0,o1,o2,o3,o4,o5,o6,o7,o8,o9,o10,o11,o12,o13,o14,o15}, {b8,b9,b10,b11}, d2, p1, 1, 1, 1;\n"
        "wgmma.mma_async.sync.aligned.m64n32k16.f32.bf16.bf16 {o16,o17,o18,o19,o20,o21,o22,o23,o24,o25,o26,o27,o28,o29,o30,o31}, {b8,b9,b10,b11}, d10, p1, 1, 1, 1;\n"
        "wgmma.mma_async.sync.aligned.m64n32k16.f32.bf16.bf16 {o0,o1,o2,o3,o4,o5,o6,o7,o8,o9,o10,o11,o12,o13,o14,o15}, {b12,b13,b14,b15}, d3, p1, 1, 1, 1;\n"
        "wgmma.mma_async.sync.aligned.m64n32k16.f32.bf16.bf16 {o16,o17,o18,o19,o20,o21,o22,o23,o24,o25,o26,o27,o28,o29,o30,o31}, {b12,b13,b14,b15}, d11, p1, 1, 1, 1;\n"
        "wgmma.mma_async.sync.aligned.m64n32k16.f32.bf16.bf16 {o0,o1,o2,o3,o4,o5,o6,o7,o8,o9,o10,o11,o12,o13,o14,o15}, {b16,b17,b18,b19}, d4, p1, 1, 1, 1;\n"
        "wgmma.mma_async.sync.aligned.m64n32k16.f32.bf16.bf16 {o16,o17,o18,o19,o20,o21,o22,o23,o24,o25,o26,o27,o28,o29,o30,o31}, {b16,b17,b18,b19}, d12, p1, 1, 1, 1;\n"
        "wgmma.mma_async.sync.aligned.m64n32k16.f32.bf16.bf16 {o0,o1,o2,o3,o4,o5,o6,o7,o8,o9,o10,o11,o12,o13,o14,o15}, {b20,b21,b22,b23}, d5, p1, 1, 1, 1;\n"
        "wgmma.mma_async.sync.aligned.m64n32k16.f32.bf16.bf16 {o16,o17,o18,o19,o20,o21,o22,o23,o24,o25,o26,o27,o28,o29,o30,o31}, {b20,b21,b22,b23}, d13, p1, 1, 1, 1;\n"
        "wgmma.mma_async.sync.aligned.m64n32k16.f32.bf16.bf16 {o0,o1,o2,o3,o4,o5,o6,o7,o8,o9,o10,o11,o12,o13,o14,o15}, {b24,b25,b26,b27}, d6, p1, 1, 1, 1;\n"
        "wgmma.mma_async.sync.aligned.m64n32k16.f32.bf16.bf16 {o16,o17,o18,o19,o20,o21,o22,o23,o24,o25,o26,o27,o28,o29,o30,o31}, {b24,b25,b26,b27}, d14, p1, 1, 1, 1;\n"
        "wgmma.mma_async.sync.aligned.m64n32k16.f32.bf16.bf16 {o0,o1,o2,o3,o4,o5,o6,o7,o8,o9,o10,o11,o12,o13,o14,o15}, {b28,b29,b30,b31}, d7, p1, 1, 1, 1;\n"
        "wgmma.mma_async.sync.aligned.m64n32k16.f32.bf16.bf16 {o16,o17,o18,o19,o20,o21,o22,o23,o24,o25,o26,o27,o28,o29,o30,o31}, {b28,b29,b30,b31}, d15, p1, 1, 1, 1;\n"
        "wgmma.commit_group.sync.aligned;\n@nv bra.uni END;\n@s2 st.global.v4.b32 [%51+0], {k0,k1,k2,k3};\n@s2 st.global.v4.b32 [%51+64], {k8,k9,k10,k11};\n"
        "@nv bra.uni END;\nwgmma.wait_group.sync.aligned 0;\ncvt.rn.bf16x2.f32 k0, o1, o0;\ncvt.rn.bf16x2.f32 k1, o5, o4;\ncvt.rn.bf16x2.f32 k2, o9, o8;\n"
        "cvt.rn.bf16x2.f32 k3, o13, o12;\ncvt.rn.bf16x2.f32 k8, o17, o16;\ncvt.rn.bf16x2.f32 k9, o21, o20;\ncvt.rn.bf16x2.f32 k10, o25, o24;\n"
        "cvt.rn.bf16x2.f32 k11, o29, o28;\n@s2 st.global.v4.b32 [%51+128], {k0,k1,k2,k3};\n@s2 st.global.v4.b32 [%51+192], {k8,k9,k10,k11};\n"
        "END:\n}\n"
        ::"r"(pk[0]), "r"(pk[1]), "r"(pk[2]), "r"(pk[3]), "r"(pk[4]), "r"(pk[5]), "r"(pk[6]), "r"(pk[7]), "r"(pk[8]), "r"(pk[9]), "r"(pk[10]),
          "r"(pk[11]), "r"(pk[12]), "r"(pk[13]), "r"(pk[14]), "r"(pk[15]), "r"(pk[16]), "r"(pk[17]), "r"(pk[18]), "r"(pk[19]), "r"(pk[20]),
          "r"(pk[21]), "r"(pk[22]), "r"(pk[23]), "r"(pk[24]), "r"(pk[25]), "r"(pk[26]), "r"(pk[27]), "r"(pk[28]), "r"(pk[29]), "r"(pk[30]),
          "r"(pk[31]), "r"(pk[32]), "r"(pk[33]), "r"(pk[34]), "r"(pk[35]), "r"(pk[36]), "r"(pk[37]), "r"(pk[38]), "r"(pk[39]), "r"(pk[40]),
          "r"(pk[41]), "r"(pk[42]), "r"(pk[43]), "r"(pk[44]), "r"(pk[45]), "r"(pk[46]), "r"(pk[47]), "r"(ra), "l"(p[0]), "l"(p[1]), "l"(p[2]),
          "r"(v[0]), "r"(v[1]), "r"(v[2]), "r"(ba)
        : "memory");
}
__device__ __forceinline__ int cta_id() {
    int v;
    asm volatile("mov.u32 %0, %ctaid.x;" : "=r"(v));
    return v;
}
__device__ __forceinline__ int thread_id() {
    int v;
    asm volatile("mov.u32 %0, %tid.x;" : "=r"(v));
    return v;
}

__device__ __forceinline__ void slow_edge(int ee, int s, float* accn, const __nv_bfloat16* __restrict__ x,
                                          const __nv_bfloat16* __restrict__ sh, const __nv_bfloat16* __restrict__ ea,
                                          const __nv_bfloat16* __restrict__ cg, const __nv_bfloat16* __restrict__ wr,
                                          int lane) {
    float rwv[4] = {0.f, 0.f, 0.f, 0.f};
#pragma unroll 4
    for (int d = 0; d < 16; d++) {
        const float a = __bfloat162float(ea[(size_t)ee * 16 + d]);
        const uint2 wv = *(const uint2*)(wr + d * 128 + lane * 4);
        rwv[0] += a * __uint_as_float(wv.x << 16);
        rwv[1] += a * __uint_as_float(wv.x & 0xffff0000u);
        rwv[2] += a * __uint_as_float(wv.y << 16);
        rwv[3] += a * __uint_as_float(wv.y & 0xffff0000u);
    }
    float A = 0.f;
#pragma unroll
    for (int v = 0; v < 4; v++)
        A += __bfloat162float(cg[((lane >> 2) & 3) * 16 + v * 4 + (lane & 3)]) * __bfloat162float(sh[(size_t)ee * 4 + v]);
    float m[4][4];
#pragma unroll
    for (int w = 0; w < 4; w++)
#pragma unroll
        for (int j = 0; j < 4; j++) m[w][j] = 0.f;
#pragma unroll
    for (int u = 0; u < 4; u++) {
        const uint2 xv = *(const uint2*)(x + (size_t)s * 512 + u * 128 + lane * 4);
        const float x0 = __uint_as_float(xv.x << 16), x1 = __uint_as_float(xv.x & 0xffff0000u);
        const float x2 = __uint_as_float(xv.y << 16), x3 = __uint_as_float(xv.y & 0xffff0000u);
#pragma unroll
        for (int w = 0; w < 4; w++) {
            const float a = __shfl_sync(0xffffffffu, A, u * 4 + w);
            m[w][0] += a * x0;
            m[w][1] += a * x1;
            m[w][2] += a * x2;
            m[w][3] += a * x3;
        }
    }
#pragma unroll
    for (int w = 0; w < 4; w++)
#pragma unroll
        for (int j = 0; j < 4; j++) atomicAdd(accn + w * 128 + lane * 4 + j, m[w][j] * rwv[j]);
}

__device__ __forceinline__ void slow_out(const float* accn, const __nv_bfloat16* __restrict__ wout,
                                         __nv_bfloat16* __restrict__ outn, int lane) {
    float o[4][4];
#pragma unroll
    for (int w = 0; w < 4; w++)
#pragma unroll
        for (int j = 0; j < 4; j++) o[w][j] = 0.f;
#pragma unroll 2
    for (int c = 0; c < 128; c++) {
        const uint2 wv = *(const uint2*)(wout + c * 128 + lane * 4);
        const float w0 = __uint_as_float(wv.x << 16), w1 = __uint_as_float(wv.x & 0xffff0000u);
        const float w2 = __uint_as_float(wv.y << 16), w3 = __uint_as_float(wv.y & 0xffff0000u);
#pragma unroll
        for (int w = 0; w < 4; w++) {
            const float a = __bfloat162float(__float2bfloat16(accn[w * 128 + c]));
            o[w][0] += a * w0;
            o[w][1] += a * w1;
            o[w][2] += a * w2;
            o[w][3] += a * w3;
        }
    }
#pragma unroll
    for (int w = 0; w < 4; w++)
        *(uint2*)(outn + w * 128 + lane * 4) = make_uint2(pack_bf16(o[w][0], o[w][1]), pack_bf16(o[w][2], o[w][3]));
}

__device__ __forceinline__ void consume4(uint32_t (&pk)[64], const uint32_t (&w)[36], uint32_t olp, uint32_t xa, uint32_t ln,
                                      uint32_t lc, uint32_t linc, uint32_t lt, const __nv_bfloat16* ea, const __nv_bfloat16* sh, const void* wf, uint4 first) {
    ea += lt * 4, sh += lt & 2;
    asm volatile(
        "{\n.reg .pred p, q, psw, prdy, ps1, ps2, ps3, pz, pq, pt;\n.reg .f32 d<32>, fz;\n"
        ".reg .b32 h<64>, x<32>, y<32>, ra<8>, rb<8>, bA0, bA1, bB0, bB1, c0, c1, c2, c3, e0, e1, s0, kept;\n"
        ".reg .b32 olp, v, vB, m, id, ida, bar, xb, pos, t0, t1, t2, t3, n, z<16>, kept2, g<4>, f0, f1, s1;\n.reg .b16 lo, hi, i16;\n.reg .b64 pa, pb;\n"
        "mov.f32 fz, 0f00000000;\nmov.b32 h0, 0;\nmov.b32 h1, 0;\nmov.b32 h2, 0;\nmov.b32 h3, 0;\nmov.b32 h4, 0;\nmov.b32 h5, 0;\nmov.b32 h6, 0;\n"
        "mov.b32 h7, 0;\nmov.b32 h8, 0;\nmov.b32 h9, 0;\nmov.b32 h10, 0;\nmov.b32 h11, 0;\nmov.b32 h12, 0;\nmov.b32 h13, 0;\nmov.b32 h14, 0;\nmov.b32 h15, 0;\n"
        "mov.b32 h16, 0;\nmov.b32 h17, 0;\nmov.b32 h18, 0;\nmov.b32 h19, 0;\nmov.b32 h20, 0;\nmov.b32 h21, 0;\nmov.b32 h22, 0;\nmov.b32 h23, 0;\n"
        "mov.b32 h24, 0;\nmov.b32 h25, 0;\nmov.b32 h26, 0;\nmov.b32 h27, 0;\nmov.b32 h28, 0;\nmov.b32 h29, 0;\nmov.b32 h30, 0;\nmov.b32 h31, 0;\n"
        "mov.b32 h32, 0;\nmov.b32 h33, 0;\nmov.b32 h34, 0;\nmov.b32 h35, 0;\nmov.b32 h36, 0;\nmov.b32 h37, 0;\nmov.b32 h38, 0;\nmov.b32 h39, 0;\n"
        "mov.b32 h40, 0;\nmov.b32 h41, 0;\nmov.b32 h42, 0;\nmov.b32 h43, 0;\nmov.b32 h44, 0;\nmov.b32 h45, 0;\nmov.b32 h46, 0;\nmov.b32 h47, 0;\n"
        "mov.b32 h48, 0;\nmov.b32 h49, 0;\nmov.b32 h50, 0;\nmov.b32 h51, 0;\nmov.b32 h52, 0;\nmov.b32 h53, 0;\nmov.b32 h54, 0;\nmov.b32 h55, 0;\n"
        "mov.b32 h56, 0;\nmov.b32 h57, 0;\nmov.b32 h58, 0;\nmov.b32 h59, 0;\nmov.b32 h60, 0;\nmov.b32 h61, 0;\nmov.b32 h62, 0;\nmov.b32 h63, 0;\n"
        "mov.b32 olp, %64;\nand.b32 t0, %66, 32;\nsetp.ne.u32 psw, t0, 0;\nsetp.eq.u32 pz, %64, 0;\nvote.sync.any.pred pz, pz, 0xffffffff;\nmov.b32 e0, %73;\n"
        "mov.b32 e1, %74;\nmov.b32 s0, %75;\nmov.b32 kept, %76;\nadd.u32 olp, olp, 4;\nsetp.ne.u64 p, %72, 0;\n@p fence.proxy.async.global;\n"
        "@p red.release.gpu.global.add.u32 [%72+12], 1;\nbar.warp.sync 0xffffffff;\nshfl.sync.idx.b32 v, kept, %67, 0x1f, 0xffffffff;\nor.b32 t3, %67, 4;\n"
        "shfl.sync.idx.b32 vB, kept, t3, 0x1f, 0xffffffff;\n"
        "RW:\nmma.sync.aligned.m16n8k8.row.col.f32.bf16.bf16.f32 {d0,d1,d2,d3}, {%114,%115}, {s0}, {fz,fz,fz,fz};\n"
        "mma.sync.aligned.m16n8k8.row.col.f32.bf16.bf16.f32 {d4,d5,d6,d7}, {%116,%117}, {s0}, {fz,fz,fz,fz};\ncvt.rn.bf16x2.f32 c0, d2, d0;\n"
        "cvt.rn.bf16x2.f32 c1, d3, d1;\ncvt.rn.bf16x2.f32 c2, d6, d4;\ncvt.rn.bf16x2.f32 c3, d7, d5;\nselp.b32 bA0, c2, c0, psw;\nselp.b32 bA1, c0, c2, psw;\n"
        "selp.b32 bB0, c3, c1, psw;\nselp.b32 bB1, c1, c3, psw;\n"
        "mma.sync.aligned.m16n8k16.row.col.f32.bf16.bf16.f32 {d0,d1,d2,d3}, {%82,%83,%84,%85}, {e0,e1}, {fz,fz,fz,fz};\ncvt.rn.bf16x2.f32 ra0, d2, d0;\n"
        "cvt.rn.bf16x2.f32 rb0, d3, d1;\nmma.sync.aligned.m16n8k16.row.col.f32.bf16.bf16.f32 {d4,d5,d6,d7}, {%86,%87,%88,%89}, {e0,e1}, {fz,fz,fz,fz};\n"
        "cvt.rn.bf16x2.f32 ra1, d6, d4;\ncvt.rn.bf16x2.f32 rb1, d7, d5;\n"
        "mma.sync.aligned.m16n8k16.row.col.f32.bf16.bf16.f32 {d8,d9,d10,d11}, {%90,%91,%92,%93}, {e0,e1}, {fz,fz,fz,fz};\ncvt.rn.bf16x2.f32 ra2, d10, d8;\n"
        "cvt.rn.bf16x2.f32 rb2, d11, d9;\nmma.sync.aligned.m16n8k16.row.col.f32.bf16.bf16.f32 {d12,d13,d14,d15}, {%94,%95,%96,%97}, {e0,e1}, {fz,fz,fz,fz};\n"
        "cvt.rn.bf16x2.f32 ra3, d14, d12;\ncvt.rn.bf16x2.f32 rb3, d15, d13;\n"
        "mma.sync.aligned.m16n8k16.row.col.f32.bf16.bf16.f32 {d16,d17,d18,d19}, {%98,%99,%100,%101}, {e0,e1}, {fz,fz,fz,fz};\ncvt.rn.bf16x2.f32 ra4, d18, d16;\n"
        "cvt.rn.bf16x2.f32 rb4, d19, d17;\n"
        "mma.sync.aligned.m16n8k16.row.col.f32.bf16.bf16.f32 {d20,d21,d22,d23}, {%102,%103,%104,%105}, {e0,e1}, {fz,fz,fz,fz};\n"
        "cvt.rn.bf16x2.f32 ra5, d22, d20;\ncvt.rn.bf16x2.f32 rb5, d23, d21;\n"
        "mma.sync.aligned.m16n8k16.row.col.f32.bf16.bf16.f32 {d24,d25,d26,d27}, {%106,%107,%108,%109}, {e0,e1}, {fz,fz,fz,fz};\n"
        "cvt.rn.bf16x2.f32 ra6, d26, d24;\ncvt.rn.bf16x2.f32 rb6, d27, d25;\n"
        "mma.sync.aligned.m16n8k16.row.col.f32.bf16.bf16.f32 {d28,d29,d30,d31}, {%110,%111,%112,%113}, {e0,e1}, {fz,fz,fz,fz};\n"
        "cvt.rn.bf16x2.f32 ra7, d30, d28;\ncvt.rn.bf16x2.f32 rb7, d31, d29;\nld.shared.u16 t0, [olp];\nadd.u32 olp, olp, 4;\n"
        "lop3.b32 t1, t0, %66, 0x3ff0, 0xe4;\nld.shared.b32 t1, [t1+%77];\nlop3.b32 kept, t1, t0, 0x1ffc, 0xe4;\nlop3.b32 t2, t1, %67, 3, 0x80;\n"
        "setp.ne.u32 q, t2, 0;\nshr.u32 t2, t1, 13;\nmad.wide.u32 pa, t2, 32, %70;\nmad.wide.u32 pb, t2, 8, %71;\nmov.b32 s0, 0;\n"
        "ld.global.cg.L2::128B.v2.b32 {e0,e1}, [pa];\n@q ld.global.cg.L2::128B.b32 s0, [pb];\nshr.u32 bar, v, 1;\nand.b32 bar, bar, 0xff8;\n"
        "mbarrier.test_wait.parity.shared.b64 p, [bar+%79], 0;\nlop3.b32 ida, v, %67, 0x1fff, 0xe4;\nld.volatile.shared.u16 id, [ida+%78];\n"
        "vote.sync.all.pred prdy, p, 0xffffffff;\n@!prdy bra.uni WA;\n"
        "HA:\nmad.lo.u32 xb, id, 64, %65;\ncvt.u16.u32 i16, id;\natom.shared.add.u32 pos, [%66+%80], %68;\n"
        "ldmatrix.sync.aligned.m8n8.x4.trans.shared.b16 {x0,x1,x2,x3}, [xb];\nldmatrix.sync.aligned.m8n8.x4.trans.shared.b16 {x24,x25,x26,x27}, [xb+512];\n"
        "xor.b32 t1, xb, 32;\nldmatrix.sync.aligned.m8n8.x4.trans.shared.b16 {x4,x5,x6,x7}, [t1];\n"
        "ldmatrix.sync.aligned.m8n8.x4.trans.shared.b16 {x28,x29,x30,x31}, [t1+512];\nxor.b32 t1, xb, 64;\n"
        "ldmatrix.sync.aligned.m8n8.x4.trans.shared.b16 {x8,x9,x10,x11}, [t1];\nldmatrix.sync.aligned.m8n8.x4.trans.shared.b16 {x16,x17,x18,x19}, [t1+512];\n"
        "xor.b32 t1, xb, 96;\nldmatrix.sync.aligned.m8n8.x4.trans.shared.b16 {x12,x13,x14,x15}, [t1];\n"
        "ldmatrix.sync.aligned.m8n8.x4.trans.shared.b16 {x20,x21,x22,x23}, [t1+512];\nst.volatile.shared.u16 [pos], i16;\nand.b32 t0, v, 16384;\n"
        "setp.ne.u32 ps1, t0, 0;\nvote.sync.any.pred ps1, ps1, 0xffffffff;\nand.b32 t0, v, 32768;\nsetp.ne.u32 ps2, t0, 0;\n"
        "vote.sync.any.pred ps2, ps2, 0xffffffff;\nmov.b32 v, vB;\nshr.u32 bar, v, 1;\nand.b32 bar, bar, 0xff8;\n"
        "mbarrier.test_wait.parity.shared.b64 p, [bar+%79], 0;\nlop3.b32 ida, v, %67, 0x1fff, 0xe4;\nld.volatile.shared.u16 id, [ida+%78];\n"
        "vote.sync.all.pred prdy, p, 0xffffffff;\nmov.b32 {lo, hi}, ra0;\nmov.b32 t2, {lo, lo};\nmul.rn.bf16x2 y0, x0, t2;\nmul.rn.bf16x2 y2, x2, t2;\n"
        "mov.b32 t2, {hi, hi};\nmul.rn.bf16x2 y1, x1, t2;\nmul.rn.bf16x2 y3, x3, t2;\n"
        "mma.sync.aligned.m16n8k16.row.col.f32.bf16.bf16.f32 {d0,d1,d2,d3}, {y0,y1,y2,y3}, {bA0,bA1}, {fz,fz,fz,fz};\ncvt.rn.bf16x2.f32 z0, d1, d0;\n"
        "cvt.rn.bf16x2.f32 z1, d3, d2;\nmov.b32 {lo, hi}, ra6;\nmov.b32 t2, {lo, lo};\nmul.rn.bf16x2 y24, x24, t2;\nmul.rn.bf16x2 y26, x26, t2;\n"
        "mov.b32 t2, {hi, hi};\nmul.rn.bf16x2 y25, x25, t2;\nmul.rn.bf16x2 y27, x27, t2;\n"
        "mma.sync.aligned.m16n8k16.row.col.f32.bf16.bf16.f32 {d24,d25,d26,d27}, {y24,y25,y26,y27}, {bA0,bA1}, {fz,fz,fz,fz};\ncvt.rn.bf16x2.f32 z12, d25, d24;\n"
        "cvt.rn.bf16x2.f32 z13, d27, d26;\nmov.b32 {lo, hi}, ra1;\nmov.b32 t2, {lo, lo};\nmul.rn.bf16x2 y4, x4, t2;\nmul.rn.bf16x2 y6, x6, t2;\n"
        "mov.b32 t2, {hi, hi};\nmul.rn.bf16x2 y5, x5, t2;\nmul.rn.bf16x2 y7, x7, t2;\n"
        "mma.sync.aligned.m16n8k16.row.col.f32.bf16.bf16.f32 {d4,d5,d6,d7}, {y4,y5,y6,y7}, {bA0,bA1}, {fz,fz,fz,fz};\ncvt.rn.bf16x2.f32 z2, d5, d4;\n"
        "cvt.rn.bf16x2.f32 z3, d7, d6;\nmov.b32 {lo, hi}, ra7;\nmov.b32 t2, {lo, lo};\nmul.rn.bf16x2 y28, x28, t2;\nmul.rn.bf16x2 y30, x30, t2;\n"
        "mov.b32 t2, {hi, hi};\nmul.rn.bf16x2 y29, x29, t2;\nmul.rn.bf16x2 y31, x31, t2;\n"
        "mma.sync.aligned.m16n8k16.row.col.f32.bf16.bf16.f32 {d28,d29,d30,d31}, {y28,y29,y30,y31}, {bA0,bA1}, {fz,fz,fz,fz};\ncvt.rn.bf16x2.f32 z14, d29, d28;\n"
        "cvt.rn.bf16x2.f32 z15, d31, d30;\nmov.b32 {lo, hi}, ra2;\nmov.b32 t2, {lo, lo};\nmul.rn.bf16x2 y8, x8, t2;\nmul.rn.bf16x2 y10, x10, t2;\n"
        "mov.b32 t2, {hi, hi};\nmul.rn.bf16x2 y9, x9, t2;\nmul.rn.bf16x2 y11, x11, t2;\n"
        "mma.sync.aligned.m16n8k16.row.col.f32.bf16.bf16.f32 {d8,d9,d10,d11}, {y8,y9,y10,y11}, {bA0,bA1}, {fz,fz,fz,fz};\ncvt.rn.bf16x2.f32 z4, d9, d8;\n"
        "cvt.rn.bf16x2.f32 z5, d11, d10;\nmov.b32 {lo, hi}, ra4;\nmov.b32 t2, {lo, lo};\nmul.rn.bf16x2 y16, x16, t2;\nmul.rn.bf16x2 y18, x18, t2;\n"
        "mov.b32 t2, {hi, hi};\nmul.rn.bf16x2 y17, x17, t2;\nmul.rn.bf16x2 y19, x19, t2;\n"
        "mma.sync.aligned.m16n8k16.row.col.f32.bf16.bf16.f32 {d16,d17,d18,d19}, {y16,y17,y18,y19}, {bA0,bA1}, {fz,fz,fz,fz};\ncvt.rn.bf16x2.f32 z8, d17, d16;\n"
        "cvt.rn.bf16x2.f32 z9, d19, d18;\nmov.b32 {lo, hi}, ra3;\nmov.b32 t2, {lo, lo};\nmul.rn.bf16x2 y12, x12, t2;\nmul.rn.bf16x2 y14, x14, t2;\n"
        "mov.b32 t2, {hi, hi};\nmul.rn.bf16x2 y13, x13, t2;\nmul.rn.bf16x2 y15, x15, t2;\n"
        "mma.sync.aligned.m16n8k16.row.col.f32.bf16.bf16.f32 {d12,d13,d14,d15}, {y12,y13,y14,y15}, {bA0,bA1}, {fz,fz,fz,fz};\ncvt.rn.bf16x2.f32 z6, d13, d12;\n"
        "cvt.rn.bf16x2.f32 z7, d15, d14;\nmov.b32 {lo, hi}, ra5;\nmov.b32 t2, {lo, lo};\nmul.rn.bf16x2 y20, x20, t2;\nmul.rn.bf16x2 y22, x22, t2;\n"
        "mov.b32 t2, {hi, hi};\nmul.rn.bf16x2 y21, x21, t2;\nmul.rn.bf16x2 y23, x23, t2;\n"
        "mma.sync.aligned.m16n8k16.row.col.f32.bf16.bf16.f32 {d20,d21,d22,d23}, {y20,y21,y22,y23}, {bA0,bA1}, {fz,fz,fz,fz};\ncvt.rn.bf16x2.f32 z10, d21, d20;\n"
        "cvt.rn.bf16x2.f32 z11, d23, d22;\n@ps2 bra.uni TA2;\n@ps1 bra.uni TA1;\n"
        "TA0:\nadd.rn.bf16x2 h0, h0, z0;\nadd.rn.bf16x2 h1, h1, z1;\nadd.rn.bf16x2 h2, h2, z2;\nadd.rn.bf16x2 h3, h3, z3;\nadd.rn.bf16x2 h4, h4, z4;\n"
        "add.rn.bf16x2 h5, h5, z5;\nadd.rn.bf16x2 h6, h6, z6;\nadd.rn.bf16x2 h7, h7, z7;\nadd.rn.bf16x2 h8, h8, z8;\nadd.rn.bf16x2 h9, h9, z9;\n"
        "add.rn.bf16x2 h10, h10, z10;\nadd.rn.bf16x2 h11, h11, z11;\nadd.rn.bf16x2 h12, h12, z12;\nadd.rn.bf16x2 h13, h13, z13;\nadd.rn.bf16x2 h14, h14, z14;\n"
        "add.rn.bf16x2 h15, h15, z15;\n@prdy bra.uni HB;\nbra.uni WB;\n"
        "TA1:\nadd.rn.bf16x2 h16, h16, z0;\nadd.rn.bf16x2 h17, h17, z1;\nadd.rn.bf16x2 h18, h18, z2;\nadd.rn.bf16x2 h19, h19, z3;\nadd.rn.bf16x2 h20, h20, z4;\n"
        "add.rn.bf16x2 h21, h21, z5;\nadd.rn.bf16x2 h22, h22, z6;\nadd.rn.bf16x2 h23, h23, z7;\nadd.rn.bf16x2 h24, h24, z8;\nadd.rn.bf16x2 h25, h25, z9;\n"
        "add.rn.bf16x2 h26, h26, z10;\nadd.rn.bf16x2 h27, h27, z11;\nadd.rn.bf16x2 h28, h28, z12;\nadd.rn.bf16x2 h29, h29, z13;\nadd.rn.bf16x2 h30, h30, z14;\n"
        "add.rn.bf16x2 h31, h31, z15;\n@prdy bra.uni HB;\nbra.uni WB;\n"
        "TA2:\n@ps1 bra.uni TA3;\nadd.rn.bf16x2 h32, h32, z0;\nadd.rn.bf16x2 h33, h33, z1;\nadd.rn.bf16x2 h34, h34, z2;\nadd.rn.bf16x2 h35, h35, z3;\n"
        "add.rn.bf16x2 h36, h36, z4;\nadd.rn.bf16x2 h37, h37, z5;\nadd.rn.bf16x2 h38, h38, z6;\nadd.rn.bf16x2 h39, h39, z7;\nadd.rn.bf16x2 h40, h40, z8;\n"
        "add.rn.bf16x2 h41, h41, z9;\nadd.rn.bf16x2 h42, h42, z10;\nadd.rn.bf16x2 h43, h43, z11;\nadd.rn.bf16x2 h44, h44, z12;\nadd.rn.bf16x2 h45, h45, z13;\n"
        "add.rn.bf16x2 h46, h46, z14;\nadd.rn.bf16x2 h47, h47, z15;\n@prdy bra.uni HB;\nbra.uni WB;\n"
        "TA3:\nadd.rn.bf16x2 h48, h48, z0;\nadd.rn.bf16x2 h49, h49, z1;\nadd.rn.bf16x2 h50, h50, z2;\nadd.rn.bf16x2 h51, h51, z3;\nadd.rn.bf16x2 h52, h52, z4;\n"
        "add.rn.bf16x2 h53, h53, z5;\nadd.rn.bf16x2 h54, h54, z6;\nadd.rn.bf16x2 h55, h55, z7;\nadd.rn.bf16x2 h56, h56, z8;\nadd.rn.bf16x2 h57, h57, z9;\n"
        "add.rn.bf16x2 h58, h58, z10;\nadd.rn.bf16x2 h59, h59, z11;\nadd.rn.bf16x2 h60, h60, z12;\nadd.rn.bf16x2 h61, h61, z13;\nadd.rn.bf16x2 h62, h62, z14;\n"
        "add.rn.bf16x2 h63, h63, z15;\n@prdy bra.uni HB;\nbra.uni WB;\n"
        "HB:\nmad.lo.u32 xb, id, 64, %65;\ncvt.u16.u32 i16, id;\natom.shared.add.u32 pos, [%66+%80], %68;\n"
        "ldmatrix.sync.aligned.m8n8.x4.trans.shared.b16 {x0,x1,x2,x3}, [xb];\nldmatrix.sync.aligned.m8n8.x4.trans.shared.b16 {x24,x25,x26,x27}, [xb+512];\n"
        "xor.b32 t1, xb, 32;\nldmatrix.sync.aligned.m8n8.x4.trans.shared.b16 {x4,x5,x6,x7}, [t1];\n"
        "ldmatrix.sync.aligned.m8n8.x4.trans.shared.b16 {x28,x29,x30,x31}, [t1+512];\nxor.b32 t1, xb, 64;\n"
        "ldmatrix.sync.aligned.m8n8.x4.trans.shared.b16 {x8,x9,x10,x11}, [t1];\nldmatrix.sync.aligned.m8n8.x4.trans.shared.b16 {x16,x17,x18,x19}, [t1+512];\n"
        "xor.b32 t1, xb, 96;\nldmatrix.sync.aligned.m8n8.x4.trans.shared.b16 {x12,x13,x14,x15}, [t1];\n"
        "ldmatrix.sync.aligned.m8n8.x4.trans.shared.b16 {x20,x21,x22,x23}, [t1+512];\nst.volatile.shared.u16 [pos], i16;\nand.b32 t0, v, 16384;\n"
        "setp.ne.u32 ps1, t0, 0;\nvote.sync.any.pred ps1, ps1, 0xffffffff;\nand.b32 t0, v, 32768;\nsetp.ne.u32 ps2, t0, 0;\n"
        "vote.sync.any.pred ps2, ps2, 0xffffffff;\nshfl.sync.idx.b32 v, kept, %67, 0x1f, 0xffffffff;\nor.b32 t3, %67, 4;\n"
        "shfl.sync.idx.b32 vB, kept, t3, 0x1f, 0xffffffff;\nmov.b32 {lo, hi}, rb0;\nmov.b32 t2, {lo, lo};\nmul.rn.bf16x2 y0, x0, t2;\nmul.rn.bf16x2 y2, x2, t2;\n"
        "mov.b32 t2, {hi, hi};\nmul.rn.bf16x2 y1, x1, t2;\nmul.rn.bf16x2 y3, x3, t2;\n"
        "mma.sync.aligned.m16n8k16.row.col.f32.bf16.bf16.f32 {d0,d1,d2,d3}, {y0,y1,y2,y3}, {bB0,bB1}, {fz,fz,fz,fz};\ncvt.rn.bf16x2.f32 z0, d1, d0;\n"
        "cvt.rn.bf16x2.f32 z1, d3, d2;\nmov.b32 {lo, hi}, rb6;\nmov.b32 t2, {lo, lo};\nmul.rn.bf16x2 y24, x24, t2;\nmul.rn.bf16x2 y26, x26, t2;\n"
        "mov.b32 t2, {hi, hi};\nmul.rn.bf16x2 y25, x25, t2;\nmul.rn.bf16x2 y27, x27, t2;\n"
        "mma.sync.aligned.m16n8k16.row.col.f32.bf16.bf16.f32 {d24,d25,d26,d27}, {y24,y25,y26,y27}, {bB0,bB1}, {fz,fz,fz,fz};\ncvt.rn.bf16x2.f32 z12, d25, d24;\n"
        "cvt.rn.bf16x2.f32 z13, d27, d26;\nmov.b32 {lo, hi}, rb1;\nmov.b32 t2, {lo, lo};\nmul.rn.bf16x2 y4, x4, t2;\nmul.rn.bf16x2 y6, x6, t2;\n"
        "mov.b32 t2, {hi, hi};\nmul.rn.bf16x2 y5, x5, t2;\nmul.rn.bf16x2 y7, x7, t2;\n"
        "mma.sync.aligned.m16n8k16.row.col.f32.bf16.bf16.f32 {d4,d5,d6,d7}, {y4,y5,y6,y7}, {bB0,bB1}, {fz,fz,fz,fz};\ncvt.rn.bf16x2.f32 z2, d5, d4;\n"
        "cvt.rn.bf16x2.f32 z3, d7, d6;\nmov.b32 {lo, hi}, rb7;\nmov.b32 t2, {lo, lo};\nmul.rn.bf16x2 y28, x28, t2;\nmul.rn.bf16x2 y30, x30, t2;\n"
        "mov.b32 t2, {hi, hi};\nmul.rn.bf16x2 y29, x29, t2;\nmul.rn.bf16x2 y31, x31, t2;\n"
        "mma.sync.aligned.m16n8k16.row.col.f32.bf16.bf16.f32 {d28,d29,d30,d31}, {y28,y29,y30,y31}, {bB0,bB1}, {fz,fz,fz,fz};\ncvt.rn.bf16x2.f32 z14, d29, d28;\n"
        "cvt.rn.bf16x2.f32 z15, d31, d30;\nmov.b32 {lo, hi}, rb2;\nmov.b32 t2, {lo, lo};\nmul.rn.bf16x2 y8, x8, t2;\nmul.rn.bf16x2 y10, x10, t2;\n"
        "mov.b32 t2, {hi, hi};\nmul.rn.bf16x2 y9, x9, t2;\nmul.rn.bf16x2 y11, x11, t2;\n"
        "mma.sync.aligned.m16n8k16.row.col.f32.bf16.bf16.f32 {d8,d9,d10,d11}, {y8,y9,y10,y11}, {bB0,bB1}, {fz,fz,fz,fz};\ncvt.rn.bf16x2.f32 z4, d9, d8;\n"
        "cvt.rn.bf16x2.f32 z5, d11, d10;\nmov.b32 {lo, hi}, rb4;\nmov.b32 t2, {lo, lo};\nmul.rn.bf16x2 y16, x16, t2;\nmul.rn.bf16x2 y18, x18, t2;\n"
        "mov.b32 t2, {hi, hi};\nmul.rn.bf16x2 y17, x17, t2;\nmul.rn.bf16x2 y19, x19, t2;\n"
        "mma.sync.aligned.m16n8k16.row.col.f32.bf16.bf16.f32 {d16,d17,d18,d19}, {y16,y17,y18,y19}, {bB0,bB1}, {fz,fz,fz,fz};\ncvt.rn.bf16x2.f32 z8, d17, d16;\n"
        "cvt.rn.bf16x2.f32 z9, d19, d18;\nmov.b32 {lo, hi}, rb3;\nmov.b32 t2, {lo, lo};\nmul.rn.bf16x2 y12, x12, t2;\nmul.rn.bf16x2 y14, x14, t2;\n"
        "mov.b32 t2, {hi, hi};\nmul.rn.bf16x2 y13, x13, t2;\nmul.rn.bf16x2 y15, x15, t2;\n"
        "mma.sync.aligned.m16n8k16.row.col.f32.bf16.bf16.f32 {d12,d13,d14,d15}, {y12,y13,y14,y15}, {bB0,bB1}, {fz,fz,fz,fz};\ncvt.rn.bf16x2.f32 z6, d13, d12;\n"
        "cvt.rn.bf16x2.f32 z7, d15, d14;\nmov.b32 {lo, hi}, rb5;\nmov.b32 t2, {lo, lo};\nmul.rn.bf16x2 y20, x20, t2;\nmul.rn.bf16x2 y22, x22, t2;\n"
        "mov.b32 t2, {hi, hi};\nmul.rn.bf16x2 y21, x21, t2;\nmul.rn.bf16x2 y23, x23, t2;\n"
        "mma.sync.aligned.m16n8k16.row.col.f32.bf16.bf16.f32 {d20,d21,d22,d23}, {y20,y21,y22,y23}, {bB0,bB1}, {fz,fz,fz,fz};\ncvt.rn.bf16x2.f32 z10, d21, d20;\n"
        "cvt.rn.bf16x2.f32 z11, d23, d22;\n@ps2 bra.uni TB2;\n@ps1 bra.uni TB1;\n"
        "TB0:\nadd.rn.bf16x2 h0, h0, z0;\nadd.rn.bf16x2 h1, h1, z1;\nadd.rn.bf16x2 h2, h2, z2;\nadd.rn.bf16x2 h3, h3, z3;\nadd.rn.bf16x2 h4, h4, z4;\n"
        "add.rn.bf16x2 h5, h5, z5;\nadd.rn.bf16x2 h6, h6, z6;\nadd.rn.bf16x2 h7, h7, z7;\nadd.rn.bf16x2 h8, h8, z8;\nadd.rn.bf16x2 h9, h9, z9;\n"
        "add.rn.bf16x2 h10, h10, z10;\nadd.rn.bf16x2 h11, h11, z11;\nadd.rn.bf16x2 h12, h12, z12;\nadd.rn.bf16x2 h13, h13, z13;\nadd.rn.bf16x2 h14, h14, z14;\n"
        "add.rn.bf16x2 h15, h15, z15;\nbra.uni RW;\n"
        "TB1:\nadd.rn.bf16x2 h16, h16, z0;\nadd.rn.bf16x2 h17, h17, z1;\nadd.rn.bf16x2 h18, h18, z2;\nadd.rn.bf16x2 h19, h19, z3;\nadd.rn.bf16x2 h20, h20, z4;\n"
        "add.rn.bf16x2 h21, h21, z5;\nadd.rn.bf16x2 h22, h22, z6;\nadd.rn.bf16x2 h23, h23, z7;\nadd.rn.bf16x2 h24, h24, z8;\nadd.rn.bf16x2 h25, h25, z9;\n"
        "add.rn.bf16x2 h26, h26, z10;\nadd.rn.bf16x2 h27, h27, z11;\nadd.rn.bf16x2 h28, h28, z12;\nadd.rn.bf16x2 h29, h29, z13;\nadd.rn.bf16x2 h30, h30, z14;\n"
        "add.rn.bf16x2 h31, h31, z15;\nbra.uni RW;\n"
        "TB2:\n@ps1 bra.uni TB3;\nadd.rn.bf16x2 h32, h32, z0;\nadd.rn.bf16x2 h33, h33, z1;\nadd.rn.bf16x2 h34, h34, z2;\nadd.rn.bf16x2 h35, h35, z3;\n"
        "add.rn.bf16x2 h36, h36, z4;\nadd.rn.bf16x2 h37, h37, z5;\nadd.rn.bf16x2 h38, h38, z6;\nadd.rn.bf16x2 h39, h39, z7;\nadd.rn.bf16x2 h40, h40, z8;\n"
        "add.rn.bf16x2 h41, h41, z9;\nadd.rn.bf16x2 h42, h42, z10;\nadd.rn.bf16x2 h43, h43, z11;\nadd.rn.bf16x2 h44, h44, z12;\nadd.rn.bf16x2 h45, h45, z13;\n"
        "add.rn.bf16x2 h46, h46, z14;\nadd.rn.bf16x2 h47, h47, z15;\nbra.uni RW;\n"
        "TB3:\nadd.rn.bf16x2 h48, h48, z0;\nadd.rn.bf16x2 h49, h49, z1;\nadd.rn.bf16x2 h50, h50, z2;\nadd.rn.bf16x2 h51, h51, z3;\nadd.rn.bf16x2 h52, h52, z4;\n"
        "add.rn.bf16x2 h53, h53, z5;\nadd.rn.bf16x2 h54, h54, z6;\nadd.rn.bf16x2 h55, h55, z7;\nadd.rn.bf16x2 h56, h56, z8;\nadd.rn.bf16x2 h57, h57, z9;\n"
        "add.rn.bf16x2 h58, h58, z10;\nadd.rn.bf16x2 h59, h59, z11;\nadd.rn.bf16x2 h60, h60, z12;\nadd.rn.bf16x2 h61, h61, z13;\nadd.rn.bf16x2 h62, h62, z14;\n"
        "add.rn.bf16x2 h63, h63, z15;\nbra.uni RW;\n"
        "WA:\nshr.u32 t2, v, 1;\nand.b32 t2, t2, 0xff8;\nsetp.eq.u32 p, t2, 0;\nvote.sync.all.pred p, p, 0xffffffff;\n@p bra.uni DONE;\nmov.b32 n, 0;\n"
        "WA3:\nmbarrier.try_wait.parity.shared.b64 p, [t2+%79], 0;\nvote.sync.all.pred p, p, 0xffffffff;\nadd.u32 n, n, 1;\nsetp.lt.and.u32 q, n, 1000000, !p;\n"
        "@q bra.uni WA3;\nlop3.b32 ida, v, %67, 0x1fff, 0xe4;\nld.volatile.shared.u16 id, [ida+%78];\nbra.uni HA;\n"
        "WB:\nshr.u32 t2, v, 1;\nand.b32 t2, t2, 0xff8;\nsetp.eq.u32 p, t2, 0;\nvote.sync.all.pred p, p, 0xffffffff;\n@p bra.uni DONE;\nmov.b32 n, 0;\n"
        "WB3:\nmbarrier.try_wait.parity.shared.b64 p, [t2+%79], 0;\nvote.sync.all.pred p, p, 0xffffffff;\nadd.u32 n, n, 1;\nsetp.lt.and.u32 q, n, 1000000, !p;\n"
        "@q bra.uni WB3;\nlop3.b32 ida, v, %67, 0x1fff, 0xe4;\nld.volatile.shared.u16 id, [ida+%78];\nbra.uni HB;\n"
        "DONE:\nmov.b32 %0, h0;\nmov.b32 %1, h1;\nmov.b32 %2, h2;\nmov.b32 %3, h3;\nmov.b32 %4, h4;\nmov.b32 %5, h5;\nmov.b32 %6, h6;\nmov.b32 %7, h7;\n"
        "mov.b32 %8, h8;\nmov.b32 %9, h9;\nmov.b32 %10, h10;\nmov.b32 %11, h11;\nmov.b32 %12, h12;\nmov.b32 %13, h13;\nmov.b32 %14, h14;\nmov.b32 %15, h15;\n"
        "mov.b32 %16, h16;\nmov.b32 %17, h17;\nmov.b32 %18, h18;\nmov.b32 %19, h19;\nmov.b32 %20, h20;\nmov.b32 %21, h21;\nmov.b32 %22, h22;\nmov.b32 %23, h23;\n"
        "mov.b32 %24, h24;\nmov.b32 %25, h25;\nmov.b32 %26, h26;\nmov.b32 %27, h27;\nmov.b32 %28, h28;\nmov.b32 %29, h29;\nmov.b32 %30, h30;\nmov.b32 %31, h31;\n"
        "mov.b32 %32, h32;\nmov.b32 %33, h33;\nmov.b32 %34, h34;\nmov.b32 %35, h35;\nmov.b32 %36, h36;\nmov.b32 %37, h37;\nmov.b32 %38, h38;\nmov.b32 %39, h39;\n"
        "mov.b32 %40, h40;\nmov.b32 %41, h41;\nmov.b32 %42, h42;\nmov.b32 %43, h43;\nmov.b32 %44, h44;\nmov.b32 %45, h45;\nmov.b32 %46, h46;\nmov.b32 %47, h47;\n"
        "mov.b32 %48, h48;\nmov.b32 %49, h49;\nmov.b32 %50, h50;\nmov.b32 %51, h51;\nmov.b32 %52, h52;\nmov.b32 %53, h53;\nmov.b32 %54, h54;\nmov.b32 %55, h55;\n"
        "mov.b32 %56, h56;\nmov.b32 %57, h57;\nmov.b32 %58, h58;\nmov.b32 %59, h59;\nmov.b32 %60, h60;\nmov.b32 %61, h61;\nmov.b32 %62, h62;\nmov.b32 %63, h63;\n"
        "}\n"
        : "=r"(pk[0]), "=r"(pk[1]), "=r"(pk[2]), "=r"(pk[3]), "=r"(pk[4]), "=r"(pk[5]), "=r"(pk[6]), "=r"(pk[7]), "=r"(pk[8]), "=r"(pk[9]),
          "=r"(pk[10]), "=r"(pk[11]), "=r"(pk[12]), "=r"(pk[13]), "=r"(pk[14]), "=r"(pk[15]), "=r"(pk[16]), "=r"(pk[17]), "=r"(pk[18]), "=r"(pk[19]),
          "=r"(pk[20]), "=r"(pk[21]), "=r"(pk[22]), "=r"(pk[23]), "=r"(pk[24]), "=r"(pk[25]), "=r"(pk[26]), "=r"(pk[27]), "=r"(pk[28]), "=r"(pk[29]),
          "=r"(pk[30]), "=r"(pk[31]), "=r"(pk[32]), "=r"(pk[33]), "=r"(pk[34]), "=r"(pk[35]), "=r"(pk[36]), "=r"(pk[37]), "=r"(pk[38]), "=r"(pk[39]),
          "=r"(pk[40]), "=r"(pk[41]), "=r"(pk[42]), "=r"(pk[43]), "=r"(pk[44]), "=r"(pk[45]), "=r"(pk[46]), "=r"(pk[47]), "=r"(pk[48]), "=r"(pk[49]),
          "=r"(pk[50]), "=r"(pk[51]), "=r"(pk[52]), "=r"(pk[53]), "=r"(pk[54]), "=r"(pk[55]), "=r"(pk[56]), "=r"(pk[57]), "=r"(pk[58]), "=r"(pk[59]),
          "=r"(pk[60]), "=r"(pk[61]), "=r"(pk[62]), "=r"(pk[63])
        : "r"(olp), "r"(xa), "r"(ln), "r"(lc), "r"(linc), "r"(lt), "l"(ea), "l"(sh), "l"(wf), "r"(first.x), "r"(first.y), "r"(first.z), "r"(first.w),
          "n"(sb + SM_REC), "n"(sb + SM_R), "n"(sb + SM_BAR), "n"(sb + SM_CTR), "n"(sb + SM_CGF),
          "r"(w[0]), "r"(w[1]), "r"(w[2]), "r"(w[3]), "r"(w[4]), "r"(w[5]), "r"(w[6]), "r"(w[7]), "r"(w[8]), "r"(w[9]), "r"(w[10]), "r"(w[11]),
          "r"(w[12]), "r"(w[13]), "r"(w[14]), "r"(w[15]), "r"(w[16]), "r"(w[17]), "r"(w[18]), "r"(w[19]), "r"(w[20]), "r"(w[21]), "r"(w[22]),
          "r"(w[23]), "r"(w[24]), "r"(w[25]), "r"(w[26]), "r"(w[27]), "r"(w[28]), "r"(w[29]), "r"(w[30]), "r"(w[31]), "r"(w[32]), "r"(w[33]),
          "r"(w[34]), "r"(w[35])
        : "memory");
}
__device__ __forceinline__ void consume3(uint32_t (&pk)[48], const uint32_t (&w)[36], uint32_t olp, uint32_t xa, uint32_t ln,
                                      uint32_t lc, uint32_t linc, uint32_t lt, const __nv_bfloat16* ea, const __nv_bfloat16* sh, const void* wf, uint4 first) {
    ea += lt * 4, sh += lt & 2;
    asm volatile(
        "{\n.reg .pred p, q, psw, prdy, ps1, ps2, ps3, pz, pq, pt;\n.reg .f32 d<32>, fz;\n"
        ".reg .b32 h<48>, x<32>, y<32>, ra<8>, rb<8>, bA0, bA1, bB0, bB1, c0, c1, c2, c3, e0, e1, s0, kept;\n"
        ".reg .b32 olp, v, vB, m, id, ida, bar, xb, pos, t0, t1, t2, t3, n, z<16>, kept2, g<4>, f0, f1, s1;\n.reg .b16 lo, hi, i16;\n.reg .b64 pa, pb;\n"
        "mov.f32 fz, 0f00000000;\nmov.b32 h0, 0;\nmov.b32 h1, 0;\nmov.b32 h2, 0;\nmov.b32 h3, 0;\nmov.b32 h4, 0;\nmov.b32 h5, 0;\nmov.b32 h6, 0;\n"
        "mov.b32 h7, 0;\nmov.b32 h8, 0;\nmov.b32 h9, 0;\nmov.b32 h10, 0;\nmov.b32 h11, 0;\nmov.b32 h12, 0;\nmov.b32 h13, 0;\nmov.b32 h14, 0;\nmov.b32 h15, 0;\n"
        "mov.b32 h16, 0;\nmov.b32 h17, 0;\nmov.b32 h18, 0;\nmov.b32 h19, 0;\nmov.b32 h20, 0;\nmov.b32 h21, 0;\nmov.b32 h22, 0;\nmov.b32 h23, 0;\n"
        "mov.b32 h24, 0;\nmov.b32 h25, 0;\nmov.b32 h26, 0;\nmov.b32 h27, 0;\nmov.b32 h28, 0;\nmov.b32 h29, 0;\nmov.b32 h30, 0;\nmov.b32 h31, 0;\n"
        "mov.b32 h32, 0;\nmov.b32 h33, 0;\nmov.b32 h34, 0;\nmov.b32 h35, 0;\nmov.b32 h36, 0;\nmov.b32 h37, 0;\nmov.b32 h38, 0;\nmov.b32 h39, 0;\n"
        "mov.b32 h40, 0;\nmov.b32 h41, 0;\nmov.b32 h42, 0;\nmov.b32 h43, 0;\nmov.b32 h44, 0;\nmov.b32 h45, 0;\nmov.b32 h46, 0;\nmov.b32 h47, 0;\n"
        "mov.b32 olp, %48;\nor.b32 t3, %51, 4;\nshfl.sync.bfly.b32 t3, t3, 8, 0x1f, 0xffffffff;\nand.b32 t0, %50, 32;\nsetp.ne.u32 psw, t0, 0;\n"
        "setp.eq.u32 pz, %48, 0;\nvote.sync.any.pred pz, pz, 0xffffffff;\nmov.b32 e0, %57;\nmov.b32 e1, %58;\nmov.b32 s0, %59;\nmov.b32 kept, %60;\n"
        "add.u32 olp, olp, 4;\nsetp.ne.u64 p, %56, 0;\n@p fence.proxy.async.global;\n@p red.release.gpu.global.add.u32 [%56+12], 1;\nbar.warp.sync 0xffffffff;\n"
        "shfl.sync.idx.b32 v, kept, %51, 0x1f, 0xffffffff;\nshfl.sync.idx.b32 vB, kept, t3, 0x1f, 0xffffffff;\n"
        "RW:\nmma.sync.aligned.m16n8k8.row.col.f32.bf16.bf16.f32 {d0,d1,d2,d3}, {%98,%99}, {s0}, {fz,fz,fz,fz};\n"
        "mma.sync.aligned.m16n8k8.row.col.f32.bf16.bf16.f32 {d4,d5,d6,d7}, {%100,%101}, {s0}, {fz,fz,fz,fz};\ncvt.rn.bf16x2.f32 c0, d2, d0;\n"
        "cvt.rn.bf16x2.f32 c1, d3, d1;\ncvt.rn.bf16x2.f32 c2, d6, d4;\ncvt.rn.bf16x2.f32 c3, d7, d5;\nselp.b32 bA0, c2, c0, psw;\nselp.b32 bA1, c0, c2, psw;\n"
        "selp.b32 bB0, c3, c1, psw;\nselp.b32 bB1, c1, c3, psw;\n"
        "mma.sync.aligned.m16n8k16.row.col.f32.bf16.bf16.f32 {d0,d1,d2,d3}, {%66,%67,%68,%69}, {e0,e1}, {fz,fz,fz,fz};\ncvt.rn.bf16x2.f32 ra0, d2, d0;\n"
        "cvt.rn.bf16x2.f32 rb0, d3, d1;\nmma.sync.aligned.m16n8k16.row.col.f32.bf16.bf16.f32 {d4,d5,d6,d7}, {%70,%71,%72,%73}, {e0,e1}, {fz,fz,fz,fz};\n"
        "cvt.rn.bf16x2.f32 ra1, d6, d4;\ncvt.rn.bf16x2.f32 rb1, d7, d5;\n"
        "mma.sync.aligned.m16n8k16.row.col.f32.bf16.bf16.f32 {d8,d9,d10,d11}, {%74,%75,%76,%77}, {e0,e1}, {fz,fz,fz,fz};\ncvt.rn.bf16x2.f32 ra2, d10, d8;\n"
        "cvt.rn.bf16x2.f32 rb2, d11, d9;\nmma.sync.aligned.m16n8k16.row.col.f32.bf16.bf16.f32 {d12,d13,d14,d15}, {%78,%79,%80,%81}, {e0,e1}, {fz,fz,fz,fz};\n"
        "cvt.rn.bf16x2.f32 ra3, d14, d12;\ncvt.rn.bf16x2.f32 rb3, d15, d13;\n"
        "mma.sync.aligned.m16n8k16.row.col.f32.bf16.bf16.f32 {d16,d17,d18,d19}, {%82,%83,%84,%85}, {e0,e1}, {fz,fz,fz,fz};\ncvt.rn.bf16x2.f32 ra4, d18, d16;\n"
        "cvt.rn.bf16x2.f32 rb4, d19, d17;\nmma.sync.aligned.m16n8k16.row.col.f32.bf16.bf16.f32 {d20,d21,d22,d23}, {%86,%87,%88,%89}, {e0,e1}, {fz,fz,fz,fz};\n"
        "cvt.rn.bf16x2.f32 ra5, d22, d20;\ncvt.rn.bf16x2.f32 rb5, d23, d21;\n"
        "mma.sync.aligned.m16n8k16.row.col.f32.bf16.bf16.f32 {d24,d25,d26,d27}, {%90,%91,%92,%93}, {e0,e1}, {fz,fz,fz,fz};\ncvt.rn.bf16x2.f32 ra6, d26, d24;\n"
        "cvt.rn.bf16x2.f32 rb6, d27, d25;\nmma.sync.aligned.m16n8k16.row.col.f32.bf16.bf16.f32 {d28,d29,d30,d31}, {%94,%95,%96,%97}, {e0,e1}, {fz,fz,fz,fz};\n"
        "cvt.rn.bf16x2.f32 ra7, d30, d28;\ncvt.rn.bf16x2.f32 rb7, d31, d29;\nld.shared.u16 t0, [olp];\nadd.u32 olp, olp, 4;\n"
        "lop3.b32 t1, t0, %50, 0x3ff0, 0xe4;\nld.shared.b32 t1, [t1+%61];\nlop3.b32 kept, t1, t0, 0x1ffc, 0xe4;\nlop3.b32 t2, t1, %51, 3, 0x80;\n"
        "setp.ne.u32 q, t2, 0;\nshr.u32 t2, t1, 13;\nmad.wide.u32 pa, t2, 32, %54;\nmad.wide.u32 pb, t2, 8, %55;\nmov.b32 s0, 0;\n"
        "ld.global.cg.L2::128B.v2.b32 {e0,e1}, [pa];\n@q ld.global.cg.L2::128B.b32 s0, [pb];\nshr.u32 bar, v, 1;\nand.b32 bar, bar, 0xff8;\n"
        "mbarrier.test_wait.parity.shared.b64 p, [bar+%63], 0;\nlop3.b32 ida, v, %51, 0x1fff, 0xe4;\nld.volatile.shared.u16 id, [ida+%62];\n"
        "vote.sync.all.pred prdy, p, 0xffffffff;\n@!prdy bra.uni WA;\n"
        "HA:\nmad.lo.u32 xb, id, 64, %49;\ncvt.u16.u32 i16, id;\natom.shared.add.u32 pos, [%50+%64], %52;\n"
        "ldmatrix.sync.aligned.m8n8.x4.trans.shared.b16 {x0,x1,x2,x3}, [xb];\nldmatrix.sync.aligned.m8n8.x4.trans.shared.b16 {x24,x25,x26,x27}, [xb+512];\n"
        "xor.b32 t1, xb, 32;\nldmatrix.sync.aligned.m8n8.x4.trans.shared.b16 {x4,x5,x6,x7}, [t1];\n"
        "ldmatrix.sync.aligned.m8n8.x4.trans.shared.b16 {x28,x29,x30,x31}, [t1+512];\nxor.b32 t1, xb, 64;\n"
        "ldmatrix.sync.aligned.m8n8.x4.trans.shared.b16 {x8,x9,x10,x11}, [t1];\nldmatrix.sync.aligned.m8n8.x4.trans.shared.b16 {x16,x17,x18,x19}, [t1+512];\n"
        "xor.b32 t1, xb, 96;\nldmatrix.sync.aligned.m8n8.x4.trans.shared.b16 {x12,x13,x14,x15}, [t1];\n"
        "ldmatrix.sync.aligned.m8n8.x4.trans.shared.b16 {x20,x21,x22,x23}, [t1+512];\nst.volatile.shared.u16 [pos], i16;\nand.b32 t0, v, 16384;\n"
        "setp.ne.u32 ps1, t0, 0;\nvote.sync.any.pred ps1, ps1, 0xffffffff;\nand.b32 t0, v, 32768;\nsetp.ne.u32 ps2, t0, 0;\n"
        "vote.sync.any.pred ps2, ps2, 0xffffffff;\nmov.b32 v, vB;\nshr.u32 bar, v, 1;\nand.b32 bar, bar, 0xff8;\n"
        "mbarrier.test_wait.parity.shared.b64 p, [bar+%63], 0;\nlop3.b32 ida, v, %51, 0x1fff, 0xe4;\nld.volatile.shared.u16 id, [ida+%62];\n"
        "vote.sync.all.pred prdy, p, 0xffffffff;\nmov.b32 {lo, hi}, ra0;\nmov.b32 t2, {lo, lo};\nmul.rn.bf16x2 y0, x0, t2;\nmul.rn.bf16x2 y2, x2, t2;\n"
        "mov.b32 t2, {hi, hi};\nmul.rn.bf16x2 y1, x1, t2;\nmul.rn.bf16x2 y3, x3, t2;\n"
        "mma.sync.aligned.m16n8k16.row.col.f32.bf16.bf16.f32 {d0,d1,d2,d3}, {y0,y1,y2,y3}, {bA0,bA1}, {fz,fz,fz,fz};\ncvt.rn.bf16x2.f32 z0, d1, d0;\n"
        "cvt.rn.bf16x2.f32 z1, d3, d2;\nmov.b32 {lo, hi}, ra6;\nmov.b32 t2, {lo, lo};\nmul.rn.bf16x2 y24, x24, t2;\nmul.rn.bf16x2 y26, x26, t2;\n"
        "mov.b32 t2, {hi, hi};\nmul.rn.bf16x2 y25, x25, t2;\nmul.rn.bf16x2 y27, x27, t2;\n"
        "mma.sync.aligned.m16n8k16.row.col.f32.bf16.bf16.f32 {d24,d25,d26,d27}, {y24,y25,y26,y27}, {bA0,bA1}, {fz,fz,fz,fz};\ncvt.rn.bf16x2.f32 z12, d25, d24;\n"
        "cvt.rn.bf16x2.f32 z13, d27, d26;\nmov.b32 {lo, hi}, ra1;\nmov.b32 t2, {lo, lo};\nmul.rn.bf16x2 y4, x4, t2;\nmul.rn.bf16x2 y6, x6, t2;\n"
        "mov.b32 t2, {hi, hi};\nmul.rn.bf16x2 y5, x5, t2;\nmul.rn.bf16x2 y7, x7, t2;\n"
        "mma.sync.aligned.m16n8k16.row.col.f32.bf16.bf16.f32 {d4,d5,d6,d7}, {y4,y5,y6,y7}, {bA0,bA1}, {fz,fz,fz,fz};\ncvt.rn.bf16x2.f32 z2, d5, d4;\n"
        "cvt.rn.bf16x2.f32 z3, d7, d6;\nmov.b32 {lo, hi}, ra7;\nmov.b32 t2, {lo, lo};\nmul.rn.bf16x2 y28, x28, t2;\nmul.rn.bf16x2 y30, x30, t2;\n"
        "mov.b32 t2, {hi, hi};\nmul.rn.bf16x2 y29, x29, t2;\nmul.rn.bf16x2 y31, x31, t2;\n"
        "mma.sync.aligned.m16n8k16.row.col.f32.bf16.bf16.f32 {d28,d29,d30,d31}, {y28,y29,y30,y31}, {bA0,bA1}, {fz,fz,fz,fz};\ncvt.rn.bf16x2.f32 z14, d29, d28;\n"
        "cvt.rn.bf16x2.f32 z15, d31, d30;\nmov.b32 {lo, hi}, ra2;\nmov.b32 t2, {lo, lo};\nmul.rn.bf16x2 y8, x8, t2;\nmul.rn.bf16x2 y10, x10, t2;\n"
        "mov.b32 t2, {hi, hi};\nmul.rn.bf16x2 y9, x9, t2;\nmul.rn.bf16x2 y11, x11, t2;\n"
        "mma.sync.aligned.m16n8k16.row.col.f32.bf16.bf16.f32 {d8,d9,d10,d11}, {y8,y9,y10,y11}, {bA0,bA1}, {fz,fz,fz,fz};\ncvt.rn.bf16x2.f32 z4, d9, d8;\n"
        "cvt.rn.bf16x2.f32 z5, d11, d10;\nmov.b32 {lo, hi}, ra4;\nmov.b32 t2, {lo, lo};\nmul.rn.bf16x2 y16, x16, t2;\nmul.rn.bf16x2 y18, x18, t2;\n"
        "mov.b32 t2, {hi, hi};\nmul.rn.bf16x2 y17, x17, t2;\nmul.rn.bf16x2 y19, x19, t2;\n"
        "mma.sync.aligned.m16n8k16.row.col.f32.bf16.bf16.f32 {d16,d17,d18,d19}, {y16,y17,y18,y19}, {bA0,bA1}, {fz,fz,fz,fz};\ncvt.rn.bf16x2.f32 z8, d17, d16;\n"
        "cvt.rn.bf16x2.f32 z9, d19, d18;\nmov.b32 {lo, hi}, ra3;\nmov.b32 t2, {lo, lo};\nmul.rn.bf16x2 y12, x12, t2;\nmul.rn.bf16x2 y14, x14, t2;\n"
        "mov.b32 t2, {hi, hi};\nmul.rn.bf16x2 y13, x13, t2;\nmul.rn.bf16x2 y15, x15, t2;\n"
        "mma.sync.aligned.m16n8k16.row.col.f32.bf16.bf16.f32 {d12,d13,d14,d15}, {y12,y13,y14,y15}, {bA0,bA1}, {fz,fz,fz,fz};\ncvt.rn.bf16x2.f32 z6, d13, d12;\n"
        "cvt.rn.bf16x2.f32 z7, d15, d14;\nmov.b32 {lo, hi}, ra5;\nmov.b32 t2, {lo, lo};\nmul.rn.bf16x2 y20, x20, t2;\nmul.rn.bf16x2 y22, x22, t2;\n"
        "mov.b32 t2, {hi, hi};\nmul.rn.bf16x2 y21, x21, t2;\nmul.rn.bf16x2 y23, x23, t2;\n"
        "mma.sync.aligned.m16n8k16.row.col.f32.bf16.bf16.f32 {d20,d21,d22,d23}, {y20,y21,y22,y23}, {bA0,bA1}, {fz,fz,fz,fz};\ncvt.rn.bf16x2.f32 z10, d21, d20;\n"
        "cvt.rn.bf16x2.f32 z11, d23, d22;\n@ps2 bra.uni TA2;\n@ps1 bra.uni TA1;\n"
        "TA0:\nadd.rn.bf16x2 h0, h0, z0;\nadd.rn.bf16x2 h1, h1, z1;\nadd.rn.bf16x2 h2, h2, z2;\nadd.rn.bf16x2 h3, h3, z3;\nadd.rn.bf16x2 h4, h4, z4;\n"
        "add.rn.bf16x2 h5, h5, z5;\nadd.rn.bf16x2 h6, h6, z6;\nadd.rn.bf16x2 h7, h7, z7;\nadd.rn.bf16x2 h8, h8, z8;\nadd.rn.bf16x2 h9, h9, z9;\n"
        "add.rn.bf16x2 h10, h10, z10;\nadd.rn.bf16x2 h11, h11, z11;\nadd.rn.bf16x2 h12, h12, z12;\nadd.rn.bf16x2 h13, h13, z13;\nadd.rn.bf16x2 h14, h14, z14;\n"
        "add.rn.bf16x2 h15, h15, z15;\n@prdy bra.uni HB;\nbra.uni WB;\n"
        "TA1:\nadd.rn.bf16x2 h16, h16, z0;\nadd.rn.bf16x2 h17, h17, z1;\nadd.rn.bf16x2 h18, h18, z2;\nadd.rn.bf16x2 h19, h19, z3;\nadd.rn.bf16x2 h20, h20, z4;\n"
        "add.rn.bf16x2 h21, h21, z5;\nadd.rn.bf16x2 h22, h22, z6;\nadd.rn.bf16x2 h23, h23, z7;\nadd.rn.bf16x2 h24, h24, z8;\nadd.rn.bf16x2 h25, h25, z9;\n"
        "add.rn.bf16x2 h26, h26, z10;\nadd.rn.bf16x2 h27, h27, z11;\nadd.rn.bf16x2 h28, h28, z12;\nadd.rn.bf16x2 h29, h29, z13;\nadd.rn.bf16x2 h30, h30, z14;\n"
        "add.rn.bf16x2 h31, h31, z15;\n@prdy bra.uni HB;\nbra.uni WB;\n"
        "TA2:\nadd.rn.bf16x2 h32, h32, z0;\nadd.rn.bf16x2 h33, h33, z1;\nadd.rn.bf16x2 h34, h34, z2;\nadd.rn.bf16x2 h35, h35, z3;\nadd.rn.bf16x2 h36, h36, z4;\n"
        "add.rn.bf16x2 h37, h37, z5;\nadd.rn.bf16x2 h38, h38, z6;\nadd.rn.bf16x2 h39, h39, z7;\nadd.rn.bf16x2 h40, h40, z8;\nadd.rn.bf16x2 h41, h41, z9;\n"
        "add.rn.bf16x2 h42, h42, z10;\nadd.rn.bf16x2 h43, h43, z11;\nadd.rn.bf16x2 h44, h44, z12;\nadd.rn.bf16x2 h45, h45, z13;\nadd.rn.bf16x2 h46, h46, z14;\n"
        "add.rn.bf16x2 h47, h47, z15;\n@prdy bra.uni HB;\nbra.uni WB;\n"
        "HB:\nmad.lo.u32 xb, id, 64, %49;\ncvt.u16.u32 i16, id;\natom.shared.add.u32 pos, [%50+%64], %52;\n"
        "ldmatrix.sync.aligned.m8n8.x4.trans.shared.b16 {x0,x1,x2,x3}, [xb];\nldmatrix.sync.aligned.m8n8.x4.trans.shared.b16 {x24,x25,x26,x27}, [xb+512];\n"
        "xor.b32 t1, xb, 32;\nldmatrix.sync.aligned.m8n8.x4.trans.shared.b16 {x4,x5,x6,x7}, [t1];\n"
        "ldmatrix.sync.aligned.m8n8.x4.trans.shared.b16 {x28,x29,x30,x31}, [t1+512];\nxor.b32 t1, xb, 64;\n"
        "ldmatrix.sync.aligned.m8n8.x4.trans.shared.b16 {x8,x9,x10,x11}, [t1];\nldmatrix.sync.aligned.m8n8.x4.trans.shared.b16 {x16,x17,x18,x19}, [t1+512];\n"
        "xor.b32 t1, xb, 96;\nldmatrix.sync.aligned.m8n8.x4.trans.shared.b16 {x12,x13,x14,x15}, [t1];\n"
        "ldmatrix.sync.aligned.m8n8.x4.trans.shared.b16 {x20,x21,x22,x23}, [t1+512];\nst.volatile.shared.u16 [pos], i16;\nand.b32 t0, v, 16384;\n"
        "setp.ne.u32 ps1, t0, 0;\nvote.sync.any.pred ps1, ps1, 0xffffffff;\nand.b32 t0, v, 32768;\nsetp.ne.u32 ps2, t0, 0;\n"
        "vote.sync.any.pred ps2, ps2, 0xffffffff;\nshfl.sync.idx.b32 v, kept, %51, 0x1f, 0xffffffff;\nshfl.sync.idx.b32 vB, kept, t3, 0x1f, 0xffffffff;\n"
        "mov.b32 {lo, hi}, rb0;\nmov.b32 t2, {lo, lo};\nmul.rn.bf16x2 y0, x0, t2;\nmul.rn.bf16x2 y2, x2, t2;\nmov.b32 t2, {hi, hi};\nmul.rn.bf16x2 y1, x1, t2;\n"
        "mul.rn.bf16x2 y3, x3, t2;\nmma.sync.aligned.m16n8k16.row.col.f32.bf16.bf16.f32 {d0,d1,d2,d3}, {y0,y1,y2,y3}, {bB0,bB1}, {fz,fz,fz,fz};\n"
        "cvt.rn.bf16x2.f32 z0, d1, d0;\ncvt.rn.bf16x2.f32 z1, d3, d2;\nmov.b32 {lo, hi}, rb6;\nmov.b32 t2, {lo, lo};\nmul.rn.bf16x2 y24, x24, t2;\n"
        "mul.rn.bf16x2 y26, x26, t2;\nmov.b32 t2, {hi, hi};\nmul.rn.bf16x2 y25, x25, t2;\nmul.rn.bf16x2 y27, x27, t2;\n"
        "mma.sync.aligned.m16n8k16.row.col.f32.bf16.bf16.f32 {d24,d25,d26,d27}, {y24,y25,y26,y27}, {bB0,bB1}, {fz,fz,fz,fz};\ncvt.rn.bf16x2.f32 z12, d25, d24;\n"
        "cvt.rn.bf16x2.f32 z13, d27, d26;\nmov.b32 {lo, hi}, rb1;\nmov.b32 t2, {lo, lo};\nmul.rn.bf16x2 y4, x4, t2;\nmul.rn.bf16x2 y6, x6, t2;\n"
        "mov.b32 t2, {hi, hi};\nmul.rn.bf16x2 y5, x5, t2;\nmul.rn.bf16x2 y7, x7, t2;\n"
        "mma.sync.aligned.m16n8k16.row.col.f32.bf16.bf16.f32 {d4,d5,d6,d7}, {y4,y5,y6,y7}, {bB0,bB1}, {fz,fz,fz,fz};\ncvt.rn.bf16x2.f32 z2, d5, d4;\n"
        "cvt.rn.bf16x2.f32 z3, d7, d6;\nmov.b32 {lo, hi}, rb7;\nmov.b32 t2, {lo, lo};\nmul.rn.bf16x2 y28, x28, t2;\nmul.rn.bf16x2 y30, x30, t2;\n"
        "mov.b32 t2, {hi, hi};\nmul.rn.bf16x2 y29, x29, t2;\nmul.rn.bf16x2 y31, x31, t2;\n"
        "mma.sync.aligned.m16n8k16.row.col.f32.bf16.bf16.f32 {d28,d29,d30,d31}, {y28,y29,y30,y31}, {bB0,bB1}, {fz,fz,fz,fz};\ncvt.rn.bf16x2.f32 z14, d29, d28;\n"
        "cvt.rn.bf16x2.f32 z15, d31, d30;\nmov.b32 {lo, hi}, rb2;\nmov.b32 t2, {lo, lo};\nmul.rn.bf16x2 y8, x8, t2;\nmul.rn.bf16x2 y10, x10, t2;\n"
        "mov.b32 t2, {hi, hi};\nmul.rn.bf16x2 y9, x9, t2;\nmul.rn.bf16x2 y11, x11, t2;\n"
        "mma.sync.aligned.m16n8k16.row.col.f32.bf16.bf16.f32 {d8,d9,d10,d11}, {y8,y9,y10,y11}, {bB0,bB1}, {fz,fz,fz,fz};\ncvt.rn.bf16x2.f32 z4, d9, d8;\n"
        "cvt.rn.bf16x2.f32 z5, d11, d10;\nmov.b32 {lo, hi}, rb4;\nmov.b32 t2, {lo, lo};\nmul.rn.bf16x2 y16, x16, t2;\nmul.rn.bf16x2 y18, x18, t2;\n"
        "mov.b32 t2, {hi, hi};\nmul.rn.bf16x2 y17, x17, t2;\nmul.rn.bf16x2 y19, x19, t2;\n"
        "mma.sync.aligned.m16n8k16.row.col.f32.bf16.bf16.f32 {d16,d17,d18,d19}, {y16,y17,y18,y19}, {bB0,bB1}, {fz,fz,fz,fz};\ncvt.rn.bf16x2.f32 z8, d17, d16;\n"
        "cvt.rn.bf16x2.f32 z9, d19, d18;\nmov.b32 {lo, hi}, rb3;\nmov.b32 t2, {lo, lo};\nmul.rn.bf16x2 y12, x12, t2;\nmul.rn.bf16x2 y14, x14, t2;\n"
        "mov.b32 t2, {hi, hi};\nmul.rn.bf16x2 y13, x13, t2;\nmul.rn.bf16x2 y15, x15, t2;\n"
        "mma.sync.aligned.m16n8k16.row.col.f32.bf16.bf16.f32 {d12,d13,d14,d15}, {y12,y13,y14,y15}, {bB0,bB1}, {fz,fz,fz,fz};\ncvt.rn.bf16x2.f32 z6, d13, d12;\n"
        "cvt.rn.bf16x2.f32 z7, d15, d14;\nmov.b32 {lo, hi}, rb5;\nmov.b32 t2, {lo, lo};\nmul.rn.bf16x2 y20, x20, t2;\nmul.rn.bf16x2 y22, x22, t2;\n"
        "mov.b32 t2, {hi, hi};\nmul.rn.bf16x2 y21, x21, t2;\nmul.rn.bf16x2 y23, x23, t2;\n"
        "mma.sync.aligned.m16n8k16.row.col.f32.bf16.bf16.f32 {d20,d21,d22,d23}, {y20,y21,y22,y23}, {bB0,bB1}, {fz,fz,fz,fz};\ncvt.rn.bf16x2.f32 z10, d21, d20;\n"
        "cvt.rn.bf16x2.f32 z11, d23, d22;\n@ps2 bra.uni TB2;\n@ps1 bra.uni TB1;\n"
        "TB0:\nadd.rn.bf16x2 h0, h0, z0;\nadd.rn.bf16x2 h1, h1, z1;\nadd.rn.bf16x2 h2, h2, z2;\nadd.rn.bf16x2 h3, h3, z3;\nadd.rn.bf16x2 h4, h4, z4;\n"
        "add.rn.bf16x2 h5, h5, z5;\nadd.rn.bf16x2 h6, h6, z6;\nadd.rn.bf16x2 h7, h7, z7;\nadd.rn.bf16x2 h8, h8, z8;\nadd.rn.bf16x2 h9, h9, z9;\n"
        "add.rn.bf16x2 h10, h10, z10;\nadd.rn.bf16x2 h11, h11, z11;\nadd.rn.bf16x2 h12, h12, z12;\nadd.rn.bf16x2 h13, h13, z13;\nadd.rn.bf16x2 h14, h14, z14;\n"
        "add.rn.bf16x2 h15, h15, z15;\nbra.uni RW;\n"
        "TB1:\nadd.rn.bf16x2 h16, h16, z0;\nadd.rn.bf16x2 h17, h17, z1;\nadd.rn.bf16x2 h18, h18, z2;\nadd.rn.bf16x2 h19, h19, z3;\nadd.rn.bf16x2 h20, h20, z4;\n"
        "add.rn.bf16x2 h21, h21, z5;\nadd.rn.bf16x2 h22, h22, z6;\nadd.rn.bf16x2 h23, h23, z7;\nadd.rn.bf16x2 h24, h24, z8;\nadd.rn.bf16x2 h25, h25, z9;\n"
        "add.rn.bf16x2 h26, h26, z10;\nadd.rn.bf16x2 h27, h27, z11;\nadd.rn.bf16x2 h28, h28, z12;\nadd.rn.bf16x2 h29, h29, z13;\nadd.rn.bf16x2 h30, h30, z14;\n"
        "add.rn.bf16x2 h31, h31, z15;\nbra.uni RW;\n"
        "TB2:\nadd.rn.bf16x2 h32, h32, z0;\nadd.rn.bf16x2 h33, h33, z1;\nadd.rn.bf16x2 h34, h34, z2;\nadd.rn.bf16x2 h35, h35, z3;\nadd.rn.bf16x2 h36, h36, z4;\n"
        "add.rn.bf16x2 h37, h37, z5;\nadd.rn.bf16x2 h38, h38, z6;\nadd.rn.bf16x2 h39, h39, z7;\nadd.rn.bf16x2 h40, h40, z8;\nadd.rn.bf16x2 h41, h41, z9;\n"
        "add.rn.bf16x2 h42, h42, z10;\nadd.rn.bf16x2 h43, h43, z11;\nadd.rn.bf16x2 h44, h44, z12;\nadd.rn.bf16x2 h45, h45, z13;\nadd.rn.bf16x2 h46, h46, z14;\n"
        "add.rn.bf16x2 h47, h47, z15;\nbra.uni RW;\n"
        "WA:\nshr.u32 t2, v, 1;\nand.b32 t2, t2, 0xff8;\nsetp.eq.u32 p, t2, 0;\nvote.sync.all.pred p, p, 0xffffffff;\n@p bra.uni DONE;\nmov.b32 n, 0;\n"
        "WA3:\nmbarrier.try_wait.parity.shared.b64 p, [t2+%63], 0;\nvote.sync.all.pred p, p, 0xffffffff;\nadd.u32 n, n, 1;\nsetp.lt.and.u32 q, n, 1000000, !p;\n"
        "@q bra.uni WA3;\nlop3.b32 ida, v, %51, 0x1fff, 0xe4;\nld.volatile.shared.u16 id, [ida+%62];\nbra.uni HA;\n"
        "WB:\nshr.u32 t2, v, 1;\nand.b32 t2, t2, 0xff8;\nsetp.eq.u32 p, t2, 0;\nvote.sync.all.pred p, p, 0xffffffff;\n@p bra.uni DONE;\nmov.b32 n, 0;\n"
        "WB3:\nmbarrier.try_wait.parity.shared.b64 p, [t2+%63], 0;\nvote.sync.all.pred p, p, 0xffffffff;\nadd.u32 n, n, 1;\nsetp.lt.and.u32 q, n, 1000000, !p;\n"
        "@q bra.uni WB3;\nlop3.b32 ida, v, %51, 0x1fff, 0xe4;\nld.volatile.shared.u16 id, [ida+%62];\nbra.uni HB;\n"
        "DONE:\nmov.b32 %0, h0;\nmov.b32 %1, h1;\nmov.b32 %2, h2;\nmov.b32 %3, h3;\nmov.b32 %4, h4;\nmov.b32 %5, h5;\nmov.b32 %6, h6;\nmov.b32 %7, h7;\n"
        "mov.b32 %8, h8;\nmov.b32 %9, h9;\nmov.b32 %10, h10;\nmov.b32 %11, h11;\nmov.b32 %12, h12;\nmov.b32 %13, h13;\nmov.b32 %14, h14;\nmov.b32 %15, h15;\n"
        "mov.b32 %16, h16;\nmov.b32 %17, h17;\nmov.b32 %18, h18;\nmov.b32 %19, h19;\nmov.b32 %20, h20;\nmov.b32 %21, h21;\nmov.b32 %22, h22;\nmov.b32 %23, h23;\n"
        "mov.b32 %24, h24;\nmov.b32 %25, h25;\nmov.b32 %26, h26;\nmov.b32 %27, h27;\nmov.b32 %28, h28;\nmov.b32 %29, h29;\nmov.b32 %30, h30;\nmov.b32 %31, h31;\n"
        "mov.b32 %32, h32;\nmov.b32 %33, h33;\nmov.b32 %34, h34;\nmov.b32 %35, h35;\nmov.b32 %36, h36;\nmov.b32 %37, h37;\nmov.b32 %38, h38;\nmov.b32 %39, h39;\n"
        "mov.b32 %40, h40;\nmov.b32 %41, h41;\nmov.b32 %42, h42;\nmov.b32 %43, h43;\nmov.b32 %44, h44;\nmov.b32 %45, h45;\nmov.b32 %46, h46;\nmov.b32 %47, h47;\n"
        "}\n"
        : "=r"(pk[0]), "=r"(pk[1]), "=r"(pk[2]), "=r"(pk[3]), "=r"(pk[4]), "=r"(pk[5]), "=r"(pk[6]), "=r"(pk[7]), "=r"(pk[8]), "=r"(pk[9]),
          "=r"(pk[10]), "=r"(pk[11]), "=r"(pk[12]), "=r"(pk[13]), "=r"(pk[14]), "=r"(pk[15]), "=r"(pk[16]), "=r"(pk[17]), "=r"(pk[18]), "=r"(pk[19]),
          "=r"(pk[20]), "=r"(pk[21]), "=r"(pk[22]), "=r"(pk[23]), "=r"(pk[24]), "=r"(pk[25]), "=r"(pk[26]), "=r"(pk[27]), "=r"(pk[28]), "=r"(pk[29]),
          "=r"(pk[30]), "=r"(pk[31]), "=r"(pk[32]), "=r"(pk[33]), "=r"(pk[34]), "=r"(pk[35]), "=r"(pk[36]), "=r"(pk[37]), "=r"(pk[38]), "=r"(pk[39]),
          "=r"(pk[40]), "=r"(pk[41]), "=r"(pk[42]), "=r"(pk[43]), "=r"(pk[44]), "=r"(pk[45]), "=r"(pk[46]), "=r"(pk[47])
        : "r"(olp), "r"(xa), "r"(ln), "r"(lc), "r"(linc), "r"(lt), "l"(ea), "l"(sh), "l"(wf), "r"(first.x), "r"(first.y), "r"(first.z), "r"(first.w),
          "n"(sb + SM_REC), "n"(sb + SM_R), "n"(sb + SM_BAR), "n"(sb + SM_CTR), "n"(sb + SM_CGF),
          "r"(w[0]), "r"(w[1]), "r"(w[2]), "r"(w[3]), "r"(w[4]), "r"(w[5]), "r"(w[6]), "r"(w[7]), "r"(w[8]), "r"(w[9]), "r"(w[10]), "r"(w[11]),
          "r"(w[12]), "r"(w[13]), "r"(w[14]), "r"(w[15]), "r"(w[16]), "r"(w[17]), "r"(w[18]), "r"(w[19]), "r"(w[20]), "r"(w[21]), "r"(w[22]),
          "r"(w[23]), "r"(w[24]), "r"(w[25]), "r"(w[26]), "r"(w[27]), "r"(w[28]), "r"(w[29]), "r"(w[30]), "r"(w[31]), "r"(w[32]), "r"(w[33]),
          "r"(w[34]), "r"(w[35])
        : "memory");
}

__device__ __forceinline__ void wf_done() {
    asm volatile("fence.proxy.async.global;\nred.release.gpu.global.add.u32 [%0+12], 1;" ::"l"(g_sync) : "memory");
}

template <int NS>
__device__ __forceinline__ void consumer(const __nv_bfloat16* __restrict__ sh,
                                         const __nv_bfloat16* __restrict__ ea, __nv_bfloat16* __restrict__ out, int N, int npb, uint4 first) {
    uint32_t pk[NS * 16];
    {
        const int lane = threadIdx.x & 31, warp = threadIdx.x >> 5;
        const int mi = lane >> 3, r = lane & 7, j = r >> 1;
        const int u = 2 * ((mi >> 1) ^ (j >> 1)) + (r & 1), ph = (j ^ (j >> 1)) & 1;
        uint32_t w[36];
        {
            const uint32_t a = sb + SC_WR + (4 * j + (r & 1) + (mi & 2)) * 272 + (mi & 1) * 16;
#pragma unroll
            for (int c = 0; c < 8; c++)
                asm volatile("ldmatrix.sync.aligned.m8n8.x4.trans.shared.b16 {%0,%1,%2,%3}, [%4];"
                             : "=r"(w[4 * c]), "=r"(w[4 * c + 1]), "=r"(w[4 * c + 2]), "=r"(w[4 * c + 3]) : "r"(a + c * 32) : "memory");
            const uint32_t ca = sb + SC_CG + (lane & 2) * 8 + ((lane >> 2) & 3) * 2;
#pragma unroll
            for (int k = 0; k < 4; k++) {
                const uint32_t f = lds16(ca + 32 * k) | (lds16(ca + 32 * k + 8) << 16);
                w[32 + k] = (lane & 1) == (lane >> 4) ? f : 0;
            }
            if (warp == 0) sts128(sb + SM_CGF + lane * 16, w[32], w[33], w[34], w[35]);
            asm volatile("fence.proxy.async.shared::cta;\nbar.sync 2, %0;" ::"n"(NCW * 32) : "memory");
            if (threadIdx.x < WSL) sts16(sb + SM_R + 0x2000 + (4 + SP - WSL + lane) * 4, (sb + SC_WR) / 64 + lane * 16);
        }
        const uint32_t xa = __shfl_sync(0xffffffffu, u * 128 + (((u + 4 * ph) ^ (mi & 1)) << 4), lane);
        const uint32_t ln = __shfl_sync(0xffffffffu, lane * 16 + (lane >> 3) * 4, lane);
        const uint32_t lc = __shfl_sync(0xffffffffu, j * 8 + (1 << (lane & 1)) + (ph << 13), lane);
        const uint32_t linc = __shfl_sync(0xffffffffu, (lane & 0x19) ? 0 : 8, lane);
        const uint32_t lt = __shfl_sync(0xffffffffu, lane & 3, lane);
        const void* wfp = (threadIdx.x >> 2) == WFT && blockIdx.x < 128 ? g_sync : nullptr;
        const uint32_t olp = sb + SM_OL + warp * (OLN * 2) + ((lane & 4) >> 1);
        if constexpr (NS == 4) consume4(pk, w, olp, xa, ln, lc, linc, lt, ea, sh, wfp, first);
        else consume3(pk, w, olp, xa, ln, lc, linc, lt, ea, sh, wfp, first);
    }
    TLMAX(10);
    const int tid = thread_id(), lane = tid & 31, warp = tid >> 5, g = lane >> 2, t = lane & 3;
    const uint32_t wc = lds32(sb + SM_MISC + 12) + 1;
    const uint32_t inv = lds32(sb + SM_INV + warp * 4);
    const int node0 = cta_id() * npb, nnodes = min(npb, N - node0);
    uint4* op[NS];
    uint32_t on[NS];
#pragma unroll
    for (int s = 0; s < NS; s++) {
        const int nl = ((inv >> (8 * s)) & 255) + (g >> 2) * 40;
        op[s] = (uint4*)(out + ((size_t)(node0 + nl) * 4 + (g & 3)) * 128 + 8 * t);
        on[s] = nl < nnodes;
    }
    if constexpr (NS == 4) project4(pk, sb + SM_R + wc * 16, sb + SM_BAR + (wc + EM3 * t) * 8, op, on);
    else project3(pk, sb + SM_R + wc * 16, sb + SM_BAR + (wc + EM3 * t) * 8, op, on);
}

#define TLHI "shl.b32 d, tb, 16;\n"
#define RAOFF ((threadIdx.x & 96) >> 1)
#define UNPACK(v) "dp2a.lo.u32.u32 d, " #v ", k64, 0;\nshr.s32 r, " #v ", 14;\n"
#define XSTR(x) XSTR2(x)
#define XSTR2(x) #x
__device__ __forceinline__ void producer(const CUtensorMap* tmx, int pw) {
    const uint32_t nch = lds32(sb + SM_MISC + 12), c0 = lds32(sb + SM_MISC + 24);
    asm volatile("bar.sync 1, 512;" ::: "memory");
    if (elect()) {
        asm volatile(
            "{\n.reg .pred p, q, lead, never;\n.reg .b32 ra, oa, off, due, now, a<4>, b<4>, d, r, z<8>, bar<4>, t, n, tb, ta, k64, ktx;\n"
            ".reg .b64 lg, t64, tm;\n"
            "mov.b32 ta, %5;\nld.volatile.shared.v4.b32 {z0,z1,z2,z3}, [ta+32];\nld.volatile.shared.v4.b32 {z4,z5,z6,z7}, [ta+32];\n"
            "mov.b32 ra, %9;\nmad.lo.u32 t, %0, 8, %10;\n"
            "add.u32 bar0, t, z0;\nadd.u32 bar1, t, z1;\nadd.u32 bar2, t, z2;\nadd.u32 bar3, t, z3;\nsetp.ne.u32 never, z0, 0;\n"
            "add.u32 k64, z4, 64;\nadd.u32 ktx, z5, 8192;\ncvt.u64.u32 tm, z6;\nadd.u64 tm, tm, %3;\n"
            "mov.b32 n, 0;\nld.volatile.shared.b32 tb, [ta];\nsetp.eq.u32 lead, %0, 0;\n"
            "mov.u32 due, %%globaltimer_lo;\n"
            "setp.gt.u32 p, ra, %1;\n@p bra.uni END;\nshr.u32 oa, ra, 3;\n"
            "ld.volatile.shared.u16 off, [oa+%11-8];\nadd.u32 due, tb, off;\n"
            "FIRST:\n"
            "mov.u32 now, %%globaltimer_lo;\nsub.u32 t, due, now;\n"
            "setp.gt.s32 p, t, %12;\n@p bra.uni FIRST;\n"
            "GO:\n"
            "ld.volatile.shared.v4.b32 {a0,a1,a2,a3}, [ra];\nld.volatile.shared.v4.b32 {b0,b1,b2,b3}, [ra+0x2000];\n"
            "shr.u32 oa, ra, 3;\nld.volatile.shared.u16 off, [oa+%11];\nld.volatile.shared.b32 tb, [ta];\n"
            "mov.u32 now, %%globaltimer_lo;\n"
            "lop3.b32 t, a0, a1, a2, 0xfe;\nlop3.b32 d, a3, b0, b1, 0xfe;\nlop3.b32 t, t, d, b2, 0xfe;\nor.b32 t, t, b3;\nand.b32 t, t, 1;\n"
            "setp.ne.u32 p, t, 0;\n"
            "@p bra.uni BACK;\n"
            "shl.b32 t, oa, 2;\nmbarrier.arrive.expect_tx.shared.b64 _, [t+%13], ktx;\n"
            "add.u32 bar0, bar0, 32;\nadd.u32 bar1, bar1, 32;\nadd.u32 bar2, bar2, 32;\nadd.u32 bar3, bar3, 32;\n"
            UNPACK(a0)
            "cp.async.bulk.tensor.3d.shared::cluster.global.mbarrier::complete_tx::bytes [d], [tm, {z0, r, z1}], [bar0];\n"
            UNPACK(b0)
            "cp.async.bulk.tensor.3d.shared::cluster.global.mbarrier::complete_tx::bytes [d], [tm, {z2, r, z3}], [bar1];\n"
            UNPACK(a1)
            "cp.async.bulk.tensor.3d.shared::cluster.global.mbarrier::complete_tx::bytes [d], [tm, {z4, r, z5}], [bar2];\n"
            UNPACK(b1)
            "cp.async.bulk.tensor.3d.shared::cluster.global.mbarrier::complete_tx::bytes [d], [tm, {z6, r, z7}], [bar3];\n"
            "@never bra.uni END;\n"
            "add.u32 ra, ra, 64;\nadd.u32 due, off, tb;\nsub.u32 t, due, now;\nsetp.le.u32 q, ra, %1;\nsetp.le.and.u32 q, t, %2, q;\n"
            UNPACK(a2)
            "cp.async.bulk.tensor.3d.shared::cluster.global.mbarrier::complete_tx::bytes [d], [tm, {z0, r, z1}], [bar0];\n"
            UNPACK(b2)
            "cp.async.bulk.tensor.3d.shared::cluster.global.mbarrier::complete_tx::bytes [d], [tm, {z2, r, z3}], [bar1];\n"
            UNPACK(a3)
            "cp.async.bulk.tensor.3d.shared::cluster.global.mbarrier::complete_tx::bytes [d], [tm, {z4, r, z5}], [bar2];\n"
            UNPACK(b3)
            "cp.async.bulk.tensor.3d.shared::cluster.global.mbarrier::complete_tx::bytes [d], [tm, {z6, r, z7}], [bar3];\n"
            "@q bra.uni GO;\n"
            "setp.gt.u32 p, ra, %1;\n@p bra.uni END;\n@!lead bra.uni WAIT;\n"
            "add.u32 d, ta, 16;\ncp.async.bulk.shared::cluster.global.mbarrier::complete_tx::bytes [ta], [%4], 16, [d];\n"
            "setp.ge.s32 p, t, 0;\n@p bra.uni WAIT;\n"
            "setp.lt.u32 p, ra, %8;\n@p bra.uni GO;\nadd.u32 r, ra, " XSTR(SLIPEND) ";\nsetp.gt.u32 p, r, %1;\n@p bra.uni GO;\n"
            "ld.volatile.shared.b64 t64, [ta];\ncvt.u32.u64 r, t64;\nsub.u32 r, tb, r;\nsub.u32 d, %7, t;\nadd.s32 d, d, r;\n"
            "cvt.s64.s32 lg, d;\nadd.u64 t64, t64, lg;\n"
            "red.relaxed.gpu.global.max.u64 [%4], t64;\n"
            "bra.uni GO;\n"
            "SLEEP:\n"
            "nanosleep.u32 32;\n"
            "WAIT:\n"
            "mov.u32 now, %%globaltimer_lo;\nsub.u32 t, due, now;\nsetp.gt.s32 p, t, %6;\n@p bra.uni SLEEP;\n"
            "setp.le.s32 p, t, %12;\n@p bra.uni GO;\n"
            "SPIN:\n"
            "mov.u32 now, %%globaltimer_lo;\nsub.u32 t, due, now;\nsetp.gt.s32 p, t, %12;\n@p bra.uni SPIN;\n"
            "bra.uni GO;\n"
            "BACK:\n"
            "nanosleep.u32 32;\nsub.u32 t, now, tb;\nsetp.lt.s32 p, t, 200000000;\n@p bra.uni GO;\n"
            "END:\n}" ::"r"(pw),
            "r"(sb + SM_R + nch * 16), "n"(AHEAD + EARLY + SLIPTH), "l"(tmx), "l"(g_sync), "n"(sb + SM_MISC + 32), "n"(SPINT + SLIPTH), "n"(SLIPADD),
            "n"(sb + SM_R + SLIPFROM * 16), "r"(sb + SM_R + 16 + c0 * 16 + RAOFF), "r"(sb + SM_BAR + 8 - 32 + c0 * 8),
            "n"(sb + SM_OFF + 8 - (sb + SM_R) / 8), "n"(EARLY + SLIPTH), "n"(sb + SM_BAR - (sb + SM_R) / 2)
            : "memory");
        const uint32_t wch = lds32(sb + SM_MISC + 12) + 1 + pw;
        const uint32_t ra = sb + SM_R + wch * 16, bar = sb + SM_BAR + wch * 8;
        const uint32_t target = lds32(sb + SM_MISC + 16);
        uint32_t cnt = lds128(sb + SM_MISC + 32).w;
        for (int n = 0; n < 1000000 && (int)(cnt - target) < 0; n++)
            asm volatile("ld.acquire.gpu.global.u32 %0, [%1+12];" : "=r"(cnt) : "l"(g_sync) : "memory");
        uint4 a, b;
        for (int n = 0; n < 1000000; n++) {
            a = lds128(ra), b = lds128(ra + 0x2000);
            if (!((a.x | a.y | a.z | a.w | b.x | b.y | b.z | b.w) & 1)) break;
        }
        asm volatile("fence.proxy.async.global;" ::: "memory");
        asm volatile("mbarrier.arrive.expect_tx.shared.b64 _, [%0], 8192;" ::"r"(bar) : "memory");
        const uint32_t c[8] = {a.x, a.y, a.z, a.w, b.x, b.y, b.z, b.w};
#pragma unroll
        for (int i = 0; i < 8; i++)
            asm volatile("cp.async.bulk.shared::cluster.global.mbarrier::complete_tx::bytes [%0], [%1], 1024, [%2];" ::"r"(
                             (c[i] & 0xffe) << 6),
                         "l"(g_wf + (pw * 8 + i) * 64), "r"(bar)
                         : "memory");
    }
}

#define BARINIT(w, n)                                                                                              \
    if (elect()) {                                                                                                 \
        _Pragma("unroll") for (int k = 0; k < (NBAR + n - 1) / n; k++)                                             \
            asm volatile("mbarrier.init.shared.b64 [%0], 1;" ::"r"(sb + SM_BAR + ((w) * ((NBAR + n - 1) / n) + k) * 8)); \
        asm volatile("fence.mbarrier_init.release.cluster;" ::: "memory");                                         \
    }                                                                                                              \
    __syncwarp();

__global__ void __launch_bounds__(NT, 1)
main_kernel(const __grid_constant__ CUtensorMap tmx, const __nv_bfloat16* __restrict__ x, const int* __restrict__ src,
            const int* __restrict__ dst, const __nv_bfloat16* __restrict__ sh, const __nv_bfloat16* __restrict__ ea,
            const __nv_bfloat16* __restrict__ cg, const __nv_bfloat16* __restrict__ wr,
            const __nv_bfloat16* __restrict__ wout, __nv_bfloat16* __restrict__ out, int N, int E, int npb,
            unsigned npb_magic, int chunk, unsigned wsz, unsigned wmagic, unsigned bkm, int tau, int ramp, int rampn, int tdelay, unsigned polld, int spr, int sprn) {
    extern __shared__ __align__(1024) unsigned char smem[];
    if (s2u(smem) != sb) __trap();
    const int tid = threadIdx.x, lane = tid & 31;
    const int warp = __shfl_sync(0xffffffffu, tid >> 5, 0);
    const int nbins = gridDim.x;
    bool fast = chunk > 0;
    uint4 first = make_uint4(0, 0, 0, 0);
    TLSTAMP(0);
    if (fast) {
        const int e0 = blockIdx.x * chunk + tid, left = min(E, (int)(blockIdx.x + 1) * chunk) - e0;
        uint32_t pd[KE], ps[KE];
        {
            const int* dp = dst + e0;
            const int* sp = src + e0;
#pragma unroll
            for (int k = 0; k < KE; k++) {
                pd[k] = (nbins + (k == KE - 1 ? lane : 0)) * npb, ps[k] = 0;
                asm volatile("{\n.reg .pred p;\nsetp.gt.s32 p, %4, %5;\n@p ld.global.nc.u32 %0, [%2];\n@p ld.global.nc.u32 %1, [%3];\n}"
                             : "+r"(pd[k]), "+r"(ps[k]) : "l"(dp + k * NT), "l"(sp + k * NT), "r"(left), "r"(k * NT));
            }
        }
        uint32_t epoch = 0;
        if (tid == NT - 1) asm volatile("ld.relaxed.gpu.global.u32 %0, [%1];" : "=r"(epoch) : "l"(&g_epoch) : "memory");
        uint4 wv, wo[3];
        const bool wrow = (tid >> 2) == WFT && blockIdx.x < 128;
        {
            const uint4* wp = tid < 256 ? (const uint4*)wr + tid
                              : wrow    ? (const uint4*)(wout + blockIdx.x * 128 + (tid & 3) * 32)
                                        : (const uint4*)cg + (tid & 7);
            if (tid < 264 || wrow) wv = __ldg(wp);
            if (wrow) wo[0] = __ldg(wp + 1), wo[1] = __ldg(wp + 2), wo[2] = __ldg(wp + 3);
        }
        const uint32_t t16 = sb + tid * 16;
        const uint32_t sa = sb + SC_STG + (tid >> 3) * CP + (tid & 7) * 16;
        const uint32_t sm = sb + SC_STG + (tid >> 2) * CP + (tid & 3) * 16 + 128;
        const uint32_t none = (40 * NWIN + (lane & 7) + (blockIdx.x & 3) * 8) << 2;
        const uint32_t pade = min(blockIdx.x * chunk, E - 1) << 13;
        const bool third = warp * 4 + 128 < nbins, second = warp * 8 + 128 < nbins;
#pragma unroll
        for (int k = 0; k < 3; k++)
            if (k < 2 || third) sts128(sa + k * 64 * CP, none, none, none, none);
#pragma unroll
        for (int k = 0; k < 2; k++)
            if (k < 1 || second) sts128(sm + k * 128 * CP, none, none, none, none);
        if (tid < MAXB + 32) sts32(sb + SC_CNT + tid * 4, 0);
#pragma unroll
        for (int k = 0; k < 3; k++) sts128(t16 + SC_TABB + k * NT * 16, 0, 0, 0, 0);
        const uint32_t ecomp = -(wsz * (CH << 13));
#pragma unroll
        for (int k = 0; k < 3; k++)
            sts128(t16 + SC_TMP + k * NT * 16, 0, pade + ecomp, 0, pade + ecomp);
#pragma unroll
        for (int k = 0; k < ZSL / 8; k++) sts128(t16 + k * NT * 16, 0, 0, 0, 0), sts128(t16 + SP * 1024 + PH + k * NT * 16, 0, 0, 0, 0);
        if (tid < RP / 4) {
            uint32_t c[4], d[4];
#pragma unroll
            for (int i = 0; i < 4; i++) {
                const uint32_t k = tid * 4 - 4 + i;
                c[i] = d[i] = 0xc0000001u;
                if (warp == 0 && k < SP) c[i] += sb / 64 - 1 + k * 16;
                if (warp == 0 && k < SP - WSL) d[i] = c[i] + (SP * 1024 + PH) / 64;
            }
            static_assert(SP + 4 <= 128, "first warp");
            sts128(t16 + SM_R, c[0], c[1], c[2], c[3]);
            sts128(t16 + SM_R + 0x2000, d[0], d[1], d[2], d[3]);
        }
        constexpr uint32_t OLEND = (RECN - 4) * 4 * 0x10001;
        if (tid < NCW * OLN / 8) sts128(t16 + SM_OL, OLEND, OLEND, OLEND, OLEND);
        if (warp == 12) {
            sts32(sb + SM_CTR + lane * 16 + (lane >> 3) * 4,
                  sb + SM_R + ((lane & 0x19) ? (RP - 1) * 4 : (4 + SP) * 4 + (((lane >> 1) ^ (lane >> 2)) & 1) * 0x2000 + (lane & 4)));
            if (lane < 3) sts32(sb + SM_MISC + (lane ? 16 + lane * 4 : 4), 0);
            if (lane == 8) sts128(sb + SM_REC + (RECN - 4) * 4, pade, pade, pade, pade), sts128(sb + SM_MISC + 64, 0, 0, 0, 0);
            if (lane == 9) asm volatile("prefetch.tensormap [%0];" ::"l"(&tmx) : "memory");
        }
        __syncthreads();
        TLSTAMP(1);

        {
            uint32_t b[KE], r[KE];
#pragma unroll
            for (int k = 0; k < KE; k++) {
                b[k] = __umulhi(pd[k], npb_magic);
                r[k] = atoms_add(sb + SC_CNT + b[k] * 4, 4);
                if (k == KE - 1) b[k] = min(b[k], nbins);
            }
            if (tid == NT - 1) {
                sts32(sb + SM_MISC + 8, epoch % 3 + 1);
                asm volatile("{\n.reg .b64 t;\nmov.u64 t, %%globaltimer;\nred.relaxed.gpu.global.max.u64 [%0], t;\n"
                             "red.relaxed.gpu.global.add.u32 [%0+8], 1;\n}" ::"l"(g_sync) : "memory");
            }
            __syncwarp();
#pragma unroll
            for (int k = 0; k < KE; k++) {
                asm volatile(
                    "{\n.reg .pred p;\n.reg .b32 d, t, u;\nmad.lo.u32 d, %1, %3, %0;\nsetp.ge.u32 p, d, 40;\nmul.hi.u32 u, %2, %4;\n"
                    "mad.lo.u32 t, %2, %10, %5;\nmad.lo.u32 t, d, %11, t;\nmad.lo.u32 t, u, %12, t;\n@p add.u32 t, t, %7;\n"
                    "min.u32 d, %6, 188;\nmad.lo.u32 d, %1, %9, d;\nst.shared.b32 [d+%8], t;\n}" ::"r"(pd[k]),
                    "r"(b[k]), "r"(ps[k]), "r"(-npb), "r"(wmagic), "r"(((tid + k * NT) << 14) + 4), "r"(r[k]), "n"(2 - 40 * NWIN * 4),
                    "n"(sb + SC_STG), "n"(CP), "n"(CH << 14), "n"(NWIN * 4), "r"(4 - wsz * (CH << 14))
                    : "memory");
            }
        }
        if (tid < 264) sts128(sb + SC_WR + (tid >> 4) * 272 + (tid & 15) * 16, wv.x, wv.y, wv.z, wv.w);
        uint4* gp = g_cell + ((tid >> 3) * MAXB + blockIdx.x) * 8 + (tid & 7);
        uint4* gm = g_more + ((tid >> 2) * MAXB + blockIdx.x) * 4 + (tid & 3);
        __syncthreads();
        TLSTAMP(6);
        const uint32_t tag = lds32(sb + SM_MISC + 8), t0 = tag & 1, t1 = tag >> 1;
        {
            uint4 v[5];
#pragma unroll
            for (int k = 0; k < 5; k++)
                if (k != 2 && k != 4 || (k == 2 ? third : second)) v[k] = lds128(k < 3 ? sa + k * 64 * CP : sm + (k - 3) * 128 * CP);
#pragma unroll
            for (int k = 0; k < 5; k++)
                if (k != 2 && k != 4 || (k == 2 ? third : second))
                    st_cell(k < 3 ? gp + k * 64 * MAXB * 8 : gm + (k - 3) * 128 * MAXB * 4, v[k].x | t0, v[k].y | t1, v[k].z | t0, v[k].w | t1);
        }
        if (wrow) {
            const int k = blockIdx.x;
            uint4* dp = &g_wf[((tid & 3) * 8 + (k >> 4)) * 64 + (k & 8) * 4 + (k & 7)];
            dp[0] = make_uint4(wv.x, wo[0].x, wo[1].x, wo[2].x);
            dp[8] = make_uint4(wv.y, wo[0].y, wo[1].y, wo[2].y);
            dp[16] = make_uint4(wv.z, wo[0].z, wo[1].z, wo[2].z);
            dp[24] = make_uint4(wv.w, wo[0].w, wo[1].w, wo[2].w);
        }
        if (warp < 14) { BARINIT(warp, 14) }
        __syncwarp();
        if (tid == NT - 1) {
            uint4 q;
            for (int n = 0; n < (1 << 22); n++) {
                q = ld_cell((const uint4*)g_sync);
                if ((int)(q.z - (epoch + 1) * nbins) >= 0) break;
            }
            sts128(sb + SM_MISC + 32, q.x, q.y, q.z, q.w), sts32(sb + SM_MISC + 16, (epoch + 1) * 512);
            asm volatile("mbarrier.init.shared.b64 [%0], 1;" ::"r"(sb + SM_MISC + 48) : "memory");
            while ((uint32_t)(gt_lo() - q.x) < polld) {}
        }
        __syncthreads();
        TLSTAMP(14);
        uint32_t m[20], rk[20], ia[20], eb[2];
        eb[0] = (((tid >> 3) * chunk) << 13) + ecomp + 1;
        eb[1] = eb[0] + (chunk << 19);
        asm volatile("" : "+r"(eb[0]), "+r"(eb[1]));
        bool ext;
        {
            const uint4* hp = g_cell + blockIdx.x * (MAXB * 8) + tid;
            const uint4* hm = g_more + blockIdx.x * (MAXB * 4) + tid;
            uint4 q[5];
            q[2] = q[4] = make_uint4(none | t0, none | t1, none | t0, none | t1);
            for (int n = 0; n < (1 << 22); n++) {
                q[0] = ld_cell(hp), q[1] = ld_cell(hp + NT), q[3] = ld_cell(hm);
                if ((tid >> 3) + 128 < nbins) q[2] = ld_cell(hp + 2 * NT);
                if ((tid >> 2) + 128 < nbins) q[4] = ld_cell(hm + NT);
                uint32_t bad = 0;
#pragma unroll
                for (int k = 0; k < 5; k++)
                    asm("{\n.reg .b32 a, b;\nlop3.b32 a, %1, %2, %5, 0x7e;\nlop3.b32 b, %3, %4, %6, 0x7e;\nlop3.b32 %0, %0, a, b, 0xfe;\n}"
                        : "+r"(bad) : "r"(q[k].x), "r"(q[k].z), "r"(q[k].y), "r"(q[k].w), "r"(t0), "r"(t1));
                if (!(bad & 1)) break;
            }
            __syncwarp();
            TLSTAMP(8);
#pragma unroll
            for (int k = 0; k < 5; k++) m[4 * k] = q[k].x, m[4 * k + 1] = q[k].y, m[4 * k + 2] = q[k].z, m[4 * k + 3] = q[k].w;
#pragma unroll
            for (int k = 0; k < 12; k++)
                if (k < 8 || third) ia[k] = m[k] & 0x3ffc, rk[k] = atoms_add(sb + SC_TABB + ia[k], 8);
            ext = __any_sync(0xffffffffu, min(m[12] & 0x3ffc, m[16] & 0x3ffc) < 40 * NWIN * 4);
            if (ext) {
#pragma unroll
                for (int k = 12; k < 20; k++) ia[k] = m[k] & 0x3ffc, rk[k] = atoms_add(sb + SC_TABB + ia[k], 8);
                if ((tid & 3) == 3 && min(m[15] & 0x3ffc, m[19] & 0x3ffc) < 40 * NWIN * 4) sts32(sb + SM_MISC + 4, 1);
            }
        }
        __syncthreads();
        TLSTAMP(5);
        const uint32_t tr = sb + warp * (NWIN * 4) + lane * 16;
        if (tid >= NT - PFT) {
            const int i = NT - 1 - tid;
            const char* p = i < 76 ? (const char*)sh + (size_t)min(blockIdx.x * chunk + i * 32, E - 32) * 8
                                   : (const char*)ea + (size_t)min(blockIdx.x * chunk + (i - 76) * 8, E - 8) * 32;
            asm volatile("prefetch.global.L2 [%0];\nprefetch.global.L2 [%0+128];" ::"l"(p));
        }
        if (tid == NT - 1 && blockIdx.x == 0) g_epoch = epoch + 1;
        {
            uint4 c[3];
            uint32_t tt[3];
#pragma unroll
            for (int i = 0; i < 3; i++) {
                c[i] = make_uint4(0, 0, 0, 0);
                if ((i < 2 || warp < 8) && lane < NWIN / 4) c[i] = lds128(tr + SC_TABB + i * 16 * NWIN * 4);
                tt[i] = c[i].x + c[i].y + c[i].z + c[i].w;
            }
            const uint32_t sum = (tt[0] >> 3) + (tt[1] << 7) + (tt[2] << 17);
            const uint32_t tot = __reduce_add_sync(0xffffffffu, sum);
            uint32_t inc = scan_step(scan_step(sum, 1), 2);
            const uint32_t q = (tot + 0x300c03) & 0x3fcff3fc, q0 = q & 1023, q1 = q0 + ((q >> 10) & 1023);
            uint32_t base = atoms_add(sb + (lane ? SC_CNT + lane * 4 : SM_MISC + 20), q1 + (q >> 20));
            inc = scan_step(scan_step(scan_step(inc, 4), 8), 16);
            base = __shfl_sync(0xffffffffu, base, 0);
            const uint32_t l3 = min(lane, 2);
            sts32(sb + SC_KEY + (warp + 16 * l3) * 4, ((tot >> (10 * l3)) & 1023) * 64 + 63 - warp - 16 * l3);
            if (max(tt[0], max(tt[1], tt[2])) > 31 * 8) sts32(sb + SM_MISC + 4, 1);
            inc += q - tot - sum;
#pragma unroll
            for (int i = 0; i < 3; i++) {
                const uint32_t e = (((inc >> (10 * i)) & 1023) + base + (i == 0 ? 0 : i == 1 ? q0 : q1)) * 8;
                if ((i < 2 || warp < 8) && lane < NWIN / 4) sts128(tr + SC_TABB + i * 16 * NWIN * 4, e, e + c[i].x, e + c[i].x + c[i].y, e + tt[i] - c[i].w);
            }
        }
        __syncthreads();
        TLSTAMP(2);
        if (warp >= 11) {
            const uint32_t st = (tid - 352) >> 2, key = lds32(sb + SC_KEY + st * 4);
            uint32_t rank = 0;
#pragma unroll
            for (int i = 0; i < 5; i++) {
                const uint2 q = lds64(sb + SC_KEY + (lane & 3) * 40 + i * 8);
                rank += ((key - q.x) >> 31) + ((key - q.y) >> 31);
            }
            rank += __shfl_xor_sync(0xffffffffu, rank, 1);
            rank += __shfl_xor_sync(0xffffffffu, rank, 2);
            const uint32_t lv = rank >> 2, cw = ((0x969u >> (2 * lv)) & 3) * 4 + ((rank ^ -(lv & 1)) & 3);
            const uint32_t sid = (0xe4a50u >> (2 * lv)) & 3;
            sts32(sb + SC_MAP + st * 4, cw * (NWIN * 4) - st * (NWIN * 4) + 0x10000 + (sid << 30));
            asm volatile("st.shared.u8 [%0], %1;" ::"r"(sb + SM_INV + cw * 4 + sid), "r"(st) : "memory");
        }
        const int total = lds32(sb + SM_MISC + 20);
        fast = lds32(sb + SM_MISC + 4) == 0 && total <= RECN - 4;
        auto lookup = [&](int k) {
            asm volatile("{\n.reg .pred p;\n.reg .b32 t;\nsetp.lt.u32 p, %1, %2;\nmov.b32 t, 0x80000000;\n@p ld.shared.b32 t, [%1+%3];\nadd.u32 %0, %0, t;\n}"
                         : "+r"(rk[k]) : "r"(ia[k]), "n"(40 * NWIN * 4), "n"(sb + SC_TABB) : "memory");
        };
        auto place = [&](int k, uint32_t e) {
            asm volatile("{\n.reg .pred p;\nsetp.ge.s32 p, %0, 0;\n@p st.shared.v2.b32 [%0+%3], {%1, %2};\n}" ::"r"(rk[k]), "r"(m[k]), "r"(e),
                         "n"(sb + SC_TMP) : "memory");
        };
#pragma unroll
        for (int k = 0; k < 8; k++) lookup(k);
        if (fast) {
#pragma unroll
            for (int k = 0; k < 8; k++) place(k, eb[k >> 2]);
            if (third) {
#pragma unroll
                for (int k = 8; k < 12; k++) lookup(k);
#pragma unroll
                for (int k = 8; k < 12; k++) place(k, 2 * eb[1] - eb[0]);
            }
            if (ext) {
#pragma unroll
                for (int k = 12; k < 20; k++) lookup(k);
#pragma unroll
                for (int k = 12; k < 20; k++) place(k, ((((tid >> 2) + (k >> 4) * 128) * chunk) << 13) + ecomp + 1);
            }
            constexpr int KD = (RECN + NT - 1) / NT;
            const uint32_t P = (lane ^ (lane >> 1)) & 1;
            const uint32_t binc = (P ? 1u << 11 : 1u) + ((lane & 3) == 3 ? 1u << 22 : 0u);
            const bool last = warp * 32 + (KD - 1) * NT < total, q2 = warp * 128 + NT * 4 < total;
            const int rest = total - tid, restq = (total >> 2) - tid;
            uint2 en[KD];
            uint32_t bk[KD], r2[KD], ca[2], ol[2], r3[2];
            __syncthreads();
            TLSTAMP(9);
#pragma unroll
            for (int k = 0; k < KD; k++)
                if (k < KD - 1 || last) en[k] = lds64(sb + SC_TMP + tid * 8 + k * NT * 8);
#pragma unroll
            for (int k = 0; k < 2; k++)
                if (k == 0 || q2) ca[k] = lds32(sb + SC_TMP + (tid + k * NT) * 32 + 24);
#pragma unroll
            for (int k = 0; k < 2; k++)
                if (k == 0 || q2) ca[k] &= 0x3ffc, ol[k] = lds32(sb + SC_MAP + __umulhi(ca[k], 0xffffffffu / (NWIN * 4) + 1) * 4);
#pragma unroll
            for (int k = 0; k < KD; k++) {
                if (k < KD - 1 || last) {
                    const uint32_t v = en[k].x, f = v >> 14, i = v & 0x3ffc;
                    const uint32_t w4 = i - __umulhi(i, 0xffffffffu / (NWIN * 4) + 1) * (NWIN * 4);
                    const uint32_t o = __umulhi(f, 0xffffffffu / CH + 1) - wsz;
                    bk[k] = (__umulhi(f, bkm) + w4) * 4;
                    en[k].x = (w4 >> 2) * wsz + o;
                    en[k].y += ((v >> 1) & 0xffffe001u) - o * (CH << 13);
                    if (rest <= k * NT) bk[k] = 2048 + lane * 4;
                    r2[k] = atoms_add(sb + SC_TABA + bk[k], binc);
                }
            }
#pragma unroll
            for (int k = 0; k < 2; k++) {
                if (k == 0 || q2) {
                    ca[k] = (ca[k] + ol[k]) & 0xffff;
                    ol[k] = (tid + k * NT) * 16 + (ol[k] >> 30 << 14);
                    r3[k] = atoms_add(sb + SC_TABC + ca[k], restq > k * NT ? 2 : 0);
                }
            }
            __syncthreads();
            TLSTAMP(12);
            if (warp < NCW) {
                uint4 c = make_uint4(0, 0, 0, 0);
                if (lane < NWIN / 4) c = lds128(tr + SC_TABC);
                const uint32_t tt = c.x + c.y + c.z + c.w;
                uint32_t inc = tt;
#pragma unroll
                for (int o = 1; o < 32; o <<= 1) inc = scan_step(inc, o);
                if (inc > (OLN - 8) * 2) sts32(sb + SM_MISC + 4, 1);
                inc += warp * (OLN * 2) - tt;
                if (lane < NWIN / 4) sts128(tr + SC_TABC, inc, inc + c.x, inc + c.x + c.y, inc + tt - c.w);
            } else {
                const uint32_t mine = (warp + lane) & 3;
                uint4 c;
                uint32_t cs, inc = 0, e = 4 + (4 << 11);
#pragma unroll
                for (int i = 0; i < 4; i++) {
                    const uint32_t pc = (mine + i) & 3;
                    const uint4 v = lds128(sb + SC_TABA + lane * 64 + (pc << 4));
                    const uint32_t sum = v.x + v.y + v.z + v.w;
                    inc += sum;
                    if (i == 0) c = v, cs = sum;
                    if (pc >= mine) e -= sum;
                }
#pragma unroll
                for (int o = 1; o < 32; o <<= 1) inc = scan_step(inc, o);
                e += inc;
                sts128(sb + SC_TABB + lane * 64 + (mine << 4), e, e + c.x, e + c.x + c.y, e + cs - c.w);
                if ((int)max((e + cs) & 0x7ff, ((e + cs) >> 11) & 0x7ff) - (int)(e >> 22) * 2 > SP) sts32(sb + SM_MISC + 4, 1);
                if (tid == NCW * 32) {
                    const uint32_t c0 = min(min(c.x & 0x7ff, (c.x >> 11) & 0x7ff), ZSL) >> 2;
                    sts32(sb + SM_MISC + 12, ((total >> 2) + 1) >> 1), sts32(sb + SM_MISC + 24, c0);
                }
            }
            __syncthreads();
            TLSTAMP(13);
            fast = lds32(sb + SM_MISC + 4) == 0;
            if (warp == 15 && lane < lds32(sb + SM_MISC + 24))
                asm volatile("mbarrier.arrive.shared.b64 _, [%0];" ::"r"(sb + SM_BAR + 8 + lane * 8) : "memory");
#pragma unroll
            for (int k = 0; k < KD; k++)
                if (k < KD - 1 || last) r2[k] += lds32(sb + SC_TABB + bk[k]);
#pragma unroll
            for (int k = 0; k < 2; k++)
                if (k == 0 || q2) r3[k] += lds32(sb + SC_TABC + ca[k]);
            if (fast) {
                const uint32_t rot = P ? 9 : 30;
#pragma unroll
                for (int k = 0; k < KD; k++) {
                    if (k < KD - 1 || last) {
                        const uint32_t k4 = __funnelshift_r(r2[k], r2[k], rot);
                        if (rest > k * NT) {
                            sts16(sb + SM_R + 2 + bitsel(k4, P << 13), en[k].x);
                            sts32(sb + SM_REC + tid * 4 + k * NT * 4, bitsel(k4, en[k].y));
                        }
                    }
                }
#pragma unroll
                for (int k = 0; k < 2; k++)
                    if ((k == 0 || q2) && restq > k * NT) sts16(sb + SM_OL + r3[k], ol[k]);
            }
        }
        asm volatile("fence.mbarrier_init.release.cluster;\nfence.proxy.async.shared::cta;" ::: "memory");
        __syncthreads();
        TLSTAMP(3);
        if (!fast && wrow) wf_done();
        if (fast && tid < NOFF) {
            const uint4 a = lds128(t16 + SM_R), b = lds128(t16 + SM_R + 0x2000);
            const int s = (((int)a.x >> 3) + ((int)a.y >> 3) + ((int)a.z >> 3) + ((int)a.w >> 3) + ((int)b.x >> 3) + ((int)b.y >> 3) +
                           ((int)b.z >> 3) + ((int)b.w >> 3)) >> 16;
            sts16(sb + SM_OFF + tid * 2, min(max(tdelay + SLIPTH + ((s * tau + min(s, rampn) * ramp - max(s - sprn, 0) * spr) >> 10), 0), 0xffff));
        }
        __syncwarp();
        if (fast && warp < NCW) {
            asm volatile("bar.arrive 1, 512;" ::: "memory");
            const uint32_t e = lds16(sb + SM_OL + warp * (OLN * 2) + ((lane & 4) >> 1));
            const uint32_t rec = lds32(sb + SM_REC + (e & 0x3ff0) + (lane >> 3) * 4);
            first.w = bitsel(rec, e);
            asm volatile("{\n.reg .pred q;\nsetp.ne.u32 q, %5, 0;\nld.global.cg.v2.b32 {%0,%1}, [%3];\n@q ld.global.cg.b32 %2, [%4];\n}"
                         : "=r"(first.x), "=r"(first.y), "+r"(first.z)
                         : "l"(ea + (size_t)(rec >> 13) * 16 + (lane & 3) * 4), "l"(sh + (size_t)(rec >> 13) * 4 + (lane & 2)), "r"(rec & (1 << (lane & 1))));
        }
    }

    if (!fast) {
        float* accs = (float*)smem;
        constexpr int NACC = 96;
        const int node0 = blockIdx.x * npb, nnodes = max(0, min(npb, N - node0));
#pragma unroll 1
        for (int nb = 0; nb < nnodes; nb += NACC) {
            __syncthreads();
            for (int i = tid; i < NACC * 512; i += NT) accs[i] = 0.f;
            __syncthreads();
            const int lim = min(NACC, nnodes - nb);
#pragma unroll 1
            for (int base = warp * 32; base < E; base += NT) {
                const int e = base + lane;
                const int dl = e < E ? dst[e] - node0 - nb : -1;
                unsigned mask = __ballot_sync(0xffffffffu, dl >= 0 && dl < lim);
#pragma unroll 1
                while (mask) {
                    const int l = __ffs(mask) - 1;
                    mask &= mask - 1;
                    const int dd = __shfl_sync(0xffffffffu, dl, l);
                    slow_edge(base + l, src[base + l], accs + dd * 512, x, sh, ea, cg, wr, lane);
                }
            }
            __syncthreads();
#pragma unroll 1
            for (int nl = warp; nl < lim; nl += NT / 32) slow_out(accs + nl * 512, wout, out + (size_t)(node0 + nb + nl) * 512, lane);
        }
    } else if (warp >= NCW) {
        asm volatile("setmaxnreg.dec.sync.aligned.u32 %0;" ::"n"(PREG));
        producer(&tmx, warp - NCW);
    } else if (warp >= 4) {
        asm volatile("setmaxnreg.inc.sync.aligned.u32 %0;" ::"n"(R1));
        consumer<3>(sh, ea, out, N, npb, first);
        TLMAX(4);
    } else {
        asm volatile("setmaxnreg.inc.sync.aligned.u32 %0;" ::"n"(R0));
        consumer<4>(sh, ea, out, N, npb, first);
        TLMAX(4);
    }
}

typedef CUresult (*EncodeTiledFn)(CUtensorMap*, CUtensorMapDataType, cuuint32_t, void*, const cuuint64_t*,
                                  const cuuint64_t*, const cuuint32_t*, const cuuint32_t*, CUtensorMapInterleave,
                                  CUtensorMapSwizzle, CUtensorMapL2promotion, CUtensorMapFloatOOBfill);

extern "C" void kernel_launch(void* const* d_in, const int* in_sizes, int n_in, void* d_out, int out_size) {
    const __nv_bfloat16* x = (const __nv_bfloat16*)d_in[0];
    const int* src = (const int*)d_in[1];
    const int* dst = (const int*)d_in[2];
    const __nv_bfloat16* sh = (const __nv_bfloat16*)d_in[3];
    const __nv_bfloat16* ea = (const __nv_bfloat16*)d_in[4];
    const __nv_bfloat16* cg = (const __nv_bfloat16*)d_in[5];
    const __nv_bfloat16* wr = (const __nv_bfloat16*)d_in[6];
    const __nv_bfloat16* wout = (const __nv_bfloat16*)d_in[7];
    __nv_bfloat16* out = (__nv_bfloat16*)d_out;
    const int N = in_sizes[0] / 512;
    const int E = in_sizes[1];

    static int num_sms = 0, coresident = 0;
    static EncodeTiledFn encode = nullptr;
    if (num_sms == 0) {
        int dev = 0;
        cudaGetDevice(&dev);
        cudaDeviceGetAttribute(&num_sms, cudaDevAttrMultiProcessorCount, dev);
        cudaFuncSetAttribute(main_kernel, cudaFuncAttributeMaxDynamicSharedMemorySize, SM_TOTAL);
        int occ = 0;
        cudaOccupancyMaxActiveBlocksPerMultiprocessor(&occ, main_kernel, NT, SM_TOTAL);
        coresident = occ * num_sms;
        void* fn = nullptr;
        cudaDriverEntryPointQueryResult qr;
        cudaGetDriverEntryPoint("cuTensorMapEncodeTiled", &fn, cudaEnableDefault, &qr);
        encode = (EncodeTiledFn)fn;
    }
    CUtensorMap tmx;
    const int rank = 3;
    const cuuint64_t gd[3] = {64, (cuuint64_t)N * 4, 2}, gs[2] = {256, 128};
    const cuuint32_t bd[3] = {64, 4, 2}, es[3] = {1, 1, 1};
    encode(&tmx, CU_TENSOR_MAP_DATA_TYPE_BFLOAT16, rank, (void*)x, gd, gs, bd, es, CU_TENSOR_MAP_INTERLEAVE_NONE,
           CU_TENSOR_MAP_SWIZZLE_128B, CU_TENSOR_MAP_L2_PROMOTION_NONE, CU_TENSOR_MAP_FLOAT_OOB_FILL_NONE);

    int nbins = num_sms < MAXB ? num_sms : MAXB;
    int npb = (N + nbins - 1) / nbins;
    if (npb < 2) npb = 2;
    nbins = (N + npb - 1) / npb;
    const unsigned npb_magic = (unsigned)((0x100000000ull + npb - 1) / npb);
    int chunk = (E + nbins - 1) / nbins;
    const unsigned wsz = (N + NWIN - 2) / (NWIN - 1);
    if (nbins > coresident || nbins < 128 || npb > MAXNPB || chunk > CH || wsz > (1 << 18) / CH || N < 512 || E < 32 || E > (1 << 19)) chunk = 0;
    const unsigned wmagic = 0xffffffffu / wsz + 1, bkm = (unsigned)((4ull << 32) / (wsz * CH));
    double pace = PACE, rampt = RAMP, rampf = RAMPF, sprt = SPRINT, sprf = SPRINTF;
    int tdelay = TDELAY, polld = POLLD;
    const int tau = (int)(1024.0 * pace * ((double)E / nbins) / N);
    const int rampn = (int)(N * rampf), ramp = (int)(1024.0 * rampt / rampn);
    main_kernel<<<nbins, NT, SM_TOTAL, cudaStreamPerThread>>>(tmx, x, src, dst, sh, ea, cg, wr, wout, out, N, E, npb, npb_magic,
                                                              chunk, wsz, wmagic, bkm, tau, ramp, rampn, tdelay, polld, (int)(1024.0 * sprt / (N * sprf)), (int)(N * (1 - sprf)));
}
```

```cpp
#include <cuda_runtime.h>
#include <cuda.h>
#include <cuda_bf16.h>
#include <stdint.h>
#include <stdlib.h>

#define NT 512
#define NCW 12
#define MAXB 144
#define MAXNPB 80
#define KE 5
#define SP 99
#define RECN 2752
#define RP 1488
#define OLN 80
#define NBAR 350
#define NOFF 352
#define R0 168
#define R1 160
#define PREG 24
#define PACE 9.85
#define TDELAY 4550
#define POLLD 1000
#define WFT 80
#define SLIPTH 200
#define SLIPADD 150
#define SLIPFROM 36
#define AHEAD 96
#define EARLY 32
#define RAMPF 0.1
#define SPRINT 400
#define SPRINTF 0.5
#define SLIPEND 320
#define SPINT 96
#define PFT 224
#define EM3 1
#define RAMP 500

__device__ __align__(1024) uint4 g_cell[MAXB * MAXB * 8];
__device__ __align__(1024) uint4 g_more[MAXB * MAXB * 4];
__device__ __align__(1024) uint4 g_wf[2048];
__device__ __align__(256) ulonglong2 g_sync[16];
__device__ __align__(256) unsigned g_epoch;
#define TLSTAMP(i)
#define TLMAX(i)

constexpr uint32_t sb = 1024;
#define PH 512
#define SM_R (2 * SP * 1024 + PH)
#define SM_CTR (SP * 1024)
#define SM_MISC (SM_R + RP * 2)
#define SM_INV (SM_MISC + 80)
#define SM_OFF (SM_INV + 48)
#define SM_S (SM_R + 0x1000 + RP * 2)
#define SM_REC (SM_S + NOFF * 16)
#define SM_OL (SM_REC + RECN * 4)
#define SM_BAR (SM_OL + NCW * OLN * 2)
#define SM_CGF 0
#define SM_TOTAL (SM_BAR + NBAR * 8)
static_assert(SM_TOTAL <= 232448 && SM_OFF + NOFF * 2 <= SM_R + 0x1000 && RP % 8 == 0 && SM_BAR % 16 == 0, "shared memory");
static_assert(4 + RECN / 2 + SP + 2 <= RP && RECN / 8 + 5 <= NBAR && NBAR % 14 == 0 && RECN / 8 + 4 <= NOFF, "tables");
#define ZSL 32
#define NWIN 96
#define CH 2432
#define CP 208
#define SC_STG ((SP + ZSL) * 1024 + PH)
#define SC_TMP (ZSL * 1024)
#define SC_TABB (SC_TMP + 3072 * 8)
#define SC_TABC (SC_TABB + 41 * NWIN * 4)
#define SC_TABA (SC_TABC + NCW * NWIN * 4)
#define SC_ZEND (SC_TABB + 3 * NT * 16)
#define SC_CNT SC_ZEND
#define SC_KEY (SC_CNT + (MAXB + 32) * 4)
#define SC_MAP (SC_KEY + 192)
#define WSL 5
#define SC_WR ((2 * SP - WSL) * 1024 + PH)
#define SC_CG (SC_WR + 16 * 272)
static_assert(SC_TABA + 2048 + 128 <= SC_ZEND && RECN <= 3072 && SC_MAP + 192 <= SP * 1024 && SC_STG + (MAXB + 1) * CP <= SC_WR, "scratch");

__device__ __forceinline__ uint32_t pack_bf16(float lo, float hi) {
    uint32_t r;
    asm("cvt.rn.bf16x2.f32 %0, %1, %2;" : "=r"(r) : "f"(hi), "f"(lo));
    return r;
}
__device__ __forceinline__ uint32_t s2u(const void* p) { return (uint32_t)__cvta_generic_to_shared(p); }
__device__ __forceinline__ void mbar_wait0(uint32_t a) {
    asm volatile(
        "{\n.reg .pred p, q;\n.reg .u32 n;\nmov.u32 n, 0;\n"
        "LAB_WAIT:\nmbarrier.try_wait.parity.shared.b64 p, [%0], 0;\nadd.u32 n, n, 1;\nsetp.lt.and.u32 q, n, 1000000, !p;\n@q bra LAB_WAIT;\n}" ::"r"(a)
        : "memory");
}
__device__ __forceinline__ uint32_t lds8(uint32_t a) { uint32_t v; asm volatile("ld.shared.u8 %0, [%1];" : "=r"(v) : "r"(a) : "memory"); return v; }
__device__ __forceinline__ uint32_t lds16(uint32_t a) { uint32_t v; asm volatile("ld.shared.u16 %0, [%1];" : "=r"(v) : "r"(a) : "memory"); return v; }
__device__ __forceinline__ uint32_t lds32(uint32_t a) { uint32_t v; asm volatile("ld.shared.u32 %0, [%1];" : "=r"(v) : "r"(a) : "memory"); return v; }
__device__ __forceinline__ uint2 lds64(uint32_t a) {
    uint2 v; asm volatile("ld.shared.v2.u32 {%0,%1}, [%2];" : "=r"(v.x), "=r"(v.y) : "r"(a) : "memory"); return v;
}
__device__ __forceinline__ uint4 lds128(uint32_t a) {
    uint4 v; asm volatile("ld.volatile.shared.v4.u32 {%0,%1,%2,%3}, [%4];" : "=r"(v.x), "=r"(v.y), "=r"(v.z), "=r"(v.w) : "r"(a) : "memory"); return v;
}
__device__ __forceinline__ void sts16(uint32_t a, uint32_t v) { asm volatile("st.shared.u16 [%0], %1;" ::"r"(a), "h"((unsigned short)v) : "memory"); }
__device__ __forceinline__ void sts32(uint32_t a, uint32_t v) { asm volatile("st.shared.u32 [%0], %1;" ::"r"(a), "r"(v) : "memory"); }
__device__ __forceinline__ void sts64(uint32_t a, uint32_t x, uint32_t y) { asm volatile("st.shared.v2.u32 [%0], {%1,%2};" ::"r"(a), "r"(x), "r"(y) : "memory"); }
__device__ __forceinline__ void sts128(uint32_t a, uint32_t x, uint32_t y, uint32_t z, uint32_t w) {
    asm volatile("st.shared.v4.u32 [%0], {%1,%2,%3,%4};" ::"r"(a), "r"(x), "r"(y), "r"(z), "r"(w) : "memory");
}
__device__ __forceinline__ uint32_t atoms_add(uint32_t a, uint32_t v) {
    uint32_t r;
    asm volatile("atom.shared.add.u32 %0, [%1], %2;" : "=r"(r) : "r"(a), "r"(v) : "memory");
    return r;
}
__device__ __forceinline__ uint4 ld_cell(const uint4* p) {
    uint4 v;
    asm volatile("{\n.reg .b64 a, b;\nld.relaxed.gpu.global.v2.b64 {a, b}, [%4];\nmov.b64 {%0,%1}, a;\nmov.b64 {%2,%3}, b;\n}"
                 : "=r"(v.x), "=r"(v.y), "=r"(v.z), "=r"(v.w) : "l"(p) : "memory");
    return v;
}
__device__ __forceinline__ void st_cell(uint4* p, uint32_t x, uint32_t y, uint32_t z, uint32_t w) {
    asm volatile("st.relaxed.gpu.global.v2.b64 [%0], {%1, %2};" ::"l"(p), "l"(x | (uint64_t)y << 32), "l"(z | (uint64_t)w << 32) : "memory");
}
__device__ __forceinline__ uint32_t scan_step(uint32_t v, int o) {
    asm volatile("{\n.reg .pred p;\n.reg .b32 y;\nshfl.sync.up.b32 y|p, %0, %1, 0, 0xffffffff;\n@p add.u32 %0, %0, y;\n}" : "+r"(v) : "r"(o));
    return v;
}
__device__ __forceinline__ uint32_t bitsel(uint32_t a, uint32_t b) {
    uint32_t r;
    asm("lop3.b32 %0, %1, %2, 0x1ffc, 0xe4;" : "=r"(r) : "r"(a), "r"(b));
    return r;
}
__device__ __forceinline__ uint32_t movm(uint32_t a) {
    uint32_t r;
    asm volatile("movmatrix.sync.aligned.m8n8.trans.b16 %0, %1;" : "=r"(r) : "r"(a));
    return r;
}
__device__ __forceinline__ uint32_t gt_lo() {
    uint32_t t;
    asm volatile("mov.u32 %0, %globaltimer_lo;" : "=r"(t));
    return t;
}
__device__ __forceinline__ bool elect() {
    uint32_t p;
    asm volatile("{\n.reg .pred P;\nelect.sync _|P, 0xffffffff;\nselp.u32 %0, 1, 0, P;\n}" : "=r"(p));
    return p;
}
__device__ __forceinline__ void project4(const uint32_t (&pk)[64], uint32_t ra, uint32_t ba, uint4* const (&p)[4], const uint32_t (&v)[4]) {
    asm volatile(
        "{\n.reg .pred p0, p1, q0, q1, nv, s<4>;\n.reg .b32 t, h, c<16>, a<32>, b<32>, k<16>;\n.reg .b64 d<16>;\n.reg .f32 o<32>;\nsetp.ne.b32 p0, 0, 0;\n"
        "setp.eq.b32 p1, 0, 0;\nmov.b32 h, 8;\nsetp.eq.u32 nv, %64, 0;\nvote.sync.any.pred nv, nv, 0xffffffff;\nsetp.ne.b32 s0, %69, 0;\n"
        "setp.ne.b32 s1, %70, 0;\nsetp.ne.b32 s2, %71, 0;\nsetp.ne.b32 s3, %72, 0;\nmov.b32 t, 0;\n"
        "W0:\nmbarrier.try_wait.parity.shared.b64 q0, [%73], 0;\nvote.sync.all.pred q0, q0, 0xffffffff;\nadd.u32 t, t, 1;\nsetp.lt.and.u32 q1, t, 1000000, !q0;\n"
        "@q1 bra.uni W0;\nld.volatile.shared.v2.b32 {c0,c1}, [%64+0];\nld.volatile.shared.v2.b32 {c2,c3}, [%64+4096];\n"
        "ld.volatile.shared.v2.b32 {c4,c5}, [%64+8];\nld.volatile.shared.v2.b32 {c6,c7}, [%64+4104];\ndp2a.lo.u32.u32 t, c0, 0x04000004, 0x200000;\n"
        "mov.b64 d0, {t, h};\ndp2a.hi.u32.u32 t, c0, 0x04000004, 0x200000;\nmov.b64 d1, {t, h};\ndp2a.lo.u32.u32 t, c1, 0x04000004, 0x200000;\n"
        "mov.b64 d2, {t, h};\ndp2a.hi.u32.u32 t, c1, 0x04000004, 0x200000;\nmov.b64 d3, {t, h};\ndp2a.lo.u32.u32 t, c2, 0x04000004, 0x200000;\n"
        "mov.b64 d4, {t, h};\ndp2a.hi.u32.u32 t, c2, 0x04000004, 0x200000;\nmov.b64 d5, {t, h};\ndp2a.lo.u32.u32 t, c3, 0x04000004, 0x200000;\n"
        "mov.b64 d6, {t, h};\ndp2a.hi.u32.u32 t, c3, 0x04000004, 0x200000;\nmov.b64 d7, {t, h};\ndp2a.lo.u32.u32 t, c4, 0x04000004, 0x200000;\n"
        "mov.b64 d8, {t, h};\ndp2a.hi.u32.u32 t, c4, 0x04000004, 0x200000;\nmov.b64 d9, {t, h};\ndp2a.lo.u32.u32 t, c5, 0x04000004, 0x200000;\n"
        "mov.b64 d10, {t, h};\ndp2a.hi.u32.u32 t, c5, 0x04000004, 0x200000;\nmov.b64 d11, {t, h};\ndp2a.lo.u32.u32 t, c6, 0x04000004, 0x200000;\n"
        "mov.b64 d12, {t, h};\ndp2a.hi.u32.u32 t, c6, 0x04000004, 0x200000;\nmov.b64 d13, {t, h};\ndp2a.lo.u32.u32 t, c7, 0x04000004, 0x200000;\n"
        "mov.b64 d14, {t, h};\ndp2a.hi.u32.u32 t, c7, 0x04000004, 0x200000;\nmov.b64 d15, {t, h};\nmovmatrix.sync.aligned.m8n8.trans.b16 a0, %0;\n"
        "movmatrix.sync.aligned.m8n8.trans.b16 a1, %16;\nmovmatrix.sync.aligned.m8n8.trans.b16 a2, %1;\nmovmatrix.sync.aligned.m8n8.trans.b16 a3, %17;\n"
        "movmatrix.sync.aligned.m8n8.trans.b16 a4, %2;\nmovmatrix.sync.aligned.m8n8.trans.b16 a5, %18;\nmovmatrix.sync.aligned.m8n8.trans.b16 a6, %3;\n"
        "movmatrix.sync.aligned.m8n8.trans.b16 a7, %19;\nmovmatrix.sync.aligned.m8n8.trans.b16 a8, %4;\nmovmatrix.sync.aligned.m8n8.trans.b16 a9, %20;\n"
        "movmatrix.sync.aligned.m8n8.trans.b16 a10, %5;\nmovmatrix.sync.aligned.m8n8.trans.b16 a11, %21;\nmovmatrix.sync.aligned.m8n8.trans.b16 a12, %6;\n"
        "movmatrix.sync.aligned.m8n8.trans.b16 a13, %22;\nmovmatrix.sync.aligned.m8n8.trans.b16 a14, %7;\nmovmatrix.sync.aligned.m8n8.trans.b16 a15, %23;\n"
        "movmatrix.sync.aligned.m8n8.trans.b16 a16, %8;\nmovmatrix.sync.aligned.m8n8.trans.b16 a17, %24;\nmovmatrix.sync.aligned.m8n8.trans.b16 a18, %9;\n"
        "movmatrix.sync.aligned.m8n8.trans.b16 a19, %25;\nmovmatrix.sync.aligned.m8n8.trans.b16 a20, %10;\nmovmatrix.sync.aligned.m8n8.trans.b16 a21, %26;\n"
        "movmatrix.sync.aligned.m8n8.trans.b16 a22, %11;\nmovmatrix.sync.aligned.m8n8.trans.b16 a23, %27;\nmovmatrix.sync.aligned.m8n8.trans.b16 a24, %12;\n"
        "movmatrix.sync.aligned.m8n8.trans.b16 a25, %28;\nmovmatrix.sync.aligned.m8n8.trans.b16 a26, %13;\nmovmatrix.sync.aligned.m8n8.trans.b16 a27, %29;\n"
        "movmatrix.sync.aligned.m8n8.trans.b16 a28, %14;\nmovmatrix.sync.aligned.m8n8.trans.b16 a29, %30;\nmovmatrix.sync.aligned.m8n8.trans.b16 a30, %15;\n"
        "movmatrix.sync.aligned.m8n8.trans.b16 a31, %31;\nwgmma.fence.sync.aligned;\n"
        "wgmma.mma_async.sync.aligned.m64n32k16.f32.bf16.bf16 {o0,o1,o2,o3,o4,o5,o6,o7,o8,o9,o10,o11,o12,o13,o14,o15}, {a0,a1,a2,a3}, d0, p0, 1, 1, 1;\n"
        "wgmma.mma_async.sync.aligned.m64n32k16.f32.bf16.bf16 {o0,o1,o2,o3,o4,o5,o6,o7,o8,o9,o10,o11,o12,o13,o14,o15}, {a4,a5,a6,a7}, d1, p1, 1, 1, 1;\n"
        "wgmma.mma_async.sync.aligned.m64n32k16.f32.bf16.bf16 {o0,o1,o2,o3,o4,o5,o6,o7,o8,o9,o10,o11,o12,o13,o14,o15}, {a8,a9,a10,a11}, d2, p1, 1, 1, 1;\n"
        "wgmma.mma_async.sync.aligned.m64n32k16.f32.bf16.bf16 {o0,o1,o2,o3,o4,o5,o6,o7,o8,o9,o10,o11,o12,o13,o14,o15}, {a12,a13,a14,a15}, d3, p1, 1, 1, 1;\n"
        "wgmma.mma_async.sync.aligned.m64n32k16.f32.bf16.bf16 {o0,o1,o2,o3,o4,o5,o6,o7,o8,o9,o10,o11,o12,o13,o14,o15}, {a16,a17,a18,a19}, d4, p1, 1, 1, 1;\n"
        "wgmma.mma_async.sync.aligned.m64n32k16.f32.bf16.bf16 {o0,o1,o2,o3,o4,o5,o6,o7,o8,o9,o10,o11,o12,o13,o14,o15}, {a20,a21,a22,a23}, d5, p1, 1, 1, 1;\n"
        "wgmma.mma_async.sync.aligned.m64n32k16.f32.bf16.bf16 {o0,o1,o2,o3,o4,o5,o6,o7,o8,o9,o10,o11,o12,o13,o14,o15}, {a24,a25,a26,a27}, d6, p1, 1, 1, 1;\n"
        "wgmma.mma_async.sync.aligned.m64n32k16.f32.bf16.bf16 {o0,o1,o2,o3,o4,o5,o6,o7,o8,o9,o10,o11,o12,o13,o14,o15}, {a28,a29,a30,a31}, d7, p1, 1, 1, 1;\n"
        "wgmma.commit_group.sync.aligned;\n"
        "wgmma.mma_async.sync.aligned.m64n32k16.f32.bf16.bf16 {o16,o17,o18,o19,o20,o21,o22,o23,o24,o25,o26,o27,o28,o29,o30,o31}, {a0,a1,a2,a3}, d8, p0, 1, 1, 1;\n"
        "wgmma.mma_async.sync.aligned.m64n32k16.f32.bf16.bf16 {o16,o17,o18,o19,o20,o21,o22,o23,o24,o25,o26,o27,o28,o29,o30,o31}, {a4,a5,a6,a7}, d9, p1, 1, 1, 1;\n"
        "wgmma.mma_async.sync.aligned.m64n32k16.f32.bf16.bf16 {o16,o17,o18,o19,o20,o21,o22,o23,o24,o25,o26,o27,o28,o29,o30,o31}, {a8,a9,a10,a11}, d10, p1, 1, 1, 1;\n"
        "wgmma.mma_async.sync.aligned.m64n32k16.f32.bf16.bf16 {o16,o17,o18,o19,o20,o21,o22,o23,o24,o25,o26,o27,o28,o29,o30,o31}, {a12,a13,a14,a15}, d11, p1, 1, 1, 1;\n"
        "wgmma.mma_async.sync.aligned.m64n32k16.f32.bf16.bf16 {o16,o17,o18,o19,o20,o21,o22,o23,o24,o25,o26,o27,o28,o29,o30,o31}, {a16,a17,a18,a19}, d12, p1, 1, 1, 1;\n"
        "wgmma.mma_async.sync.aligned.m64n32k16.f32.bf16.bf16 {o16,o17,o18,o19,o20,o21,o22,o23,o24,o25,o26,o27,o28,o29,o30,o31}, {a20,a21,a22,a23}, d13, p1, 1, 1, 1;\n"
        "wgmma.mma_async.sync.aligned.m64n32k16.f32.bf16.bf16 {o16,o17,o18,o19,o20,o21,o22,o23,o24,o25,o26,o27,o28,o29,o30,o31}, {a24,a25,a26,a27}, d14, p1, 1, 1, 1;\n"
        "wgmma.mma_async.sync.aligned.m64n32k16.f32.bf16.bf16 {o16,o17,o18,o19,o20,o21,o22,o23,o24,o25,o26,o27,o28,o29,o30,o31}, {a28,a29,a30,a31}, d15, p1, 1, 1, 1;\n"
        "wgmma.commit_group.sync.aligned;\nwgmma.wait_group.sync.aligned 1;\ncvt.rn.bf16x2.f32 k0, o1, o0;\ncvt.rn.bf16x2.f32 k1, o5, o4;\n"
        "cvt.rn.bf16x2.f32 k2, o9, o8;\ncvt.rn.bf16x2.f32 k3, o13, o12;\n@s0 st.global.v4.b32 [%65+0], {k0,k1,k2,k3};\ncvt.rn.bf16x2.f32 k4, o3, o2;\n"
        "cvt.rn.bf16x2.f32 k5, o7, o6;\ncvt.rn.bf16x2.f32 k6, o11, o10;\ncvt.rn.bf16x2.f32 k7, o15, o14;\n@s1 st.global.v4.b32 [%66+0], {k4,k5,k6,k7};\n"
        "@nv bra.uni END;\nwgmma.wait_group.sync.aligned 0;\ncvt.rn.bf16x2.f32 k8, o17, o16;\ncvt.rn.bf16x2.f32 k9, o21, o20;\ncvt.rn.bf16x2.f32 k10, o25, o24;\n"
        "cvt.rn.bf16x2.f32 k11, o29, o28;\n@s0 st.global.v4.b32 [%65+64], {k8,k9,k10,k11};\ncvt.rn.bf16x2.f32 k12, o19, o18;\ncvt.rn.bf16x2.f32 k13, o23, o22;\n"
        "cvt.rn.bf16x2.f32 k14, o27, o26;\ncvt.rn.bf16x2.f32 k15, o31, o30;\n@s1 st.global.v4.b32 [%66+64], {k12,k13,k14,k15};\n@nv bra.uni END;\n"
        "ld.volatile.shared.v2.b32 {c0,c1}, [%64+16];\nld.volatile.shared.v2.b32 {c2,c3}, [%64+4112];\nld.volatile.shared.v2.b32 {c4,c5}, [%64+24];\n"
        "ld.volatile.shared.v2.b32 {c6,c7}, [%64+4120];\ndp2a.lo.u32.u32 t, c0, 0x04000004, 0x200000;\nmov.b64 d0, {t, h};\n"
        "dp2a.hi.u32.u32 t, c0, 0x04000004, 0x200000;\nmov.b64 d1, {t, h};\ndp2a.lo.u32.u32 t, c1, 0x04000004, 0x200000;\nmov.b64 d2, {t, h};\n"
        "dp2a.hi.u32.u32 t, c1, 0x04000004, 0x200000;\nmov.b64 d3, {t, h};\ndp2a.lo.u32.u32 t, c2, 0x04000004, 0x200000;\nmov.b64 d4, {t, h};\n"
        "dp2a.hi.u32.u32 t, c2, 0x04000004, 0x200000;\nmov.b64 d5, {t, h};\ndp2a.lo.u32.u32 t, c3, 0x04000004, 0x200000;\nmov.b64 d6, {t, h};\n"
        "dp2a.hi.u32.u32 t, c3, 0x04000004, 0x200000;\nmov.b64 d7, {t, h};\ndp2a.lo.u32.u32 t, c4, 0x04000004, 0x200000;\nmov.b64 d8, {t, h};\n"
        "dp2a.hi.u32.u32 t, c4, 0x04000004, 0x200000;\nmov.b64 d9, {t, h};\ndp2a.lo.u32.u32 t, c5, 0x04000004, 0x200000;\nmov.b64 d10, {t, h};\n"
        "dp2a.hi.u32.u32 t, c5, 0x04000004, 0x200000;\nmov.b64 d11, {t, h};\ndp2a.lo.u32.u32 t, c6, 0x04000004, 0x200000;\nmov.b64 d12, {t, h};\n"
        "dp2a.hi.u32.u32 t, c6, 0x04000004, 0x200000;\nmov.b64 d13, {t, h};\ndp2a.lo.u32.u32 t, c7, 0x04000004, 0x200000;\nmov.b64 d14, {t, h};\n"
        "dp2a.hi.u32.u32 t, c7, 0x04000004, 0x200000;\nmov.b64 d15, {t, h};\nwgmma.fence.sync.aligned;\n"
        "wgmma.mma_async.sync.aligned.m64n32k16.f32.bf16.bf16 {o0,o1,o2,o3,o4,o5,o6,o7,o8,o9,o10,o11,o12,o13,o14,o15}, {a0,a1,a2,a3}, d0, p0, 1, 1, 1;\n"
        "wgmma.mma_async.sync.aligned.m64n32k16.f32.bf16.bf16 {o16,o17,o18,o19,o20,o21,o22,o23,o24,o25,o26,o27,o28,o29,o30,o31}, {a0,a1,a2,a3}, d8, p0, 1, 1, 1;\n"
        "wgmma.mma_async.sync.aligned.m64n32k16.f32.bf16.bf16 {o0,o1,o2,o3,o4,o5,o6,o7,o8,o9,o10,o11,o12,o13,o14,o15}, {a4,a5,a6,a7}, d1, p1, 1, 1, 1;\n"
        "wgmma.mma_async.sync.aligned.m64n32k16.f32.bf16.bf16 {o16,o17,o18,o19,o20,o21,o22,o23,o24,o25,o26,o27,o28,o29,o30,o31}, {a4,a5,a6,a7}, d9, p1, 1, 1, 1;\n"
        "wgmma.mma_async.sync.aligned.m64n32k16.f32.bf16.bf16 {o0,o1,o2,o3,o4,o5,o6,o7,o8,o9,o10,o11,o12,o13,o14,o15}, {a8,a9,a10,a11}, d2, p1, 1, 1, 1;\n"
        "wgmma.mma_async.sync.aligned.m64n32k16.f32.bf16.bf16 {o16,o17,o18,o19,o20,o21,o22,o23,o24,o25,o26,o27,o28,o29,o30,o31}, {a8,a9,a10,a11}, d10, p1, 1, 1, 1;\n"
        "wgmma.mma_async.sync.aligned.m64n32k16.f32.bf16.bf16 {o0,o1,o2,o3,o4,o5,o6,o7,o8,o9,o10,o11,o12,o13,o14,o15}, {a12,a13,a14,a15}, d3, p1, 1, 1, 1;\n"
        "wgmma.mma_async.sync.aligned.m64n32k16.f32.bf16.bf16 {o16,o17,o18,o19,o20,o21,o22,o23,o24,o25,o26,o27,o28,o29,o30,o31}, {a12,a13,a14,a15}, d11, p1, 1, 1, 1;\n"
        "wgmma.mma_async.sync.aligned.m64n32k16.f32.bf16.bf16 {o0,o1,o2,o3,o4,o5,o6,o7,o8,o9,o10,o11,o12,o13,o14,o15}, {a16,a17,a18,a19}, d4, p1, 1, 1, 1;\n"
        "wgmma.mma_async.sync.aligned.m64n32k16.f32.bf16.bf16 {o16,o17,o18,o19,o20,o21,o22,o23,o24,o25,o26,o27,o28,o29,o30,o31}, {a16,a17,a18,a19}, d12, p1, 1, 1, 1;\n"
        "wgmma.mma_async.sync.aligned.m64n32k16.f32.bf16.bf16 {o0,o1,o2,o3,o4,o5,o6,o7,o8,o9,o10,o11,o12,o13,o14,o15}, {a20,a21,a22,a23}, d5, p1, 1, 1, 1;\n"
        "wgmma.mma_async.sync.aligned.m64n32k16.f32.bf16.bf16 {o16,o17,o18,o19,o20,o21,o22,o23,o24,o25,o26,o27,o28,o29,o30,o31}, {a20,a21,a22,a23}, d13, p1, 1, 1, 1;\n"
        "wgmma.mma_async.sync.aligned.m64n32k16.f32.bf16.bf16 {o0,o1,o2,o3,o4,o5,o6,o7,o8,o9,o10,o11,o12,o13,o14,o15}, {a24,a25,a26,a27}, d6, p1, 1, 1, 1;\n"
        "wgmma.mma_async.sync.aligned.m64n32k16.f32.bf16.bf16 {o16,o17,o18,o19,o20,o21,o22,o23,o24,o25,o26,o27,o28,o29,o30,o31}, {a24,a25,a26,a27}, d14, p1, 1, 1, 1;\n"
        "wgmma.mma_async.sync.aligned.m64n32k16.f32.bf16.bf16 {o0,o1,o2,o3,o4,o5,o6,o7,o8,o9,o10,o11,o12,o13,o14,o15}, {a28,a29,a30,a31}, d7, p1, 1, 1, 1;\n"
        "wgmma.mma_async.sync.aligned.m64n32k16.f32.bf16.bf16 {o16,o17,o18,o19,o20,o21,o22,o23,o24,o25,o26,o27,o28,o29,o30,o31}, {a28,a29,a30,a31}, d15, p1, 1, 1, 1;\n"
        "wgmma.commit_group.sync.aligned;\n@nv bra.uni END;\nmovmatrix.sync.aligned.m8n8.trans.b16 b0, %32;\nmovmatrix.sync.aligned.m8n8.trans.b16 b1, %48;\n"
        "movmatrix.sync.aligned.m8n8.trans.b16 b2, %33;\nmovmatrix.sync.aligned.m8n8.trans.b16 b3, %49;\nmovmatrix.sync.aligned.m8n8.trans.b16 b4, %34;\n"
        "movmatrix.sync.aligned.m8n8.trans.b16 b5, %50;\nmovmatrix.sync.aligned.m8n8.trans.b16 b6, %35;\nmovmatrix.sync.aligned.m8n8.trans.b16 b7, %51;\n"
        "movmatrix.sync.aligned.m8n8.trans.b16 b8, %36;\nmovmatrix.sync.aligned.m8n8.trans.b16 b9, %52;\nmovmatrix.sync.aligned.m8n8.trans.b16 b10, %37;\n"
        "movmatrix.sync.aligned.m8n8.trans.b16 b11, %53;\nmovmatrix.sync.aligned.m8n8.trans.b16 b12, %38;\nmovmatrix.sync.aligned.m8n8.trans.b16 b13, %54;\n"
        "movmatrix.sync.aligned.m8n8.trans.b16 b14, %39;\nmovmatrix.sync.aligned.m8n8.trans.b16 b15, %55;\nmovmatrix.sync.aligned.m8n8.trans.b16 b16, %40;\n"
        "movmatrix.sync.aligned.m8n8.trans.b16 b17, %56;\nmovmatrix.sync.aligned.m8n8.trans.b16 b18, %41;\nmovmatrix.sync.aligned.m8n8.trans.b16 b19, %57;\n"
        "movmatrix.sync.aligned.m8n8.trans.b16 b20, %42;\nmovmatrix.sync.aligned.m8n8.trans.b16 b21, %58;\nmovmatrix.sync.aligned.m8n8.trans.b16 b22, %43;\n"
        "movmatrix.sync.aligned.m8n8.trans.b16 b23, %59;\nmovmatrix.sync.aligned.m8n8.trans.b16 b24, %44;\nmovmatrix.sync.aligned.m8n8.trans.b16 b25, %60;\n"
        "movmatrix.sync.aligned.m8n8.trans.b16 b26, %45;\nmovmatrix.sync.aligned.m8n8.trans.b16 b27, %61;\nmovmatrix.sync.aligned.m8n8.trans.b16 b28, %46;\n"
        "movmatrix.sync.aligned.m8n8.trans.b16 b29, %62;\nmovmatrix.sync.aligned.m8n8.trans.b16 b30, %47;\nmovmatrix.sync.aligned.m8n8.trans.b16 b31, %63;\n"
        "@nv bra.uni END;\nwgmma.wait_group.sync.aligned 0;\ncvt.rn.bf16x2.f32 k0, o1, o0;\ncvt.rn.bf16x2.f32 k1, o5, o4;\ncvt.rn.bf16x2.f32 k2, o9, o8;\n"
        "cvt.rn.bf16x2.f32 k3, o13, o12;\ncvt.rn.bf16x2.f32 k4, o3, o2;\ncvt.rn.bf16x2.f32 k5, o7, o6;\ncvt.rn.bf16x2.f32 k6, o11, o10;\n"
        "cvt.rn.bf16x2.f32 k7, o15, o14;\ncvt.rn.bf16x2.f32 k8, o17, o16;\ncvt.rn.bf16x2.f32 k9, o21, o20;\ncvt.rn.bf16x2.f32 k10, o25, o24;\n"
        "cvt.rn.bf16x2.f32 k11, o29, o28;\ncvt.rn.bf16x2.f32 k12, o19, o18;\ncvt.rn.bf16x2.f32 k13, o23, o22;\ncvt.rn.bf16x2.f32 k14, o27, o26;\n"
        "cvt.rn.bf16x2.f32 k15, o31, o30;\nld.volatile.shared.v2.b32 {c0,c1}, [%64+0];\nld.volatile.shared.v2.b32 {c2,c3}, [%64+4096];\n"
        "ld.volatile.shared.v2.b32 {c4,c5}, [%64+8];\nld.volatile.shared.v2.b32 {c6,c7}, [%64+4104];\ndp2a.lo.u32.u32 t, c0, 0x04000004, 0x200000;\n"
        "mov.b64 d0, {t, h};\ndp2a.hi.u32.u32 t, c0, 0x04000004, 0x200000;\nmov.b64 d1, {t, h};\ndp2a.lo.u32.u32 t, c1, 0x04000004, 0x200000;\n"
        "mov.b64 d2, {t, h};\ndp2a.hi.u32.u32 t, c1, 0x04000004, 0x200000;\nmov.b64 d3, {t, h};\ndp2a.lo.u32.u32 t, c2, 0x04000004, 0x200000;\n"
        "mov.b64 d4, {t, h};\ndp2a.hi.u32.u32 t, c2, 0x04000004, 0x200000;\nmov.b64 d5, {t, h};\ndp2a.lo.u32.u32 t, c3, 0x04000004, 0x200000;\n"
        "mov.b64 d6, {t, h};\ndp2a.hi.u32.u32 t, c3, 0x04000004, 0x200000;\nmov.b64 d7, {t, h};\ndp2a.lo.u32.u32 t, c4, 0x04000004, 0x200000;\n"
        "mov.b64 d8, {t, h};\ndp2a.hi.u32.u32 t, c4, 0x04000004, 0x200000;\nmov.b64 d9, {t, h};\ndp2a.lo.u32.u32 t, c5, 0x04000004, 0x200000;\n"
        "mov.b64 d10, {t, h};\ndp2a.hi.u32.u32 t, c5, 0x04000004, 0x200000;\nmov.b64 d11, {t, h};\ndp2a.lo.u32.u32 t, c6, 0x04000004, 0x200000;\n"
        "mov.b64 d12, {t, h};\ndp2a.hi.u32.u32 t, c6, 0x04000004, 0x200000;\nmov.b64 d13, {t, h};\ndp2a.lo.u32.u32 t, c7, 0x04000004, 0x200000;\n"
        "mov.b64 d14, {t, h};\ndp2a.hi.u32.u32 t, c7, 0x04000004, 0x200000;\nmov.b64 d15, {t, h};\nwgmma.fence.sync.aligned;\n"
        "wgmma.mma_async.sync.aligned.m64n32k16.f32.bf16.bf16 {o0,o1,o2,o3,o4,o5,o6,o7,o8,o9,o10,o11,o12,o13,o14,o15}, {b0,b1,b2,b3}, d0, p0, 1, 1, 1;\n"
        "wgmma.mma_async.sync.aligned.m64n32k16.f32.bf16.bf16 {o16,o17,o18,o19,o20,o21,o22,o23,o24,o25,o26,o27,o28,o29,o30,o31}, {b0,b1,b2,b3}, d8, p0, 1, 1, 1;\n"
        "wgmma.mma_async.sync.aligned.m64n32k16.f32.bf16.bf16 {o0,o1,o2,o3,o4,o5,o6,o7,o8,o9,o10,o11,o12,o13,o14,o15}, {b4,b5,b6,b7}, d1, p1, 1, 1, 1;\n"
        "wgmma.mma_async.sync.aligned.m64n32k16.f32.bf16.bf16 {o16,o17,o18,o19,o20,o21,o22,o23,o24,o25,o26,o27,o28,o29,o30,o31}, {b4,b5,b6,b7}, d9, p1, 1, 1, 1;\n"
        "wgmma.mma_async.sync.aligned.m64n32k16.f32.bf16.bf16 {o0,o1,o2,o3,o4,o5,o6,o7,o8,o9,o10,o11,o12,o13,o14,o15}, {b8,b9,b10,b11}, d2, p1, 1, 1, 1;\n"
        "wgmma.mma_async.sync.aligned.m64n32k16.f32.bf16.bf16 {o16,o17,o18,o19,o20,o21,o22,o23,o24,o25,o26,o27,o28,o29,o30,o31}, {b8,b9,b10,b11}, d10, p1, 1, 1, 1;\n"
        "wgmma.mma_async.sync.aligned.m64n32k16.f32.bf16.bf16 {o0,o1,o2,o3,o4,o5,o6,o7,o8,o9,o10,o11,o12,o13,o14,o15}, {b12,b13,b14,b15}, d3, p1, 1, 1, 1;\n"
        "wgmma.mma_async.sync.aligned.m64n32k16.f32.bf16.bf16 {o16,o17,o18,o19,o20,o21,o22,o23,o24,o25,o26,o27,o28,o29,o30,o31}, {b12,b13,b14,b15}, d11, p1, 1, 1, 1;\n"
        "wgmma.mma_async.sync.aligned.m64n32k16.f32.bf16.bf16 {o0,o1,o2,o3,o4,o5,o6,o7,o8,o9,o10,o11,o12,o13,o14,o15}, {b16,b17,b18,b19}, d4, p1, 1, 1, 1;\n"
        "wgmma.mma_async.sync.aligned.m64n32k16.f32.bf16.bf16 {o16,o17,o18,o19,o20,o21,o22,o23,o24,o25,o26,o27,o28,o29,o30,o31}, {b16,b17,b18,b19}, d12, p1, 1, 1, 1;\n"
        "wgmma.mma_async.sync.aligned.m64n32k16.f32.bf16.bf16 {o0,o1,o2,o3,o4,o5,o6,o7,o8,o9,o10,o11,o12,o13,o14,o15}, {b20,b21,b22,b23}, d5, p1, 1, 1, 1;\n"
        "wgmma.mma_async.sync.aligned.m64n32k16.f32.bf16.bf16 {o16,o17,o18,o19,o20,o21,o22,o23,o24,o25,o26,o27,o28,o29,o30,o31}, {b20,b21,b22,b23}, d13, p1, 1, 1, 1;\n"
        "wgmma.mma_async.sync.aligned.m64n32k16.f32.bf16.bf16 {o0,o1,o2,o3,o4,o5,o6,o7,o8,o9,o10,o11,o12,o13,o14,o15}, {b24,b25,b26,b27}, d6, p1, 1, 1, 1;\n"
        "wgmma.mma_async.sync.aligned.m64n32k16.f32.bf16.bf16 {o16,o17,o18,o19,o20,o21,o22,o23,o24,o25,o26,o27,o28,o29,o30,o31}, {b24,b25,b26,b27}, d14, p1, 1, 1, 1;\n"
        "wgmma.mma_async.sync.aligned.m64n32k16.f32.bf16.bf16 {o0,o1,o2,o3,o4,o5,o6,o7,o8,o9,o10,o11,o12,o13,o14,o15}, {b28,b29,b30,b31}, d7, p1, 1, 1, 1;\n"
        "wgmma.mma_async.sync.aligned.m64n32k16.f32.bf16.bf16 {o16,o17,o18,o19,o20,o21,o22,o23,o24,o25,o26,o27,o28,o29,o30,o31}, {b28,b29,b30,b31}, d15, p1, 1, 1, 1;\n"
        "wgmma.commit_group.sync.aligned;\n@nv bra.uni END;\n@s0 st.global.v4.b32 [%65+128], {k0,k1,k2,k3};\n@s1 st.global.v4.b32 [%66+128], {k4,k5,k6,k7};\n"
        "@s0 st.global.v4.b32 [%65+192], {k8,k9,k10,k11};\n@s1 st.global.v4.b32 [%66+192], {k12,k13,k14,k15};\n@nv bra.uni END;\n"
        "wgmma.wait_group.sync.aligned 0;\ncvt.rn.bf16x2.f32 k0, o1, o0;\ncvt.rn.bf16x2.f32 k1, o5, o4;\ncvt.rn.bf16x2.f32 k2, o9, o8;\n"
        "cvt.rn.bf16x2.f32 k3, o13, o12;\ncvt.rn.bf16x2.f32 k4, o3, o2;\ncvt.rn.bf16x2.f32 k5, o7, o6;\ncvt.rn.bf16x2.f32 k6, o11, o10;\n"
        "cvt.rn.bf16x2.f32 k7, o15, o14;\ncvt.rn.bf16x2.f32 k8, o17, o16;\ncvt.rn.bf16x2.f32 k9, o21, o20;\ncvt.rn.bf16x2.f32 k10, o25, o24;\n"
        "cvt.rn.bf16x2.f32 k11, o29, o28;\ncvt.rn.bf16x2.f32 k12, o19, o18;\ncvt.rn.bf16x2.f32 k13, o23, o22;\ncvt.rn.bf16x2.f32 k14, o27, o26;\n"
        "cvt.rn.bf16x2.f32 k15, o31, o30;\nld.volatile.shared.v2.b32 {c0,c1}, [%64+16];\nld.volatile.shared.v2.b32 {c2,c3}, [%64+4112];\n"
        "ld.volatile.shared.v2.b32 {c4,c5}, [%64+24];\nld.volatile.shared.v2.b32 {c6,c7}, [%64+4120];\ndp2a.lo.u32.u32 t, c0, 0x04000004, 0x200000;\n"
        "mov.b64 d0, {t, h};\ndp2a.hi.u32.u32 t, c0, 0x04000004, 0x200000;\nmov.b64 d1, {t, h};\ndp2a.lo.u32.u32 t, c1, 0x04000004, 0x200000;\n"
        "mov.b64 d2, {t, h};\ndp2a.hi.u32.u32 t, c1, 0x04000004, 0x200000;\nmov.b64 d3, {t, h};\ndp2a.lo.u32.u32 t, c2, 0x04000004, 0x200000;\n"
        "mov.b64 d4, {t, h};\ndp2a.hi.u32.u32 t, c2, 0x04000004, 0x200000;\nmov.b64 d5, {t, h};\ndp2a.lo.u32.u32 t, c3, 0x04000004, 0x200000;\n"
        "mov.b64 d6, {t, h};\ndp2a.hi.u32.u32 t, c3, 0x04000004, 0x200000;\nmov.b64 d7, {t, h};\ndp2a.lo.u32.u32 t, c4, 0x04000004, 0x200000;\n"
        "mov.b64 d8, {t, h};\ndp2a.hi.u32.u32 t, c4, 0x04000004, 0x200000;\nmov.b64 d9, {t, h};\ndp2a.lo.u32.u32 t, c5, 0x04000004, 0x200000;\n"
        "mov.b64 d10, {t, h};\ndp2a.hi.u32.u32 t, c5, 0x04000004, 0x200000;\nmov.b64 d11, {t, h};\ndp2a.lo.u32.u32 t, c6, 0x04000004, 0x200000;\n"
        "mov.b64 d12, {t, h};\ndp2a.hi.u32.u32 t, c6, 0x04000004, 0x200000;\nmov.b64 d13, {t, h};\ndp2a.lo.u32.u32 t, c7, 0x04000004, 0x200000;\n"
        "mov.b64 d14, {t, h};\ndp2a.hi.u32.u32 t, c7, 0x04000004, 0x200000;\nmov.b64 d15, {t, h};\nwgmma.fence.sync.aligned;\n"
        "wgmma.mma_async.sync.aligned.m64n32k16.f32.bf16.bf16 {o0,o1,o2,o3,o4,o5,o6,o7,o8,o9,o10,o11,o12,o13,o14,o15}, {b0,b1,b2,b3}, d0, p0, 1, 1, 1;\n"
        "wgmma.mma_async.sync.aligned.m64n32k16.f32.bf16.bf16 {o16,o17,o18,o19,o20,o21,o22,o23,o24,o25,o26,o27,o28,o29,o30,o31}, {b0,b1,b2,b3}, d8, p0, 1, 1, 1;\n"
        "wgmma.mma_async.sync.aligned.m64n32k16.f32.bf16.bf16 {o0,o1,o2,o3,o4,o5,o6,o7,o8,o9,o10,o11,o12,o13,o14,o15}, {b4,b5,b6,b7}, d1, p1, 1, 1, 1;\n"
        "wgmma.mma_async.sync.aligned.m64n32k16.f32.bf16.bf16 {o16,o17,o18,o19,o20,o21,o22,o23,o24,o25,o26,o27,o28,o29,o30,o31}, {b4,b5,b6,b7}, d9, p1, 1, 1, 1;\n"
        "wgmma.mma_async.sync.aligned.m64n32k16.f32.bf16.bf16 {o0,o1,o2,o3,o4,o5,o6,o7,o8,o9,o10,o11,o12,o13,o14,o15}, {b8,b9,b10,b11}, d2, p1, 1, 1, 1;\n"
        "wgmma.mma_async.sync.aligned.m64n32k16.f32.bf16.bf16 {o16,o17,o18,o19,o20,o21,o22,o23,o24,o25,o26,o27,o28,o29,o30,o31}, {b8,b9,b10,b11}, d10, p1, 1, 1, 1;\n"
        "wgmma.mma_async.sync.aligned.m64n32k16.f32.bf16.bf16 {o0,o1,o2,o3,o4,o5,o6,o7,o8,o9,o10,o11,o12,o13,o14,o15}, {b12,b13,b14,b15}, d3, p1, 1, 1, 1;\n"
        "wgmma.mma_async.sync.aligned.m64n32k16.f32.bf16.bf16 {o16,o17,o18,o19,o20,o21,o22,o23,o24,o25,o26,o27,o28,o29,o30,o31}, {b12,b13,b14,b15}, d11, p1, 1, 1, 1;\n"
        "wgmma.mma_async.sync.aligned.m64n32k16.f32.bf16.bf16 {o0,o1,o2,o3,o4,o5,o6,o7,o8,o9,o10,o11,o12,o13,o14,o15}, {b16,b17,b18,b19}, d4, p1, 1, 1, 1;\n"
        "wgmma.mma_async.sync.aligned.m64n32k16.f32.bf16.bf16 {o16,o17,o18,o19,o20,o21,o22,o23,o24,o25,o26,o27,o28,o29,o30,o31}, {b16,b17,b18,b19}, d12, p1, 1, 1, 1;\n"
        "wgmma.mma_async.sync.aligned.m64n32k16.f32.bf16.bf16 {o0,o1,o2,o3,o4,o5,o6,o7,o8,o9,o10,o11,o12,o13,o14,o15}, {b20,b21,b22,b23}, d5, p1, 1, 1, 1;\n"
        "wgmma.mma_async.sync.aligned.m64n32k16.f32.bf16.bf16 {o16,o17,o18,o19,o20,o21,o22,o23,o24,o25,o26,o27,o28,o29,o30,o31}, {b20,b21,b22,b23}, d13, p1, 1, 1, 1;\n"
        "wgmma.mma_async.sync.aligned.m64n32k16.f32.bf16.bf16 {o0,o1,o2,o3,o4,o5,o6,o7,o8,o9,o10,o11,o12,o13,o14,o15}, {b24,b25,b26,b27}, d6, p1, 1, 1, 1;\n"
        "wgmma.mma_async.sync.aligned.m64n32k16.f32.bf16.bf16 {o16,o17,o18,o19,o20,o21,o22,o23,o24,o25,o26,o27,o28,o29,o30,o31}, {b24,b25,b26,b27}, d14, p1, 1, 1, 1;\n"
        "wgmma.mma_async.sync.aligned.m64n32k16.f32.bf16.bf16 {o0,o1,o2,o3,o4,o5,o6,o7,o8,o9,o10,o11,o12,o13,o14,o15}, {b28,b29,b30,b31}, d7, p1, 1, 1, 1;\n"
        "wgmma.mma_async.sync.aligned.m64n32k16.f32.bf16.bf16 {o16,o17,o18,o19,o20,o21,o22,o23,o24,o25,o26,o27,o28,o29,o30,o31}, {b28,b29,b30,b31}, d15, p1, 1, 1, 1;\n"
        "wgmma.commit_group.sync.aligned;\n@nv bra.uni END;\n@s2 st.global.v4.b32 [%67+0], {k0,k1,k2,k3};\n@s3 st.global.v4.b32 [%68+0], {k4,k5,k6,k7};\n"
        "@s2 st.global.v4.b32 [%67+64], {k8,k9,k10,k11};\n@s3 st.global.v4.b32 [%68+64], {k12,k13,k14,k15};\n@nv bra.uni END;\nwgmma.wait_group.sync.aligned 0;\n"
        "cvt.rn.bf16x2.f32 k0, o1, o0;\ncvt.rn.bf16x2.f32 k1, o5, o4;\ncvt.rn.bf16x2.f32 k2, o9, o8;\ncvt.rn.bf16x2.f32 k3, o13, o12;\n"
        "cvt.rn.bf16x2.f32 k4, o3, o2;\ncvt.rn.bf16x2.f32 k5, o7, o6;\ncvt.rn.bf16x2.f32 k6, o11, o10;\ncvt.rn.bf16x2.f32 k7, o15, o14;\n"
        "cvt.rn.bf16x2.f32 k8, o17, o16;\ncvt.rn.bf16x2.f32 k9, o21, o20;\ncvt.rn.bf16x2.f32 k10, o25, o24;\ncvt.rn.bf16x2.f32 k11, o29, o28;\n"
        "cvt.rn.bf16x2.f32 k12, o19, o18;\ncvt.rn.bf16x2.f32 k13, o23, o22;\ncvt.rn.bf16x2.f32 k14, o27, o26;\ncvt.rn.bf16x2.f32 k15, o31, o30;\n"
        "@s2 st.global.v4.b32 [%67+128], {k0,k1,k2,k3};\n@s3 st.global.v4.b32 [%68+128], {k4,k5,k6,k7};\n@s2 st.global.v4.b32 [%67+192], {k8,k9,k10,k11};\n"
        "@s3 st.global.v4.b32 [%68+192], {k12,k13,k14,k15};\n"
        "END:\n}\n"
        ::"r"(pk[0]), "r"(pk[1]), "r"(pk[2]), "r"(pk[3]), "r"(pk[4]), "r"(pk[5]), "r"(pk[6]), "r"(pk[7]), "r"(pk[8]), "r"(pk[9]), "r"(pk[10]),
          "r"(pk[11]), "r"(pk[12]), "r"(pk[13]), "r"(pk[14]), "r"(pk[15]), "r"(pk[16]), "r"(pk[17]), "r"(pk[18]), "r"(pk[19]), "r"(pk[20]),
          "r"(pk[21]), "r"(pk[22]), "r"(pk[23]), "r"(pk[24]), "r"(pk[25]), "r"(pk[26]), "r"(pk[27]), "r"(pk[28]), "r"(pk[29]), "r"(pk[30]),
          "r"(pk[31]), "r"(pk[32]), "r"(pk[33]), "r"(pk[34]), "r"(pk[35]), "r"(pk[36]), "r"(pk[37]), "r"(pk[38]), "r"(pk[39]), "r"(pk[40]),
          "r"(pk[41]), "r"(pk[42]), "r"(pk[43]), "r"(pk[44]), "r"(pk[45]), "r"(pk[46]), "r"(pk[47]), "r"(pk[48]), "r"(pk[49]), "r"(pk[50]),
          "r"(pk[51]), "r"(pk[52]), "r"(pk[53]), "r"(pk[54]), "r"(pk[55]), "r"(pk[56]), "r"(pk[57]), "r"(pk[58]), "r"(pk[59]), "r"(pk[60]),
          "r"(pk[61]), "r"(pk[62]), "r"(pk[63]), "r"(ra), "l"(p[0]), "l"(p[1]), "l"(p[2]), "l"(p[3]), "r"(v[0]), "r"(v[1]), "r"(v[2]), "r"(v[3]),
          "r"(ba)
        : "memory");
}
__device__ __forceinline__ void project3(const uint32_t (&pk)[48], uint32_t ra, uint32_t ba, uint4* const (&p)[3], const uint32_t (&v)[3]) {
    asm volatile(
        "{\n.reg .pred p0, p1, q0, q1, nv, s<4>;\n.reg .b32 t, h, c<16>, a<32>, b<32>, k<16>;\n.reg .b64 d<16>;\n.reg .f32 o<32>;\nsetp.ne.b32 p0, 0, 0;\n"
        "setp.eq.b32 p1, 0, 0;\nmov.b32 h, 8;\nsetp.eq.u32 nv, %48, 0;\nvote.sync.any.pred nv, nv, 0xffffffff;\nsetp.ne.b32 s0, %52, 0;\n"
        "setp.ne.b32 s1, %53, 0;\nsetp.ne.b32 s2, %54, 0;\nmov.b32 t, 0;\n"
        "W0:\nmbarrier.try_wait.parity.shared.b64 q0, [%55], 0;\nvote.sync.all.pred q0, q0, 0xffffffff;\nadd.u32 t, t, 1;\nsetp.lt.and.u32 q1, t, 1000000, !q0;\n"
        "@q1 bra.uni W0;\nld.volatile.shared.v2.b32 {c0,c1}, [%48+0];\nld.volatile.shared.v2.b32 {c2,c3}, [%48+4096];\n"
        "ld.volatile.shared.v2.b32 {c4,c5}, [%48+8];\nld.volatile.shared.v2.b32 {c6,c7}, [%48+4104];\ndp2a.lo.u32.u32 t, c0, 0x04000004, 0x200000;\n"
        "mov.b64 d0, {t, h};\ndp2a.hi.u32.u32 t, c0, 0x04000004, 0x200000;\nmov.b64 d1, {t, h};\ndp2a.lo.u32.u32 t, c1, 0x04000004, 0x200000;\n"
        "mov.b64 d2, {t, h};\ndp2a.hi.u32.u32 t, c1, 0x04000004, 0x200000;\nmov.b64 d3, {t, h};\ndp2a.lo.u32.u32 t, c2, 0x04000004, 0x200000;\n"
        "mov.b64 d4, {t, h};\ndp2a.hi.u32.u32 t, c2, 0x04000004, 0x200000;\nmov.b64 d5, {t, h};\ndp2a.lo.u32.u32 t, c3, 0x04000004, 0x200000;\n"
        "mov.b64 d6, {t, h};\ndp2a.hi.u32.u32 t, c3, 0x04000004, 0x200000;\nmov.b64 d7, {t, h};\ndp2a.lo.u32.u32 t, c4, 0x04000004, 0x200000;\n"
        "mov.b64 d8, {t, h};\ndp2a.hi.u32.u32 t, c4, 0x04000004, 0x200000;\nmov.b64 d9, {t, h};\ndp2a.lo.u32.u32 t, c5, 0x04000004, 0x200000;\n"
        "mov.b64 d10, {t, h};\ndp2a.hi.u32.u32 t, c5, 0x04000004, 0x200000;\nmov.b64 d11, {t, h};\ndp2a.lo.u32.u32 t, c6, 0x04000004, 0x200000;\n"
        "mov.b64 d12, {t, h};\ndp2a.hi.u32.u32 t, c6, 0x04000004, 0x200000;\nmov.b64 d13, {t, h};\ndp2a.lo.u32.u32 t, c7, 0x04000004, 0x200000;\n"
        "mov.b64 d14, {t, h};\ndp2a.hi.u32.u32 t, c7, 0x04000004, 0x200000;\nmov.b64 d15, {t, h};\nmovmatrix.sync.aligned.m8n8.trans.b16 a0, %0;\n"
        "movmatrix.sync.aligned.m8n8.trans.b16 a1, %16;\nmovmatrix.sync.aligned.m8n8.trans.b16 a2, %1;\nmovmatrix.sync.aligned.m8n8.trans.b16 a3, %17;\n"
        "movmatrix.sync.aligned.m8n8.trans.b16 a4, %2;\nmovmatrix.sync.aligned.m8n8.trans.b16 a5, %18;\nmovmatrix.sync.aligned.m8n8.trans.b16 a6, %3;\n"
        "movmatrix.sync.aligned.m8n8.trans.b16 a7, %19;\nmovmatrix.sync.aligned.m8n8.trans.b16 a8, %4;\nmovmatrix.sync.aligned.m8n8.trans.b16 a9, %20;\n"
        "movmatrix.sync.aligned.m8n8.trans.b16 a10, %5;\nmovmatrix.sync.aligned.m8n8.trans.b16 a11, %21;\nmovmatrix.sync.aligned.m8n8.trans.b16 a12, %6;\n"
        "movmatrix.sync.aligned.m8n8.trans.b16 a13, %22;\nmovmatrix.sync.aligned.m8n8.trans.b16 a14, %7;\nmovmatrix.sync.aligned.m8n8.trans.b16 a15, %23;\n"
        "movmatrix.sync.aligned.m8n8.trans.b16 a16, %8;\nmovmatrix.sync.aligned.m8n8.trans.b16 a17, %24;\nmovmatrix.sync.aligned.m8n8.trans.b16 a18, %9;\n"
        "movmatrix.sync.aligned.m8n8.trans.b16 a19, %25;\nmovmatrix.sync.aligned.m8n8.trans.b16 a20, %10;\nmovmatrix.sync.aligned.m8n8.trans.b16 a21, %26;\n"
        "movmatrix.sync.aligned.m8n8.trans.b16 a22, %11;\nmovmatrix.sync.aligned.m8n8.trans.b16 a23, %27;\nmovmatrix.sync.aligned.m8n8.trans.b16 a24, %12;\n"
        "movmatrix.sync.aligned.m8n8.trans.b16 a25, %28;\nmovmatrix.sync.aligned.m8n8.trans.b16 a26, %13;\nmovmatrix.sync.aligned.m8n8.trans.b16 a27, %29;\n"
        "movmatrix.sync.aligned.m8n8.trans.b16 a28, %14;\nmovmatrix.sync.aligned.m8n8.trans.b16 a29, %30;\nmovmatrix.sync.aligned.m8n8.trans.b16 a30, %15;\n"
        "movmatrix.sync.aligned.m8n8.trans.b16 a31, %31;\nwgmma.fence.sync.aligned;\n"
        "wgmma.mma_async.sync.aligned.m64n32k16.f32.bf16.bf16 {o0,o1,o2,o3,o4,o5,o6,o7,o8,o9,o10,o11,o12,o13,o14,o15}, {a0,a1,a2,a3}, d0, p0, 1, 1, 1;\n"
        "wgmma.mma_async.sync.aligned.m64n32k16.f32.bf16.bf16 {o0,o1,o2,o3,o4,o5,o6,o7,o8,o9,o10,o11,o12,o13,o14,o15}, {a4,a5,a6,a7}, d1, p1, 1, 1, 1;\n"
        "wgmma.mma_async.sync.aligned.m64n32k16.f32.bf16.bf16 {o0,o1,o2,o3,o4,o5,o6,o7,o8,o9,o10,o11,o12,o13,o14,o15}, {a8,a9,a10,a11}, d2, p1, 1, 1, 1;\n"
        "wgmma.mma_async.sync.aligned.m64n32k16.f32.bf16.bf16 {o0,o1,o2,o3,o4,o5,o6,o7,o8,o9,o10,o11,o12,o13,o14,o15}, {a12,a13,a14,a15}, d3, p1, 1, 1, 1;\n"
        "wgmma.mma_async.sync.aligned.m64n32k16.f32.bf16.bf16 {o0,o1,o2,o3,o4,o5,o6,o7,o8,o9,o10,o11,o12,o13,o14,o15}, {a16,a17,a18,a19}, d4, p1, 1, 1, 1;\n"
        "wgmma.mma_async.sync.aligned.m64n32k16.f32.bf16.bf16 {o0,o1,o2,o3,o4,o5,o6,o7,o8,o9,o10,o11,o12,o13,o14,o15}, {a20,a21,a22,a23}, d5, p1, 1, 1, 1;\n"
        "wgmma.mma_async.sync.aligned.m64n32k16.f32.bf16.bf16 {o0,o1,o2,o3,o4,o5,o6,o7,o8,o9,o10,o11,o12,o13,o14,o15}, {a24,a25,a26,a27}, d6, p1, 1, 1, 1;\n"
        "wgmma.mma_async.sync.aligned.m64n32k16.f32.bf16.bf16 {o0,o1,o2,o3,o4,o5,o6,o7,o8,o9,o10,o11,o12,o13,o14,o15}, {a28,a29,a30,a31}, d7, p1, 1, 1, 1;\n"
        "wgmma.commit_group.sync.aligned;\n"
        "wgmma.mma_async.sync.aligned.m64n32k16.f32.bf16.bf16 {o16,o17,o18,o19,o20,o21,o22,o23,o24,o25,o26,o27,o28,o29,o30,o31}, {a0,a1,a2,a3}, d8, p0, 1, 1, 1;\n"
        "wgmma.mma_async.sync.aligned.m64n32k16.f32.bf16.bf16 {o16,o17,o18,o19,o20,o21,o22,o23,o24,o25,o26,o27,o28,o29,o30,o31}, {a4,a5,a6,a7}, d9, p1, 1, 1, 1;\n"
        "wgmma.mma_async.sync.aligned.m64n32k16.f32.bf16.bf16 {o16,o17,o18,o19,o20,o21,o22,o23,o24,o25,o26,o27,o28,o29,o30,o31}, {a8,a9,a10,a11}, d10, p1, 1, 1, 1;\n"
        "wgmma.mma_async.sync.aligned.m64n32k16.f32.bf16.bf16 {o16,o17,o18,o19,o20,o21,o22,o23,o24,o25,o26,o27,o28,o29,o30,o31}, {a12,a13,a14,a15}, d11, p1, 1, 1, 1;\n"
        "wgmma.mma_async.sync.aligned.m64n32k16.f32.bf16.bf16 {o16,o17,o18,o19,o20,o21,o22,o23,o24,o25,o26,o27,o28,o29,o30,o31}, {a16,a17,a18,a19}, d12, p1, 1, 1, 1;\n"
        "wgmma.mma_async.sync.aligned.m64n32k16.f32.bf16.bf16 {o16,o17,o18,o19,o20,o21,o22,o23,o24,o25,o26,o27,o28,o29,o30,o31}, {a20,a21,a22,a23}, d13, p1, 1, 1, 1;\n"
        "wgmma.mma_async.sync.aligned.m64n32k16.f32.bf16.bf16 {o16,o17,o18,o19,o20,o21,o22,o23,o24,o25,o26,o27,o28,o29,o30,o31}, {a24,a25,a26,a27}, d14, p1, 1, 1, 1;\n"
        "wgmma.mma_async.sync.aligned.m64n32k16.f32.bf16.bf16 {o16,o17,o18,o19,o20,o21,o22,o23,o24,o25,o26,o27,o28,o29,o30,o31}, {a28,a29,a30,a31}, d15, p1, 1, 1, 1;\n"
        "wgmma.commit_group.sync.aligned;\nwgmma.wait_group.sync.aligned 1;\ncvt.rn.bf16x2.f32 k0, o1, o0;\ncvt.rn.bf16x2.f32 k1, o5, o4;\n"
        "cvt.rn.bf16x2.f32 k2, o9, o8;\ncvt.rn.bf16x2.f32 k3, o13, o12;\n@s0 st.global.v4.b32 [%49+0], {k0,k1,k2,k3};\ncvt.rn.bf16x2.f32 k4, o3, o2;\n"
        "cvt.rn.bf16x2.f32 k5, o7, o6;\ncvt.rn.bf16x2.f32 k6, o11, o10;\ncvt.rn.bf16x2.f32 k7, o15, o14;\n@s1 st.global.v4.b32 [%50+0], {k4,k5,k6,k7};\n"
        "@nv bra.uni END;\nwgmma.wait_group.sync.aligned 0;\ncvt.rn.bf16x2.f32 k8, o17, o16;\ncvt.rn.bf16x2.f32 k9, o21, o20;\ncvt.rn.bf16x2.f32 k10, o25, o24;\n"
        "cvt.rn.bf16x2.f32 k11, o29, o28;\n@s0 st.global.v4.b32 [%49+64], {k8,k9,k10,k11};\ncvt.rn.bf16x2.f32 k12, o19, o18;\ncvt.rn.bf16x2.f32 k13, o23, o22;\n"
        "cvt.rn.bf16x2.f32 k14, o27, o26;\ncvt.rn.bf16x2.f32 k15, o31, o30;\n@s1 st.global.v4.b32 [%50+64], {k12,k13,k14,k15};\n@nv bra.uni END;\n"
        "ld.volatile.shared.v2.b32 {c0,c1}, [%48+16];\nld.volatile.shared.v2.b32 {c2,c3}, [%48+4112];\nld.volatile.shared.v2.b32 {c4,c5}, [%48+24];\n"
        "ld.volatile.shared.v2.b32 {c6,c7}, [%48+4120];\ndp2a.lo.u32.u32 t, c0, 0x04000004, 0x200000;\nmov.b64 d0, {t, h};\n"
        "dp2a.hi.u32.u32 t, c0, 0x04000004, 0x200000;\nmov.b64 d1, {t, h};\ndp2a.lo.u32.u32 t, c1, 0x04000004, 0x200000;\nmov.b64 d2, {t, h};\n"
        "dp2a.hi.u32.u32 t, c1, 0x04000004, 0x200000;\nmov.b64 d3, {t, h};\ndp2a.lo.u32.u32 t, c2, 0x04000004, 0x200000;\nmov.b64 d4, {t, h};\n"
        "dp2a.hi.u32.u32 t, c2, 0x04000004, 0x200000;\nmov.b64 d5, {t, h};\ndp2a.lo.u32.u32 t, c3, 0x04000004, 0x200000;\nmov.b64 d6, {t, h};\n"
        "dp2a.hi.u32.u32 t, c3, 0x04000004, 0x200000;\nmov.b64 d7, {t, h};\ndp2a.lo.u32.u32 t, c4, 0x04000004, 0x200000;\nmov.b64 d8, {t, h};\n"
        "dp2a.hi.u32.u32 t, c4, 0x04000004, 0x200000;\nmov.b64 d9, {t, h};\ndp2a.lo.u32.u32 t, c5, 0x04000004, 0x200000;\nmov.b64 d10, {t, h};\n"
        "dp2a.hi.u32.u32 t, c5, 0x04000004, 0x200000;\nmov.b64 d11, {t, h};\ndp2a.lo.u32.u32 t, c6, 0x04000004, 0x200000;\nmov.b64 d12, {t, h};\n"
        "dp2a.hi.u32.u32 t, c6, 0x04000004, 0x200000;\nmov.b64 d13, {t, h};\ndp2a.lo.u32.u32 t, c7, 0x04000004, 0x200000;\nmov.b64 d14, {t, h};\n"
        "dp2a.hi.u32.u32 t, c7, 0x04000004, 0x200000;\nmov.b64 d15, {t, h};\nwgmma.fence.sync.aligned;\n"
        "wgmma.mma_async.sync.aligned.m64n32k16.f32.bf16.bf16 {o0,o1,o2,o3,o4,o5,o6,o7,o8,o9,o10,o11,o12,o13,o14,o15}, {a0,a1,a2,a3}, d0, p0, 1, 1, 1;\n"
        "wgmma.mma_async.sync.aligned.m64n32k16.f32.bf16.bf16 {o16,o17,o18,o19,o20,o21,o22,o23,o24,o25,o26,o27,o28,o29,o30,o31}, {a0,a1,a2,a3}, d8, p0, 1, 1, 1;\n"
        "wgmma.mma_async.sync.aligned.m64n32k16.f32.bf16.bf16 {o0,o1,o2,o3,o4,o5,o6,o7,o8,o9,o10,o11,o12,o13,o14,o15}, {a4,a5,a6,a7}, d1, p1, 1, 1, 1;\n"
        "wgmma.mma_async.sync.aligned.m64n32k16.f32.bf16.bf16 {o16,o17,o18,o19,o20,o21,o22,o23,o24,o25,o26,o27,o28,o29,o30,o31}, {a4,a5,a6,a7}, d9, p1, 1, 1, 1;\n"
        "wgmma.mma_async.sync.aligned.m64n32k16.f32.bf16.bf16 {o0,o1,o2,o3,o4,o5,o6,o7,o8,o9,o10,o11,o12,o13,o14,o15}, {a8,a9,a10,a11}, d2, p1, 1, 1, 1;\n"
        "wgmma.mma_async.sync.aligned.m64n32k16.f32.bf16.bf16 {o16,o17,o18,o19,o20,o21,o22,o23,o24,o25,o26,o27,o28,o29,o30,o31}, {a8,a9,a10,a11}, d10, p1, 1, 1, 1;\n"
        "wgmma.mma_async.sync.aligned.m64n32k16.f32.bf16.bf16 {o0,o1,o2,o3,o4,o5,o6,o7,o8,o9,o10,o11,o12,o13,o14,o15}, {a12,a13,a14,a15}, d3, p1, 1, 1, 1;\n"
        "wgmma.mma_async.sync.aligned.m64n32k16.f32.bf16.bf16 {o16,o17,o18,o19,o20,o21,o22,o23,o24,o25,o26,o27,o28,o29,o30,o31}, {a12,a13,a14,a15}, d11, p1, 1, 1, 1;\n"
        "wgmma.mma_async.sync.aligned.m64n32k16.f32.bf16.bf16 {o0,o1,o2,o3,o4,o5,o6,o7,o8,o9,o10,o11,o12,o13,o14,o15}, {a16,a17,a18,a19}, d4, p1, 1, 1, 1;\n"
        "wgmma.mma_async.sync.aligned.m64n32k16.f32.bf16.bf16 {o16,o17,o18,o19,o20,o21,o22,o23,o24,o25,o26,o27,o28,o29,o30,o31}, {a16,a17,a18,a19}, d12, p1, 1, 1, 1;\n"
        "wgmma.mma_async.sync.aligned.m64n32k16.f32.bf16.bf16 {o0,o1,o2,o3,o4,o5,o6,o7,o8,o9,o10,o11,o12,o13,o14,o15}, {a20,a21,a22,a23}, d5, p1, 1, 1, 1;\n"
        "wgmma.mma_async.sync.aligned.m64n32k16.f32.bf16.bf16 {o16,o17,o18,o19,o20,o21,o22,o23,o24,o25,o26,o27,o28,o29,o30,o31}, {a20,a21,a22,a23}, d13, p1, 1, 1, 1;\n"
        "wgmma.mma_async.sync.aligned.m64n32k16.f32.bf16.bf16 {o0,o1,o2,o3,o4,o5,o6,o7,o8,o9,o10,o11,o12,o13,o14,o15}, {a24,a25,a26,a27}, d6, p1, 1, 1, 1;\n"
        "wgmma.mma_async.sync.aligned.m64n32k16.f32.bf16.bf16 {o16,o17,o18,o19,o20,o21,o22,o23,o24,o25,o26,o27,o28,o29,o30,o31}, {a24,a25,a26,a27}, d14, p1, 1, 1, 1;\n"
        "wgmma.mma_async.sync.aligned.m64n32k16.f32.bf16.bf16 {o0,o1,o2,o3,o4,o5,o6,o7,o8,o9,o10,o11,o12,o13,o14,o15}, {a28,a29,a30,a31}, d7, p1, 1, 1, 1;\n"
        "wgmma.mma_async.sync.aligned.m64n32k16.f32.bf16.bf16 {o16,o17,o18,o19,o20,o21,o22,o23,o24,o25,o26,o27,o28,o29,o30,o31}, {a28,a29,a30,a31}, d15, p1, 1, 1, 1;\n"
        "wgmma.commit_group.sync.aligned;\n@nv bra.uni END;\nmovmatrix.sync.aligned.m8n8.trans.b16 b0, %32;\nmovmatrix.sync.aligned.m8n8.trans.b16 b1, %32;\n"
        "movmatrix.sync.aligned.m8n8.trans.b16 b2, %33;\nmovmatrix.sync.aligned.m8n8.trans.b16 b3, %33;\nmovmatrix.sync.aligned.m8n8.trans.b16 b4, %34;\n"
        "movmatrix.sync.aligned.m8n8.trans.b16 b5, %34;\nmovmatrix.sync.aligned.m8n8.trans.b16 b6, %35;\nmovmatrix.sync.aligned.m8n8.trans.b16 b7, %35;\n"
        "movmatrix.sync.aligned.m8n8.trans.b16 b8, %36;\nmovmatrix.sync.aligned.m8n8.trans.b16 b9, %36;\nmovmatrix.sync.aligned.m8n8.trans.b16 b10, %37;\n"
        "movmatrix.sync.aligned.m8n8.trans.b16 b11, %37;\nmovmatrix.sync.aligned.m8n8.trans.b16 b12, %38;\nmovmatrix.sync.aligned.m8n8.trans.b16 b13, %38;\n"
        "movmatrix.sync.aligned.m8n8.trans.b16 b14, %39;\nmovmatrix.sync.aligned.m8n8.trans.b16 b15, %39;\nmovmatrix.sync.aligned.m8n8.trans.b16 b16, %40;\n"
        "movmatrix.sync.aligned.m8n8.trans.b16 b17, %40;\nmovmatrix.sync.aligned.m8n8.trans.b16 b18, %41;\nmovmatrix.sync.aligned.m8n8.trans.b16 b19, %41;\n"
        "movmatrix.sync.aligned.m8n8.trans.b16 b20, %42;\nmovmatrix.sync.aligned.m8n8.trans.b16 b21, %42;\nmovmatrix.sync.aligned.m8n8.trans.b16 b22, %43;\n"
        "movmatrix.sync.aligned.m8n8.trans.b16 b23, %43;\nmovmatrix.sync.aligned.m8n8.trans.b16 b24, %44;\nmovmatrix.sync.aligned.m8n8.trans.b16 b25, %44;\n"
        "movmatrix.sync.aligned.m8n8.trans.b16 b26, %45;\nmovmatrix.sync.aligned.m8n8.trans.b16 b27, %45;\nmovmatrix.sync.aligned.m8n8.trans.b16 b28, %46;\n"
        "movmatrix.sync.aligned.m8n8.trans.b16 b29, %46;\nmovmatrix.sync.aligned.m8n8.trans.b16 b30, %47;\nmovmatrix.sync.aligned.m8n8.trans.b16 b31, %47;\n"
        "@nv bra.uni END;\nwgmma.wait_group.sync.aligned 0;\ncvt.rn.bf16x2.f32 k0, o1, o0;\ncvt.rn.bf16x2.f32 k1, o5, o4;\ncvt.rn.bf16x2.f32 k2, o9, o8;\n"
        "cvt.rn.bf16x2.f32 k3, o13, o12;\ncvt.rn.bf16x2.f32 k4, o3, o2;\ncvt.rn.bf16x2.f32 k5, o7, o6;\ncvt.rn.bf16x2.f32 k6, o11, o10;\n"
        "cvt.rn.bf16x2.f32 k7, o15, o14;\ncvt.rn.bf16x2.f32 k8, o17, o16;\ncvt.rn.bf16x2.f32 k9, o21, o20;\ncvt.rn.bf16x2.f32 k10, o25, o24;\n"
        "cvt.rn.bf16x2.f32 k11, o29, o28;\ncvt.rn.bf16x2.f32 k12, o19, o18;\ncvt.rn.bf16x2.f32 k13, o23, o22;\ncvt.rn.bf16x2.f32 k14, o27, o26;\n"
        "cvt.rn.bf16x2.f32 k15, o31, o30;\nld.volatile.shared.v2.b32 {c0,c1}, [%48+0];\nld.volatile.shared.v2.b32 {c2,c3}, [%48+4096];\n"
        "ld.volatile.shared.v2.b32 {c4,c5}, [%48+8];\nld.volatile.shared.v2.b32 {c6,c7}, [%48+4104];\ndp2a.lo.u32.u32 t, c0, 0x04000004, 0x200000;\n"
        "mov.b64 d0, {t, h};\ndp2a.hi.u32.u32 t, c0, 0x04000004, 0x200000;\nmov.b64 d1, {t, h};\ndp2a.lo.u32.u32 t, c1, 0x04000004, 0x200000;\n"
        "mov.b64 d2, {t, h};\ndp2a.hi.u32.u32 t, c1, 0x04000004, 0x200000;\nmov.b64 d3, {t, h};\ndp2a.lo.u32.u32 t, c2, 0x04000004, 0x200000;\n"
        "mov.b64 d4, {t, h};\ndp2a.hi.u32.u32 t, c2, 0x04000004, 0x200000;\nmov.b64 d5, {t, h};\ndp2a.lo.u32.u32 t, c3, 0x04000004, 0x200000;\n"
        "mov.b64 d6, {t, h};\ndp2a.hi.u32.u32 t, c3, 0x04000004, 0x200000;\nmov.b64 d7, {t, h};\ndp2a.lo.u32.u32 t, c4, 0x04000004, 0x200000;\n"
        "mov.b64 d8, {t, h};\ndp2a.hi.u32.u32 t, c4, 0x04000004, 0x200000;\nmov.b64 d9, {t, h};\ndp2a.lo.u32.u32 t, c5, 0x04000004, 0x200000;\n"
        "mov.b64 d10, {t, h};\ndp2a.hi.u32.u32 t, c5, 0x04000004, 0x200000;\nmov.b64 d11, {t, h};\ndp2a.lo.u32.u32 t, c6, 0x04000004, 0x200000;\n"
        "mov.b64 d12, {t, h};\ndp2a.hi.u32.u32 t, c6, 0x04000004, 0x200000;\nmov.b64 d13, {t, h};\ndp2a.lo.u32.u32 t, c7, 0x04000004, 0x200000;\n"
        "mov.b64 d14, {t, h};\ndp2a.hi.u32.u32 t, c7, 0x04000004, 0x200000;\nmov.b64 d15, {t, h};\nwgmma.fence.sync.aligned;\n"
        "wgmma.mma_async.sync.aligned.m64n32k16.f32.bf16.bf16 {o0,o1,o2,o3,o4,o5,o6,o7,o8,o9,o10,o11,o12,o13,o14,o15}, {b0,b1,b2,b3}, d0, p0, 1, 1, 1;\n"
        "wgmma.mma_async.sync.aligned.m64n32k16.f32.bf16.bf16 {o16,o17,o18,o19,o20,o21,o22,o23,o24,o25,o26,o27,o28,o29,o30,o31}, {b0,b1,b2,b3}, d8, p0, 1, 1, 1;\n"
        "wgmma.mma_async.sync.aligned.m64n32k16.f32.bf16.bf16 {o0,o1,o2,o3,o4,o5,o6,o7,o8,o9,o10,o11,o12,o13,o14,o15}, {b4,b5,b6,b7}, d1, p1, 1, 1, 1;\n"
        "wgmma.mma_async.sync.aligned.m64n32k16.f32.bf16.bf16 {o16,o17,o18,o19,o20,o21,o22,o23,o24,o25,o26,o27,o28,o29,o30,o31}, {b4,b5,b6,b7}, d9, p1, 1, 1, 1;\n"
        "wgmma.mma_async.sync.aligned.m64n32k16.f32.bf16.bf16 {o0,o1,o2,o3,o4,o5,o6,o7,o8,o9,o10,o11,o12,o13,o14,o15}, {b8,b9,b10,b11}, d2, p1, 1, 1, 1;\n"
        "wgmma.mma_async.sync.aligned.m64n32k16.f32.bf16.bf16 {o16,o17,o18,o19,o20,o21,o22,o23,o24,o25,o26,o27,o28,o29,o30,o31}, {b8,b9,b10,b11}, d10, p1, 1, 1, 1;\n"
        "wgmma.mma_async.sync.aligned.m64n32k16.f32.bf16.bf16 {o0,o1,o2,o3,o4,o5,o6,o7,o8,o9,o10,o11,o12,o13,o14,o15}, {b12,b13,b14,b15}, d3, p1, 1, 1, 1;\n"
        "wgmma.mma_async.sync.aligned.m64n32k16.f32.bf16.bf16 {o16,o17,o18,o19,o20,o21,o22,o23,o24,o25,o26,o27,o28,o29,o30,o31}, {b12,b13,b14,b15}, d11, p1, 1, 1, 1;\n"
        "wgmma.mma_async.sync.aligned.m64n32k16.f32.bf16.bf16 {o0,o1,o2,o3,o4,o5,o6,o7,o8,o9,o10,o11,o12,o13,o14,o15}, {b16,b17,b18,b19}, d4, p1, 1, 1, 1;\n"
        "wgmma.mma_async.sync.aligned.m64n32k16.f32.bf16.bf16 {o16,o17,o18,o19,o20,o21,o22,o23,o24,o25,o26,o27,o28,o29,o30,o31}, {b16,b17,b18,b19}, d12, p1, 1, 1, 1;\n"
        "wgmma.mma_async.sync.aligned.m64n32k16.f32.bf16.bf16 {o0,o1,o2,o3,o4,o5,o6,o7,o8,o9,o10,o11,o12,o13,o14,o15}, {b20,b21,b22,b23}, d5, p1, 1, 1, 1;\n"
        "wgmma.mma_async.sync.aligned.m64n32k16.f32.bf16.bf16 {o16,o17,o18,o19,o20,o21,o22,o23,o24,o25,o26,o27,o28,o29,o30,o31}, {b20,b21,b22,b23}, d13, p1, 1, 1, 1;\n"
        "wgmma.mma_async.sync.aligned.m64n32k16.f32.bf16.bf16 {o0,o1,o2,o3,o4,o5,o6,o7,o8,o9,o10,o11,o12,o13,o14,o15}, {b24,b25,b26,b27}, d6, p1, 1, 1, 1;\n"
        "wgmma.mma_async.sync.aligned.m64n32k16.f32.bf16.bf16 {o16,o17,o18,o19,o20,o21,o22,o23,o24,o25,o26,o27,o28,o29,o30,o31}, {b24,b25,b26,b27}, d14, p1, 1, 1, 1;\n"
        "wgmma.mma_async.sync.aligned.m64n32k16.f32.bf16.bf16 {o0,o1,o2,o3,o4,o5,o6,o7,o8,o9,o10,o11,o12,o13,o14,o15}, {b28,b29,b30,b31}, d7, p1, 1, 1, 1;\n"
        "wgmma.mma_async.sync.aligned.m64n32k16.f32.bf16.bf16 {o16,o17,o18,o19,o20,o21,o22,o23,o24,o25,o26,o27,o28,o29,o30,o31}, {b28,b29,b30,b31}, d15, p1, 1, 1, 1;\n"
        "wgmma.commit_group.sync.aligned;\n@nv bra.uni END;\n@s0 st.global.v4.b32 [%49+128], {k0,k1,k2,k3};\n@s1 st.global.v4.b32 [%50+128], {k4,k5,k6,k7};\n"
        "@s0 st.global.v4.b32 [%49+192], {k8,k9,k10,k11};\n@s1 st.global.v4.b32 [%50+192], {k12,k13,k14,k15};\n@nv bra.uni END;\n"
        "wgmma.wait_group.sync.aligned 0;\ncvt.rn.bf16x2.f32 k0, o1, o0;\ncvt.rn.bf16x2.f32 k1, o5, o4;\ncvt.rn.bf16x2.f32 k2, o9, o8;\n"
        "cvt.rn.bf16x2.f32 k3, o13, o12;\ncvt.rn.bf16x2.f32 k8, o17, o16;\ncvt.rn.bf16x2.f32 k9, o21, o20;\ncvt.rn.bf16x2.f32 k10, o25, o24;\n"
        "cvt.rn.bf16x2.f32 k11, o29, o28;\nld.volatile.shared.v2.b32 {c0,c1}, [%48+16];\nld.volatile.shared.v2.b32 {c2,c3}, [%48+4112];\n"
        "ld.volatile.shared.v2.b32 {c4,c5}, [%48+24];\nld.volatile.shared.v2.b32 {c6,c7}, [%48+4120];\ndp2a.lo.u32.u32 t, c0, 0x04000004, 0x200000;\n"
        "mov.b64 d0, {t, h};\ndp2a.hi.u32.u32 t, c0, 0x04000004, 0x200000;\nmov.b64 d1, {t, h};\ndp2a.lo.u32.u32 t, c1, 0x04000004, 0x200000;\n"
        "mov.b64 d2, {t, h};\ndp2a.hi.u32.u32 t, c1, 0x04000004, 0x200000;\nmov.b64 d3, {t, h};\ndp2a.lo.u32.u32 t, c2, 0x04000004, 0x200000;\n"
        "mov.b64 d4, {t, h};\ndp2a.hi.u32.u32 t, c2, 0x04000004, 0x200000;\nmov.b64 d5, {t, h};\ndp2a.lo.u32.u32 t, c3, 0x04000004, 0x200000;\n"
        "mov.b64 d6, {t, h};\ndp2a.hi.u32.u32 t, c3, 0x04000004, 0x200000;\nmov.b64 d7, {t, h};\ndp2a.lo.u32.u32 t, c4, 0x04000004, 0x200000;\n"
        "mov.b64 d8, {t, h};\ndp2a.hi.u32.u32 t, c4, 0x04000004, 0x200000;\nmov.b64 d9, {t, h};\ndp2a.lo.u32.u32 t, c5, 0x04000004, 0x200000;\n"
        "mov.b64 d10, {t, h};\ndp2a.hi.u32.u32 t, c5, 0x04000004, 0x200000;\nmov.b64 d11, {t, h};\ndp2a.lo.u32.u32 t, c6, 0x04000004, 0x200000;\n"
        "mov.b64 d12, {t, h};\ndp2a.hi.u32.u32 t, c6, 0x04000004, 0x200000;\nmov.b64 d13, {t, h};\ndp2a.lo.u32.u32 t, c7, 0x04000004, 0x200000;\n"
        "mov.b64 d14, {t, h};\ndp2a.hi.u32.u32 t, c7, 0x04000004, 0x200000;\nmov.b64 d15, {t, h};\nwgmma.fence.sync.aligned;\n"
        "wgmma.mma_async.sync.aligned.m64n32k16.f32.bf16.bf16 {o0,o1,o2,o3,o4,o5,o6,o7,o8,o9,o10,o11,o12,o13,o14,o15}, {b0,b1,b2,b3}, d0, p0, 1, 1, 1;\n"
        "wgmma.mma_async.sync.aligned.m64n32k16.f32.bf16.bf16 {o16,o17,o18,o19,o20,o21,o22,o23,o24,o25,o26,o27,o28,o29,o30,o31}, {b0,b1,b2,b3}, d8, p0, 1, 1, 1;\n"
        "wgmma.mma_async.sync.aligned.m64n32k16.f32.bf16.bf16 {o0,o1,o2,o3,o4,o5,o6,o7,o8,o9,o10,o11,o12,o13,o14,o15}, {b4,b5,b6,b7}, d1, p1, 1, 1, 1;\n"
        "wgmma.mma_async.sync.aligned.m64n32k16.f32.bf16.bf16 {o16,o17,o18,o19,o20,o21,o22,o23,o24,o25,o26,o27,o28,o29,o30,o31}, {b4,b5,b6,b7}, d9, p1, 1, 1, 1;\n"
        "wgmma.mma_async.sync.aligned.m64n32k16.f32.bf16.bf16 {o0,o1,o2,o3,o4,o5,o6,o7,o8,o9,o10,o11,o12,o13,o14,o15}, {b8,b9,b10,b11}, d2, p1, 1, 1, 1;\n"
        "wgmma.mma_async.sync.aligned.m64n32k16.f32.bf16.bf16 {o16,o17,o18,o19,o20,o21,o22,o23,o24,o25,o26,o27,o28,o29,o30,o31}, {b8,b9,b10,b11}, d10, p1, 1, 1, 1;\n"
        "wgmma.mma_async.sync.aligned.m64n32k16.f32.bf16.bf16 {o0,o1,o2,o3,o4,o5,o6,o7,o8,o9,o10,o11,o12,o13,o14,o15}, {b12,b13,b14,b15}, d3, p1, 1, 1, 1;\n"
        "wgmma.mma_async.sync.aligned.m64n32k16.f32.bf16.bf16 {o16,o17,o18,o19,o20,o21,o22,o23,o24,o25,o26,o27,o28,o29,o30,o31}, {b12,b13,b14,b15}, d11, p1, 1, 1, 1;\n"
        "wgmma.mma_async.sync.aligned.m64n32k16.f32.bf16.bf16 {o0,o1,o2,o3,o4,o5,o6,o7,o8,o9,o10,o11,o12,o13,o14,o15}, {b16,b17,b18,b19}, d4, p1, 1, 1, 1;\n"
        "wgmma.mma_async.sync.aligned.m64n32k16.f32.bf16.bf16 {o16,o17,o18,o19,o20,o21,o22,o23,o24,o25,o26,o27,o28,o29,o30,o31}, {b16,b17,b18,b19}, d12, p1, 1, 1, 1;\n"
        "wgmma.mma_async.sync.aligned.m64n32k16.f32.bf16.bf16 {o0,o1,o2,o3,o4,o5,o6,o7,o8,o9,o10,o11,o12,o13,o14,o15}, {b20,b21,b22,b23}, d5, p1, 1, 1, 1;\n"
        "wgmma.mma_async.sync.aligned.m64n32k16.f32.bf16.bf16 {o16,o17,o18,o19,o20,o21,o22,o23,o24,o25,o26,o27,o28,o29,o30,o31}, {b20,b21,b22,b23}, d13, p1, 1, 1, 1;\n"
        "wgmma.mma_async.sync.aligned.m64n32k16.f32.bf16.bf16 {o0,o1,o2,o3,o4,o5,o6,o7,o8,o9,o10,o11,o12,o13,o14,o15}, {b24,b25,b26,b27}, d6, p1, 1, 1, 1;\n"
        "wgmma.mma_async.sync.aligned.m64n32k16.f32.bf16.bf16 {o16,o17,o18,o19,o20,o21,o22,o23,o24,o25,o26,o27,o28,o29,o30,o31}, {b24,b25,b26,b27}, d14, p1, 1, 1, 1;\n"
        "wgmma.mma_async.sync.aligned.m64n32k16.f32.bf16.bf16 {o0,o1,o2,o3,o4,o5,o6,o7,o8,o9,o10,o11,o12,o13,o14,o15}, {b28,b29,b30,b31}, d7, p1, 1, 1, 1;\n"
        "wgmma.mma_async.sync.aligned.m64n32k16.f32.bf16.bf16 {o16,o17,o18,o19,o20,o21,o22,o23,o24,o25,o26,o27,o28,o29,o30,o31}, {b28,b29,b30,b31}, d15, p1, 1, 1, 1;\n"
        "wgmma.commit_group.sync.aligned;\n@nv bra.uni END;\n@s2 st.global.v4.b32 [%51+0], {k0,k1,k2,k3};\n@s2 st.global.v4.b32 [%51+64], {k8,k9,k10,k11};\n"
        "@nv bra.uni END;\nwgmma.wait_group.sync.aligned 0;\ncvt.rn.bf16x2.f32 k0, o1, o0;\ncvt.rn.bf16x2.f32 k1, o5, o4;\ncvt.rn.bf16x2.f32 k2, o9, o8;\n"
        "cvt.rn.bf16x2.f32 k3, o13, o12;\ncvt.rn.bf16x2.f32 k8, o17, o16;\ncvt.rn.bf16x2.f32 k9, o21, o20;\ncvt.rn.bf16x2.f32 k10, o25, o24;\n"
        "cvt.rn.bf16x2.f32 k11, o29, o28;\n@s2 st.global.v4.b32 [%51+128], {k0,k1,k2,k3};\n@s2 st.global.v4.b32 [%51+192], {k8,k9,k10,k11};\n"
        "END:\n}\n"
        ::"r"(pk[0]), "r"(pk[1]), "r"(pk[2]), "r"(pk[3]), "r"(pk[4]), "r"(pk[5]), "r"(pk[6]), "r"(pk[7]), "r"(pk[8]), "r"(pk[9]), "r"(pk[10]),
          "r"(pk[11]), "r"(pk[12]), "r"(pk[13]), "r"(pk[14]), "r"(pk[15]), "r"(pk[16]), "r"(pk[17]), "r"(pk[18]), "r"(pk[19]), "r"(pk[20]),
          "r"(pk[21]), "r"(pk[22]), "r"(pk[23]), "r"(pk[24]), "r"(pk[25]), "r"(pk[26]), "r"(pk[27]), "r"(pk[28]), "r"(pk[29]), "r"(pk[30]),
          "r"(pk[31]), "r"(pk[32]), "r"(pk[33]), "r"(pk[34]), "r"(pk[35]), "r"(pk[36]), "r"(pk[37]), "r"(pk[38]), "r"(pk[39]), "r"(pk[40]),
          "r"(pk[41]), "r"(pk[42]), "r"(pk[43]), "r"(pk[44]), "r"(pk[45]), "r"(pk[46]), "r"(pk[47]), "r"(ra), "l"(p[0]), "l"(p[1]), "l"(p[2]),
          "r"(v[0]), "r"(v[1]), "r"(v[2]), "r"(ba)
        : "memory");
}
__device__ __forceinline__ int cta_id() {
    int v;
    asm volatile("mov.u32 %0, %ctaid.x;" : "=r"(v));
    return v;
}
__device__ __forceinline__ int thread_id() {
    int v;
    asm volatile("mov.u32 %0, %tid.x;" : "=r"(v));
    return v;
}

__device__ __forceinline__ void slow_edge(int ee, int s, float* accn, const __nv_bfloat16* __restrict__ x,
                                          const __nv_bfloat16* __restrict__ sh, const __nv_bfloat16* __restrict__ ea,
                                          const __nv_bfloat16* __restrict__ cg, const __nv_bfloat16* __restrict__ wr,
                                          int lane) {
    float rwv[4] = {0.f, 0.f, 0.f, 0.f};
#pragma unroll 4
    for (int d = 0; d < 16; d++) {
        const float a = __bfloat162float(ea[(size_t)ee * 16 + d]);
        const uint2 wv = *(const uint2*)(wr + d * 128 + lane * 4);
        rwv[0] += a * __uint_as_float(wv.x << 16);
        rwv[1] += a * __uint_as_float(wv.x & 0xffff0000u);
        rwv[2] += a * __uint_as_float(wv.y << 16);
        rwv[3] += a * __uint_as_float(wv.y & 0xffff0000u);
    }
    float A = 0.f;
#pragma unroll
    for (int v = 0; v < 4; v++)
        A += __bfloat162float(cg[((lane >> 2) & 3) * 16 + v * 4 + (lane & 3)]) * __bfloat162float(sh[(size_t)ee * 4 + v]);
    float m[4][4];
#pragma unroll
    for (int w = 0; w < 4; w++)
#pragma unroll
        for (int j = 0; j < 4; j++) m[w][j] = 0.f;
#pragma unroll
    for (int u = 0; u < 4; u++) {
        const uint2 xv = *(const uint2*)(x + (size_t)s * 512 + u * 128 + lane * 4);
        const float x0 = __uint_as_float(xv.x << 16), x1 = __uint_as_float(xv.x & 0xffff0000u);
        const float x2 = __uint_as_float(xv.y << 16), x3 = __uint_as_float(xv.y & 0xffff0000u);
#pragma unroll
        for (int w = 0; w < 4; w++) {
            const float a = __shfl_sync(0xffffffffu, A, u * 4 + w);
            m[w][0] += a * x0;
            m[w][1] += a * x1;
            m[w][2] += a * x2;
            m[w][3] += a * x3;
        }
    }
#pragma unroll
    for (int w = 0; w < 4; w++)
#pragma unroll
        for (int j = 0; j < 4; j++) atomicAdd(accn + w * 128 + lane * 4 + j, m[w][j] * rwv[j]);
}

__device__ __forceinline__ void slow_out(const float* accn, const __nv_bfloat16* __restrict__ wout,
                                         __nv_bfloat16* __restrict__ outn, int lane) {
    float o[4][4];
#pragma unroll
    for (int w = 0; w < 4; w++)
#pragma unroll
        for (int j = 0; j < 4; j++) o[w][j] = 0.f;
#pragma unroll 2
    for (int c = 0; c < 128; c++) {
        const uint2 wv = *(const uint2*)(wout + c * 128 + lane * 4);
        const float w0 = __uint_as_float(wv.x << 16), w1 = __uint_as_float(wv.x & 0xffff0000u);
        const float w2 = __uint_as_float(wv.y << 16), w3 = __uint_as_float(wv.y & 0xffff0000u);
#pragma unroll
        for (int w = 0; w < 4; w++) {
            const float a = __bfloat162float(__float2bfloat16(accn[w * 128 + c]));
            o[w][0] += a * w0;
            o[w][1] += a * w1;
            o[w][2] += a * w2;
            o[w][3] += a * w3;
        }
    }
#pragma unroll
    for (int w = 0; w < 4; w++)
        *(uint2*)(outn + w * 128 + lane * 4) = make_uint2(pack_bf16(o[w][0], o[w][1]), pack_bf16(o[w][2], o[w][3]));
}

__device__ __forceinline__ void consume4(uint32_t (&pk)[64], const uint32_t (&w)[36], uint32_t olp, uint32_t xa, uint32_t ln,
                                      uint32_t lc, uint32_t linc, uint32_t lt, const __nv_bfloat16* ea, const __nv_bfloat16* sh, const void* wf, uint4 first) {
    ea += lt * 4, sh += lt & 2;
    asm volatile(
        "{\n.reg .pred p, q, psw, prdy, ps1, ps2, ps3, pz, pq, pt;\n.reg .f32 d<32>, fz;\n"
        ".reg .b32 h<64>, x<32>, y<32>, ra<8>, rb<8>, bA0, bA1, bB0, bB1, c0, c1, c2, c3, e0, e1, s0, kept;\n"
        ".reg .b32 olp, v, vB, m, id, ida, bar, xb, pos, t0, t1, t2, t3, n, z<16>, kept2, g<4>, f0, f1, s1;\n.reg .b16 lo, hi, i16;\n.reg .b64 pa, pb;\n"
        "mov.f32 fz, 0f00000000;\nmov.b32 h0, 0;\nmov.b32 h1, 0;\nmov.b32 h2, 0;\nmov.b32 h3, 0;\nmov.b32 h4, 0;\nmov.b32 h5, 0;\nmov.b32 h6, 0;\n"
        "mov.b32 h7, 0;\nmov.b32 h8, 0;\nmov.b32 h9, 0;\nmov.b32 h10, 0;\nmov.b32 h11, 0;\nmov.b32 h12, 0;\nmov.b32 h13, 0;\nmov.b32 h14, 0;\nmov.b32 h15, 0;\n"
        "mov.b32 h16, 0;\nmov.b32 h17, 0;\nmov.b32 h18, 0;\nmov.b32 h19, 0;\nmov.b32 h20, 0;\nmov.b32 h21, 0;\nmov.b32 h22, 0;\nmov.b32 h23, 0;\n"
        "mov.b32 h24, 0;\nmov.b32 h25, 0;\nmov.b32 h26, 0;\nmov.b32 h27, 0;\nmov.b32 h28, 0;\nmov.b32 h29, 0;\nmov.b32 h30, 0;\nmov.b32 h31, 0;\n"
        "mov.b32 h32, 0;\nmov.b32 h33, 0;\nmov.b32 h34, 0;\nmov.b32 h35, 0;\nmov.b32 h36, 0;\nmov.b32 h37, 0;\nmov.b32 h38, 0;\nmov.b32 h39, 0;\n"
        "mov.b32 h40, 0;\nmov.b32 h41, 0;\nmov.b32 h42, 0;\nmov.b32 h43, 0;\nmov.b32 h44, 0;\nmov.b32 h45, 0;\nmov.b32 h46, 0;\nmov.b32 h47, 0;\n"
        "mov.b32 h48, 0;\nmov.b32 h49, 0;\nmov.b32 h50, 0;\nmov.b32 h51, 0;\nmov.b32 h52, 0;\nmov.b32 h53, 0;\nmov.b32 h54, 0;\nmov.b32 h55, 0;\n"
        "mov.b32 h56, 0;\nmov.b32 h57, 0;\nmov.b32 h58, 0;\nmov.b32 h59, 0;\nmov.b32 h60, 0;\nmov.b32 h61, 0;\nmov.b32 h62, 0;\nmov.b32 h63, 0;\n"
        "mov.b32 olp, %64;\nand.b32 t0, %66, 32;\nsetp.ne.u32 psw, t0, 0;\nsetp.eq.u32 pz, %64, 0;\nvote.sync.any.pred pz, pz, 0xffffffff;\nmov.b32 e0, %73;\n"
        "mov.b32 e1, %74;\nmov.b32 s0, %75;\nmov.b32 kept, %76;\nadd.u32 olp, olp, 4;\nsetp.ne.u64 p, %72, 0;\n@p fence.proxy.async.global;\n"
        "@p red.release.gpu.global.add.u32 [%72+12], 1;\nbar.warp.sync 0xffffffff;\nshfl.sync.idx.b32 v, kept, %67, 0x1f, 0xffffffff;\nor.b32 t3, %67, 4;\n"
        "shfl.sync.idx.b32 vB, kept, t3, 0x1f, 0xffffffff;\n"
        "RW:\nmma.sync.aligned.m16n8k8.row.col.f32.bf16.bf16.f32 {d0,d1,d2,d3}, {%114,%115}, {s0}, {fz,fz,fz,fz};\n"
        "mma.sync.aligned.m16n8k8.row.col.f32.bf16.bf16.f32 {d4,d5,d6,d7}, {%116,%117}, {s0}, {fz,fz,fz,fz};\ncvt.rn.bf16x2.f32 c0, d2, d0;\n"
        "cvt.rn.bf16x2.f32 c1, d3, d1;\ncvt.rn.bf16x2.f32 c2, d6, d4;\ncvt.rn.bf16x2.f32 c3, d7, d5;\nselp.b32 bA0, c2, c0, psw;\nselp.b32 bA1, c0, c2, psw;\n"
        "selp.b32 bB0, c3, c1, psw;\nselp.b32 bB1, c1, c3, psw;\n"
        "mma.sync.aligned.m16n8k16.row.col.f32.bf16.bf16.f32 {d0,d1,d2,d3}, {%82,%83,%84,%85}, {e0,e1}, {fz,fz,fz,fz};\ncvt.rn.bf16x2.f32 ra0, d2, d0;\n"
        "cvt.rn.bf16x2.f32 rb0, d3, d1;\nmma.sync.aligned.m16n8k16.row.col.f32.bf16.bf16.f32 {d4,d5,d6,d7}, {%86,%87,%88,%89}, {e0,e1}, {fz,fz,fz,fz};\n"
        "cvt.rn.bf16x2.f32 ra1, d6, d4;\ncvt.rn.bf16x2.f32 rb1, d7, d5;\n"
        "mma.sync.aligned.m16n8k16.row.col.f32.bf16.bf16.f32 {d8,d9,d10,d11}, {%90,%91,%92,%93}, {e0,e1}, {fz,fz,fz,fz};\ncvt.rn.bf16x2.f32 ra2, d10, d8;\n"
        "cvt.rn.bf16x2.f32 rb2, d11, d9;\nmma.sync.aligned.m16n8k16.row.col.f32.bf16.bf16.f32 {d12,d13,d14,d15}, {%94,%95,%96,%97}, {e0,e1}, {fz,fz,fz,fz};\n"
        "cvt.rn.bf16x2.f32 ra3, d14, d12;\ncvt.rn.bf16x2.f32 rb3, d15, d13;\n"
        "mma.sync.aligned.m16n8k16.row.col.f32.bf16.bf16.f32 {d16,d17,d18,d19}, {%98,%99,%100,%101}, {e0,e1}, {fz,fz,fz,fz};\ncvt.rn.bf16x2.f32 ra4, d18, d16;\n"
        "cvt.rn.bf16x2.f32 rb4, d19, d17;\n"
        "mma.sync.aligned.m16n8k16.row.col.f32.bf16.bf16.f32 {d20,d21,d22,d23}, {%102,%103,%104,%105}, {e0,e1}, {fz,fz,fz,fz};\n"
        "cvt.rn.bf16x2.f32 ra5, d22, d20;\ncvt.rn.bf16x2.f32 rb5, d23, d21;\n"
        "mma.sync.aligned.m16n8k16.row.col.f32.bf16.bf16.f32 {d24,d25,d26,d27}, {%106,%107,%108,%109}, {e0,e1}, {fz,fz,fz,fz};\n"
        "cvt.rn.bf16x2.f32 ra6, d26, d24;\ncvt.rn.bf16x2.f32 rb6, d27, d25;\n"
        "mma.sync.aligned.m16n8k16.row.col.f32.bf16.bf16.f32 {d28,d29,d30,d31}, {%110,%111,%112,%113}, {e0,e1}, {fz,fz,fz,fz};\n"
        "cvt.rn.bf16x2.f32 ra7, d30, d28;\ncvt.rn.bf16x2.f32 rb7, d31, d29;\nld.shared.u16 t0, [olp];\nadd.u32 olp, olp, 4;\n"
        "lop3.b32 t1, t0, %66, 0x3ff0, 0xe4;\nld.shared.b32 t1, [t1+%77];\nshr.u32 t2, t1, 1;\nlop3.b32 kept, t2, t0, 0xffe, 0xe4;\n"
        "lop3.b32 t2, t1, %67, 3, 0x80;\nsetp.ne.u32 q, t2, 0;\nshr.u32 t2, t1, 13;\nmad.wide.u32 pa, t2, 32, %70;\nmad.wide.u32 pb, t2, 8, %71;\n"
        "mov.b32 s0, 0;\nld.global.cg.L2::128B.v2.b32 {e0,e1}, [pa];\n@q ld.global.cg.L2::128B.b32 s0, [pb];\nand.b32 bar, v, 0xff8;\n"
        "mbarrier.test_wait.parity.shared.b64 p, [bar+%79], 0;\nlop3.b32 ida, v, %67, 0xfff, 0xe4;\nld.volatile.shared.u16 id, [ida+%78];\n"
        "vote.sync.all.pred prdy, p, 0xffffffff;\n@!prdy bra.uni WA;\n"
        "HA:\nmad.lo.u32 xb, id, 64, %65;\ncvt.u16.u32 i16, id;\natom.shared.add.u32 pos, [%66+%80], %68;\n"
        "ldmatrix.sync.aligned.m8n8.x4.trans.shared.b16 {x0,x1,x2,x3}, [xb];\nldmatrix.sync.aligned.m8n8.x4.trans.shared.b16 {x24,x25,x26,x27}, [xb+512];\n"
        "xor.b32 t1, xb, 32;\nldmatrix.sync.aligned.m8n8.x4.trans.shared.b16 {x4,x5,x6,x7}, [t1];\n"
        "ldmatrix.sync.aligned.m8n8.x4.trans.shared.b16 {x28,x29,x30,x31}, [t1+512];\nxor.b32 t1, xb, 64;\n"
        "ldmatrix.sync.aligned.m8n8.x4.trans.shared.b16 {x8,x9,x10,x11}, [t1];\nldmatrix.sync.aligned.m8n8.x4.trans.shared.b16 {x16,x17,x18,x19}, [t1+512];\n"
        "xor.b32 t1, xb, 96;\nldmatrix.sync.aligned.m8n8.x4.trans.shared.b16 {x12,x13,x14,x15}, [t1];\n"
        "ldmatrix.sync.aligned.m8n8.x4.trans.shared.b16 {x20,x21,x22,x23}, [t1+512];\nst.volatile.shared.u16 [pos], i16;\nand.b32 t0, v, 16384;\n"
        "setp.ne.u32 ps1, t0, 0;\nvote.sync.any.pred ps1, ps1, 0xffffffff;\nand.b32 t0, v, 32768;\nsetp.ne.u32 ps2, t0, 0;\n"
        "vote.sync.any.pred ps2, ps2, 0xffffffff;\nmov.b32 v, vB;\nand.b32 bar, v, 0xff8;\nmbarrier.test_wait.parity.shared.b64 p, [bar+%79], 0;\n"
        "lop3.b32 ida, v, %67, 0xfff, 0xe4;\nld.volatile.shared.u16 id, [ida+%78];\nvote.sync.all.pred prdy, p, 0xffffffff;\nmov.b32 {lo, hi}, ra0;\n"
        "mov.b32 t2, {lo, lo};\nmul.rn.bf16x2 y0, x0, t2;\nmul.rn.bf16x2 y2, x2, t2;\nmov.b32 t2, {hi, hi};\nmul.rn.bf16x2 y1, x1, t2;\n"
        "mul.rn.bf16x2 y3, x3, t2;\nmma.sync.aligned.m16n8k16.row.col.f32.bf16.bf16.f32 {d0,d1,d2,d3}, {y0,y1,y2,y3}, {bA0,bA1}, {fz,fz,fz,fz};\n"
        "cvt.rn.bf16x2.f32 z0, d1, d0;\ncvt.rn.bf16x2.f32 z1, d3, d2;\nmov.b32 {lo, hi}, ra6;\nmov.b32 t2, {lo, lo};\nmul.rn.bf16x2 y24, x24, t2;\n"
        "mul.rn.bf16x2 y26, x26, t2;\nmov.b32 t2, {hi, hi};\nmul.rn.bf16x2 y25, x25, t2;\nmul.rn.bf16x2 y27, x27, t2;\n"
        "mma.sync.aligned.m16n8k16.row.col.f32.bf16.bf16.f32 {d24,d25,d26,d27}, {y24,y25,y26,y27}, {bA0,bA1}, {fz,fz,fz,fz};\ncvt.rn.bf16x2.f32 z12, d25, d24;\n"
        "cvt.rn.bf16x2.f32 z13, d27, d26;\nmov.b32 {lo, hi}, ra1;\nmov.b32 t2, {lo, lo};\nmul.rn.bf16x2 y4, x4, t2;\nmul.rn.bf16x2 y6, x6, t2;\n"
        "mov.b32 t2, {hi, hi};\nmul.rn.bf16x2 y5, x5, t2;\nmul.rn.bf16x2 y7, x7, t2;\n"
        "mma.sync.aligned.m16n8k16.row.col.f32.bf16.bf16.f32 {d4,d5,d6,d7}, {y4,y5,y6,y7}, {bA0,bA1}, {fz,fz,fz,fz};\ncvt.rn.bf16x2.f32 z2, d5, d4;\n"
        "cvt.rn.bf16x2.f32 z3, d7, d6;\nmov.b32 {lo, hi}, ra7;\nmov.b32 t2, {lo, lo};\nmul.rn.bf16x2 y28, x28, t2;\nmul.rn.bf16x2 y30, x30, t2;\n"
        "mov.b32 t2, {hi, hi};\nmul.rn.bf16x2 y29, x29, t2;\nmul.rn.bf16x2 y31, x31, t2;\n"
        "mma.sync.aligned.m16n8k16.row.col.f32.bf16.bf16.f32 {d28,d29,d30,d31}, {y28,y29,y30,y31}, {bA0,bA1}, {fz,fz,fz,fz};\ncvt.rn.bf16x2.f32 z14, d29, d28;\n"
        "cvt.rn.bf16x2.f32 z15, d31, d30;\nmov.b32 {lo, hi}, ra2;\nmov.b32 t2, {lo, lo};\nmul.rn.bf16x2 y8, x8, t2;\nmul.rn.bf16x2 y10, x10, t2;\n"
        "mov.b32 t2, {hi, hi};\nmul.rn.bf16x2 y9, x9, t2;\nmul.rn.bf16x2 y11, x11, t2;\n"
        "mma.sync.aligned.m16n8k16.row.col.f32.bf16.bf16.f32 {d8,d9,d10,d11}, {y8,y9,y10,y11}, {bA0,bA1}, {fz,fz,fz,fz};\ncvt.rn.bf16x2.f32 z4, d9, d8;\n"
        "cvt.rn.bf16x2.f32 z5, d11, d10;\nmov.b32 {lo, hi}, ra4;\nmov.b32 t2, {lo, lo};\nmul.rn.bf16x2 y16, x16, t2;\nmul.rn.bf16x2 y18, x18, t2;\n"
        "mov.b32 t2, {hi, hi};\nmul.rn.bf16x2 y17, x17, t2;\nmul.rn.bf16x2 y19, x19, t2;\n"
        "mma.sync.aligned.m16n8k16.row.col.f32.bf16.bf16.f32 {d16,d17,d18,d19}, {y16,y17,y18,y19}, {bA0,bA1}, {fz,fz,fz,fz};\ncvt.rn.bf16x2.f32 z8, d17, d16;\n"
        "cvt.rn.bf16x2.f32 z9, d19, d18;\nmov.b32 {lo, hi}, ra3;\nmov.b32 t2, {lo, lo};\nmul.rn.bf16x2 y12, x12, t2;\nmul.rn.bf16x2 y14, x14, t2;\n"
        "mov.b32 t2, {hi, hi};\nmul.rn.bf16x2 y13, x13, t2;\nmul.rn.bf16x2 y15, x15, t2;\n"
        "mma.sync.aligned.m16n8k16.row.col.f32.bf16.bf16.f32 {d12,d13,d14,d15}, {y12,y13,y14,y15}, {bA0,bA1}, {fz,fz,fz,fz};\ncvt.rn.bf16x2.f32 z6, d13, d12;\n"
        "cvt.rn.bf16x2.f32 z7, d15, d14;\nmov.b32 {lo, hi}, ra5;\nmov.b32 t2, {lo, lo};\nmul.rn.bf16x2 y20, x20, t2;\nmul.rn.bf16x2 y22, x22, t2;\n"
        "mov.b32 t2, {hi, hi};\nmul.rn.bf16x2 y21, x21, t2;\nmul.rn.bf16x2 y23, x23, t2;\n"
        "mma.sync.aligned.m16n8k16.row.col.f32.bf16.bf16.f32 {d20,d21,d22,d23}, {y20,y21,y22,y23}, {bA0,bA1}, {fz,fz,fz,fz};\ncvt.rn.bf16x2.f32 z10, d21, d20;\n"
        "cvt.rn.bf16x2.f32 z11, d23, d22;\n@ps2 bra.uni TA2;\n@ps1 bra.uni TA1;\n"
        "TA0:\nadd.rn.bf16x2 h0, h0, z0;\nadd.rn.bf16x2 h1, h1, z1;\nadd.rn.bf16x2 h2, h2, z2;\nadd.rn.bf16x2 h3, h3, z3;\nadd.rn.bf16x2 h4, h4, z4;\n"
        "add.rn.bf16x2 h5, h5, z5;\nadd.rn.bf16x2 h6, h6, z6;\nadd.rn.bf16x2 h7, h7, z7;\nadd.rn.bf16x2 h8, h8, z8;\nadd.rn.bf16x2 h9, h9, z9;\n"
        "add.rn.bf16x2 h10, h10, z10;\nadd.rn.bf16x2 h11, h11, z11;\nadd.rn.bf16x2 h12, h12, z12;\nadd.rn.bf16x2 h13, h13, z13;\nadd.rn.bf16x2 h14, h14, z14;\n"
        "add.rn.bf16x2 h15, h15, z15;\n@prdy bra.uni HB;\nbra.uni WB;\n"
        "TA1:\nadd.rn.bf16x2 h16, h16, z0;\nadd.rn.bf16x2 h17, h17, z1;\nadd.rn.bf16x2 h18, h18, z2;\nadd.rn.bf16x2 h19, h19, z3;\nadd.rn.bf16x2 h20, h20, z4;\n"
        "add.rn.bf16x2 h21, h21, z5;\nadd.rn.bf16x2 h22, h22, z6;\nadd.rn.bf16x2 h23, h23, z7;\nadd.rn.bf16x2 h24, h24, z8;\nadd.rn.bf16x2 h25, h25, z9;\n"
        "add.rn.bf16x2 h26, h26, z10;\nadd.rn.bf16x2 h27, h27, z11;\nadd.rn.bf16x2 h28, h28, z12;\nadd.rn.bf16x2 h29, h29, z13;\nadd.rn.bf16x2 h30, h30, z14;\n"
        "add.rn.bf16x2 h31, h31, z15;\n@prdy bra.uni HB;\nbra.uni WB;\n"
        "TA2:\n@ps1 bra.uni TA3;\nadd.rn.bf16x2 h32, h32, z0;\nadd.rn.bf16x2 h33, h33, z1;\nadd.rn.bf16x2 h34, h34, z2;\nadd.rn.bf16x2 h35, h35, z3;\n"
        "add.rn.bf16x2 h36, h36, z4;\nadd.rn.bf16x2 h37, h37, z5;\nadd.rn.bf16x2 h38, h38, z6;\nadd.rn.bf16x2 h39, h39, z7;\nadd.rn.bf16x2 h40, h40, z8;\n"
        "add.rn.bf16x2 h41, h41, z9;\nadd.rn.bf16x2 h42, h42, z10;\nadd.rn.bf16x2 h43, h43, z11;\nadd.rn.bf16x2 h44, h44, z12;\nadd.rn.bf16x2 h45, h45, z13;\n"
        "add.rn.bf16x2 h46, h46, z14;\nadd.rn.bf16x2 h47, h47, z15;\n@prdy bra.uni HB;\nbra.uni WB;\n"
        "TA3:\nadd.rn.bf16x2 h48, h48, z0;\nadd.rn.bf16x2 h49, h49, z1;\nadd.rn.bf16x2 h50, h50, z2;\nadd.rn.bf16x2 h51, h51, z3;\nadd.rn.bf16x2 h52, h52, z4;\n"
        "add.rn.bf16x2 h53, h53, z5;\nadd.rn.bf16x2 h54, h54, z6;\nadd.rn.bf16x2 h55, h55, z7;\nadd.rn.bf16x2 h56, h56, z8;\nadd.rn.bf16x2 h57, h57, z9;\n"
        "add.rn.bf16x2 h58, h58, z10;\nadd.rn.bf16x2 h59, h59, z11;\nadd.rn.bf16x2 h60, h60, z12;\nadd.rn.bf16x2 h61, h61, z13;\nadd.rn.bf16x2 h62, h62, z14;\n"
        "add.rn.bf16x2 h63, h63, z15;\n@prdy bra.uni HB;\nbra.uni WB;\n"
        "HB:\nmad.lo.u32 xb, id, 64, %65;\ncvt.u16.u32 i16, id;\natom.shared.add.u32 pos, [%66+%80], %68;\n"
        "ldmatrix.sync.aligned.m8n8.x4.trans.shared.b16 {x0,x1,x2,x3}, [xb];\nldmatrix.sync.aligned.m8n8.x4.trans.shared.b16 {x24,x25,x26,x27}, [xb+512];\n"
        "xor.b32 t1, xb, 32;\nldmatrix.sync.aligned.m8n8.x4.trans.shared.b16 {x4,x5,x6,x7}, [t1];\n"
        "ldmatrix.sync.aligned.m8n8.x4.trans.shared.b16 {x28,x29,x30,x31}, [t1+512];\nxor.b32 t1, xb, 64;\n"
        "ldmatrix.sync.aligned.m8n8.x4.trans.shared.b16 {x8,x9,x10,x11}, [t1];\nldmatrix.sync.aligned.m8n8.x4.trans.shared.b16 {x16,x17,x18,x19}, [t1+512];\n"
        "xor.b32 t1, xb, 96;\nldmatrix.sync.aligned.m8n8.x4.trans.shared.b16 {x12,x13,x14,x15}, [t1];\n"
        "ldmatrix.sync.aligned.m8n8.x4.trans.shared.b16 {x20,x21,x22,x23}, [t1+512];\nst.volatile.shared.u16 [pos], i16;\nand.b32 t0, v, 16384;\n"
        "setp.ne.u32 ps1, t0, 0;\nvote.sync.any.pred ps1, ps1, 0xffffffff;\nand.b32 t0, v, 32768;\nsetp.ne.u32 ps2, t0, 0;\n"
        "vote.sync.any.pred ps2, ps2, 0xffffffff;\nshfl.sync.idx.b32 v, kept, %67, 0x1f, 0xffffffff;\nor.b32 t3, %67, 4;\n"
        "shfl.sync.idx.b32 vB, kept, t3, 0x1f, 0xffffffff;\nmov.b32 {lo, hi}, rb0;\nmov.b32 t2, {lo, lo};\nmul.rn.bf16x2 y0, x0, t2;\nmul.rn.bf16x2 y2, x2, t2;\n"
        "mov.b32 t2, {hi, hi};\nmul.rn.bf16x2 y1, x1, t2;\nmul.rn.bf16x2 y3, x3, t2;\n"
        "mma.sync.aligned.m16n8k16.row.col.f32.bf16.bf16.f32 {d0,d1,d2,d3}, {y0,y1,y2,y3}, {bB0,bB1}, {fz,fz,fz,fz};\ncvt.rn.bf16x2.f32 z0, d1, d0;\n"
        "cvt.rn.bf16x2.f32 z1, d3, d2;\nmov.b32 {lo, hi}, rb6;\nmov.b32 t2, {lo, lo};\nmul.rn.bf16x2 y24, x24, t2;\nmul.rn.bf16x2 y26, x26, t2;\n"
        "mov.b32 t2, {hi, hi};\nmul.rn.bf16x2 y25, x25, t2;\nmul.rn.bf16x2 y27, x27, t2;\n"
        "mma.sync.aligned.m16n8k16.row.col.f32.bf16.bf16.f32 {d24,d25,d26,d27}, {y24,y25,y26,y27}, {bB0,bB1}, {fz,fz,fz,fz};\ncvt.rn.bf16x2.f32 z12, d25, d24;\n"
        "cvt.rn.bf16x2.f32 z13, d27, d26;\nmov.b32 {lo, hi}, rb1;\nmov.b32 t2, {lo, lo};\nmul.rn.bf16x2 y4, x4, t2;\nmul.rn.bf16x2 y6, x6, t2;\n"
        "mov.b32 t2, {hi, hi};\nmul.rn.bf16x2 y5, x5, t2;\nmul.rn.bf16x2 y7, x7, t2;\n"
        "mma.sync.aligned.m16n8k16.row.col.f32.bf16.bf16.f32 {d4,d5,d6,d7}, {y4,y5,y6,y7}, {bB0,bB1}, {fz,fz,fz,fz};\ncvt.rn.bf16x2.f32 z2, d5, d4;\n"
        "cvt.rn.bf16x2.f32 z3, d7, d6;\nmov.b32 {lo, hi}, rb7;\nmov.b32 t2, {lo, lo};\nmul.rn.bf16x2 y28, x28, t2;\nmul.rn.bf16x2 y30, x30, t2;\n"
        "mov.b32 t2, {hi, hi};\nmul.rn.bf16x2 y29, x29, t2;\nmul.rn.bf16x2 y31, x31, t2;\n"
        "mma.sync.aligned.m16n8k16.row.col.f32.bf16.bf16.f32 {d28,d29,d30,d31}, {y28,y29,y30,y31}, {bB0,bB1}, {fz,fz,fz,fz};\ncvt.rn.bf16x2.f32 z14, d29, d28;\n"
        "cvt.rn.bf16x2.f32 z15, d31, d30;\nmov.b32 {lo, hi}, rb2;\nmov.b32 t2, {lo, lo};\nmul.rn.bf16x2 y8, x8, t2;\nmul.rn.bf16x2 y10, x10, t2;\n"
        "mov.b32 t2, {hi, hi};\nmul.rn.bf16x2 y9, x9, t2;\nmul.rn.bf16x2 y11, x11, t2;\n"
        "mma.sync.aligned.m16n8k16.row.col.f32.bf16.bf16.f32 {d8,d9,d10,d11}, {y8,y9,y10,y11}, {bB0,bB1}, {fz,fz,fz,fz};\ncvt.rn.bf16x2.f32 z4, d9, d8;\n"
        "cvt.rn.bf16x2.f32 z5, d11, d10;\nmov.b32 {lo, hi}, rb4;\nmov.b32 t2, {lo, lo};\nmul.rn.bf16x2 y16, x16, t2;\nmul.rn.bf16x2 y18, x18, t2;\n"
        "mov.b32 t2, {hi, hi};\nmul.rn.bf16x2 y17, x17, t2;\nmul.rn.bf16x2 y19, x19, t2;\n"
        "mma.sync.aligned.m16n8k16.row.col.f32.bf16.bf16.f32 {d16,d17,d18,d19}, {y16,y17,y18,y19}, {bB0,bB1}, {fz,fz,fz,fz};\ncvt.rn.bf16x2.f32 z8, d17, d16;\n"
        "cvt.rn.bf16x2.f32 z9, d19, d18;\nmov.b32 {lo, hi}, rb3;\nmov.b32 t2, {lo, lo};\nmul.rn.bf16x2 y12, x12, t2;\nmul.rn.bf16x2 y14, x14, t2;\n"
        "mov.b32 t2, {hi, hi};\nmul.rn.bf16x2 y13, x13, t2;\nmul.rn.bf16x2 y15, x15, t2;\n"
        "mma.sync.aligned.m16n8k16.row.col.f32.bf16.bf16.f32 {d12,d13,d14,d15}, {y12,y13,y14,y15}, {bB0,bB1}, {fz,fz,fz,fz};\ncvt.rn.bf16x2.f32 z6, d13, d12;\n"
        "cvt.rn.bf16x2.f32 z7, d15, d14;\nmov.b32 {lo, hi}, rb5;\nmov.b32 t2, {lo, lo};\nmul.rn.bf16x2 y20, x20, t2;\nmul.rn.bf16x2 y22, x22, t2;\n"
        "mov.b32 t2, {hi, hi};\nmul.rn.bf16x2 y21, x21, t2;\nmul.rn.bf16x2 y23, x23, t2;\n"
        "mma.sync.aligned.m16n8k16.row.col.f32.bf16.bf16.f32 {d20,d21,d22,d23}, {y20,y21,y22,y23}, {bB0,bB1}, {fz,fz,fz,fz};\ncvt.rn.bf16x2.f32 z10, d21, d20;\n"
        "cvt.rn.bf16x2.f32 z11, d23, d22;\n@ps2 bra.uni TB2;\n@ps1 bra.uni TB1;\n"
        "TB0:\nadd.rn.bf16x2 h0, h0, z0;\nadd.rn.bf16x2 h1, h1, z1;\nadd.rn.bf16x2 h2, h2, z2;\nadd.rn.bf16x2 h3, h3, z3;\nadd.rn.bf16x2 h4, h4, z4;\n"
        "add.rn.bf16x2 h5, h5, z5;\nadd.rn.bf16x2 h6, h6, z6;\nadd.rn.bf16x2 h7, h7, z7;\nadd.rn.bf16x2 h8, h8, z8;\nadd.rn.bf16x2 h9, h9, z9;\n"
        "add.rn.bf16x2 h10, h10, z10;\nadd.rn.bf16x2 h11, h11, z11;\nadd.rn.bf16x2 h12, h12, z12;\nadd.rn.bf16x2 h13, h13, z13;\nadd.rn.bf16x2 h14, h14, z14;\n"
        "add.rn.bf16x2 h15, h15, z15;\nbra.uni RW;\n"
        "TB1:\nadd.rn.bf16x2 h16, h16, z0;\nadd.rn.bf16x2 h17, h17, z1;\nadd.rn.bf16x2 h18, h18, z2;\nadd.rn.bf16x2 h19, h19, z3;\nadd.rn.bf16x2 h20, h20, z4;\n"
        "add.rn.bf16x2 h21, h21, z5;\nadd.rn.bf16x2 h22, h22, z6;\nadd.rn.bf16x2 h23, h23, z7;\nadd.rn.bf16x2 h24, h24, z8;\nadd.rn.bf16x2 h25, h25, z9;\n"
        "add.rn.bf16x2 h26, h26, z10;\nadd.rn.bf16x2 h27, h27, z11;\nadd.rn.bf16x2 h28, h28, z12;\nadd.rn.bf16x2 h29, h29, z13;\nadd.rn.bf16x2 h30, h30, z14;\n"
        "add.rn.bf16x2 h31, h31, z15;\nbra.uni RW;\n"
        "TB2:\n@ps1 bra.uni TB3;\nadd.rn.bf16x2 h32, h32, z0;\nadd.rn.bf16x2 h33, h33, z1;\nadd.rn.bf16x2 h34, h34, z2;\nadd.rn.bf16x2 h35, h35, z3;\n"
        "add.rn.bf16x2 h36, h36, z4;\nadd.rn.bf16x2 h37, h37, z5;\nadd.rn.bf16x2 h38, h38, z6;\nadd.rn.bf16x2 h39, h39, z7;\nadd.rn.bf16x2 h40, h40, z8;\n"
        "add.rn.bf16x2 h41, h41, z9;\nadd.rn.bf16x2 h42, h42, z10;\nadd.rn.bf16x2 h43, h43, z11;\nadd.rn.bf16x2 h44, h44, z12;\nadd.rn.bf16x2 h45, h45, z13;\n"
        "add.rn.bf16x2 h46, h46, z14;\nadd.rn.bf16x2 h47, h47, z15;\nbra.uni RW;\n"
        "TB3:\nadd.rn.bf16x2 h48, h48, z0;\nadd.rn.bf16x2 h49, h49, z1;\nadd.rn.bf16x2 h50, h50, z2;\nadd.rn.bf16x2 h51, h51, z3;\nadd.rn.bf16x2 h52, h52, z4;\n"
        "add.rn.bf16x2 h53, h53, z5;\nadd.rn.bf16x2 h54, h54, z6;\nadd.rn.bf16x2 h55, h55, z7;\nadd.rn.bf16x2 h56, h56, z8;\nadd.rn.bf16x2 h57, h57, z9;\n"
        "add.rn.bf16x2 h58, h58, z10;\nadd.rn.bf16x2 h59, h59, z11;\nadd.rn.bf16x2 h60, h60, z12;\nadd.rn.bf16x2 h61, h61, z13;\nadd.rn.bf16x2 h62, h62, z14;\n"
        "add.rn.bf16x2 h63, h63, z15;\nbra.uni RW;\n"
        "WA:\nand.b32 t2, v, 0xff8;\nsetp.eq.u32 p, t2, 0;\nvote.sync.all.pred p, p, 0xffffffff;\n@p bra.uni DONE;\nmov.b32 n, 0;\n"
        "WA3:\nmbarrier.try_wait.parity.shared.b64 p, [t2+%79], 0;\nvote.sync.all.pred p, p, 0xffffffff;\nadd.u32 n, n, 1;\nsetp.lt.and.u32 q, n, 1000000, !p;\n"
        "@q bra.uni WA3;\nlop3.b32 ida, v, %67, 0xfff, 0xe4;\nld.volatile.shared.u16 id, [ida+%78];\nbra.uni HA;\n"
        "WB:\nand.b32 t2, v, 0xff8;\nsetp.eq.u32 p, t2, 0;\nvote.sync.all.pred p, p, 0xffffffff;\n@p bra.uni DONE;\nmov.b32 n, 0;\n"
        "WB3:\nmbarrier.try_wait.parity.shared.b64 p, [t2+%79], 0;\nvote.sync.all.pred p, p, 0xffffffff;\nadd.u32 n, n, 1;\nsetp.lt.and.u32 q, n, 1000000, !p;\n"
        "@q bra.uni WB3;\nlop3.b32 ida, v, %67, 0xfff, 0xe4;\nld.volatile.shared.u16 id, [ida+%78];\nbra.uni HB;\n"
        "DONE:\nmov.b32 %0, h0;\nmov.b32 %1, h1;\nmov.b32 %2, h2;\nmov.b32 %3, h3;\nmov.b32 %4, h4;\nmov.b32 %5, h5;\nmov.b32 %6, h6;\nmov.b32 %7, h7;\n"
        "mov.b32 %8, h8;\nmov.b32 %9, h9;\nmov.b32 %10, h10;\nmov.b32 %11, h11;\nmov.b32 %12, h12;\nmov.b32 %13, h13;\nmov.b32 %14, h14;\nmov.b32 %15, h15;\n"
        "mov.b32 %16, h16;\nmov.b32 %17, h17;\nmov.b32 %18, h18;\nmov.b32 %19, h19;\nmov.b32 %20, h20;\nmov.b32 %21, h21;\nmov.b32 %22, h22;\nmov.b32 %23, h23;\n"
        "mov.b32 %24, h24;\nmov.b32 %25, h25;\nmov.b32 %26, h26;\nmov.b32 %27, h27;\nmov.b32 %28, h28;\nmov.b32 %29, h29;\nmov.b32 %30, h30;\nmov.b32 %31, h31;\n"
        "mov.b32 %32, h32;\nmov.b32 %33, h33;\nmov.b32 %34, h34;\nmov.b32 %35, h35;\nmov.b32 %36, h36;\nmov.b32 %37, h37;\nmov.b32 %38, h38;\nmov.b32 %39, h39;\n"
        "mov.b32 %40, h40;\nmov.b32 %41, h41;\nmov.b32 %42, h42;\nmov.b32 %43, h43;\nmov.b32 %44, h44;\nmov.b32 %45, h45;\nmov.b32 %46, h46;\nmov.b32 %47, h47;\n"
        "mov.b32 %48, h48;\nmov.b32 %49, h49;\nmov.b32 %50, h50;\nmov.b32 %51, h51;\nmov.b32 %52, h52;\nmov.b32 %53, h53;\nmov.b32 %54, h54;\nmov.b32 %55, h55;\n"
        "mov.b32 %56, h56;\nmov.b32 %57, h57;\nmov.b32 %58, h58;\nmov.b32 %59, h59;\nmov.b32 %60, h60;\nmov.b32 %61, h61;\nmov.b32 %62, h62;\nmov.b32 %63, h63;\n"
        "}\n"
        : "=r"(pk[0]), "=r"(pk[1]), "=r"(pk[2]), "=r"(pk[3]), "=r"(pk[4]), "=r"(pk[5]), "=r"(pk[6]), "=r"(pk[7]), "=r"(pk[8]), "=r"(pk[9]),
          "=r"(pk[10]), "=r"(pk[11]), "=r"(pk[12]), "=r"(pk[13]), "=r"(pk[14]), "=r"(pk[15]), "=r"(pk[16]), "=r"(pk[17]), "=r"(pk[18]), "=r"(pk[19]),
          "=r"(pk[20]), "=r"(pk[21]), "=r"(pk[22]), "=r"(pk[23]), "=r"(pk[24]), "=r"(pk[25]), "=r"(pk[26]), "=r"(pk[27]), "=r"(pk[28]), "=r"(pk[29]),
          "=r"(pk[30]), "=r"(pk[31]), "=r"(pk[32]), "=r"(pk[33]), "=r"(pk[34]), "=r"(pk[35]), "=r"(pk[36]), "=r"(pk[37]), "=r"(pk[38]), "=r"(pk[39]),
          "=r"(pk[40]), "=r"(pk[41]), "=r"(pk[42]), "=r"(pk[43]), "=r"(pk[44]), "=r"(pk[45]), "=r"(pk[46]), "=r"(pk[47]), "=r"(pk[48]), "=r"(pk[49]),
          "=r"(pk[50]), "=r"(pk[51]), "=r"(pk[52]), "=r"(pk[53]), "=r"(pk[54]), "=r"(pk[55]), "=r"(pk[56]), "=r"(pk[57]), "=r"(pk[58]), "=r"(pk[59]),
          "=r"(pk[60]), "=r"(pk[61]), "=r"(pk[62]), "=r"(pk[63])
        : "r"(olp), "r"(xa), "r"(ln), "r"(lc), "r"(linc), "r"(lt), "l"(ea), "l"(sh), "l"(wf), "r"(first.x), "r"(first.y), "r"(first.z), "r"(first.w),
          "n"(sb + SM_REC), "n"(sb + SM_R), "n"(sb + SM_BAR), "n"(sb + SM_CTR), "n"(sb + SM_CGF),
          "r"(w[0]), "r"(w[1]), "r"(w[2]), "r"(w[3]), "r"(w[4]), "r"(w[5]), "r"(w[6]), "r"(w[7]), "r"(w[8]), "r"(w[9]), "r"(w[10]), "r"(w[11]),
          "r"(w[12]), "r"(w[13]), "r"(w[14]), "r"(w[15]), "r"(w[16]), "r"(w[17]), "r"(w[18]), "r"(w[19]), "r"(w[20]), "r"(w[21]), "r"(w[22]),
          "r"(w[23]), "r"(w[24]), "r"(w[25]), "r"(w[26]), "r"(w[27]), "r"(w[28]), "r"(w[29]), "r"(w[30]), "r"(w[31]), "r"(w[32]), "r"(w[33]),
          "r"(w[34]), "r"(w[35])
        : "memory");
}
__device__ __forceinline__ void consume3(uint32_t (&pk)[48], const uint32_t (&w)[36], uint32_t olp, uint32_t xa, uint32_t ln,
                                      uint32_t lc, uint32_t linc, uint32_t lt, const __nv_bfloat16* ea, const __nv_bfloat16* sh, const void* wf, uint4 first) {
    ea += lt * 4, sh += lt & 2;
    asm volatile(
        "{\n.reg .pred p, q, psw, prdy, ps1, ps2, ps3, pz, pq, pt;\n.reg .f32 d<32>, fz;\n"
        ".reg .b32 h<48>, x<32>, y<32>, ra<8>, rb<8>, bA0, bA1, bB0, bB1, c0, c1, c2, c3, e0, e1, s0, kept;\n"
        ".reg .b32 olp, v, vB, m, id, ida, bar, xb, pos, t0, t1, t2, t3, n, z<16>, kept2, g<4>, f0, f1, s1;\n.reg .b16 lo, hi, i16;\n.reg .b64 pa, pb;\n"
        "mov.f32 fz, 0f00000000;\nmov.b32 h0, 0;\nmov.b32 h1, 0;\nmov.b32 h2, 0;\nmov.b32 h3, 0;\nmov.b32 h4, 0;\nmov.b32 h5, 0;\nmov.b32 h6, 0;\n"
        "mov.b32 h7, 0;\nmov.b32 h8, 0;\nmov.b32 h9, 0;\nmov.b32 h10, 0;\nmov.b32 h11, 0;\nmov.b32 h12, 0;\nmov.b32 h13, 0;\nmov.b32 h14, 0;\nmov.b32 h15, 0;\n"
        "mov.b32 h16, 0;\nmov.b32 h17, 0;\nmov.b32 h18, 0;\nmov.b32 h19, 0;\nmov.b32 h20, 0;\nmov.b32 h21, 0;\nmov.b32 h22, 0;\nmov.b32 h23, 0;\n"
        "mov.b32 h24, 0;\nmov.b32 h25, 0;\nmov.b32 h26, 0;\nmov.b32 h27, 0;\nmov.b32 h28, 0;\nmov.b32 h29, 0;\nmov.b32 h30, 0;\nmov.b32 h31, 0;\n"
        "mov.b32 h32, 0;\nmov.b32 h33, 0;\nmov.b32 h34, 0;\nmov.b32 h35, 0;\nmov.b32 h36, 0;\nmov.b32 h37, 0;\nmov.b32 h38, 0;\nmov.b32 h39, 0;\n"
        "mov.b32 h40, 0;\nmov.b32 h41, 0;\nmov.b32 h42, 0;\nmov.b32 h43, 0;\nmov.b32 h44, 0;\nmov.b32 h45, 0;\nmov.b32 h46, 0;\nmov.b32 h47, 0;\n"
        "mov.b32 olp, %48;\nor.b32 t3, %51, 4;\nshfl.sync.bfly.b32 t3, t3, 8, 0x1f, 0xffffffff;\nand.b32 t0, %50, 32;\nsetp.ne.u32 psw, t0, 0;\n"
        "setp.eq.u32 pz, %48, 0;\nvote.sync.any.pred pz, pz, 0xffffffff;\nmov.b32 e0, %57;\nmov.b32 e1, %58;\nmov.b32 s0, %59;\nmov.b32 kept, %60;\n"
        "add.u32 olp, olp, 4;\nsetp.ne.u64 p, %56, 0;\n@p fence.proxy.async.global;\n@p red.release.gpu.global.add.u32 [%56+12], 1;\nbar.warp.sync 0xffffffff;\n"
        "shfl.sync.idx.b32 v, kept, %51, 0x1f, 0xffffffff;\nshfl.sync.idx.b32 vB, kept, t3, 0x1f, 0xffffffff;\n"
        "RW:\nmma.sync.aligned.m16n8k8.row.col.f32.bf16.bf16.f32 {d0,d1,d2,d3}, {%98,%99}, {s0}, {fz,fz,fz,fz};\n"
        "mma.sync.aligned.m16n8k8.row.col.f32.bf16.bf16.f32 {d4,d5,d6,d7}, {%100,%101}, {s0}, {fz,fz,fz,fz};\ncvt.rn.bf16x2.f32 c0, d2, d0;\n"
        "cvt.rn.bf16x2.f32 c1, d3, d1;\ncvt.rn.bf16x2.f32 c2, d6, d4;\ncvt.rn.bf16x2.f32 c3, d7, d5;\nselp.b32 bA0, c2, c0, psw;\nselp.b32 bA1, c0, c2, psw;\n"
        "selp.b32 bB0, c3, c1, psw;\nselp.b32 bB1, c1, c3, psw;\n"
        "mma.sync.aligned.m16n8k16.row.col.f32.bf16.bf16.f32 {d0,d1,d2,d3}, {%66,%67,%68,%69}, {e0,e1}, {fz,fz,fz,fz};\ncvt.rn.bf16x2.f32 ra0, d2, d0;\n"
        "cvt.rn.bf16x2.f32 rb0, d3, d1;\nmma.sync.aligned.m16n8k16.row.col.f32.bf16.bf16.f32 {d4,d5,d6,d7}, {%70,%71,%72,%73}, {e0,e1}, {fz,fz,fz,fz};\n"
        "cvt.rn.bf16x2.f32 ra1, d6, d4;\ncvt.rn.bf16x2.f32 rb1, d7, d5;\n"
        "mma.sync.aligned.m16n8k16.row.col.f32.bf16.bf16.f32 {d8,d9,d10,d11}, {%74,%75,%76,%77}, {e0,e1}, {fz,fz,fz,fz};\ncvt.rn.bf16x2.f32 ra2, d10, d8;\n"
        "cvt.rn.bf16x2.f32 rb2, d11, d9;\nmma.sync.aligned.m16n8k16.row.col.f32.bf16.bf16.f32 {d12,d13,d14,d15}, {%78,%79,%80,%81}, {e0,e1}, {fz,fz,fz,fz};\n"
        "cvt.rn.bf16x2.f32 ra3, d14, d12;\ncvt.rn.bf16x2.f32 rb3, d15, d13;\n"
        "mma.sync.aligned.m16n8k16.row.col.f32.bf16.bf16.f32 {d16,d17,d18,d19}, {%82,%83,%84,%85}, {e0,e1}, {fz,fz,fz,fz};\ncvt.rn.bf16x2.f32 ra4, d18, d16;\n"
        "cvt.rn.bf16x2.f32 rb4, d19, d17;\nmma.sync.aligned.m16n8k16.row.col.f32.bf16.bf16.f32 {d20,d21,d22,d23}, {%86,%87,%88,%89}, {e0,e1}, {fz,fz,fz,fz};\n"
        "cvt.rn.bf16x2.f32 ra5, d22, d20;\ncvt.rn.bf16x2.f32 rb5, d23, d21;\n"
        "mma.sync.aligned.m16n8k16.row.col.f32.bf16.bf16.f32 {d24,d25,d26,d27}, {%90,%91,%92,%93}, {e0,e1}, {fz,fz,fz,fz};\ncvt.rn.bf16x2.f32 ra6, d26, d24;\n"
        "cvt.rn.bf16x2.f32 rb6, d27, d25;\nmma.sync.aligned.m16n8k16.row.col.f32.bf16.bf16.f32 {d28,d29,d30,d31}, {%94,%95,%96,%97}, {e0,e1}, {fz,fz,fz,fz};\n"
        "cvt.rn.bf16x2.f32 ra7, d30, d28;\ncvt.rn.bf16x2.f32 rb7, d31, d29;\nld.shared.u16 t0, [olp];\nadd.u32 olp, olp, 4;\n"
        "lop3.b32 t1, t0, %50, 0x3ff0, 0xe4;\nld.shared.b32 t1, [t1+%61];\nshr.u32 t2, t1, 1;\nlop3.b32 kept, t2, t0, 0xffe, 0xe4;\n"
        "lop3.b32 t2, t1, %51, 3, 0x80;\nsetp.ne.u32 q, t2, 0;\nshr.u32 t2, t1, 13;\nmad.wide.u32 pa, t2, 32, %54;\nmad.wide.u32 pb, t2, 8, %55;\n"
        "mov.b32 s0, 0;\nld.global.cg.L2::128B.v2.b32 {e0,e1}, [pa];\n@q ld.global.cg.L2::128B.b32 s0, [pb];\nand.b32 bar, v, 0xff8;\n"
        "mbarrier.test_wait.parity.shared.b64 p, [bar+%63], 0;\nlop3.b32 ida, v, %51, 0xfff, 0xe4;\nld.volatile.shared.u16 id, [ida+%62];\n"
        "vote.sync.all.pred prdy, p, 0xffffffff;\n@!prdy bra.uni WA;\n"
        "HA:\nmad.lo.u32 xb, id, 64, %49;\ncvt.u16.u32 i16, id;\natom.shared.add.u32 pos, [%50+%64], %52;\n"
        "ldmatrix.sync.aligned.m8n8.x4.trans.shared.b16 {x0,x1,x2,x3}, [xb];\nldmatrix.sync.aligned.m8n8.x4.trans.shared.b16 {x24,x25,x26,x27}, [xb+512];\n"
        "xor.b32 t1, xb, 32;\nldmatrix.sync.aligned.m8n8.x4.trans.shared.b16 {x4,x5,x6,x7}, [t1];\n"
        "ldmatrix.sync.aligned.m8n8.x4.trans.shared.b16 {x28,x29,x30,x31}, [t1+512];\nxor.b32 t1, xb, 64;\n"
        "ldmatrix.sync.aligned.m8n8.x4.trans.shared.b16 {x8,x9,x10,x11}, [t1];\nldmatrix.sync.aligned.m8n8.x4.trans.shared.b16 {x16,x17,x18,x19}, [t1+512];\n"
        "xor.b32 t1, xb, 96;\nldmatrix.sync.aligned.m8n8.x4.trans.shared.b16 {x12,x13,x14,x15}, [t1];\n"
        "ldmatrix.sync.aligned.m8n8.x4.trans.shared.b16 {x20,x21,x22,x23}, [t1+512];\nst.volatile.shared.u16 [pos], i16;\nand.b32 t0, v, 16384;\n"
        "setp.ne.u32 ps1, t0, 0;\nvote.sync.any.pred ps1, ps1, 0xffffffff;\nand.b32 t0, v, 32768;\nsetp.ne.u32 ps2, t0, 0;\n"
        "vote.sync.any.pred ps2, ps2, 0xffffffff;\nmov.b32 v, vB;\nand.b32 bar, v, 0xff8;\nmbarrier.test_wait.parity.shared.b64 p, [bar+%63], 0;\n"
        "lop3.b32 ida, v, %51, 0xfff, 0xe4;\nld.volatile.shared.u16 id, [ida+%62];\nvote.sync.all.pred prdy, p, 0xffffffff;\nmov.b32 {lo, hi}, ra0;\n"
        "mov.b32 t2, {lo, lo};\nmul.rn.bf16x2 y0, x0, t2;\nmul.rn.bf16x2 y2, x2, t2;\nmov.b32 t2, {hi, hi};\nmul.rn.bf16x2 y1, x1, t2;\n"
        "mul.rn.bf16x2 y3, x3, t2;\nmma.sync.aligned.m16n8k16.row.col.f32.bf16.bf16.f32 {d0,d1,d2,d3}, {y0,y1,y2,y3}, {bA0,bA1}, {fz,fz,fz,fz};\n"
        "cvt.rn.bf16x2.f32 z0, d1, d0;\ncvt.rn.bf16x2.f32 z1, d3, d2;\nmov.b32 {lo, hi}, ra6;\nmov.b32 t2, {lo, lo};\nmul.rn.bf16x2 y24, x24, t2;\n"
        "mul.rn.bf16x2 y26, x26, t2;\nmov.b32 t2, {hi, hi};\nmul.rn.bf16x2 y25, x25, t2;\nmul.rn.bf16x2 y27, x27, t2;\n"
        "mma.sync.aligned.m16n8k16.row.col.f32.bf16.bf16.f32 {d24,d25,d26,d27}, {y24,y25,y26,y27}, {bA0,bA1}, {fz,fz,fz,fz};\ncvt.rn.bf16x2.f32 z12, d25, d24;\n"
        "cvt.rn.bf16x2.f32 z13, d27, d26;\nmov.b32 {lo, hi}, ra1;\nmov.b32 t2, {lo, lo};\nmul.rn.bf16x2 y4, x4, t2;\nmul.rn.bf16x2 y6, x6, t2;\n"
        "mov.b32 t2, {hi, hi};\nmul.rn.bf16x2 y5, x5, t2;\nmul.rn.bf16x2 y7, x7, t2;\n"
        "mma.sync.aligned.m16n8k16.row.col.f32.bf16.bf16.f32 {d4,d5,d6,d7}, {y4,y5,y6,y7}, {bA0,bA1}, {fz,fz,fz,fz};\ncvt.rn.bf16x2.f32 z2, d5, d4;\n"
        "cvt.rn.bf16x2.f32 z3, d7, d6;\nmov.b32 {lo, hi}, ra7;\nmov.b32 t2, {lo, lo};\nmul.rn.bf16x2 y28, x28, t2;\nmul.rn.bf16x2 y30, x30, t2;\n"
        "mov.b32 t2, {hi, hi};\nmul.rn.bf16x2 y29, x29, t2;\nmul.rn.bf16x2 y31, x31, t2;\n"
        "mma.sync.aligned.m16n8k16.row.col.f32.bf16.bf16.f32 {d28,d29,d30,d31}, {y28,y29,y30,y31}, {bA0,bA1}, {fz,fz,fz,fz};\ncvt.rn.bf16x2.f32 z14, d29, d28;\n"
        "cvt.rn.bf16x2.f32 z15, d31, d30;\nmov.b32 {lo, hi}, ra2;\nmov.b32 t2, {lo, lo};\nmul.rn.bf16x2 y8, x8, t2;\nmul.rn.bf16x2 y10, x10, t2;\n"
        "mov.b32 t2, {hi, hi};\nmul.rn.bf16x2 y9, x9, t2;\nmul.rn.bf16x2 y11, x11, t2;\n"
        "mma.sync.aligned.m16n8k16.row.col.f32.bf16.bf16.f32 {d8,d9,d10,d11}, {y8,y9,y10,y11}, {bA0,bA1}, {fz,fz,fz,fz};\ncvt.rn.bf16x2.f32 z4, d9, d8;\n"
        "cvt.rn.bf16x2.f32 z5, d11, d10;\nmov.b32 {lo, hi}, ra4;\nmov.b32 t2, {lo, lo};\nmul.rn.bf16x2 y16, x16, t2;\nmul.rn.bf16x2 y18, x18, t2;\n"
        "mov.b32 t2, {hi, hi};\nmul.rn.bf16x2 y17, x17, t2;\nmul.rn.bf16x2 y19, x19, t2;\n"
        "mma.sync.aligned.m16n8k16.row.col.f32.bf16.bf16.f32 {d16,d17,d18,d19}, {y16,y17,y18,y19}, {bA0,bA1}, {fz,fz,fz,fz};\ncvt.rn.bf16x2.f32 z8, d17, d16;\n"
        "cvt.rn.bf16x2.f32 z9, d19, d18;\nmov.b32 {lo, hi}, ra3;\nmov.b32 t2, {lo, lo};\nmul.rn.bf16x2 y12, x12, t2;\nmul.rn.bf16x2 y14, x14, t2;\n"
        "mov.b32 t2, {hi, hi};\nmul.rn.bf16x2 y13, x13, t2;\nmul.rn.bf16x2 y15, x15, t2;\n"
        "mma.sync.aligned.m16n8k16.row.col.f32.bf16.bf16.f32 {d12,d13,d14,d15}, {y12,y13,y14,y15}, {bA0,bA1}, {fz,fz,fz,fz};\ncvt.rn.bf16x2.f32 z6, d13, d12;\n"
        "cvt.rn.bf16x2.f32 z7, d15, d14;\nmov.b32 {lo, hi}, ra5;\nmov.b32 t2, {lo, lo};\nmul.rn.bf16x2 y20, x20, t2;\nmul.rn.bf16x2 y22, x22, t2;\n"
        "mov.b32 t2, {hi, hi};\nmul.rn.bf16x2 y21, x21, t2;\nmul.rn.bf16x2 y23, x23, t2;\n"
        "mma.sync.aligned.m16n8k16.row.col.f32.bf16.bf16.f32 {d20,d21,d22,d23}, {y20,y21,y22,y23}, {bA0,bA1}, {fz,fz,fz,fz};\ncvt.rn.bf16x2.f32 z10, d21, d20;\n"
        "cvt.rn.bf16x2.f32 z11, d23, d22;\n@ps2 bra.uni TA2;\n@ps1 bra.uni TA1;\n"
        "TA0:\nadd.rn.bf16x2 h0, h0, z0;\nadd.rn.bf16x2 h1, h1, z1;\nadd.rn.bf16x2 h2, h2, z2;\nadd.rn.bf16x2 h3, h3, z3;\nadd.rn.bf16x2 h4, h4, z4;\n"
        "add.rn.bf16x2 h5, h5, z5;\nadd.rn.bf16x2 h6, h6, z6;\nadd.rn.bf16x2 h7, h7, z7;\nadd.rn.bf16x2 h8, h8, z8;\nadd.rn.bf16x2 h9, h9, z9;\n"
        "add.rn.bf16x2 h10, h10, z10;\nadd.rn.bf16x2 h11, h11, z11;\nadd.rn.bf16x2 h12, h12, z12;\nadd.rn.bf16x2 h13, h13, z13;\nadd.rn.bf16x2 h14, h14, z14;\n"
        "add.rn.bf16x2 h15, h15, z15;\n@prdy bra.uni HB;\nbra.uni WB;\n"
        "TA1:\nadd.rn.bf16x2 h16, h16, z0;\nadd.rn.bf16x2 h17, h17, z1;\nadd.rn.bf16x2 h18, h18, z2;\nadd.rn.bf16x2 h19, h19, z3;\nadd.rn.bf16x2 h20, h20, z4;\n"
        "add.rn.bf16x2 h21, h21, z5;\nadd.rn.bf16x2 h22, h22, z6;\nadd.rn.bf16x2 h23, h23, z7;\nadd.rn.bf16x2 h24, h24, z8;\nadd.rn.bf16x2 h25, h25, z9;\n"
        "add.rn.bf16x2 h26, h26, z10;\nadd.rn.bf16x2 h27, h27, z11;\nadd.rn.bf16x2 h28, h28, z12;\nadd.rn.bf16x2 h29, h29, z13;\nadd.rn.bf16x2 h30, h30, z14;\n"
        "add.rn.bf16x2 h31, h31, z15;\n@prdy bra.uni HB;\nbra.uni WB;\n"
        "TA2:\nadd.rn.bf16x2 h32, h32, z0;\nadd.rn.bf16x2 h33, h33, z1;\nadd.rn.bf16x2 h34, h34, z2;\nadd.rn.bf16x2 h35, h35, z3;\nadd.rn.bf16x2 h36, h36, z4;\n"
        "add.rn.bf16x2 h37, h37, z5;\nadd.rn.bf16x2 h38, h38, z6;\nadd.rn.bf16x2 h39, h39, z7;\nadd.rn.bf16x2 h40, h40, z8;\nadd.rn.bf16x2 h41, h41, z9;\n"
        "add.rn.bf16x2 h42, h42, z10;\nadd.rn.bf16x2 h43, h43, z11;\nadd.rn.bf16x2 h44, h44, z12;\nadd.rn.bf16x2 h45, h45, z13;\nadd.rn.bf16x2 h46, h46, z14;\n"
        "add.rn.bf16x2 h47, h47, z15;\n@prdy bra.uni HB;\nbra.uni WB;\n"
        "HB:\nmad.lo.u32 xb, id, 64, %49;\ncvt.u16.u32 i16, id;\natom.shared.add.u32 pos, [%50+%64], %52;\n"
        "ldmatrix.sync.aligned.m8n8.x4.trans.shared.b16 {x0,x1,x2,x3}, [xb];\nldmatrix.sync.aligned.m8n8.x4.trans.shared.b16 {x24,x25,x26,x27}, [xb+512];\n"
        "xor.b32 t1, xb, 32;\nldmatrix.sync.aligned.m8n8.x4.trans.shared.b16 {x4,x5,x6,x7}, [t1];\n"
        "ldmatrix.sync.aligned.m8n8.x4.trans.shared.b16 {x28,x29,x30,x31}, [t1+512];\nxor.b32 t1, xb, 64;\n"
        "ldmatrix.sync.aligned.m8n8.x4.trans.shared.b16 {x8,x9,x10,x11}, [t1];\nldmatrix.sync.aligned.m8n8.x4.trans.shared.b16 {x16,x17,x18,x19}, [t1+512];\n"
        "xor.b32 t1, xb, 96;\nldmatrix.sync.aligned.m8n8.x4.trans.shared.b16 {x12,x13,x14,x15}, [t1];\n"
        "ldmatrix.sync.aligned.m8n8.x4.trans.shared.b16 {x20,x21,x22,x23}, [t1+512];\nst.volatile.shared.u16 [pos], i16;\nand.b32 t0, v, 16384;\n"
        "setp.ne.u32 ps1, t0, 0;\nvote.sync.any.pred ps1, ps1, 0xffffffff;\nand.b32 t0, v, 32768;\nsetp.ne.u32 ps2, t0, 0;\n"
        "vote.sync.any.pred ps2, ps2, 0xffffffff;\nshfl.sync.idx.b32 v, kept, %51, 0x1f, 0xffffffff;\nshfl.sync.idx.b32 vB, kept, t3, 0x1f, 0xffffffff;\n"
        "mov.b32 {lo, hi}, rb0;\nmov.b32 t2, {lo, lo};\nmul.rn.bf16x2 y0, x0, t2;\nmul.rn.bf16x2 y2, x2, t2;\nmov.b32 t2, {hi, hi};\nmul.rn.bf16x2 y1, x1, t2;\n"
        "mul.rn.bf16x2 y3, x3, t2;\nmma.sync.aligned.m16n8k16.row.col.f32.bf16.bf16.f32 {d0,d1,d2,d3}, {y0,y1,y2,y3}, {bB0,bB1}, {fz,fz,fz,fz};\n"
        "cvt.rn.bf16x2.f32 z0, d1, d0;\ncvt.rn.bf16x2.f32 z1, d3, d2;\nmov.b32 {lo, hi}, rb6;\nmov.b32 t2, {lo, lo};\nmul.rn.bf16x2 y24, x24, t2;\n"
        "mul.rn.bf16x2 y26, x26, t2;\nmov.b32 t2, {hi, hi};\nmul.rn.bf16x2 y25, x25, t2;\nmul.rn.bf16x2 y27, x27, t2;\n"
        "mma.sync.aligned.m16n8k16.row.col.f32.bf16.bf16.f32 {d24,d25,d26,d27}, {y24,y25,y26,y27}, {bB0,bB1}, {fz,fz,fz,fz};\ncvt.rn.bf16x2.f32 z12, d25, d24;\n"
        "cvt.rn.bf16x2.f32 z13, d27, d26;\nmov.b32 {lo, hi}, rb1;\nmov.b32 t2, {lo, lo};\nmul.rn.bf16x2 y4, x4, t2;\nmul.rn.bf16x2 y6, x6, t2;\n"
        "mov.b32 t2, {hi, hi};\nmul.rn.bf16x2 y5, x5, t2;\nmul.rn.bf16x2 y7, x7, t2;\n"
        "mma.sync.aligned.m16n8k16.row.col.f32.bf16.bf16.f32 {d4,d5,d6,d7}, {y4,y5,y6,y7}, {bB0,bB1}, {fz,fz,fz,fz};\ncvt.rn.bf16x2.f32 z2, d5, d4;\n"
        "cvt.rn.bf16x2.f32 z3, d7, d6;\nmov.b32 {lo, hi}, rb7;\nmov.b32 t2, {lo, lo};\nmul.rn.bf16x2 y28, x28, t2;\nmul.rn.bf16x2 y30, x30, t2;\n"
        "mov.b32 t2, {hi, hi};\nmul.rn.bf16x2 y29, x29, t2;\nmul.rn.bf16x2 y31, x31, t2;\n"
        "mma.sync.aligned.m16n8k16.row.col.f32.bf16.bf16.f32 {d28,d29,d30,d31}, {y28,y29,y30,y31}, {bB0,bB1}, {fz,fz,fz,fz};\ncvt.rn.bf16x2.f32 z14, d29, d28;\n"
        "cvt.rn.bf16x2.f32 z15, d31, d30;\nmov.b32 {lo, hi}, rb2;\nmov.b32 t2, {lo, lo};\nmul.rn.bf16x2 y8, x8, t2;\nmul.rn.bf16x2 y10, x10, t2;\n"
        "mov.b32 t2, {hi, hi};\nmul.rn.bf16x2 y9, x9, t2;\nmul.rn.bf16x2 y11, x11, t2;\n"
        "mma.sync.aligned.m16n8k16.row.col.f32.bf16.bf16.f32 {d8,d9,d10,d11}, {y8,y9,y10,y11}, {bB0,bB1}, {fz,fz,fz,fz};\ncvt.rn.bf16x2.f32 z4, d9, d8;\n"
        "cvt.rn.bf16x2.f32 z5, d11, d10;\nmov.b32 {lo, hi}, rb4;\nmov.b32 t2, {lo, lo};\nmul.rn.bf16x2 y16, x16, t2;\nmul.rn.bf16x2 y18, x18, t2;\n"
        "mov.b32 t2, {hi, hi};\nmul.rn.bf16x2 y17, x17, t2;\nmul.rn.bf16x2 y19, x19, t2;\n"
        "mma.sync.aligned.m16n8k16.row.col.f32.bf16.bf16.f32 {d16,d17,d18,d19}, {y16,y17,y18,y19}, {bB0,bB1}, {fz,fz,fz,fz};\ncvt.rn.bf16x2.f32 z8, d17, d16;\n"
        "cvt.rn.bf16x2.f32 z9, d19, d18;\nmov.b32 {lo, hi}, rb3;\nmov.b32 t2, {lo, lo};\nmul.rn.bf16x2 y12, x12, t2;\nmul.rn.bf16x2 y14, x14, t2;\n"
        "mov.b32 t2, {hi, hi};\nmul.rn.bf16x2 y13, x13, t2;\nmul.rn.bf16x2 y15, x15, t2;\n"
        "mma.sync.aligned.m16n8k16.row.col.f32.bf16.bf16.f32 {d12,d13,d14,d15}, {y12,y13,y14,y15}, {bB0,bB1}, {fz,fz,fz,fz};\ncvt.rn.bf16x2.f32 z6, d13, d12;\n"
        "cvt.rn.bf16x2.f32 z7, d15, d14;\nmov.b32 {lo, hi}, rb5;\nmov.b32 t2, {lo, lo};\nmul.rn.bf16x2 y20, x20, t2;\nmul.rn.bf16x2 y22, x22, t2;\n"
        "mov.b32 t2, {hi, hi};\nmul.rn.bf16x2 y21, x21, t2;\nmul.rn.bf16x2 y23, x23, t2;\n"
        "mma.sync.aligned.m16n8k16.row.col.f32.bf16.bf16.f32 {d20,d21,d22,d23}, {y20,y21,y22,y23}, {bB0,bB1}, {fz,fz,fz,fz};\ncvt.rn.bf16x2.f32 z10, d21, d20;\n"
        "cvt.rn.bf16x2.f32 z11, d23, d22;\n@ps2 bra.uni TB2;\n@ps1 bra.uni TB1;\n"
        "TB0:\nadd.rn.bf16x2 h0, h0, z0;\nadd.rn.bf16x2 h1, h1, z1;\nadd.rn.bf16x2 h2, h2, z2;\nadd.rn.bf16x2 h3, h3, z3;\nadd.rn.bf16x2 h4, h4, z4;\n"
        "add.rn.bf16x2 h5, h5, z5;\nadd.rn.bf16x2 h6, h6, z6;\nadd.rn.bf16x2 h7, h7, z7;\nadd.rn.bf16x2 h8, h8, z8;\nadd.rn.bf16x2 h9, h9, z9;\n"
        "add.rn.bf16x2 h10, h10, z10;\nadd.rn.bf16x2 h11, h11, z11;\nadd.rn.bf16x2 h12, h12, z12;\nadd.rn.bf16x2 h13, h13, z13;\nadd.rn.bf16x2 h14, h14, z14;\n"
        "add.rn.bf16x2 h15, h15, z15;\nbra.uni RW;\n"
        "TB1:\nadd.rn.bf16x2 h16, h16, z0;\nadd.rn.bf16x2 h17, h17, z1;\nadd.rn.bf16x2 h18, h18, z2;\nadd.rn.bf16x2 h19, h19, z3;\nadd.rn.bf16x2 h20, h20, z4;\n"
        "add.rn.bf16x2 h21, h21, z5;\nadd.rn.bf16x2 h22, h22, z6;\nadd.rn.bf16x2 h23, h23, z7;\nadd.rn.bf16x2 h24, h24, z8;\nadd.rn.bf16x2 h25, h25, z9;\n"
        "add.rn.bf16x2 h26, h26, z10;\nadd.rn.bf16x2 h27, h27, z11;\nadd.rn.bf16x2 h28, h28, z12;\nadd.rn.bf16x2 h29, h29, z13;\nadd.rn.bf16x2 h30, h30, z14;\n"
        "add.rn.bf16x2 h31, h31, z15;\nbra.uni RW;\n"
        "TB2:\nadd.rn.bf16x2 h32, h32, z0;\nadd.rn.bf16x2 h33, h33, z1;\nadd.rn.bf16x2 h34, h34, z2;\nadd.rn.bf16x2 h35, h35, z3;\nadd.rn.bf16x2 h36, h36, z4;\n"
        "add.rn.bf16x2 h37, h37, z5;\nadd.rn.bf16x2 h38, h38, z6;\nadd.rn.bf16x2 h39, h39, z7;\nadd.rn.bf16x2 h40, h40, z8;\nadd.rn.bf16x2 h41, h41, z9;\n"
        "add.rn.bf16x2 h42, h42, z10;\nadd.rn.bf16x2 h43, h43, z11;\nadd.rn.bf16x2 h44, h44, z12;\nadd.rn.bf16x2 h45, h45, z13;\nadd.rn.bf16x2 h46, h46, z14;\n"
        "add.rn.bf16x2 h47, h47, z15;\nbra.uni RW;\n"
        "WA:\nand.b32 t2, v, 0xff8;\nsetp.eq.u32 p, t2, 0;\nvote.sync.all.pred p, p, 0xffffffff;\n@p bra.uni DONE;\nmov.b32 n, 0;\n"
        "WA3:\nmbarrier.try_wait.parity.shared.b64 p, [t2+%63], 0;\nvote.sync.all.pred p, p, 0xffffffff;\nadd.u32 n, n, 1;\nsetp.lt.and.u32 q, n, 1000000, !p;\n"
        "@q bra.uni WA3;\nlop3.b32 ida, v, %51, 0xfff, 0xe4;\nld.volatile.shared.u16 id, [ida+%62];\nbra.uni HA;\n"
        "WB:\nand.b32 t2, v, 0xff8;\nsetp.eq.u32 p, t2, 0;\nvote.sync.all.pred p, p, 0xffffffff;\n@p bra.uni DONE;\nmov.b32 n, 0;\n"
        "WB3:\nmbarrier.try_wait.parity.shared.b64 p, [t2+%63], 0;\nvote.sync.all.pred p, p, 0xffffffff;\nadd.u32 n, n, 1;\nsetp.lt.and.u32 q, n, 1000000, !p;\n"
        "@q bra.uni WB3;\nlop3.b32 ida, v, %51, 0xfff, 0xe4;\nld.volatile.shared.u16 id, [ida+%62];\nbra.uni HB;\n"
        "DONE:\nmov.b32 %0, h0;\nmov.b32 %1, h1;\nmov.b32 %2, h2;\nmov.b32 %3, h3;\nmov.b32 %4, h4;\nmov.b32 %5, h5;\nmov.b32 %6, h6;\nmov.b32 %7, h7;\n"
        "mov.b32 %8, h8;\nmov.b32 %9, h9;\nmov.b32 %10, h10;\nmov.b32 %11, h11;\nmov.b32 %12, h12;\nmov.b32 %13, h13;\nmov.b32 %14, h14;\nmov.b32 %15, h15;\n"
        "mov.b32 %16, h16;\nmov.b32 %17, h17;\nmov.b32 %18, h18;\nmov.b32 %19, h19;\nmov.b32 %20, h20;\nmov.b32 %21, h21;\nmov.b32 %22, h22;\nmov.b32 %23, h23;\n"
        "mov.b32 %24, h24;\nmov.b32 %25, h25;\nmov.b32 %26, h26;\nmov.b32 %27, h27;\nmov.b32 %28, h28;\nmov.b32 %29, h29;\nmov.b32 %30, h30;\nmov.b32 %31, h31;\n"
        "mov.b32 %32, h32;\nmov.b32 %33, h33;\nmov.b32 %34, h34;\nmov.b32 %35, h35;\nmov.b32 %36, h36;\nmov.b32 %37, h37;\nmov.b32 %38, h38;\nmov.b32 %39, h39;\n"
        "mov.b32 %40, h40;\nmov.b32 %41, h41;\nmov.b32 %42, h42;\nmov.b32 %43, h43;\nmov.b32 %44, h44;\nmov.b32 %45, h45;\nmov.b32 %46, h46;\nmov.b32 %47, h47;\n"
        "}\n"
        : "=r"(pk[0]), "=r"(pk[1]), "=r"(pk[2]), "=r"(pk[3]), "=r"(pk[4]), "=r"(pk[5]), "=r"(pk[6]), "=r"(pk[7]), "=r"(pk[8]), "=r"(pk[9]),
          "=r"(pk[10]), "=r"(pk[11]), "=r"(pk[12]), "=r"(pk[13]), "=r"(pk[14]), "=r"(pk[15]), "=r"(pk[16]), "=r"(pk[17]), "=r"(pk[18]), "=r"(pk[19]),
          "=r"(pk[20]), "=r"(pk[21]), "=r"(pk[22]), "=r"(pk[23]), "=r"(pk[24]), "=r"(pk[25]), "=r"(pk[26]), "=r"(pk[27]), "=r"(pk[28]), "=r"(pk[29]),
          "=r"(pk[30]), "=r"(pk[31]), "=r"(pk[32]), "=r"(pk[33]), "=r"(pk[34]), "=r"(pk[35]), "=r"(pk[36]), "=r"(pk[37]), "=r"(pk[38]), "=r"(pk[39]),
          "=r"(pk[40]), "=r"(pk[41]), "=r"(pk[42]), "=r"(pk[43]), "=r"(pk[44]), "=r"(pk[45]), "=r"(pk[46]), "=r"(pk[47])
        : "r"(olp), "r"(xa), "r"(ln), "r"(lc), "r"(linc), "r"(lt), "l"(ea), "l"(sh), "l"(wf), "r"(first.x), "r"(first.y), "r"(first.z), "r"(first.w),
          "n"(sb + SM_REC), "n"(sb + SM_R), "n"(sb + SM_BAR), "n"(sb + SM_CTR), "n"(sb + SM_CGF),
          "r"(w[0]), "r"(w[1]), "r"(w[2]), "r"(w[3]), "r"(w[4]), "r"(w[5]), "r"(w[6]), "r"(w[7]), "r"(w[8]), "r"(w[9]), "r"(w[10]), "r"(w[11]),
          "r"(w[12]), "r"(w[13]), "r"(w[14]), "r"(w[15]), "r"(w[16]), "r"(w[17]), "r"(w[18]), "r"(w[19]), "r"(w[20]), "r"(w[21]), "r"(w[22]),
          "r"(w[23]), "r"(w[24]), "r"(w[25]), "r"(w[26]), "r"(w[27]), "r"(w[28]), "r"(w[29]), "r"(w[30]), "r"(w[31]), "r"(w[32]), "r"(w[33]),
          "r"(w[34]), "r"(w[35])
        : "memory");
}

__device__ __forceinline__ void wf_done() {
    asm volatile("fence.proxy.async.global;\nred.release.gpu.global.add.u32 [%0+12], 1;" ::"l"(g_sync) : "memory");
}

template <int NS>
__device__ __forceinline__ void consumer(const __nv_bfloat16* __restrict__ sh,
                                         const __nv_bfloat16* __restrict__ ea, __nv_bfloat16* __restrict__ out, int N, int npb, uint4 first) {
    uint32_t pk[NS * 16];
    {
        const int lane = threadIdx.x & 31, warp = threadIdx.x >> 5;
        const int mi = lane >> 3, r = lane & 7, j = r >> 1;
        const int u = 2 * ((mi >> 1) ^ (j >> 1)) + (r & 1), ph = (j ^ (j >> 1)) & 1;
        uint32_t w[36];
        {
            const uint32_t a = sb + SC_WR + (4 * j + (r & 1) + (mi & 2)) * 272 + (mi & 1) * 16;
#pragma unroll
            for (int c = 0; c < 8; c++)
                asm volatile("ldmatrix.sync.aligned.m8n8.x4.trans.shared.b16 {%0,%1,%2,%3}, [%4];"
                             : "=r"(w[4 * c]), "=r"(w[4 * c + 1]), "=r"(w[4 * c + 2]), "=r"(w[4 * c + 3]) : "r"(a + c * 32) : "memory");
            const uint32_t ca = sb + SC_CG + (lane & 2) * 8 + ((lane >> 2) & 3) * 2;
#pragma unroll
            for (int k = 0; k < 4; k++) {
                const uint32_t f = lds16(ca + 32 * k) | (lds16(ca + 32 * k + 8) << 16);
                w[32 + k] = (lane & 1) == (lane >> 4) ? f : 0;
            }
            asm volatile("fence.proxy.async.shared::cta;\nbar.sync 2, %0;" ::"n"(NCW * 32) : "memory");
            if (threadIdx.x < WSL) sts16(sb + SM_R + 0x1000 + (4 + SP - WSL + lane) * 2, (sb + SC_WR) / 64 + lane * 16);
        }
        const uint32_t xa = __shfl_sync(0xffffffffu, u * 128 + (((u + 4 * ph) ^ (mi & 1)) << 4), lane);
        const uint32_t ln = __shfl_sync(0xffffffffu, lane * 16 + (lane >> 3) * 4, lane);
        const uint32_t lc = __shfl_sync(0xffffffffu, j * 8 + (1 << (lane & 1)) + (ph << 12), lane);
        const uint32_t linc = __shfl_sync(0xffffffffu, (lane & 0x19) ? 0 : 4, lane);
        const uint32_t lt = __shfl_sync(0xffffffffu, lane & 3, lane);
        const void* wfp = (threadIdx.x >> 2) == WFT && blockIdx.x < 128 ? g_sync : nullptr;
        const uint32_t olp = sb + SM_OL + warp * (OLN * 2) + ((lane & 4) >> 1);
        if constexpr (NS == 4) consume4(pk, w, olp, xa, ln, lc, linc, lt, ea, sh, wfp, first);
        else consume3(pk, w, olp, xa, ln, lc, linc, lt, ea, sh, wfp, first);
    }
    TLMAX(10);
    const int tid = thread_id(), lane = tid & 31, warp = tid >> 5, g = lane >> 2, t = lane & 3;
    const uint32_t wc = lds32(sb + SM_MISC + 12) + 1;
    const uint32_t inv = lds32(sb + SM_INV + warp * 4);
    const int node0 = cta_id() * npb, nnodes = min(npb, N - node0);
    uint4* op[NS];
    uint32_t on[NS];
#pragma unroll
    for (int s = 0; s < NS; s++) {
        const int nl = ((inv >> (8 * s)) & 255) + (g >> 2) * 40;
        op[s] = (uint4*)(out + ((size_t)(node0 + nl) * 4 + (g & 3)) * 128 + 8 * t);
        on[s] = nl < nnodes;
    }
    if constexpr (NS == 4) project4(pk, sb + SM_R + wc * 8, sb + SM_BAR + (wc + EM3 * t) * 8, op, on);
    else project3(pk, sb + SM_R + wc * 8, sb + SM_BAR + (wc + EM3 * t) * 8, op, on);
}

#define TLHI "shl.b32 d, tb, 16;\n"
#define RAOFF ((threadIdx.x & 96) >> 2)
#define XSTR(x) XSTR2(x)
#define XSTR2(x) #x
__device__ __forceinline__ void producer(const CUtensorMap* tmx, int pw) {
    const uint32_t nch = lds32(sb + SM_MISC + 12), c0 = lds32(sb + SM_MISC + 24);
    asm volatile("bar.sync 1, 512;" ::: "memory");
    if (elect()) {
        asm volatile(
            "{\n.reg .pred p, q, lead, never;\n.reg .b32 ra, oa, off, due, now, a<2>, b<2>, s<4>, d, r, z<8>, bar<4>, t, n, tb, ta, k64, ktx;\n"
            ".reg .b64 lg, t64, tm;\n"
            "mov.b32 ta, %5;\nld.volatile.shared.v4.b32 {z0,z1,z2,z3}, [ta+32];\nld.volatile.shared.v4.b32 {z4,z5,z6,z7}, [ta+32];\n"
            "mov.b32 ra, %9;\nmad.lo.u32 t, %0, 8, %10;\n"
            "add.u32 bar0, t, z0;\nadd.u32 bar1, t, z1;\nadd.u32 bar2, t, z2;\nadd.u32 bar3, t, z3;\nsetp.ne.u32 never, z0, 0;\n"
            "add.u32 k64, z4, 0x40000040;\nadd.u32 ktx, z5, 8192;\ncvt.u64.u32 tm, z6;\nadd.u64 tm, tm, %3;\n"
            "mov.b32 n, 0;\nld.volatile.shared.b32 tb, [ta];\nsetp.eq.u32 lead, %0, 0;\n"
            "mov.u32 due, %%globaltimer_lo;\n"
            "setp.gt.u32 p, ra, %1;\n@p bra.uni END;\nshr.u32 oa, ra, 2;\n"
            "ld.volatile.shared.u16 off, [oa+%11-8];\nadd.u32 due, tb, off;\n"
            "FIRST:\n"
            "mov.u32 now, %%globaltimer_lo;\nsub.u32 t, due, now;\n"
            "setp.gt.s32 p, t, %12;\n@p bra.uni FIRST;\n"
            "GO:\n"
            "ld.volatile.shared.v2.b32 {a0,a1}, [ra];\nld.volatile.shared.v2.b32 {b0,b1}, [ra+0x1000];\n"
            "add.u32 t, ra, ra;\nld.volatile.shared.v4.b32 {s0,s1,s2,s3}, [t+%14];\n"
            "shr.u32 oa, ra, 2;\nld.volatile.shared.u16 off, [oa+%11];\nld.volatile.shared.b32 tb, [z7+%5];\n"
            "mov.u32 now, %%globaltimer_lo;\n"
            "lop3.b32 t, a0, a1, b0, 0xfe;\nor.b32 t, t, b1;\nand.b32 t, t, 0x10001;\n"
            "setp.ne.u32 p, t, 0;\n"
            "@p bra.uni BACK;\n"
            "mbarrier.arrive.expect_tx.shared.b64 _, [ra+%13], ktx;\n"
            "add.u32 bar0, bar0, 32;\nadd.u32 bar1, bar1, 32;\nadd.u32 bar2, bar2, 32;\nadd.u32 bar3, bar3, 32;\n"
            "dp2a.lo.u32.u32 d, a0, k64, 0;\nand.b32 r, s0, 0xffff;\n"
            "cp.async.bulk.tensor.3d.shared::cluster.global.mbarrier::complete_tx::bytes [d], [tm, {z0, r, z1}], [bar0];\n"
            "dp2a.lo.u32.u32 d, b0, k64, 0;\nshr.u32 r, s0, 16;\n"
            "cp.async.bulk.tensor.3d.shared::cluster.global.mbarrier::complete_tx::bytes [d], [tm, {z2, r, z3}], [bar1];\n"
            "dp2a.hi.u32.u32 d, a0, k64, 0;\nand.b32 r, s1, 0xffff;\n"
            "cp.async.bulk.tensor.3d.shared::cluster.global.mbarrier::complete_tx::bytes [d], [tm, {z4, r, z5}], [bar2];\n"
            "dp2a.hi.u32.u32 d, b0, k64, 0;\nshr.u32 r, s1, 16;\n"
            "cp.async.bulk.tensor.3d.shared::cluster.global.mbarrier::complete_tx::bytes [d], [tm, {z6, r, z7}], [bar3];\n"
            "@never bra.uni END;\n"
            "add.u32 ra, ra, 32;\nsub.u32 t, off, now;\nadd.u32 t, t, tb;\nsetp.le.u32 q, t, %2;\n"
            "dp2a.lo.u32.u32 d, a1, k64, 0;\nand.b32 r, s2, 0xffff;\n"
            "cp.async.bulk.tensor.3d.shared::cluster.global.mbarrier::complete_tx::bytes [d], [tm, {z0, r, z1}], [bar0];\n"
            "dp2a.lo.u32.u32 d, b1, k64, 0;\nshr.u32 r, s2, 16;\n"
            "cp.async.bulk.tensor.3d.shared::cluster.global.mbarrier::complete_tx::bytes [d], [tm, {z2, r, z3}], [bar1];\n"
            "dp2a.hi.u32.u32 d, a1, k64, 0;\nand.b32 r, s3, 0xffff;\n"
            "cp.async.bulk.tensor.3d.shared::cluster.global.mbarrier::complete_tx::bytes [d], [tm, {z4, r, z5}], [bar2];\n"
            "dp2a.hi.u32.u32 d, b1, k64, 0;\nshr.u32 r, s3, 16;\n"
            "cp.async.bulk.tensor.3d.shared::cluster.global.mbarrier::complete_tx::bytes [d], [tm, {z6, r, z7}], [bar3];\n"
            "@q bra.uni GO;\n"
            "add.u32 due, t, now;\nsetp.gt.u32 p, ra, %1;\n@p bra.uni END;\n@!lead bra.uni WAIT;\n"
            "add.u32 d, ta, 16;\ncp.async.bulk.shared::cluster.global.mbarrier::complete_tx::bytes [ta], [%4], 16, [d];\n"
            "setp.ge.s32 p, t, 0;\n@p bra.uni WAIT;\n"
            "setp.lt.u32 p, ra, %8;\n@p bra.uni GO;\nadd.u32 r, ra, " XSTR(SLIPEND) ";\nsetp.gt.u32 p, r, %1;\n@p bra.uni GO;\n"
            "ld.volatile.shared.b64 t64, [ta];\ncvt.u32.u64 r, t64;\nsub.u32 r, tb, r;\nsub.u32 d, %7, t;\nadd.s32 d, d, r;\n"
            "cvt.s64.s32 lg, d;\nadd.u64 t64, t64, lg;\n"
            "red.relaxed.gpu.global.max.u64 [%4], t64;\n"
            "bra.uni GO;\n"
            "SLEEP:\n"
            "nanosleep.u32 32;\n"
            "WAIT:\n"
            "mov.u32 now, %%globaltimer_lo;\nsub.u32 t, due, now;\nsetp.gt.s32 p, t, %6;\n@p bra.uni SLEEP;\n"
            "setp.le.s32 p, t, %12;\n@p bra.uni GO;\n"
            "SPIN:\n"
            "mov.u32 now, %%globaltimer_lo;\nsub.u32 t, due, now;\nsetp.gt.s32 p, t, %12;\n@p bra.uni SPIN;\n"
            "bra.uni GO;\n"
            "BACK:\n"
            "nanosleep.u32 32;\nsub.u32 t, now, tb;\nsetp.lt.s32 p, t, 200000000;\n@p bra.uni GO;\n"
            "END:\n}" ::"r"(pw),
            "r"(sb + SM_R + nch * 8), "n"(AHEAD + EARLY + SLIPTH), "l"(tmx), "l"(g_sync), "n"(sb + SM_MISC + 32), "n"(SPINT + SLIPTH), "n"(SLIPADD),
            "n"(sb + SM_R + SLIPFROM * 8), "r"(sb + SM_R + 8 + c0 * 8 + RAOFF), "r"(sb + SM_BAR + 8 - 32 + c0 * 8),
            "n"(sb + SM_OFF + 8 - (sb + SM_R) / 4), "n"(EARLY + SLIPTH), "n"(SM_BAR - SM_R), "n"((int)(sb + SM_S) - (int)(sb + SM_R) * 2)
            : "memory");
        const uint32_t wch = lds32(sb + SM_MISC + 12) + 1 + pw;
        const uint32_t ra = sb + SM_R + wch * 8, bar = sb + SM_BAR + wch * 8;
        const uint32_t target = lds32(sb + SM_MISC + 16);
        uint32_t cnt = lds128(sb + SM_MISC + 32).w;
        for (int n = 0; n < 1000000 && (int)(cnt - target) < 0; n++)
            asm volatile("ld.acquire.gpu.global.u32 %0, [%1+12];" : "=r"(cnt) : "l"(g_sync) : "memory");
        uint2 a, b;
        for (int n = 0; n < 1000000; n++) {
            asm volatile("ld.volatile.shared.v2.b32 {%0,%1}, [%4];\nld.volatile.shared.v2.b32 {%2,%3}, [%4+0x1000];"
                         : "=r"(a.x), "=r"(a.y), "=r"(b.x), "=r"(b.y) : "r"(ra) : "memory");
            if (!((a.x | a.y | b.x | b.y) & 0x10001)) break;
        }
        asm volatile("fence.proxy.async.global;" ::: "memory");
        asm volatile("mbarrier.arrive.expect_tx.shared.b64 _, [%0], 8192;" ::"r"(bar) : "memory");
        const uint32_t c[8] = {a.x, a.x >> 16, a.y, a.y >> 16, b.x, b.x >> 16, b.y, b.y >> 16};
#pragma unroll
        for (int i = 0; i < 8; i++)
            asm volatile("cp.async.bulk.shared::cluster.global.mbarrier::complete_tx::bytes [%0], [%1], 1024, [%2];" ::"r"(
                             (c[i] & 0xffe) << 6),
                         "l"(g_wf + (pw * 8 + i) * 64), "r"(bar)
                         : "memory");
    }
}

#define BARINIT(w, n)                                                                                              \
    if (elect()) {                                                                                                 \
        _Pragma("unroll") for (int k = 0; k < (NBAR + n - 1) / n; k++)                                             \
            asm volatile("mbarrier.init.shared.b64 [%0], 1;" ::"r"(sb + SM_BAR + ((w) * ((NBAR + n - 1) / n) + k) * 8)); \
        asm volatile("fence.mbarrier_init.release.cluster;" ::: "memory");                                         \
    }                                                                                                              \
    __syncwarp();

__global__ void __launch_bounds__(NT, 1)
main_kernel(const __grid_constant__ CUtensorMap tmx, const __nv_bfloat16* __restrict__ x, const int* __restrict__ src,
            const int* __restrict__ dst, const __nv_bfloat16* __restrict__ sh, const __nv_bfloat16* __restrict__ ea,
            const __nv_bfloat16* __restrict__ cg, const __nv_bfloat16* __restrict__ wr,
            const __nv_bfloat16* __restrict__ wout, __nv_bfloat16* __restrict__ out, int N, int E, int npb,
            unsigned npb_magic, int chunk, unsigned wsz, unsigned wmagic, unsigned bkm, int tau, int ramp, int rampn, int tdelay, unsigned polld, int spr, int sprn) {
    extern __shared__ __align__(1024) unsigned char smem[];
    if (s2u(smem) != sb) __trap();
    const int tid = threadIdx.x, lane = tid & 31;
    const int warp = __shfl_sync(0xffffffffu, tid >> 5, 0);
    const int nbins = gridDim.x;
    bool fast = chunk > 0;
    uint4 first = make_uint4(0, 0, 0, 0);
    TLSTAMP(0);
    if (fast) {
        const int e0 = blockIdx.x * chunk + tid, left = min(E, (int)(blockIdx.x + 1) * chunk) - e0;
        uint32_t pd[KE], ps[KE];
        {
            const int* dp = dst + e0;
            const int* sp = src + e0;
#pragma unroll
            for (int k = 0; k < KE; k++) {
                pd[k] = (nbins + (k == KE - 1 ? lane : 0)) * npb, ps[k] = 0;
                asm volatile("{\n.reg .pred p;\nsetp.gt.s32 p, %4, %5;\n@p ld.global.nc.u32 %0, [%2];\n@p ld.global.nc.u32 %1, [%3];\n}"
                             : "+r"(pd[k]), "+r"(ps[k]) : "l"(dp + k * NT), "l"(sp + k * NT), "r"(left), "r"(k * NT));
            }
        }
        uint32_t epoch = 0;
        if (tid == NT - 1) asm volatile("ld.relaxed.gpu.global.u32 %0, [%1];" : "=r"(epoch) : "l"(&g_epoch) : "memory");
        uint4 wv, wo[3];
        const bool wrow = (tid >> 2) == WFT && blockIdx.x < 128;
        {
            const uint4* wp = tid < 256 ? (const uint4*)wr + tid
                              : wrow    ? (const uint4*)(wout + blockIdx.x * 128 + (tid & 3) * 32)
                                        : (const uint4*)cg + (tid & 7);
            if (tid < 264 || wrow) wv = __ldg(wp);
            if (wrow) wo[0] = __ldg(wp + 1), wo[1] = __ldg(wp + 2), wo[2] = __ldg(wp + 3);
        }
        const uint32_t t16 = sb + tid * 16;
        const uint32_t sa = sb + SC_STG + (tid >> 3) * CP + (tid & 7) * 16;
        const uint32_t sm = sb + SC_STG + (tid >> 2) * CP + (tid & 3) * 16 + 128;
        const uint32_t none = (40 * NWIN + (lane & 7) + (blockIdx.x & 3) * 8) << 2;
        const uint32_t pade = min(blockIdx.x * chunk, E - 1) << 13;
        const bool third = warp * 4 + 128 < nbins, second = warp * 8 + 128 < nbins;
#pragma unroll
        for (int k = 0; k < 3; k++)
            if (k < 2 || third) sts128(sa + k * 64 * CP, none, none, none, none);
#pragma unroll
        for (int k = 0; k < 2; k++)
            if (k < 1 || second) sts128(sm + k * 128 * CP, none, none, none, none);
        if (tid < MAXB + 32) sts32(sb + SC_CNT + tid * 4, 0);
#pragma unroll
        for (int k = 0; k < 3; k++) sts128(t16 + SC_TABB + k * NT * 16, 0, 0, 0, 0);
        const uint32_t ecomp = -(wsz * (CH << 13));
#pragma unroll
        for (int k = 0; k < 3; k++)
            sts128(t16 + SC_TMP + k * NT * 16, 0, pade + ecomp, 0, pade + ecomp);
#pragma unroll
        for (int k = 0; k < ZSL / 8; k++) sts128(t16 + k * NT * 16, 0, 0, 0, 0), sts128(t16 + SP * 1024 + PH + k * NT * 16, 0, 0, 0, 0);
        if (tid < RP / 4) {
            uint32_t c[4], d[4];
#pragma unroll
            for (int i = 0; i < 4; i++) {
                const uint32_t k = tid * 4 - 4 + i;
                c[i] = d[i] = 1;
                if (warp == 0 && k < SP) c[i] = sb / 64 + k * 16;
                if (warp == 0 && k < SP - WSL) d[i] = c[i] + (SP * 1024 + PH) / 64;
            }
            static_assert(SP + 4 <= 128, "first warp");
            sts64(sb + SM_R + tid * 8, c[0] | c[1] << 16, c[2] | c[3] << 16);
            sts64(sb + SM_R + 0x1000 + tid * 8, d[0] | d[1] << 16, d[2] | d[3] << 16);
        }
        if (tid < NOFF) sts128(t16 + SM_S, 0xf000f000u, 0xf000f000u, 0xf000f000u, 0xf000f000u);
        constexpr uint32_t OLEND = (RECN - 4) * 4 * 0x10001;
        if (tid < NCW * OLN / 8) sts128(t16 + SM_OL, OLEND, OLEND, OLEND, OLEND);
        if (warp == 12) {
            sts32(sb + SM_CTR + lane * 16 + (lane >> 3) * 4,
                  sb + SM_R + ((lane & 0x19) ? (RP - 1) * 2 : (4 + SP) * 2 + (((lane >> 1) ^ (lane >> 2)) & 1) * 0x1000 + (lane & 4) / 2));
            if (lane < 3) sts32(sb + SM_MISC + (lane ? 16 + lane * 4 : 4), 0);
            if (lane == 8) sts128(sb + SM_REC + (RECN - 4) * 4, pade, pade, pade, pade), sts128(sb + SM_MISC + 64, 0, 0, 0, 0);
            if (lane == 9) asm volatile("prefetch.tensormap [%0];" ::"l"(&tmx) : "memory");
        }
        __syncthreads();
        TLSTAMP(1);

        {
            uint32_t b[KE], r[KE];
#pragma unroll
            for (int k = 0; k < KE; k++) {
                b[k] = __umulhi(pd[k], npb_magic);
                r[k] = atoms_add(sb + SC_CNT + b[k] * 4, 4);
                if (k == KE - 1) b[k] = min(b[k], nbins);
            }
            if (tid == NT - 1) {
                sts32(sb + SM_MISC + 8, epoch % 3 + 1);
                asm volatile("{\n.reg .b64 t;\nmov.u64 t, %%globaltimer;\nred.relaxed.gpu.global.max.u64 [%0], t;\n"
                             "red.relaxed.gpu.global.add.u32 [%0+8], 1;\n}" ::"l"(g_sync) : "memory");
            }
            __syncwarp();
#pragma unroll
            for (int k = 0; k < KE; k++) {
                asm volatile(
                    "{\n.reg .pred p;\n.reg .b32 d, t, u;\nmad.lo.u32 d, %1, %3, %0;\nsetp.ge.u32 p, d, 40;\nmul.hi.u32 u, %2, %4;\n"
                    "mad.lo.u32 t, %2, %10, %5;\nmad.lo.u32 t, d, %11, t;\nmad.lo.u32 t, u, %12, t;\n@p add.u32 t, t, %7;\n"
                    "min.u32 d, %6, 188;\nmad.lo.u32 d, %1, %9, d;\nst.shared.b32 [d+%8], t;\n}" ::"r"(pd[k]),
                    "r"(b[k]), "r"(ps[k]), "r"(-npb), "r"(wmagic), "r"(((tid + k * NT) << 14) + 4), "r"(r[k]), "n"(2 - 40 * NWIN * 4),
                    "n"(sb + SC_STG), "n"(CP), "n"(CH << 14), "n"(NWIN * 4), "r"(4 - wsz * (CH << 14))
                    : "memory");
            }
        }
        if (tid < 264) sts128(sb + SC_WR + (tid >> 4) * 272 + (tid & 15) * 16, wv.x, wv.y, wv.z, wv.w);
        uint4* gp = g_cell + ((tid >> 3) * MAXB + blockIdx.x) * 8 + (tid & 7);
        uint4* gm = g_more + ((tid >> 2) * MAXB + blockIdx.x) * 4 + (tid & 3);
        __syncthreads();
        TLSTAMP(6);
        const uint32_t tag = lds32(sb + SM_MISC + 8), t0 = tag & 1, t1 = tag >> 1;
        {
            uint4 v[5];
#pragma unroll
            for (int k = 0; k < 5; k++)
                if (k != 2 && k != 4 || (k == 2 ? third : second)) v[k] = lds128(k < 3 ? sa + k * 64 * CP : sm + (k - 3) * 128 * CP);
#pragma unroll
            for (int k = 0; k < 5; k++)
                if (k != 2 && k != 4 || (k == 2 ? third : second))
                    st_cell(k < 3 ? gp + k * 64 * MAXB * 8 : gm + (k - 3) * 128 * MAXB * 4, v[k].x | t0, v[k].y | t1, v[k].z | t0, v[k].w | t1);
        }
        if (wrow) {
            const int k = blockIdx.x;
            uint4* dp = &g_wf[((tid & 3) * 8 + (k >> 4)) * 64 + (k & 8) * 4 + (k & 7)];
            dp[0] = make_uint4(wv.x, wo[0].x, wo[1].x, wo[2].x);
            dp[8] = make_uint4(wv.y, wo[0].y, wo[1].y, wo[2].y);
            dp[16] = make_uint4(wv.z, wo[0].z, wo[1].z, wo[2].z);
            dp[24] = make_uint4(wv.w, wo[0].w, wo[1].w, wo[2].w);
        }
        if (warp < 14) { BARINIT(warp, 14) }
        __syncwarp();
        if (tid == NT - 1) {
            uint4 q;
            for (int n = 0; n < (1 << 22); n++) {
                q = ld_cell((const uint4*)g_sync);
                if ((int)(q.z - (epoch + 1) * nbins) >= 0) break;
            }
            sts128(sb + SM_MISC + 32, q.x, q.y, q.z, q.w), sts32(sb + SM_MISC + 16, (epoch + 1) * 512);
            asm volatile("mbarrier.init.shared.b64 [%0], 1;" ::"r"(sb + SM_MISC + 48) : "memory");
            while ((uint32_t)(gt_lo() - q.x) < polld) {}
        }
        __syncthreads();
        TLSTAMP(14);
        uint32_t m[20], rk[20], ia[20], eb[2];
        eb[0] = (((tid >> 3) * chunk) << 13) + ecomp + 1;
        eb[1] = eb[0] + (chunk << 19);
        asm volatile("" : "+r"(eb[0]), "+r"(eb[1]));
        bool ext;
        {
            const uint4* hp = g_cell + blockIdx.x * (MAXB * 8) + tid;
            const uint4* hm = g_more + blockIdx.x * (MAXB * 4) + tid;
            uint4 q[5];
            q[2] = q[4] = make_uint4(none | t0, none | t1, none | t0, none | t1);
            for (int n = 0; n < (1 << 22); n++) {
                q[0] = ld_cell(hp), q[1] = ld_cell(hp + NT), q[3] = ld_cell(hm);
                if ((tid >> 3) + 128 < nbins) q[2] = ld_cell(hp + 2 * NT);
                if ((tid >> 2) + 128 < nbins) q[4] = ld_cell(hm + NT);
                uint32_t bad = 0;
#pragma unroll
                for (int k = 0; k < 5; k++)
                    asm("{\n.reg .b32 a, b;\nlop3.b32 a, %1, %2, %5, 0x7e;\nlop3.b32 b, %3, %4, %6, 0x7e;\nlop3.b32 %0, %0, a, b, 0xfe;\n}"
                        : "+r"(bad) : "r"(q[k].x), "r"(q[k].z), "r"(q[k].y), "r"(q[k].w), "r"(t0), "r"(t1));
                if (!(bad & 1)) break;
            }
            __syncwarp();
            TLSTAMP(8);
#pragma unroll
            for (int k = 0; k < 5; k++) m[4 * k] = q[k].x, m[4 * k + 1] = q[k].y, m[4 * k + 2] = q[k].z, m[4 * k + 3] = q[k].w;
#pragma unroll
            for (int k = 0; k < 12; k++)
                if (k < 8 || third) ia[k] = m[k] & 0x3ffc, rk[k] = atoms_add(sb + SC_TABB + ia[k], 8);
            ext = __any_sync(0xffffffffu, min(m[12] & 0x3ffc, m[16] & 0x3ffc) < 40 * NWIN * 4);
            if (ext) {
#pragma unroll
                for (int k = 12; k < 20; k++) ia[k] = m[k] & 0x3ffc, rk[k] = atoms_add(sb + SC_TABB + ia[k], 8);
                if ((tid & 3) == 3 && min(m[15] & 0x3ffc, m[19] & 0x3ffc) < 40 * NWIN * 4) sts32(sb + SM_MISC + 4, 1);
            }
        }
        __syncthreads();
        TLSTAMP(5);
        const uint32_t tr = sb + warp * (NWIN * 4) + lane * 16;
        if (tid >= NT - PFT) {
            const int i = NT - 1 - tid;
            const char* p = i < 76 ? (const char*)sh + (size_t)min(blockIdx.x * chunk + i * 32, E - 32) * 8
                                   : (const char*)ea + (size_t)min(blockIdx.x * chunk + (i - 76) * 8, E - 8) * 32;
            asm volatile("prefetch.global.L2 [%0];\nprefetch.global.L2 [%0+128];" ::"l"(p));
        }
        if (tid == NT - 1 && blockIdx.x == 0) g_epoch = epoch + 1;
        {
            uint4 c[3];
            uint32_t tt[3];
#pragma unroll
            for (int i = 0; i < 3; i++) {
                c[i] = make_uint4(0, 0, 0, 0);
                if ((i < 2 || warp < 8) && lane < NWIN / 4) c[i] = lds128(tr + SC_TABB + i * 16 * NWIN * 4);
                tt[i] = c[i].x + c[i].y + c[i].z + c[i].w;
            }
            const uint32_t sum = (tt[0] >> 3) + (tt[1] << 7) + (tt[2] << 17);
            const uint32_t tot = __reduce_add_sync(0xffffffffu, sum);
            uint32_t inc = scan_step(scan_step(sum, 1), 2);
            const uint32_t q = (tot + 0x300c03) & 0x3fcff3fc, q0 = q & 1023, q1 = q0 + ((q >> 10) & 1023);
            uint32_t base = atoms_add(sb + (lane ? SC_CNT + lane * 4 : SM_MISC + 20), q1 + (q >> 20));
            inc = scan_step(scan_step(scan_step(inc, 4), 8), 16);
            base = __shfl_sync(0xffffffffu, base, 0);
            const uint32_t l3 = min(lane, 2);
            sts32(sb + SC_KEY + (warp + 16 * l3) * 4, ((tot >> (10 * l3)) & 1023) * 64 + 63 - warp - 16 * l3);
            if (max(tt[0], max(tt[1], tt[2])) > 31 * 8) sts32(sb + SM_MISC + 4, 1);
            inc += q - tot - sum;
#pragma unroll
            for (int i = 0; i < 3; i++) {
                const uint32_t e = (((inc >> (10 * i)) & 1023) + base + (i == 0 ? 0 : i == 1 ? q0 : q1)) * 8;
                if ((i < 2 || warp < 8) && lane < NWIN / 4) sts128(tr + SC_TABB + i * 16 * NWIN * 4, e, e + c[i].x, e + c[i].x + c[i].y, e + tt[i] - c[i].w);
            }
        }
        __syncthreads();
        TLSTAMP(2);
        if (warp >= 11) {
            const uint32_t st = (tid - 352) >> 2, key = lds32(sb + SC_KEY + st * 4);
            uint32_t rank = 0;
#pragma unroll
            for (int i = 0; i < 5; i++) {
                const uint2 q = lds64(sb + SC_KEY + (lane & 3) * 40 + i * 8);
                rank += ((key - q.x) >> 31) + ((key - q.y) >> 31);
            }
            rank += __shfl_xor_sync(0xffffffffu, rank, 1);
            rank += __shfl_xor_sync(0xffffffffu, rank, 2);
            const uint32_t lv = rank >> 2, cw = ((0x969u >> (2 * lv)) & 3) * 4 + ((rank ^ -(lv & 1)) & 3);
            const uint32_t sid = (0xe4a50u >> (2 * lv)) & 3;
            sts32(sb + SC_MAP + st * 4, cw * (NWIN * 4) - st * (NWIN * 4) + 0x10000 + (sid << 30));
            asm volatile("st.shared.u8 [%0], %1;" ::"r"(sb + SM_INV + cw * 4 + sid), "r"(st) : "memory");
        }
        const int total = lds32(sb + SM_MISC + 20);
        fast = lds32(sb + SM_MISC + 4) == 0 && total <= RECN - 4;
        auto lookup = [&](int k) {
            asm volatile("{\n.reg .pred p;\n.reg .b32 t;\nsetp.lt.u32 p, %1, %2;\nmov.b32 t, 0x80000000;\n@p ld.shared.b32 t, [%1+%3];\nadd.u32 %0, %0, t;\n}"
                         : "+r"(rk[k]) : "r"(ia[k]), "n"(40 * NWIN * 4), "n"(sb + SC_TABB) : "memory");
        };
        auto place = [&](int k, uint32_t e) {
            asm volatile("{\n.reg .pred p;\nsetp.ge.s32 p, %0, 0;\n@p st.shared.v2.b32 [%0+%3], {%1, %2};\n}" ::"r"(rk[k]), "r"(m[k]), "r"(e),
                         "n"(sb + SC_TMP) : "memory");
        };
#pragma unroll
        for (int k = 0; k < 8; k++) lookup(k);
        if (fast) {
#pragma unroll
            for (int k = 0; k < 8; k++) place(k, eb[k >> 2]);
            if (third) {
#pragma unroll
                for (int k = 8; k < 12; k++) lookup(k);
#pragma unroll
                for (int k = 8; k < 12; k++) place(k, 2 * eb[1] - eb[0]);
            }
            if (ext) {
#pragma unroll
                for (int k = 12; k < 20; k++) lookup(k);
#pragma unroll
                for (int k = 12; k < 20; k++) place(k, ((((tid >> 2) + (k >> 4) * 128) * chunk) << 13) + ecomp + 1);
            }
            constexpr int KD = (RECN + NT - 1) / NT;
            const uint32_t P = (lane ^ (lane >> 1)) & 1;
            const uint32_t binc = (P ? 1u << 11 : 1u) + ((lane & 3) == 3 ? 1u << 22 : 0u);
            const bool last = warp * 32 + (KD - 1) * NT < total, q2 = warp * 128 + NT * 4 < total;
            const int rest = total - tid, restq = (total >> 2) - tid;
            uint2 en[KD];
            uint32_t bk[KD], r2[KD], ca[2], ol[2], r3[2];
            __syncthreads();
            TLSTAMP(9);
#pragma unroll
            for (int k = 0; k < KD; k++)
                if (k < KD - 1 || last) en[k] = lds64(sb + SC_TMP + tid * 8 + k * NT * 8);
#pragma unroll
            for (int k = 0; k < 2; k++)
                if (k == 0 || q2) ca[k] = lds32(sb + SC_TMP + (tid + k * NT) * 32 + 24);
#pragma unroll
            for (int k = 0; k < 2; k++)
                if (k == 0 || q2) ca[k] &= 0x3ffc, ol[k] = lds32(sb + SC_MAP + __umulhi(ca[k], 0xffffffffu / (NWIN * 4) + 1) * 4);
#pragma unroll
            for (int k = 0; k < KD; k++) {
                if (k < KD - 1 || last) {
                    const uint32_t v = en[k].x, f = v >> 14, i = v & 0x3ffc;
                    const uint32_t w4 = i - __umulhi(i, 0xffffffffu / (NWIN * 4) + 1) * (NWIN * 4);
                    const uint32_t o = __umulhi(f, 0xffffffffu / CH + 1) - wsz;
                    bk[k] = (__umulhi(f, bkm) + w4) * 4;
                    en[k].x = w4 * wsz + o * 4;
                    en[k].y += ((v >> 1) & 0xffffe001u) - o * (CH << 13);
                    if (rest <= k * NT) bk[k] = 2048 + lane * 4;
                    r2[k] = atoms_add(sb + SC_TABA + bk[k], binc);
                }
            }
#pragma unroll
            for (int k = 0; k < 2; k++) {
                if (k == 0 || q2) {
                    ca[k] = (ca[k] + ol[k]) & 0xffff;
                    ol[k] = (tid + k * NT) * 16 + (ol[k] >> 30 << 14);
                    r3[k] = atoms_add(sb + SC_TABC + ca[k], restq > k * NT ? 2 : 0);
                }
            }
            __syncthreads();
            TLSTAMP(12);
            if (warp < NCW) {
                uint4 c = make_uint4(0, 0, 0, 0);
                if (lane < NWIN / 4) c = lds128(tr + SC_TABC);
                const uint32_t tt = c.x + c.y + c.z + c.w;
                uint32_t inc = tt;
#pragma unroll
                for (int o = 1; o < 32; o <<= 1) inc = scan_step(inc, o);
                if (inc > (OLN - 8) * 2) sts32(sb + SM_MISC + 4, 1);
                inc += warp * (OLN * 2) - tt;
                if (lane < NWIN / 4) sts128(tr + SC_TABC, inc, inc + c.x, inc + c.x + c.y, inc + tt - c.w);
            } else {
                const uint32_t mine = (warp + lane) & 3;
                uint4 c;
                uint32_t cs, inc = 0, e = 4 + (4 << 11);
#pragma unroll
                for (int i = 0; i < 4; i++) {
                    const uint32_t pc = (mine + i) & 3;
                    const uint4 v = lds128(sb + SC_TABA + lane * 64 + (pc << 4));
                    const uint32_t sum = v.x + v.y + v.z + v.w;
                    inc += sum;
                    if (i == 0) c = v, cs = sum;
                    if (pc >= mine) e -= sum;
                }
#pragma unroll
                for (int o = 1; o < 32; o <<= 1) inc = scan_step(inc, o);
                e += inc;
                sts128(sb + SC_TABB + lane * 64 + (mine << 4), e, e + c.x, e + c.x + c.y, e + cs - c.w);
                if ((int)max((e + cs) & 0x7ff, ((e + cs) >> 11) & 0x7ff) - (int)(e >> 22) * 2 > SP) sts32(sb + SM_MISC + 4, 1);
                if (tid == NCW * 32) {
                    const uint32_t c0 = min(min(c.x & 0x7ff, (c.x >> 11) & 0x7ff), ZSL) >> 2;
                    sts32(sb + SM_MISC + 12, ((total >> 2) + 1) >> 1), sts32(sb + SM_MISC + 24, c0);
                }
            }
            __syncthreads();
            TLSTAMP(13);
            fast = lds32(sb + SM_MISC + 4) == 0;
            if (warp == 15 && lane < lds32(sb + SM_MISC + 24))
                asm volatile("mbarrier.arrive.shared.b64 _, [%0];" ::"r"(sb + SM_BAR + 8 + lane * 8) : "memory");
#pragma unroll
            for (int k = 0; k < KD; k++)
                if (k < KD - 1 || last) r2[k] += lds32(sb + SC_TABB + bk[k]);
#pragma unroll
            for (int k = 0; k < 2; k++)
                if (k == 0 || q2) r3[k] += lds32(sb + SC_TABC + ca[k]);
            if (fast) {
                const uint32_t rot = P ? 9 : 30;
#pragma unroll
                for (int k = 0; k < KD; k++) {
                    if (k < KD - 1 || last) {
                        const uint32_t k4 = __funnelshift_r(r2[k], r2[k], rot);
                        if (rest > k * NT) {
                            sts16(sb + SM_S + bitsel(k4, P << 1), en[k].x);
                            sts32(sb + SM_REC + tid * 4 + k * NT * 4, bitsel(k4, en[k].y));
                        }
                    }
                }
#pragma unroll
                for (int k = 0; k < 2; k++)
                    if ((k == 0 || q2) && restq > k * NT) sts16(sb + SM_OL + r3[k], ol[k]);
            }
        }
        asm volatile("fence.mbarrier_init.release.cluster;\nfence.proxy.async.shared::cta;" ::: "memory");
        __syncthreads();
        TLSTAMP(3);
        if (!fast && wrow) wf_done();
        if (fast && tid < NOFF) {
            const uint4 a = lds128(t16 + SM_S);
            uint32_t sum = 0;
            sum = __dp2a_lo(__vadd2(a.x, 0x10001000u), 0x101u, sum), sum = __dp2a_lo(__vadd2(a.y, 0x10001000u), 0x101u, sum);
            sum = __dp2a_lo(__vadd2(a.z, 0x10001000u), 0x101u, sum), sum = __dp2a_lo(__vadd2(a.w, 0x10001000u), 0x101u, sum);
            const int s = (int)(sum >> 5) - 0x400;
            sts16(sb + SM_OFF + tid * 2, tid > lds32(sb + SM_MISC + 12) ? 0 : min(max(tdelay + SLIPTH + ((s * tau + min(s, rampn) * ramp - max(s - sprn, 0) * spr) >> 10), 0), 0xffff));
        }
        __syncwarp();
        if (fast && warp < NCW) {
            asm volatile("bar.arrive 1, 512;" ::: "memory");
            const uint32_t e = lds16(sb + SM_OL + warp * (OLN * 2) + ((lane & 4) >> 1));
            const uint32_t rec = lds32(sb + SM_REC + (e & 0x3ff0) + (lane >> 3) * 4);
            first.w = ((rec >> 1) & 0xffe) | (e & ~0xffeu);
            asm volatile("{\n.reg .pred q;\nsetp.ne.u32 q, %5, 0;\nld.global.cg.v2.b32 {%0,%1}, [%3];\n@q ld.global.cg.b32 %2, [%4];\n}"
                         : "=r"(first.x), "=r"(first.y), "+r"(first.z)
                         : "l"(ea + (size_t)(rec >> 13) * 16 + (lane & 3) * 4), "l"(sh + (size_t)(rec >> 13) * 4 + (lane & 2)), "r"(rec & (1 << (lane & 1))));
        }
    }

    if (!fast) {
        float* accs = (float*)smem;
        constexpr int NACC = 96;
        const int node0 = blockIdx.x * npb, nnodes = max(0, min(npb, N - node0));
#pragma unroll 1
        for (int nb = 0; nb < nnodes; nb += NACC) {
            __syncthreads();
            for (int i = tid; i < NACC * 512; i += NT) accs[i] = 0.f;
            __syncthreads();
            const int lim = min(NACC, nnodes - nb);
#pragma unroll 1
            for (int base = warp * 32; base < E; base += NT) {
                const int e = base + lane;
                const int dl = e < E ? dst[e] - node0 - nb : -1;
                unsigned mask = __ballot_sync(0xffffffffu, dl >= 0 && dl < lim);
#pragma unroll 1
                while (mask) {
                    const int l = __ffs(mask) - 1;
                    mask &= mask - 1;
                    const int dd = __shfl_sync(0xffffffffu, dl, l);
                    slow_edge(base + l, src[base + l], accs + dd * 512, x, sh, ea, cg, wr, lane);
                }
            }
            __syncthreads();
#pragma unroll 1
            for (int nl = warp; nl < lim; nl += NT / 32) slow_out(accs + nl * 512, wout, out + (size_t)(node0 + nb + nl) * 512, lane);
        }
    } else if (warp >= NCW) {
        asm volatile("setmaxnreg.dec.sync.aligned.u32 %0;" ::"n"(PREG));
        producer(&tmx, warp - NCW);
    } else if (warp >= 4) {
        asm volatile("setmaxnreg.inc.sync.aligned.u32 %0;" ::"n"(R1));
        consumer<3>(sh, ea, out, N, npb, first);
        TLMAX(4);
    } else {
        asm volatile("setmaxnreg.inc.sync.aligned.u32 %0;" ::"n"(R0));
        consumer<4>(sh, ea, out, N, npb, first);
        TLMAX(4);
    }
}

typedef CUresult (*EncodeTiledFn)(CUtensorMap*, CUtensorMapDataType, cuuint32_t, void*, const cuuint64_t*,
                                  const cuuint64_t*, const cuuint32_t*, const cuuint32_t*, CUtensorMapInterleave,
                                  CUtensorMapSwizzle, CUtensorMapL2promotion, CUtensorMapFloatOOBfill);

extern "C" void kernel_launch(void* const* d_in, const int* in_sizes, int n_in, void* d_out, int out_size) {
    const __nv_bfloat16* x = (const __nv_bfloat16*)d_in[0];
    const int* src = (const int*)d_in[1];
    const int* dst = (const int*)d_in[2];
    const __nv_bfloat16* sh = (const __nv_bfloat16*)d_in[3];
    const __nv_bfloat16* ea = (const __nv_bfloat16*)d_in[4];
    const __nv_bfloat16* cg = (const __nv_bfloat16*)d_in[5];
    const __nv_bfloat16* wr = (const __nv_bfloat16*)d_in[6];
    const __nv_bfloat16* wout = (const __nv_bfloat16*)d_in[7];
    __nv_bfloat16* out = (__nv_bfloat16*)d_out;
    const int N = in_sizes[0] / 512;
    const int E = in_sizes[1];

    static int num_sms = 0, coresident = 0;
    static EncodeTiledFn encode = nullptr;
    if (num_sms == 0) {
        int dev = 0;
        cudaGetDevice(&dev);
        cudaDeviceGetAttribute(&num_sms, cudaDevAttrMultiProcessorCount, dev);
        cudaFuncSetAttribute(main_kernel, cudaFuncAttributeMaxDynamicSharedMemorySize, SM_TOTAL);
        int occ = 0;
        cudaOccupancyMaxActiveBlocksPerMultiprocessor(&occ, main_kernel, NT, SM_TOTAL);
        coresident = occ * num_sms;
        void* fn = nullptr;
        cudaDriverEntryPointQueryResult qr;
        cudaGetDriverEntryPoint("cuTensorMapEncodeTiled", &fn, cudaEnableDefault, &qr);
        encode = (EncodeTiledFn)fn;
    }
    CUtensorMap tmx;
    const int rank = 3;
    const cuuint64_t gd[3] = {64, (cuuint64_t)N * 4, 2}, gs[2] = {256, 128};
    const cuuint32_t bd[3] = {64, 4, 2}, es[3] = {1, 1, 1};
    encode(&tmx, CU_TENSOR_MAP_DATA_TYPE_BFLOAT16, rank, (void*)x, gd, gs, bd, es, CU_TENSOR_MAP_INTERLEAVE_NONE,
           CU_TENSOR_MAP_SWIZZLE_128B, CU_TENSOR_MAP_L2_PROMOTION_NONE, CU_TENSOR_MAP_FLOAT_OOB_FILL_NONE);

    int nbins = num_sms < MAXB ? num_sms : MAXB;
    int npb = (N + nbins - 1) / nbins;
    if (npb < 2) npb = 2;
    nbins = (N + npb - 1) / npb;
    const unsigned npb_magic = (unsigned)((0x100000000ull + npb - 1) / npb);
    int chunk = (E + nbins - 1) / nbins;
    const unsigned wsz = (N + NWIN - 2) / (NWIN - 1);
    if (nbins > coresident || nbins < 128 || npb > MAXNPB || chunk > CH || wsz > (1 << 18) / CH || N < 512 || E < 32 || E > (1 << 19)) chunk = 0;
    const unsigned wmagic = 0xffffffffu / wsz + 1, bkm = (unsigned)((4ull << 32) / (wsz * CH));
    double pace = PACE, rampt = RAMP, rampf = RAMPF, sprt = SPRINT, sprf = SPRINTF;
    int tdelay = TDELAY, polld = POLLD;
    const int tau = (int)(1024.0 * pace * ((double)E / nbins) / N);
    const int rampn = (int)(N * rampf), ramp = (int)(1024.0 * rampt / rampn);
    main_kernel<<<nbins, NT, SM_TOTAL, cudaStreamPerThread>>>(tmx, x, src, dst, sh, ea, cg, wr, wout, out, N, E, npb, npb_magic,
                                                              chunk, wsz, wmagic, bkm, tau, ramp, rampn, tdelay, polld, (int)(1024.0 * sprt / (N * sprf)), (int)(N * (1 - sprf)));
}
```

```cpp
#include <cuda_runtime.h>
#include <cuda.h>
#include <cuda_bf16.h>
#include <stdint.h>
#include <stdlib.h>

#define NT 512
#define NCW 12
#define MAXB 144
#define MAXNPB 80
#define KE 5
#define SP 99
#define RECN 2752
#define RP 1488
#define OLN 80
#define NBAR 350
#define NOFF 352
#define R0 168
#define R1 160
#define PREG 24
#define PACE 9.9
#define TDELAY 4550
#define POLLD 1000
#define WFT 80
#define SLIPTH 200
#define SLIPADD 150
#define SLIPFROM 36
#define AHEAD 96
#define EARLY 32
#define RAMPF 0.1
#define SPRINT 400
#define SPRINTF 0.5
#define SLIPEND 320
#define SPINT 96
#define PFT 224
#define EM3 1
#define RAMP 500

__device__ __align__(1024) uint4 g_cell[MAXB * MAXB * 8];
__device__ __align__(1024) uint4 g_more[MAXB * MAXB * 4];
__device__ __align__(1024) uint4 g_wf[2048];
__device__ __align__(256) ulonglong2 g_sync[16];
__device__ __align__(256) unsigned g_epoch;
#define TLSTAMP(i)
#define TLMAX(i)

constexpr uint32_t sb = 1024;
#define PH 512
#define SM_R (2 * SP * 1024 + PH)
#define SM_CTR (SP * 1024)
#define SM_MISC (SM_R + RP * 2)
#define SM_INV (SM_MISC + 80)
#define SM_OFF (SM_INV + 48)
#define SM_S (SM_R + 0x1000 + RP * 2)
#define SM_REC (SM_S + NOFF * 16)
#define SM_OL (SM_REC + RECN * 4)
#define SM_BAR (SM_OL + NCW * OLN * 2)
#define SM_CGF 0
#define SM_TOTAL (SM_BAR + NBAR * 8)
static_assert(SM_TOTAL <= 232448 && SM_OFF + NOFF * 2 <= SM_R + 0x1000 && RP % 8 == 0 && SM_BAR % 16 == 0, "shared memory");
static_assert(4 + RECN / 2 + SP + 2 <= RP && RECN / 8 + 5 <= NBAR && NBAR % 14 == 0 && RECN / 8 + 4 <= NOFF, "tables");
#define ZSL 32
#define NWIN 96
#define CH 2432
#define CP 208
#define SC_STG ((SP + ZSL) * 1024 + PH)
#define SC_TMP (ZSL * 1024)
#define SC_TABB (SC_TMP + 3072 * 8)
#define SC_TABC (SC_TABB + 41 * NWIN * 4)
#define SC_TABA (SC_TABC + NCW * NWIN * 4)
#define SC_ZEND (SC_TABB + 3 * NT * 16)
#define SC_CNT SC_ZEND
#define SC_KEY (SC_CNT + (MAXB + 32) * 4)
#define SC_MAP (SC_KEY + 192)
#define WSL 5
#define SC_WR ((2 * SP - WSL) * 1024 + PH)
#define SC_CG (SC_WR + 16 * 272)
static_assert(SC_TABA + 2048 + 128 <= SC_ZEND && RECN <= 3072 && SC_MAP + 192 <= SP * 1024 && SC_STG + (MAXB + 1) * CP <= SC_WR, "scratch");

__device__ __forceinline__ uint32_t pack_bf16(float lo, float hi) {
    uint32_t r;
    asm("cvt.rn.bf16x2.f32 %0, %1, %2;" : "=r"(r) : "f"(hi), "f"(lo));
    return r;
}
__device__ __forceinline__ uint32_t s2u(const void* p) { return (uint32_t)__cvta_generic_to_shared(p); }
__device__ __forceinline__ void mbar_wait0(uint32_t a) {
    asm volatile(
        "{\n.reg .pred p, q;\n.reg .u32 n;\nmov.u32 n, 0;\n"
        "LAB_WAIT:\nmbarrier.try_wait.parity.shared.b64 p, [%0], 0;\nadd.u32 n, n, 1;\nsetp.lt.and.u32 q, n, 1000000, !p;\n@q bra LAB_WAIT;\n}" ::"r"(a)
        : "memory");
}
__device__ __forceinline__ uint32_t lds8(uint32_t a) { uint32_t v; asm volatile("ld.shared.u8 %0, [%1];" : "=r"(v) : "r"(a) : "memory"); return v; }
__device__ __forceinline__ uint32_t lds16(uint32_t a) { uint32_t v; asm volatile("ld.shared.u16 %0, [%1];" : "=r"(v) : "r"(a) : "memory"); return v; }
__device__ __forceinline__ uint32_t lds32(uint32_t a) { uint32_t v; asm volatile("ld.shared.u32 %0, [%1];" : "=r"(v) : "r"(a) : "memory"); return v; }
__device__ __forceinline__ uint2 lds64(uint32_t a) {
    uint2 v; asm volatile("ld.shared.v2.u32 {%0,%1}, [%2];" : "=r"(v.x), "=r"(v.y) : "r"(a) : "memory"); return v;
}
__device__ __forceinline__ uint4 lds128(uint32_t a) {
    uint4 v; asm volatile("ld.volatile.shared.v4.u32 {%0,%1,%2,%3}, [%4];" : "=r"(v.x), "=r"(v.y), "=r"(v.z), "=r"(v.w) : "r"(a) : "memory"); return v;
}
__device__ __forceinline__ void sts16(uint32_t a, uint32_t v) { asm volatile("st.shared.u16 [%0], %1;" ::"r"(a), "h"((unsigned short)v) : "memory"); }
__device__ __forceinline__ void sts32(uint32_t a, uint32_t v) { asm volatile("st.shared.u32 [%0], %1;" ::"r"(a), "r"(v) : "memory"); }
__device__ __forceinline__ void sts64(uint32_t a, uint32_t x, uint32_t y) { asm volatile("st.shared.v2.u32 [%0], {%1,%2};" ::"r"(a), "r"(x), "r"(y) : "memory"); }
__device__ __forceinline__ void sts128(uint32_t a, uint32_t x, uint32_t y, uint32_t z, uint32_t w) {
    asm volatile("st.shared.v4.u32 [%0], {%1,%2,%3,%4};" ::"r"(a), "r"(x), "r"(y), "r"(z), "r"(w) : "memory");
}
__device__ __forceinline__ uint32_t atoms_add(uint32_t a, uint32_t v) {
    uint32_t r;
    asm volatile("atom.shared.add.u32 %0, [%1], %2;" : "=r"(r) : "r"(a), "r"(v) : "memory");
    return r;
}
__device__ __forceinline__ uint4 ld_cell(const uint4* p) {
    uint4 v;
    asm volatile("{\n.reg .b64 a, b;\nld.relaxed.gpu.global.v2.b64 {a, b}, [%4];\nmov.b64 {%0,%1}, a;\nmov.b64 {%2,%3}, b;\n}"
                 : "=r"(v.x), "=r"(v.y), "=r"(v.z), "=r"(v.w) : "l"(p) : "memory");
    return v;
}
__device__ __forceinline__ void st_cell(uint4* p, uint32_t x, uint32_t y, uint32_t z, uint32_t w) {
    asm volatile("st.relaxed.gpu.global.v2.b64 [%0], {%1, %2};" ::"l"(p), "l"(x | (uint64_t)y << 32), "l"(z | (uint64_t)w << 32) : "memory");
}
__device__ __forceinline__ uint32_t scan_step(uint32_t v, int o) {
    asm volatile("{\n.reg .pred p;\n.reg .b32 y;\nshfl.sync.up.b32 y|p, %0, %1, 0, 0xffffffff;\n@p add.u32 %0, %0, y;\n}" : "+r"(v) : "r"(o));
    return v;
}
__device__ __forceinline__ uint32_t bitsel(uint32_t a, uint32_t b) {
    uint32_t r;
    asm("lop3.b32 %0, %1, %2, 0x1ffc, 0xe4;" : "=r"(r) : "r"(a), "r"(b));
    return r;
}
__device__ __forceinline__ uint32_t movm(uint32_t a) {
    uint32_t r;
    asm volatile("movmatrix.sync.aligned.m8n8.trans.b16 %0, %1;" : "=r"(r) : "r"(a));
    return r;
}
__device__ __forceinline__ uint32_t gt_lo() {
    uint32_t t;
    asm volatile("mov.u32 %0, %globaltimer_lo;" : "=r"(t));
    return t;
}
__device__ __forceinline__ bool elect() {
    uint32_t p;
    asm volatile("{\n.reg .pred P;\nelect.sync _|P, 0xffffffff;\nselp.u32 %0, 1, 0, P;\n}" : "=r"(p));
    return p;
}
__device__ __forceinline__ void project4(const uint32_t (&pk)[64], uint32_t ra, uint32_t ba, uint4* const (&p)[4], const uint32_t (&v)[4]) {
    asm volatile(
        "{\n.reg .pred p0, p1, q0, q1, nv, s<4>;\n.reg .b32 t, h, c<16>, a<32>, b<32>, k<16>;\n.reg .b64 d<16>;\n.reg .f32 o<32>;\nsetp.ne.b32 p0, 0, 0;\n"
        "setp.eq.b32 p1, 0, 0;\nmov.b32 h, 8;\nsetp.eq.u32 nv, %64, 0;\nvote.sync.any.pred nv, nv, 0xffffffff;\nsetp.ne.b32 s0, %69, 0;\n"
        "setp.ne.b32 s1, %70, 0;\nsetp.ne.b32 s2, %71, 0;\nsetp.ne.b32 s3, %72, 0;\nmov.b32 t, 0;\n"
        "W0:\nmbarrier.try_wait.parity.shared.b64 q0, [%73], 0;\nvote.sync.all.pred q0, q0, 0xffffffff;\nadd.u32 t, t, 1;\nsetp.lt.and.u32 q1, t, 1000000, !q0;\n"
        "@q1 bra.uni W0;\nld.volatile.shared.v2.b32 {c0,c1}, [%64+0];\nld.volatile.shared.v2.b32 {c2,c3}, [%64+4096];\n"
        "ld.volatile.shared.v2.b32 {c4,c5}, [%64+8];\nld.volatile.shared.v2.b32 {c6,c7}, [%64+4104];\ndp2a.lo.u32.u32 t, c0, 0x04000004, 0x200000;\n"
        "mov.b64 d0, {t, h};\ndp2a.hi.u32.u32 t, c0, 0x04000004, 0x200000;\nmov.b64 d1, {t, h};\ndp2a.lo.u32.u32 t, c1, 0x04000004, 0x200000;\n"
        "mov.b64 d2, {t, h};\ndp2a.hi.u32.u32 t, c1, 0x04000004, 0x200000;\nmov.b64 d3, {t, h};\ndp2a.lo.u32.u32 t, c2, 0x04000004, 0x200000;\n"
        "mov.b64 d4, {t, h};\ndp2a.hi.u32.u32 t, c2, 0x04000004, 0x200000;\nmov.b64 d5, {t, h};\ndp2a.lo.u32.u32 t, c3, 0x04000004, 0x200000;\n"
        "mov.b64 d6, {t, h};\ndp2a.hi.u32.u32 t, c3, 0x04000004, 0x200000;\nmov.b64 d7, {t, h};\ndp2a.lo.u32.u32 t, c4, 0x04000004, 0x200000;\n"
        "mov.b64 d8, {t, h};\ndp2a.hi.u32.u32 t, c4, 0x04000004, 0x200000;\nmov.b64 d9, {t, h};\ndp2a.lo.u32.u32 t, c5, 0x04000004, 0x200000;\n"
        "mov.b64 d10, {t, h};\ndp2a.hi.u32.u32 t, c5, 0x04000004, 0x200000;\nmov.b64 d11, {t, h};\ndp2a.lo.u32.u32 t, c6, 0x04000004, 0x200000;\n"
        "mov.b64 d12, {t, h};\ndp2a.hi.u32.u32 t, c6, 0x04000004, 0x200000;\nmov.b64 d13, {t, h};\ndp2a.lo.u32.u32 t, c7, 0x04000004, 0x200000;\n"
        "mov.b64 d14, {t, h};\ndp2a.hi.u32.u32 t, c7, 0x04000004, 0x200000;\nmov.b64 d15, {t, h};\nmovmatrix.sync.aligned.m8n8.trans.b16 a0, %0;\n"
        "movmatrix.sync.aligned.m8n8.trans.b16 a1, %16;\nmovmatrix.sync.aligned.m8n8.trans.b16 a2, %1;\nmovmatrix.sync.aligned.m8n8.trans.b16 a3, %17;\n"
        "movmatrix.sync.aligned.m8n8.trans.b16 a4, %2;\nmovmatrix.sync.aligned.m8n8.trans.b16 a5, %18;\nmovmatrix.sync.aligned.m8n8.trans.b16 a6, %3;\n"
        "movmatrix.sync.aligned.m8n8.trans.b16 a7, %19;\nmovmatrix.sync.aligned.m8n8.trans.b16 a8, %4;\nmovmatrix.sync.aligned.m8n8.trans.b16 a9, %20;\n"
        "movmatrix.sync.aligned.m8n8.trans.b16 a10, %5;\nmovmatrix.sync.aligned.m8n8.trans.b16 a11, %21;\nmovmatrix.sync.aligned.m8n8.trans.b16 a12, %6;\n"
        "movmatrix.sync.aligned.m8n8.trans.b16 a13, %22;\nmovmatrix.sync.aligned.m8n8.trans.b16 a14, %7;\nmovmatrix.sync.aligned.m8n8.trans.b16 a15, %23;\n"
        "movmatrix.sync.aligned.m8n8.trans.b16 a16, %8;\nmovmatrix.sync.aligned.m8n8.trans.b16 a17, %24;\nmovmatrix.sync.aligned.m8n8.trans.b16 a18, %9;\n"
        "movmatrix.sync.aligned.m8n8.trans.b16 a19, %25;\nmovmatrix.sync.aligned.m8n8.trans.b16 a20, %10;\nmovmatrix.sync.aligned.m8n8.trans.b16 a21, %26;\n"
        "movmatrix.sync.aligned.m8n8.trans.b16 a22, %11;\nmovmatrix.sync.aligned.m8n8.trans.b16 a23, %27;\nmovmatrix.sync.aligned.m8n8.trans.b16 a24, %12;\n"
        "movmatrix.sync.aligned.m8n8.trans.b16 a25, %28;\nmovmatrix.sync.aligned.m8n8.trans.b16 a26, %13;\nmovmatrix.sync.aligned.m8n8.trans.b16 a27, %29;\n"
        "movmatrix.sync.aligned.m8n8.trans.b16 a28, %14;\nmovmatrix.sync.aligned.m8n8.trans.b16 a29, %30;\nmovmatrix.sync.aligned.m8n8.trans.b16 a30, %15;\n"
        "movmatrix.sync.aligned.m8n8.trans.b16 a31, %31;\nwgmma.fence.sync.aligned;\n"
        "wgmma.mma_async.sync.aligned.m64n32k16.f32.bf16.bf16 {o0,o1,o2,o3,o4,o5,o6,o7,o8,o9,o10,o11,o12,o13,o14,o15}, {a0,a1,a2,a3}, d0, p0, 1, 1, 1;\n"
        "wgmma.mma_async.sync.aligned.m64n32k16.f32.bf16.bf16 {o0,o1,o2,o3,o4,o5,o6,o7,o8,o9,o10,o11,o12,o13,o14,o15}, {a4,a5,a6,a7}, d1, p1, 1, 1, 1;\n"
        "wgmma.mma_async.sync.aligned.m64n32k16.f32.bf16.bf16 {o0,o1,o2,o3,o4,o5,o6,o7,o8,o9,o10,o11,o12,o13,o14,o15}, {a8,a9,a10,a11}, d2, p1, 1, 1, 1;\n"
        "wgmma.mma_async.sync.aligned.m64n32k16.f32.bf16.bf16 {o0,o1,o2,o3,o4,o5,o6,o7,o8,o9,o10,o11,o12,o13,o14,o15}, {a12,a13,a14,a15}, d3, p1, 1, 1, 1;\n"
        "wgmma.mma_async.sync.aligned.m64n32k16.f32.bf16.bf16 {o0,o1,o2,o3,o4,o5,o6,o7,o8,o9,o10,o11,o12,o13,o14,o15}, {a16,a17,a18,a19}, d4, p1, 1, 1, 1;\n"
        "wgmma.mma_async.sync.aligned.m64n32k16.f32.bf16.bf16 {o0,o1,o2,o3,o4,o5,o6,o7,o8,o9,o10,o11,o12,o13,o14,o15}, {a20,a21,a22,a23}, d5, p1, 1, 1, 1;\n"
        "wgmma.mma_async.sync.aligned.m64n32k16.f32.bf16.bf16 {o0,o1,o2,o3,o4,o5,o6,o7,o8,o9,o10,o11,o12,o13,o14,o15}, {a24,a25,a26,a27}, d6, p1, 1, 1, 1;\n"
        "wgmma.mma_async.sync.aligned.m64n32k16.f32.bf16.bf16 {o0,o1,o2,o3,o4,o5,o6,o7,o8,o9,o10,o11,o12,o13,o14,o15}, {a28,a29,a30,a31}, d7, p1, 1, 1, 1;\n"
        "wgmma.commit_group.sync.aligned;\n"
        "wgmma.mma_async.sync.aligned.m64n32k16.f32.bf16.bf16 {o16,o17,o18,o19,o20,o21,o22,o23,o24,o25,o26,o27,o28,o29,o30,o31}, {a0,a1,a2,a3}, d8, p0, 1, 1, 1;\n"
        "wgmma.mma_async.sync.aligned.m64n32k16.f32.bf16.bf16 {o16,o17,o18,o19,o20,o21,o22,o23,o24,o25,o26,o27,o28,o29,o30,o31}, {a4,a5,a6,a7}, d9, p1, 1, 1, 1;\n"
        "wgmma.mma_async.sync.aligned.m64n32k16.f32.bf16.bf16 {o16,o17,o18,o19,o20,o21,o22,o23,o24,o25,o26,o27,o28,o29,o30,o31}, {a8,a9,a10,a11}, d10, p1, 1, 1, 1;\n"
        "wgmma.mma_async.sync.aligned.m64n32k16.f32.bf16.bf16 {o16,o17,o18,o19,o20,o21,o22,o23,o24,o25,o26,o27,o28,o29,o30,o31}, {a12,a13,a14,a15}, d11, p1, 1, 1, 1;\n"
        "wgmma.mma_async.sync.aligned.m64n32k16.f32.bf16.bf16 {o16,o17,o18,o19,o20,o21,o22,o23,o24,o25,o26,o27,o28,o29,o30,o31}, {a16,a17,a18,a19}, d12, p1, 1, 1, 1;\n"
        "wgmma.mma_async.sync.aligned.m64n32k16.f32.bf16.bf16 {o16,o17,o18,o19,o20,o21,o22,o23,o24,o25,o26,o27,o28,o29,o30,o31}, {a20,a21,a22,a23}, d13, p1, 1, 1, 1;\n"
        "wgmma.mma_async.sync.aligned.m64n32k16.f32.bf16.bf16 {o16,o17,o18,o19,o20,o21,o22,o23,o24,o25,o26,o27,o28,o29,o30,o31}, {a24,a25,a26,a27}, d14, p1, 1, 1, 1;\n"
        "wgmma.mma_async.sync.aligned.m64n32k16.f32.bf16.bf16 {o16,o17,o18,o19,o20,o21,o22,o23,o24,o25,o26,o27,o28,o29,o30,o31}, {a28,a29,a30,a31}, d15, p1, 1, 1, 1;\n"
        "wgmma.commit_group.sync.aligned;\nwgmma.wait_group.sync.aligned 1;\ncvt.rn.bf16x2.f32 k0, o1, o0;\ncvt.rn.bf16x2.f32 k1, o5, o4;\n"
        "cvt.rn.bf16x2.f32 k2, o9, o8;\ncvt.rn.bf16x2.f32 k3, o13, o12;\n@s0 st.global.v4.b32 [%65+0], {k0,k1,k2,k3};\ncvt.rn.bf16x2.f32 k4, o3, o2;\n"
        "cvt.rn.bf16x2.f32 k5, o7, o6;\ncvt.rn.bf16x2.f32 k6, o11, o10;\ncvt.rn.bf16x2.f32 k7, o15, o14;\n@s1 st.global.v4.b32 [%66+0], {k4,k5,k6,k7};\n"
        "@nv bra.uni END;\nwgmma.wait_group.sync.aligned 0;\ncvt.rn.bf16x2.f32 k8, o17, o16;\ncvt.rn.bf16x2.f32 k9, o21, o20;\ncvt.rn.bf16x2.f32 k10, o25, o24;\n"
        "cvt.rn.bf16x2.f32 k11, o29, o28;\n@s0 st.global.v4.b32 [%65+64], {k8,k9,k10,k11};\ncvt.rn.bf16x2.f32 k12, o19, o18;\ncvt.rn.bf16x2.f32 k13, o23, o22;\n"
        "cvt.rn.bf16x2.f32 k14, o27, o26;\ncvt.rn.bf16x2.f32 k15, o31, o30;\n@s1 st.global.v4.b32 [%66+64], {k12,k13,k14,k15};\n@nv bra.uni END;\n"
        "ld.volatile.shared.v2.b32 {c0,c1}, [%64+16];\nld.volatile.shared.v2.b32 {c2,c3}, [%64+4112];\nld.volatile.shared.v2.b32 {c4,c5}, [%64+24];\n"
        "ld.volatile.shared.v2.b32 {c6,c7}, [%64+4120];\ndp2a.lo.u32.u32 t, c0, 0x04000004, 0x200000;\nmov.b64 d0, {t, h};\n"
        "dp2a.hi.u32.u32 t, c0, 0x04000004, 0x200000;\nmov.b64 d1, {t, h};\ndp2a.lo.u32.u32 t, c1, 0x04000004, 0x200000;\nmov.b64 d2, {t, h};\n"
        "dp2a.hi.u32.u32 t, c1, 0x04000004, 0x200000;\nmov.b64 d3, {t, h};\ndp2a.lo.u32.u32 t, c2, 0x04000004, 0x200000;\nmov.b64 d4, {t, h};\n"
        "dp2a.hi.u32.u32 t, c2, 0x04000004, 0x200000;\nmov.b64 d5, {t, h};\ndp2a.lo.u32.u32 t, c3, 0x04000004, 0x200000;\nmov.b64 d6, {t, h};\n"
        "dp2a.hi.u32.u32 t, c3, 0x04000004, 0x200000;\nmov.b64 d7, {t, h};\ndp2a.lo.u32.u32 t, c4, 0x04000004, 0x200000;\nmov.b64 d8, {t, h};\n"
        "dp2a.hi.u32.u32 t, c4, 0x04000004, 0x200000;\nmov.b64 d9, {t, h};\ndp2a.lo.u32.u32 t, c5, 0x04000004, 0x200000;\nmov.b64 d10, {t, h};\n"
        "dp2a.hi.u32.u32 t, c5, 0x04000004, 0x200000;\nmov.b64 d11, {t, h};\ndp2a.lo.u32.u32 t, c6, 0x04000004, 0x200000;\nmov.b64 d12, {t, h};\n"
        "dp2a.hi.u32.u32 t, c6, 0x04000004, 0x200000;\nmov.b64 d13, {t, h};\ndp2a.lo.u32.u32 t, c7, 0x04000004, 0x200000;\nmov.b64 d14, {t, h};\n"
        "dp2a.hi.u32.u32 t, c7, 0x04000004, 0x200000;\nmov.b64 d15, {t, h};\nwgmma.fence.sync.aligned;\n"
        "wgmma.mma_async.sync.aligned.m64n32k16.f32.bf16.bf16 {o0,o1,o2,o3,o4,o5,o6,o7,o8,o9,o10,o11,o12,o13,o14,o15}, {a0,a1,a2,a3}, d0, p0, 1, 1, 1;\n"
        "wgmma.mma_async.sync.aligned.m64n32k16.f32.bf16.bf16 {o16,o17,o18,o19,o20,o21,o22,o23,o24,o25,o26,o27,o28,o29,o30,o31}, {a0,a1,a2,a3}, d8, p0, 1, 1, 1;\n"
        "wgmma.mma_async.sync.aligned.m64n32k16.f32.bf16.bf16 {o0,o1,o2,o3,o4,o5,o6,o7,o8,o9,o10,o11,o12,o13,o14,o15}, {a4,a5,a6,a7}, d1, p1, 1, 1, 1;\n"
        "wgmma.mma_async.sync.aligned.m64n32k16.f32.bf16.bf16 {o16,o17,o18,o19,o20,o21,o22,o23,o24,o25,o26,o27,o28,o29,o30,o31}, {a4,a5,a6,a7}, d9, p1, 1, 1, 1;\n"
        "wgmma.mma_async.sync.aligned.m64n32k16.f32.bf16.bf16 {o0,o1,o2,o3,o4,o5,o6,o7,o8,o9,o10,o11,o12,o13,o14,o15}, {a8,a9,a10,a11}, d2, p1, 1, 1, 1;\n"
        "wgmma.mma_async.sync.aligned.m64n32k16.f32.bf16.bf16 {o16,o17,o18,o19,o20,o21,o22,o23,o24,o25,o26,o27,o28,o29,o30,o31}, {a8,a9,a10,a11}, d10, p1, 1, 1, 1;\n"
        "wgmma.mma_async.sync.aligned.m64n32k16.f32.bf16.bf16 {o0,o1,o2,o3,o4,o5,o6,o7,o8,o9,o10,o11,o12,o13,o14,o15}, {a12,a13,a14,a15}, d3, p1, 1, 1, 1;\n"
        "wgmma.mma_async.sync.aligned.m64n32k16.f32.bf16.bf16 {o16,o17,o18,o19,o20,o21,o22,o23,o24,o25,o26,o27,o28,o29,o30,o31}, {a12,a13,a14,a15}, d11, p1, 1, 1, 1;\n"
        "wgmma.mma_async.sync.aligned.m64n32k16.f32.bf16.bf16 {o0,o1,o2,o3,o4,o5,o6,o7,o8,o9,o10,o11,o12,o13,o14,o15}, {a16,a17,a18,a19}, d4, p1, 1, 1, 1;\n"
        "wgmma.mma_async.sync.aligned.m64n32k16.f32.bf16.bf16 {o16,o17,o18,o19,o20,o21,o22,o23,o24,o25,o26,o27,o28,o29,o30,o31}, {a16,a17,a18,a19}, d12, p1, 1, 1, 1;\n"
        "wgmma.mma_async.sync.aligned.m64n32k16.f32.bf16.bf16 {o0,o1,o2,o3,o4,o5,o6,o7,o8,o9,o10,o11,o12,o13,o14,o15}, {a20,a21,a22,a23}, d5, p1, 1, 1, 1;\n"
        "wgmma.mma_async.sync.aligned.m64n32k16.f32.bf16.bf16 {o16,o17,o18,o19,o20,o21,o22,o23,o24,o25,o26,o27,o28,o29,o30,o31}, {a20,a21,a22,a23}, d13, p1, 1, 1, 1;\n"
        "wgmma.mma_async.sync.aligned.m64n32k16.f32.bf16.bf16 {o0,o1,o2,o3,o4,o5,o6,o7,o8,o9,o10,o11,o12,o13,o14,o15}, {a24,a25,a26,a27}, d6, p1, 1, 1, 1;\n"
        "wgmma.mma_async.sync.aligned.m64n32k16.f32.bf16.bf16 {o16,o17,o18,o19,o20,o21,o22,o23,o24,o25,o26,o27,o28,o29,o30,o31}, {a24,a25,a26,a27}, d14, p1, 1, 1, 1;\n"
        "wgmma.mma_async.sync.aligned.m64n32k16.f32.bf16.bf16 {o0,o1,o2,o3,o4,o5,o6,o7,o8,o9,o10,o11,o12,o13,o14,o15}, {a28,a29,a30,a31}, d7, p1, 1, 1, 1;\n"
        "wgmma.mma_async.sync.aligned.m64n32k16.f32.bf16.bf16 {o16,o17,o18,o19,o20,o21,o22,o23,o24,o25,o26,o27,o28,o29,o30,o31}, {a28,a29,a30,a31}, d15, p1, 1, 1, 1;\n"
        "wgmma.commit_group.sync.aligned;\n@nv bra.uni END;\nmovmatrix.sync.aligned.m8n8.trans.b16 b0, %32;\nmovmatrix.sync.aligned.m8n8.trans.b16 b1, %48;\n"
        "movmatrix.sync.aligned.m8n8.trans.b16 b2, %33;\nmovmatrix.sync.aligned.m8n8.trans.b16 b3, %49;\nmovmatrix.sync.aligned.m8n8.trans.b16 b4, %34;\n"
        "movmatrix.sync.aligned.m8n8.trans.b16 b5, %50;\nmovmatrix.sync.aligned.m8n8.trans.b16 b6, %35;\nmovmatrix.sync.aligned.m8n8.trans.b16 b7, %51;\n"
        "movmatrix.sync.aligned.m8n8.trans.b16 b8, %36;\nmovmatrix.sync.aligned.m8n8.trans.b16 b9, %52;\nmovmatrix.sync.aligned.m8n8.trans.b16 b10, %37;\n"
        "movmatrix.sync.aligned.m8n8.trans.b16 b11, %53;\nmovmatrix.sync.aligned.m8n8.trans.b16 b12, %38;\nmovmatrix.sync.aligned.m8n8.trans.b16 b13, %54;\n"
        "movmatrix.sync.aligned.m8n8.trans.b16 b14, %39;\nmovmatrix.sync.aligned.m8n8.trans.b16 b15, %55;\nmovmatrix.sync.aligned.m8n8.trans.b16 b16, %40;\n"
        "movmatrix.sync.aligned.m8n8.trans.b16 b17, %56;\nmovmatrix.sync.aligned.m8n8.trans.b16 b18, %41;\nmovmatrix.sync.aligned.m8n8.trans.b16 b19, %57;\n"
        "movmatrix.sync.aligned.m8n8.trans.b16 b20, %42;\nmovmatrix.sync.aligned.m8n8.trans.b16 b21, %58;\nmovmatrix.sync.aligned.m8n8.trans.b16 b22, %43;\n"
        "movmatrix.sync.aligned.m8n8.trans.b16 b23, %59;\nmovmatrix.sync.aligned.m8n8.trans.b16 b24, %44;\nmovmatrix.sync.aligned.m8n8.trans.b16 b25, %60;\n"
        "movmatrix.sync.aligned.m8n8.trans.b16 b26, %45;\nmovmatrix.sync.aligned.m8n8.trans.b16 b27, %61;\nmovmatrix.sync.aligned.m8n8.trans.b16 b28, %46;\n"
        "movmatrix.sync.aligned.m8n8.trans.b16 b29, %62;\nmovmatrix.sync.aligned.m8n8.trans.b16 b30, %47;\nmovmatrix.sync.aligned.m8n8.trans.b16 b31, %63;\n"
        "@nv bra.uni END;\nwgmma.wait_group.sync.aligned 0;\ncvt.rn.bf16x2.f32 k0, o1, o0;\ncvt.rn.bf16x2.f32 k1, o5, o4;\ncvt.rn.bf16x2.f32 k2, o9, o8;\n"
        "cvt.rn.bf16x2.f32 k3, o13, o12;\ncvt.rn.bf16x2.f32 k4, o3, o2;\ncvt.rn.bf16x2.f32 k5, o7, o6;\ncvt.rn.bf16x2.f32 k6, o11, o10;\n"
        "cvt.rn.bf16x2.f32 k7, o15, o14;\ncvt.rn.bf16x2.f32 k8, o17, o16;\ncvt.rn.bf16x2.f32 k9, o21, o20;\ncvt.rn.bf16x2.f32 k10, o25, o24;\n"
        "cvt.rn.bf16x2.f32 k11, o29, o28;\ncvt.rn.bf16x2.f32 k12, o19, o18;\ncvt.rn.bf16x2.f32 k13, o23, o22;\ncvt.rn.bf16x2.f32 k14, o27, o26;\n"
        "cvt.rn.bf16x2.f32 k15, o31, o30;\nld.volatile.shared.v2.b32 {c0,c1}, [%64+0];\nld.volatile.shared.v2.b32 {c2,c3}, [%64+4096];\n"
        "ld.volatile.shared.v2.b32 {c4,c5}, [%64+8];\nld.volatile.shared.v2.b32 {c6,c7}, [%64+4104];\ndp2a.lo.u32.u32 t, c0, 0x04000004, 0x200000;\n"
        "mov.b64 d0, {t, h};\ndp2a.hi.u32.u32 t, c0, 0x04000004, 0x200000;\nmov.b64 d1, {t, h};\ndp2a.lo.u32.u32 t, c1, 0x04000004, 0x200000;\n"
        "mov.b64 d2, {t, h};\ndp2a.hi.u32.u32 t, c1, 0x04000004, 0x200000;\nmov.b64 d3, {t, h};\ndp2a.lo.u32.u32 t, c2, 0x04000004, 0x200000;\n"
        "mov.b64 d4, {t, h};\ndp2a.hi.u32.u32 t, c2, 0x04000004, 0x200000;\nmov.b64 d5, {t, h};\ndp2a.lo.u32.u32 t, c3, 0x04000004, 0x200000;\n"
        "mov.b64 d6, {t, h};\ndp2a.hi.u32.u32 t, c3, 0x04000004, 0x200000;\nmov.b64 d7, {t, h};\ndp2a.lo.u32.u32 t, c4, 0x04000004, 0x200000;\n"
        "mov.b64 d8, {t, h};\ndp2a.hi.u32.u32 t, c4, 0x04000004, 0x200000;\nmov.b64 d9, {t, h};\ndp2a.lo.u32.u32 t, c5, 0x04000004, 0x200000;\n"
        "mov.b64 d10, {t, h};\ndp2a.hi.u32.u32 t, c5, 0x04000004, 0x200000;\nmov.b64 d11, {t, h};\ndp2a.lo.u32.u32 t, c6, 0x04000004, 0x200000;\n"
        "mov.b64 d12, {t, h};\ndp2a.hi.u32.u32 t, c6, 0x04000004, 0x200000;\nmov.b64 d13, {t, h};\ndp2a.lo.u32.u32 t, c7, 0x04000004, 0x200000;\n"
        "mov.b64 d14, {t, h};\ndp2a.hi.u32.u32 t, c7, 0x04000004, 0x200000;\nmov.b64 d15, {t, h};\nwgmma.fence.sync.aligned;\n"
        "wgmma.mma_async.sync.aligned.m64n32k16.f32.bf16.bf16 {o0,o1,o2,o3,o4,o5,o6,o7,o8,o9,o10,o11,o12,o13,o14,o15}, {b0,b1,b2,b3}, d0, p0, 1, 1, 1;\n"
        "wgmma.mma_async.sync.aligned.m64n32k16.f32.bf16.bf16 {o16,o17,o18,o19,o20,o21,o22,o23,o24,o25,o26,o27,o28,o29,o30,o31}, {b0,b1,b2,b3}, d8, p0, 1, 1, 1;\n"
        "wgmma.mma_async.sync.aligned.m64n32k16.f32.bf16.bf16 {o0,o1,o2,o3,o4,o5,o6,o7,o8,o9,o10,o11,o12,o13,o14,o15}, {b4,b5,b6,b7}, d1, p1, 1, 1, 1;\n"
        "wgmma.mma_async.sync.aligned.m64n32k16.f32.bf16.bf16 {o16,o17,o18,o19,o20,o21,o22,o23,o24,o25,o26,o27,o28,o29,o30,o31}, {b4,b5,b6,b7}, d9, p1, 1, 1, 1;\n"
        "wgmma.mma_async.sync.aligned.m64n32k16.f32.bf16.bf16 {o0,o1,o2,o3,o4,o5,o6,o7,o8,o9,o10,o11,o12,o13,o14,o15}, {b8,b9,b10,b11}, d2, p1, 1, 1, 1;\n"
        "wgmma.mma_async.sync.aligned.m64n32k16.f32.bf16.bf16 {o16,o17,o18,o19,o20,o21,o22,o23,o24,o25,o26,o27,o28,o29,o30,o31}, {b8,b9,b10,b11}, d10, p1, 1, 1, 1;\n"
        "wgmma.mma_async.sync.aligned.m64n32k16.f32.bf16.bf16 {o0,o1,o2,o3,o4,o5,o6,o7,o8,o9,o10,o11,o12,o13,o14,o15}, {b12,b13,b14,b15}, d3, p1, 1, 1, 1;\n"
        "wgmma.mma_async.sync.aligned.m64n32k16.f32.bf16.bf16 {o16,o17,o18,o19,o20,o21,o22,o23,o24,o25,o26,o27,o28,o29,o30,o31}, {b12,b13,b14,b15}, d11, p1, 1, 1, 1;\n"
        "wgmma.mma_async.sync.aligned.m64n32k16.f32.bf16.bf16 {o0,o1,o2,o3,o4,o5,o6,o7,o8,o9,o10,o11,o12,o13,o14,o15}, {b16,b17,b18,b19}, d4, p1, 1, 1, 1;\n"
        "wgmma.mma_async.sync.aligned.m64n32k16.f32.bf16.bf16 {o16,o17,o18,o19,o20,o21,o22,o23,o24,o25,o26,o27,o28,o29,o30,o31}, {b16,b17,b18,b19}, d12, p1, 1, 1, 1;\n"
        "wgmma.mma_async.sync.aligned.m64n32k16.f32.bf16.bf16 {o0,o1,o2,o3,o4,o5,o6,o7,o8,o9,o10,o11,o12,o13,o14,o15}, {b20,b21,b22,b23}, d5, p1, 1, 1, 1;\n"
        "wgmma.mma_async.sync.aligned.m64n32k16.f32.bf16.bf16 {o16,o17,o18,o19,o20,o21,o22,o23,o24,o25,o26,o27,o28,o29,o30,o31}, {b20,b21,b22,b23}, d13, p1, 1, 1, 1;\n"
        "wgmma.mma_async.sync.aligned.m64n32k16.f32.bf16.bf16 {o0,o1,o2,o3,o4,o5,o6,o7,o8,o9,o10,o11,o12,o13,o14,o15}, {b24,b25,b26,b27}, d6, p1, 1, 1, 1;\n"
        "wgmma.mma_async.sync.aligned.m64n32k16.f32.bf16.bf16 {o16,o17,o18,o19,o20,o21,o22,o23,o24,o25,o26,o27,o28,o29,o30,o31}, {b24,b25,b26,b27}, d14, p1, 1, 1, 1;\n"
        "wgmma.mma_async.sync.aligned.m64n32k16.f32.bf16.bf16 {o0,o1,o2,o3,o4,o5,o6,o7,o8,o9,o10,o11,o12,o13,o14,o15}, {b28,b29,b30,b31}, d7, p1, 1, 1, 1;\n"
        "wgmma.mma_async.sync.aligned.m64n32k16.f32.bf16.bf16 {o16,o17,o18,o19,o20,o21,o22,o23,o24,o25,o26,o27,o28,o29,o30,o31}, {b28,b29,b30,b31}, d15, p1, 1, 1, 1;\n"
        "wgmma.commit_group.sync.aligned;\n@nv bra.uni END;\n@s0 st.global.v4.b32 [%65+128], {k0,k1,k2,k3};\n@s1 st.global.v4.b32 [%66+128], {k4,k5,k6,k7};\n"
        "@s0 st.global.v4.b32 [%65+192], {k8,k9,k10,k11};\n@s1 st.global.v4.b32 [%66+192], {k12,k13,k14,k15};\n@nv bra.uni END;\n"
        "wgmma.wait_group.sync.aligned 0;\ncvt.rn.bf16x2.f32 k0, o1, o0;\ncvt.rn.bf16x2.f32 k1, o5, o4;\ncvt.rn.bf16x2.f32 k2, o9, o8;\n"
        "cvt.rn.bf16x2.f32 k3, o13, o12;\ncvt.rn.bf16x2.f32 k4, o3, o2;\ncvt.rn.bf16x2.f32 k5, o7, o6;\ncvt.rn.bf16x2.f32 k6, o11, o10;\n"
        "cvt.rn.bf16x2.f32 k7, o15, o14;\ncvt.rn.bf16x2.f32 k8, o17, o16;\ncvt.rn.bf16x2.f32 k9, o21, o20;\ncvt.rn.bf16x2.f32 k10, o25, o24;\n"
        "cvt.rn.bf16x2.f32 k11, o29, o28;\ncvt.rn.bf16x2.f32 k12, o19, o18;\ncvt.rn.bf16x2.f32 k13, o23, o22;\ncvt.rn.bf16x2.f32 k14, o27, o26;\n"
        "cvt.rn.bf16x2.f32 k15, o31, o30;\nld.volatile.shared.v2.b32 {c0,c1}, [%64+16];\nld.volatile.shared.v2.b32 {c2,c3}, [%64+4112];\n"
        "ld.volatile.shared.v2.b32 {c4,c5}, [%64+24];\nld.volatile.shared.v2.b32 {c6,c7}, [%64+4120];\ndp2a.lo.u32.u32 t, c0, 0x04000004, 0x200000;\n"
        "mov.b64 d0, {t, h};\ndp2a.hi.u32.u32 t, c0, 0x04000004, 0x200000;\nmov.b64 d1, {t, h};\ndp2a.lo.u32.u32 t, c1, 0x04000004, 0x200000;\n"
        "mov.b64 d2, {t, h};\ndp2a.hi.u32.u32 t, c1, 0x04000004, 0x200000;\nmov.b64 d3, {t, h};\ndp2a.lo.u32.u32 t, c2, 0x04000004, 0x200000;\n"
        "mov.b64 d4, {t, h};\ndp2a.hi.u32.u32 t, c2, 0x04000004, 0x200000;\nmov.b64 d5, {t, h};\ndp2a.lo.u32.u32 t, c3, 0x04000004, 0x200000;\n"
        "mov.b64 d6, {t, h};\ndp2a.hi.u32.u32 t, c3, 0x04000004, 0x200000;\nmov.b64 d7, {t, h};\ndp2a.lo.u32.u32 t, c4, 0x04000004, 0x200000;\n"
        "mov.b64 d8, {t, h};\ndp2a.hi.u32.u32 t, c4, 0x04000004, 0x200000;\nmov.b64 d9, {t, h};\ndp2a.lo.u32.u32 t, c5, 0x04000004, 0x200000;\n"
        "mov.b64 d10, {t, h};\ndp2a.hi.u32.u32 t, c5, 0x04000004, 0x200000;\nmov.b64 d11, {t, h};\ndp2a.lo.u32.u32 t, c6, 0x04000004, 0x200000;\n"
        "mov.b64 d12, {t, h};\ndp2a.hi.u32.u32 t, c6, 0x04000004, 0x200000;\nmov.b64 d13, {t, h};\ndp2a.lo.u32.u32 t, c7, 0x04000004, 0x200000;\n"
        "mov.b64 d14, {t, h};\ndp2a.hi.u32.u32 t, c7, 0x04000004, 0x200000;\nmov.b64 d15, {t, h};\nwgmma.fence.sync.aligned;\n"
        "wgmma.mma_async.sync.aligned.m64n32k16.f32.bf16.bf16 {o0,o1,o2,o3,o4,o5,o6,o7,o8,o9,o10,o11,o12,o13,o14,o15}, {b0,b1,b2,b3}, d0, p0, 1, 1, 1;\n"
        "wgmma.mma_async.sync.aligned.m64n32k16.f32.bf16.bf16 {o16,o17,o18,o19,o20,o21,o22,o23,o24,o25,o26,o27,o28,o29,o30,o31}, {b0,b1,b2,b3}, d8, p0, 1, 1, 1;\n"
        "wgmma.mma_async.sync.aligned.m64n32k16.f32.bf16.bf16 {o0,o1,o2,o3,o4,o5,o6,o7,o8,o9,o10,o11,o12,o13,o14,o15}, {b4,b5,b6,b7}, d1, p1, 1, 1, 1;\n"
        "wgmma.mma_async.sync.aligned.m64n32k16.f32.bf16.bf16 {o16,o17,o18,o19,o20,o21,o22,o23,o24,o25,o26,o27,o28,o29,o30,o31}, {b4,b5,b6,b7}, d9, p1, 1, 1, 1;\n"
        "wgmma.mma_async.sync.aligned.m64n32k16.f32.bf16.bf16 {o0,o1,o2,o3,o4,o5,o6,o7,o8,o9,o10,o11,o12,o13,o14,o15}, {b8,b9,b10,b11}, d2, p1, 1, 1, 1;\n"
        "wgmma.mma_async.sync.aligned.m64n32k16.f32.bf16.bf16 {o16,o17,o18,o19,o20,o21,o22,o23,o24,o25,o26,o27,o28,o29,o30,o31}, {b8,b9,b10,b11}, d10, p1, 1, 1, 1;\n"
        "wgmma.mma_async.sync.aligned.m64n32k16.f32.bf16.bf16 {o0,o1,o2,o3,o4,o5,o6,o7,o8,o9,o10,o11,o12,o13,o14,o15}, {b12,b13,b14,b15}, d3, p1, 1, 1, 1;\n"
        "wgmma.mma_async.sync.aligned.m64n32k16.f32.bf16.bf16 {o16,o17,o18,o19,o20,o21,o22,o23,o24,o25,o26,o27,o28,o29,o30,o31}, {b12,b13,b14,b15}, d11, p1, 1, 1, 1;\n"
        "wgmma.mma_async.sync.aligned.m64n32k16.f32.bf16.bf16 {o0,o1,o2,o3,o4,o5,o6,o7,o8,o9,o10,o11,o12,o13,o14,o15}, {b16,b17,b18,b19}, d4, p1, 1, 1, 1;\n"
        "wgmma.mma_async.sync.aligned.m64n32k16.f32.bf16.bf16 {o16,o17,o18,o19,o20,o21,o22,o23,o24,o25,o26,o27,o28,o29,o30,o31}, {b16,b17,b18,b19}, d12, p1, 1, 1, 1;\n"
        "wgmma.mma_async.sync.aligned.m64n32k16.f32.bf16.bf16 {o0,o1,o2,o3,o4,o5,o6,o7,o8,o9,o10,o11,o12,o13,o14,o15}, {b20,b21,b22,b23}, d5, p1, 1, 1, 1;\n"
        "wgmma.mma_async.sync.aligned.m64n32k16.f32.bf16.bf16 {o16,o17,o18,o19,o20,o21,o22,o23,o24,o25,o26,o27,o28,o29,o30,o31}, {b20,b21,b22,b23}, d13, p1, 1, 1, 1;\n"
        "wgmma.mma_async.sync.aligned.m64n32k16.f32.bf16.bf16 {o0,o1,o2,o3,o4,o5,o6,o7,o8,o9,o10,o11,o12,o13,o14,o15}, {b24,b25,b26,b27}, d6, p1, 1, 1, 1;\n"
        "wgmma.mma_async.sync.aligned.m64n32k16.f32.bf16.bf16 {o16,o17,o18,o19,o20,o21,o22,o23,o24,o25,o26,o27,o28,o29,o30,o31}, {b24,b25,b26,b27}, d14, p1, 1, 1, 1;\n"
        "wgmma.mma_async.sync.aligned.m64n32k16.f32.bf16.bf16 {o0,o1,o2,o3,o4,o5,o6,o7,o8,o9,o10,o11,o12,o13,o14,o15}, {b28,b29,b30,b31}, d7, p1, 1, 1, 1;\n"
        "wgmma.mma_async.sync.aligned.m64n32k16.f32.bf16.bf16 {o16,o17,o18,o19,o20,o21,o22,o23,o24,o25,o26,o27,o28,o29,o30,o31}, {b28,b29,b30,b31}, d15, p1, 1, 1, 1;\n"
        "wgmma.commit_group.sync.aligned;\n@nv bra.uni END;\n@s2 st.global.v4.b32 [%67+0], {k0,k1,k2,k3};\n@s3 st.global.v4.b32 [%68+0], {k4,k5,k6,k7};\n"
        "@s2 st.global.v4.b32 [%67+64], {k8,k9,k10,k11};\n@s3 st.global.v4.b32 [%68+64], {k12,k13,k14,k15};\n@nv bra.uni END;\nwgmma.wait_group.sync.aligned 0;\n"
        "cvt.rn.bf16x2.f32 k0, o1, o0;\ncvt.rn.bf16x2.f32 k1, o5, o4;\ncvt.rn.bf16x2.f32 k2, o9, o8;\ncvt.rn.bf16x2.f32 k3, o13, o12;\n"
        "cvt.rn.bf16x2.f32 k4, o3, o2;\ncvt.rn.bf16x2.f32 k5, o7, o6;\ncvt.rn.bf16x2.f32 k6, o11, o10;\ncvt.rn.bf16x2.f32 k7, o15, o14;\n"
        "cvt.rn.bf16x2.f32 k8, o17, o16;\ncvt.rn.bf16x2.f32 k9, o21, o20;\ncvt.rn.bf16x2.f32 k10, o25, o24;\ncvt.rn.bf16x2.f32 k11, o29, o28;\n"
        "cvt.rn.bf16x2.f32 k12, o19, o18;\ncvt.rn.bf16x2.f32 k13, o23, o22;\ncvt.rn.bf16x2.f32 k14, o27, o26;\ncvt.rn.bf16x2.f32 k15, o31, o30;\n"
        "@s2 st.global.v4.b32 [%67+128], {k0,k1,k2,k3};\n@s3 st.global.v4.b32 [%68+128], {k4,k5,k6,k7};\n@s2 st.global.v4.b32 [%67+192], {k8,k9,k10,k11};\n"
        "@s3 st.global.v4.b32 [%68+192], {k12,k13,k14,k15};\n"
        "END:\n}\n"
        ::"r"(pk[0]), "r"(pk[1]), "r"(pk[2]), "r"(pk[3]), "r"(pk[4]), "r"(pk[5]), "r"(pk[6]), "r"(pk[7]), "r"(pk[8]), "r"(pk[9]), "r"(pk[10]),
          "r"(pk[11]), "r"(pk[12]), "r"(pk[13]), "r"(pk[14]), "r"(pk[15]), "r"(pk[16]), "r"(pk[17]), "r"(pk[18]), "r"(pk[19]), "r"(pk[20]),
          "r"(pk[21]), "r"(pk[22]), "r"(pk[23]), "r"(pk[24]), "r"(pk[25]), "r"(pk[26]), "r"(pk[27]), "r"(pk[28]), "r"(pk[29]), "r"(pk[30]),
          "r"(pk[31]), "r"(pk[32]), "r"(pk[33]), "r"(pk[34]), "r"(pk[35]), "r"(pk[36]), "r"(pk[37]), "r"(pk[38]), "r"(pk[39]), "r"(pk[40]),
          "r"(pk[41]), "r"(pk[42]), "r"(pk[43]), "r"(pk[44]), "r"(pk[45]), "r"(pk[46]), "r"(pk[47]), "r"(pk[48]), "r"(pk[49]), "r"(pk[50]),
          "r"(pk[51]), "r"(pk[52]), "r"(pk[53]), "r"(pk[54]), "r"(pk[55]), "r"(pk[56]), "r"(pk[57]), "r"(pk[58]), "r"(pk[59]), "r"(pk[60]),
          "r"(pk[61]), "r"(pk[62]), "r"(pk[63]), "r"(ra), "l"(p[0]), "l"(p[1]), "l"(p[2]), "l"(p[3]), "r"(v[0]), "r"(v[1]), "r"(v[2]), "r"(v[3]),
          "r"(ba)
        : "memory");
}
__device__ __forceinline__ void project3(const uint32_t (&pk)[48], uint32_t ra, uint32_t ba, uint4* const (&p)[3], const uint32_t (&v)[3]) {
    asm volatile(
        "{\n.reg .pred p0, p1, q0, q1, nv, s<4>;\n.reg .b32 t, h, c<16>, a<32>, b<32>, k<16>;\n.reg .b64 d<16>;\n.reg .f32 o<32>;\nsetp.ne.b32 p0, 0, 0;\n"
        "setp.eq.b32 p1, 0, 0;\nmov.b32 h, 8;\nsetp.eq.u32 nv, %48, 0;\nvote.sync.any.pred nv, nv, 0xffffffff;\nsetp.ne.b32 s0, %52, 0;\n"
        "setp.ne.b32 s1, %53, 0;\nsetp.ne.b32 s2, %54, 0;\nmov.b32 t, 0;\n"
        "W0:\nmbarrier.try_wait.parity.shared.b64 q0, [%55], 0;\nvote.sync.all.pred q0, q0, 0xffffffff;\nadd.u32 t, t, 1;\nsetp.lt.and.u32 q1, t, 1000000, !q0;\n"
        "@q1 bra.uni W0;\nld.volatile.shared.v2.b32 {c0,c1}, [%48+0];\nld.volatile.shared.v2.b32 {c2,c3}, [%48+4096];\n"
        "ld.volatile.shared.v2.b32 {c4,c5}, [%48+8];\nld.volatile.shared.v2.b32 {c6,c7}, [%48+4104];\ndp2a.lo.u32.u32 t, c0, 0x04000004, 0x200000;\n"
        "mov.b64 d0, {t, h};\ndp2a.hi.u32.u32 t, c0, 0x04000004, 0x200000;\nmov.b64 d1, {t, h};\ndp2a.lo.u32.u32 t, c1, 0x04000004, 0x200000;\n"
        "mov.b64 d2, {t, h};\ndp2a.hi.u32.u32 t, c1, 0x04000004, 0x200000;\nmov.b64 d3, {t, h};\ndp2a.lo.u32.u32 t, c2, 0x04000004, 0x200000;\n"
        "mov.b64 d4, {t, h};\ndp2a.hi.u32.u32 t, c2, 0x04000004, 0x200000;\nmov.b64 d5, {t, h};\ndp2a.lo.u32.u32 t, c3, 0x04000004, 0x200000;\n"
        "mov.b64 d6, {t, h};\ndp2a.hi.u32.u32 t, c3, 0x04000004, 0x200000;\nmov.b64 d7, {t, h};\ndp2a.lo.u32.u32 t, c4, 0x04000004, 0x200000;\n"
        "mov.b64 d8, {t, h};\ndp2a.hi.u32.u32 t, c4, 0x04000004, 0x200000;\nmov.b64 d9, {t, h};\ndp2a.lo.u32.u32 t, c5, 0x04000004, 0x200000;\n"
        "mov.b64 d10, {t, h};\ndp2a.hi.u32.u32 t, c5, 0x04000004, 0x200000;\nmov.b64 d11, {t, h};\ndp2a.lo.u32.u32 t, c6, 0x04000004, 0x200000;\n"
        "mov.b64 d12, {t, h};\ndp2a.hi.u32.u32 t, c6, 0x04000004, 0x200000;\nmov.b64 d13, {t, h};\ndp2a.lo.u32.u32 t, c7, 0x04000004, 0x200000;\n"
        "mov.b64 d14, {t, h};\ndp2a.hi.u32.u32 t, c7, 0x04000004, 0x200000;\nmov.b64 d15, {t, h};\nmovmatrix.sync.aligned.m8n8.trans.b16 a0, %0;\n"
        "movmatrix.sync.aligned.m8n8.trans.b16 a1, %16;\nmovmatrix.sync.aligned.m8n8.trans.b16 a2, %1;\nmovmatrix.sync.aligned.m8n8.trans.b16 a3, %17;\n"
        "movmatrix.sync.aligned.m8n8.trans.b16 a4, %2;\nmovmatrix.sync.aligned.m8n8.trans.b16 a5, %18;\nmovmatrix.sync.aligned.m8n8.trans.b16 a6, %3;\n"
        "movmatrix.sync.aligned.m8n8.trans.b16 a7, %19;\nmovmatrix.sync.aligned.m8n8.trans.b16 a8, %4;\nmovmatrix.sync.aligned.m8n8.trans.b16 a9, %20;\n"
        "movmatrix.sync.aligned.m8n8.trans.b16 a10, %5;\nmovmatrix.sync.aligned.m8n8.trans.b16 a11, %21;\nmovmatrix.sync.aligned.m8n8.trans.b16 a12, %6;\n"
        "movmatrix.sync.aligned.m8n8.trans.b16 a13, %22;\nmovmatrix.sync.aligned.m8n8.trans.b16 a14, %7;\nmovmatrix.sync.aligned.m8n8.trans.b16 a15, %23;\n"
        "movmatrix.sync.aligned.m8n8.trans.b16 a16, %8;\nmovmatrix.sync.aligned.m8n8.trans.b16 a17, %24;\nmovmatrix.sync.aligned.m8n8.trans.b16 a18, %9;\n"
        "movmatrix.sync.aligned.m8n8.trans.b16 a19, %25;\nmovmatrix.sync.aligned.m8n8.trans.b16 a20, %10;\nmovmatrix.sync.aligned.m8n8.trans.b16 a21, %26;\n"
        "movmatrix.sync.aligned.m8n8.trans.b16 a22, %11;\nmovmatrix.sync.aligned.m8n8.trans.b16 a23, %27;\nmovmatrix.sync.aligned.m8n8.trans.b16 a24, %12;\n"
        "movmatrix.sync.aligned.m8n8.trans.b16 a25, %28;\nmovmatrix.sync.aligned.m8n8.trans.b16 a26, %13;\nmovmatrix.sync.aligned.m8n8.trans.b16 a27, %29;\n"
        "movmatrix.sync.aligned.m8n8.trans.b16 a28, %14;\nmovmatrix.sync.aligned.m8n8.trans.b16 a29, %30;\nmovmatrix.sync.aligned.m8n8.trans.b16 a30, %15;\n"
        "movmatrix.sync.aligned.m8n8.trans.b16 a31, %31;\nwgmma.fence.sync.aligned;\n"
        "wgmma.mma_async.sync.aligned.m64n32k16.f32.bf16.bf16 {o0,o1,o2,o3,o4,o5,o6,o7,o8,o9,o10,o11,o12,o13,o14,o15}, {a0,a1,a2,a3}, d0, p0, 1, 1, 1;\n"
        "wgmma.mma_async.sync.aligned.m64n32k16.f32.bf16.bf16 {o0,o1,o2,o3,o4,o5,o6,o7,o8,o9,o10,o11,o12,o13,o14,o15}, {a4,a5,a6,a7}, d1, p1, 1, 1, 1;\n"
        "wgmma.mma_async.sync.aligned.m64n32k16.f32.bf16.bf16 {o0,o1,o2,o3,o4,o5,o6,o7,o8,o9,o10,o11,o12,o13,o14,o15}, {a8,a9,a10,a11}, d2, p1, 1, 1, 1;\n"
        "wgmma.mma_async.sync.aligned.m64n32k16.f32.bf16.bf16 {o0,o1,o2,o3,o4,o5,o6,o7,o8,o9,o10,o11,o12,o13,o14,o15}, {a12,a13,a14,a15}, d3, p1, 1, 1, 1;\n"
        "wgmma.mma_async.sync.aligned.m64n32k16.f32.bf16.bf16 {o0,o1,o2,o3,o4,o5,o6,o7,o8,o9,o10,o11,o12,o13,o14,o15}, {a16,a17,a18,a19}, d4, p1, 1, 1, 1;\n"
        "wgmma.mma_async.sync.aligned.m64n32k16.f32.bf16.bf16 {o0,o1,o2,o3,o4,o5,o6,o7,o8,o9,o10,o11,o12,o13,o14,o15}, {a20,a21,a22,a23}, d5, p1, 1, 1, 1;\n"
        "wgmma.mma_async.sync.aligned.m64n32k16.f32.bf16.bf16 {o0,o1,o2,o3,o4,o5,o6,o7,o8,o9,o10,o11,o12,o13,o14,o15}, {a24,a25,a26,a27}, d6, p1, 1, 1, 1;\n"
        "wgmma.mma_async.sync.aligned.m64n32k16.f32.bf16.bf16 {o0,o1,o2,o3,o4,o5,o6,o7,o8,o9,o10,o11,o12,o13,o14,o15}, {a28,a29,a30,a31}, d7, p1, 1, 1, 1;\n"
        "wgmma.commit_group.sync.aligned;\n"
        "wgmma.mma_async.sync.aligned.m64n32k16.f32.bf16.bf16 {o16,o17,o18,o19,o20,o21,o22,o23,o24,o25,o26,o27,o28,o29,o30,o31}, {a0,a1,a2,a3}, d8, p0, 1, 1, 1;\n"
        "wgmma.mma_async.sync.aligned.m64n32k16.f32.bf16.bf16 {o16,o17,o18,o19,o20,o21,o22,o23,o24,o25,o26,o27,o28,o29,o30,o31}, {a4,a5,a6,a7}, d9, p1, 1, 1, 1;\n"
        "wgmma.mma_async.sync.aligned.m64n32k16.f32.bf16.bf16 {o16,o17,o18,o19,o20,o21,o22,o23,o24,o25,o26,o27,o28,o29,o30,o31}, {a8,a9,a10,a11}, d10, p1, 1, 1, 1;\n"
        "wgmma.mma_async.sync.aligned.m64n32k16.f32.bf16.bf16 {o16,o17,o18,o19,o20,o21,o22,o23,o24,o25,o26,o27,o28,o29,o30,o31}, {a12,a13,a14,a15}, d11, p1, 1, 1, 1;\n"
        "wgmma.mma_async.sync.aligned.m64n32k16.f32.bf16.bf16 {o16,o17,o18,o19,o20,o21,o22,o23,o24,o25,o26,o27,o28,o29,o30,o31}, {a16,a17,a18,a19}, d12, p1, 1, 1, 1;\n"
        "wgmma.mma_async.sync.aligned.m64n32k16.f32.bf16.bf16 {o16,o17,o18,o19,o20,o21,o22,o23,o24,o25,o26,o27,o28,o29,o30,o31}, {a20,a21,a22,a23}, d13, p1, 1, 1, 1;\n"
        "wgmma.mma_async.sync.aligned.m64n32k16.f32.bf16.bf16 {o16,o17,o18,o19,o20,o21,o22,o23,o24,o25,o26,o27,o28,o29,o30,o31}, {a24,a25,a26,a27}, d14, p1, 1, 1, 1;\n"
        "wgmma.mma_async.sync.aligned.m64n32k16.f32.bf16.bf16 {o16,o17,o18,o19,o20,o21,o22,o23,o24,o25,o26,o27,o28,o29,o30,o31}, {a28,a29,a30,a31}, d15, p1, 1, 1, 1;\n"
        "wgmma.commit_group.sync.aligned;\nwgmma.wait_group.sync.aligned 1;\ncvt.rn.bf16x2.f32 k0, o1, o0;\ncvt.rn.bf16x2.f32 k1, o5, o4;\n"
        "cvt.rn.bf16x2.f32 k2, o9, o8;\ncvt.rn.bf16x2.f32 k3, o13, o12;\n@s0 st.global.v4.b32 [%49+0], {k0,k1,k2,k3};\ncvt.rn.bf16x2.f32 k4, o3, o2;\n"
        "cvt.rn.bf16x2.f32 k5, o7, o6;\ncvt.rn.bf16x2.f32 k6, o11, o10;\ncvt.rn.bf16x2.f32 k7, o15, o14;\n@s1 st.global.v4.b32 [%50+0], {k4,k5,k6,k7};\n"
        "@nv bra.uni END;\nwgmma.wait_group.sync.aligned 0;\ncvt.rn.bf16x2.f32 k8, o17, o16;\ncvt.rn.bf16x2.f32 k9, o21, o20;\ncvt.rn.bf16x2.f32 k10, o25, o24;\n"
        "cvt.rn.bf16x2.f32 k11, o29, o28;\n@s0 st.global.v4.b32 [%49+64], {k8,k9,k10,k11};\ncvt.rn.bf16x2.f32 k12, o19, o18;\ncvt.rn.bf16x2.f32 k13, o23, o22;\n"
        "cvt.rn.bf16x2.f32 k14, o27, o26;\ncvt.rn.bf16x2.f32 k15, o31, o30;\n@s1 st.global.v4.b32 [%50+64], {k12,k13,k14,k15};\n@nv bra.uni END;\n"
        "ld.volatile.shared.v2.b32 {c0,c1}, [%48+16];\nld.volatile.shared.v2.b32 {c2,c3}, [%48+4112];\nld.volatile.shared.v2.b32 {c4,c5}, [%48+24];\n"
        "ld.volatile.shared.v2.b32 {c6,c7}, [%48+4120];\ndp2a.lo.u32.u32 t, c0, 0x04000004, 0x200000;\nmov.b64 d0, {t, h};\n"
        "dp2a.hi.u32.u32 t, c0, 0x04000004, 0x200000;\nmov.b64 d1, {t, h};\ndp2a.lo.u32.u32 t, c1, 0x04000004, 0x200000;\nmov.b64 d2, {t, h};\n"
        "dp2a.hi.u32.u32 t, c1, 0x04000004, 0x200000;\nmov.b64 d3, {t, h};\ndp2a.lo.u32.u32 t, c2, 0x04000004, 0x200000;\nmov.b64 d4, {t, h};\n"
        "dp2a.hi.u32.u32 t, c2, 0x04000004, 0x200000;\nmov.b64 d5, {t, h};\ndp2a.lo.u32.u32 t, c3, 0x04000004, 0x200000;\nmov.b64 d6, {t, h};\n"
        "dp2a.hi.u32.u32 t, c3, 0x04000004, 0x200000;\nmov.b64 d7, {t, h};\ndp2a.lo.u32.u32 t, c4, 0x04000004, 0x200000;\nmov.b64 d8, {t, h};\n"
        "dp2a.hi.u32.u32 t, c4, 0x04000004, 0x200000;\nmov.b64 d9, {t, h};\ndp2a.lo.u32.u32 t, c5, 0x04000004, 0x200000;\nmov.b64 d10, {t, h};\n"
        "dp2a.hi.u32.u32 t, c5, 0x04000004, 0x200000;\nmov.b64 d11, {t, h};\ndp2a.lo.u32.u32 t, c6, 0x04000004, 0x200000;\nmov.b64 d12, {t, h};\n"
        "dp2a.hi.u32.u32 t, c6, 0x04000004, 0x200000;\nmov.b64 d13, {t, h};\ndp2a.lo.u32.u32 t, c7, 0x04000004, 0x200000;\nmov.b64 d14, {t, h};\n"
        "dp2a.hi.u32.u32 t, c7, 0x04000004, 0x200000;\nmov.b64 d15, {t, h};\nwgmma.fence.sync.aligned;\n"
        "wgmma.mma_async.sync.aligned.m64n32k16.f32.bf16.bf16 {o0,o1,o2,o3,o4,o5,o6,o7,o8,o9,o10,o11,o12,o13,o14,o15}, {a0,a1,a2,a3}, d0, p0, 1, 1, 1;\n"
        "wgmma.mma_async.sync.aligned.m64n32k16.f32.bf16.bf16 {o16,o17,o18,o19,o20,o21,o22,o23,o24,o25,o26,o27,o28,o29,o30,o31}, {a0,a1,a2,a3}, d8, p0, 1, 1, 1;\n"
        "wgmma.mma_async.sync.aligned.m64n32k16.f32.bf16.bf16 {o0,o1,o2,o3,o4,o5,o6,o7,o8,o9,o10,o11,o12,o13,o14,o15}, {a4,a5,a6,a7}, d1, p1, 1, 1, 1;\n"
        "wgmma.mma_async.sync.aligned.m64n32k16.f32.bf16.bf16 {o16,o17,o18,o19,o20,o21,o22,o23,o24,o25,o26,o27,o28,o29,o30,o31}, {a4,a5,a6,a7}, d9, p1, 1, 1, 1;\n"
        "wgmma.mma_async.sync.aligned.m64n32k16.f32.bf16.bf16 {o0,o1,o2,o3,o4,o5,o6,o7,o8,o9,o10,o11,o12,o13,o14,o15}, {a8,a9,a10,a11}, d2, p1, 1, 1, 1;\n"
        "wgmma.mma_async.sync.aligned.m64n32k16.f32.bf16.bf16 {o16,o17,o18,o19,o20,o21,o22,o23,o24,o25,o26,o27,o28,o29,o30,o31}, {a8,a9,a10,a11}, d10, p1, 1, 1, 1;\n"
        "wgmma.mma_async.sync.aligned.m64n32k16.f32.bf16.bf16 {o0,o1,o2,o3,o4,o5,o6,o7,o8,o9,o10,o11,o12,o13,o14,o15}, {a12,a13,a14,a15}, d3, p1, 1, 1, 1;\n"
        "wgmma.mma_async.sync.aligned.m64n32k16.f32.bf16.bf16 {o16,o17,o18,o19,o20,o21,o22,o23,o24,o25,o26,o27,o28,o29,o30,o31}, {a12,a13,a14,a15}, d11, p1, 1, 1, 1;\n"
        "wgmma.mma_async.sync.aligned.m64n32k16.f32.bf16.bf16 {o0,o1,o2,o3,o4,o5,o6,o7,o8,o9,o10,o11,o12,o13,o14,o15}, {a16,a17,a18,a19}, d4, p1, 1, 1, 1;\n"
        "wgmma.mma_async.sync.aligned.m64n32k16.f32.bf16.bf16 {o16,o17,o18,o19,o20,o21,o22,o23,o24,o25,o26,o27,o28,o29,o30,o31}, {a16,a17,a18,a19}, d12, p1, 1, 1, 1;\n"
        "wgmma.mma_async.sync.aligned.m64n32k16.f32.bf16.bf16 {o0,o1,o2,o3,o4,o5,o6,o7,o8,o9,o10,o11,o12,o13,o14,o15}, {a20,a21,a22,a23}, d5, p1, 1, 1, 1;\n"
        "wgmma.mma_async.sync.aligned.m64n32k16.f32.bf16.bf16 {o16,o17,o18,o19,o20,o21,o22,o23,o24,o25,o26,o27,o28,o29,o30,o31}, {a20,a21,a22,a23}, d13, p1, 1, 1, 1;\n"
        "wgmma.mma_async.sync.aligned.m64n32k16.f32.bf16.bf16 {o0,o1,o2,o3,o4,o5,o6,o7,o8,o9,o10,o11,o12,o13,o14,o15}, {a24,a25,a26,a27}, d6, p1, 1, 1, 1;\n"
        "wgmma.mma_async.sync.aligned.m64n32k16.f32.bf16.bf16 {o16,o17,o18,o19,o20,o21,o22,o23,o24,o25,o26,o27,o28,o29,o30,o31}, {a24,a25,a26,a27}, d14, p1, 1, 1, 1;\n"
        "wgmma.mma_async.sync.aligned.m64n32k16.f32.bf16.bf16 {o0,o1,o2,o3,o4,o5,o6,o7,o8,o9,o10,o11,o12,o13,o14,o15}, {a28,a29,a30,a31}, d7, p1, 1, 1, 1;\n"
        "wgmma.mma_async.sync.aligned.m64n32k16.f32.bf16.bf16 {o16,o17,o18,o19,o20,o21,o22,o23,o24,o25,o26,o27,o28,o29,o30,o31}, {a28,a29,a30,a31}, d15, p1, 1, 1, 1;\n"
        "wgmma.commit_group.sync.aligned;\n@nv bra.uni END;\nmovmatrix.sync.aligned.m8n8.trans.b16 b0, %32;\nmovmatrix.sync.aligned.m8n8.trans.b16 b1, %32;\n"
        "movmatrix.sync.aligned.m8n8.trans.b16 b2, %33;\nmovmatrix.sync.aligned.m8n8.trans.b16 b3, %33;\nmovmatrix.sync.aligned.m8n8.trans.b16 b4, %34;\n"
        "movmatrix.sync.aligned.m8n8.trans.b16 b5, %34;\nmovmatrix.sync.aligned.m8n8.trans.b16 b6, %35;\nmovmatrix.sync.aligned.m8n8.trans.b16 b7, %35;\n"
        "movmatrix.sync.aligned.m8n8.trans.b16 b8, %36;\nmovmatrix.sync.aligned.m8n8.trans.b16 b9, %36;\nmovmatrix.sync.aligned.m8n8.trans.b16 b10, %37;\n"
        "movmatrix.sync.aligned.m8n8.trans.b16 b11, %37;\nmovmatrix.sync.aligned.m8n8.trans.b16 b12, %38;\nmovmatrix.sync.aligned.m8n8.trans.b16 b13, %38;\n"
        "movmatrix.sync.aligned.m8n8.trans.b16 b14, %39;\nmovmatrix.sync.aligned.m8n8.trans.b16 b15, %39;\nmovmatrix.sync.aligned.m8n8.trans.b16 b16, %40;\n"
        "movmatrix.sync.aligned.m8n8.trans.b16 b17, %40;\nmovmatrix.sync.aligned.m8n8.trans.b16 b18, %41;\nmovmatrix.sync.aligned.m8n8.trans.b16 b19, %41;\n"
        "movmatrix.sync.aligned.m8n8.trans.b16 b20, %42;\nmovmatrix.sync.aligned.m8n8.trans.b16 b21, %42;\nmovmatrix.sync.aligned.m8n8.trans.b16 b22, %43;\n"
        "movmatrix.sync.aligned.m8n8.trans.b16 b23, %43;\nmovmatrix.sync.aligned.m8n8.trans.b16 b24, %44;\nmovmatrix.sync.aligned.m8n8.trans.b16 b25, %44;\n"
        "movmatrix.sync.aligned.m8n8.trans.b16 b26, %45;\nmovmatrix.sync.aligned.m8n8.trans.b16 b27, %45;\nmovmatrix.sync.aligned.m8n8.trans.b16 b28, %46;\n"
        "movmatrix.sync.aligned.m8n8.trans.b16 b29, %46;\nmovmatrix.sync.aligned.m8n8.trans.b16 b30, %47;\nmovmatrix.sync.aligned.m8n8.trans.b16 b31, %47;\n"
        "@nv bra.uni END;\nwgmma.wait_group.sync.aligned 0;\ncvt.rn.bf16x2.f32 k0, o1, o0;\ncvt.rn.bf16x2.f32 k1, o5, o4;\ncvt.rn.bf16x2.f32 k2, o9, o8;\n"
        "cvt.rn.bf16x2.f32 k3, o13, o12;\ncvt.rn.bf16x2.f32 k4, o3, o2;\ncvt.rn.bf16x2.f32 k5, o7, o6;\ncvt.rn.bf16x2.f32 k6, o11, o10;\n"
        "cvt.rn.bf16x2.f32 k7, o15, o14;\ncvt.rn.bf16x2.f32 k8, o17, o16;\ncvt.rn.bf16x2.f32 k9, o21, o20;\ncvt.rn.bf16x2.f32 k10, o25, o24;\n"
        "cvt.rn.bf16x2.f32 k11, o29, o28;\ncvt.rn.bf16x2.f32 k12, o19, o18;\ncvt.rn.bf16x2.f32 k13, o23, o22;\ncvt.rn.bf16x2.f32 k14, o27, o26;\n"
        "cvt.rn.bf16x2.f32 k15, o31, o30;\nld.volatile.shared.v2.b32 {c0,c1}, [%48+0];\nld.volatile.shared.v2.b32 {c2,c3}, [%48+4096];\n"
        "ld.volatile.shared.v2.b32 {c4,c5}, [%48+8];\nld.volatile.shared.v2.b32 {c6,c7}, [%48+4104];\ndp2a.lo.u32.u32 t, c0, 0x04000004, 0x200000;\n"
        "mov.b64 d0, {t, h};\ndp2a.hi.u32.u32 t, c0, 0x04000004, 0x200000;\nmov.b64 d1, {t, h};\ndp2a.lo.u32.u32 t, c1, 0x04000004, 0x200000;\n"
        "mov.b64 d2, {t, h};\ndp2a.hi.u32.u32 t, c1, 0x04000004, 0x200000;\nmov.b64 d3, {t, h};\ndp2a.lo.u32.u32 t, c2, 0x04000004, 0x200000;\n"
        "mov.b64 d4, {t, h};\ndp2a.hi.u32.u32 t, c2, 0x04000004, 0x200000;\nmov.b64 d5, {t, h};\ndp2a.lo.u32.u32 t, c3, 0x04000004, 0x200000;\n"
        "mov.b64 d6, {t, h};\ndp2a.hi.u32.u32 t, c3, 0x04000004, 0x200000;\nmov.b64 d7, {t, h};\ndp2a.lo.u32.u32 t, c4, 0x04000004, 0x200000;\n"
        "mov.b64 d8, {t, h};\ndp2a.hi.u32.u32 t, c4, 0x04000004, 0x200000;\nmov.b64 d9, {t, h};\ndp2a.lo.u32.u32 t, c5, 0x04000004, 0x200000;\n"
        "mov.b64 d10, {t, h};\ndp2a.hi.u32.u32 t, c5, 0x04000004, 0x200000;\nmov.b64 d11, {t, h};\ndp2a.lo.u32.u32 t, c6, 0x04000004, 0x200000;\n"
        "mov.b64 d12, {t, h};\ndp2a.hi.u32.u32 t, c6, 0x04000004, 0x200000;\nmov.b64 d13, {t, h};\ndp2a.lo.u32.u32 t, c7, 0x04000004, 0x200000;\n"
        "mov.b64 d14, {t, h};\ndp2a.hi.u32.u32 t, c7, 0x04000004, 0x200000;\nmov.b64 d15, {t, h};\nwgmma.fence.sync.aligned;\n"
        "wgmma.mma_async.sync.aligned.m64n32k16.f32.bf16.bf16 {o0,o1,o2,o3,o4,o5,o6,o7,o8,o9,o10,o11,o12,o13,o14,o15}, {b0,b1,b2,b3}, d0, p0, 1, 1, 1;\n"
        "wgmma.mma_async.sync.aligned.m64n32k16.f32.bf16.bf16 {o16,o17,o18,o19,o20,o21,o22,o23,o24,o25,o26,o27,o28,o29,o30,o31}, {b0,b1,b2,b3}, d8, p0, 1, 1, 1;\n"
        "wgmma.mma_async.sync.aligned.m64n32k16.f32.bf16.bf16 {o0,o1,o2,o3,o4,o5,o6,o7,o8,o9,o10,o11,o12,o13,o14,o15}, {b4,b5,b6,b7}, d1, p1, 1, 1, 1;\n"
        "wgmma.mma_async.sync.aligned.m64n32k16.f32.bf16.bf16 {o16,o17,o18,o19,o20,o21,o22,o23,o24,o25,o26,o27,o28,o29,o30,o31}, {b4,b5,b6,b7}, d9, p1, 1, 1, 1;\n"
        "wgmma.mma_async.sync.aligned.m64n32k16.f32.bf16.bf16 {o0,o1,o2,o3,o4,o5,o6,o7,o8,o9,o10,o11,o12,o13,o14,o15}, {b8,b9,b10,b11}, d2, p1, 1, 1, 1;\n"
        "wgmma.mma_async.sync.aligned.m64n32k16.f32.bf16.bf16 {o16,o17,o18,o19,o20,o21,o22,o23,o24,o25,o26,o27,o28,o29,o30,o31}, {b8,b9,b10,b11}, d10, p1, 1, 1, 1;\n"
        "wgmma.mma_async.sync.aligned.m64n32k16.f32.bf16.bf16 {o0,o1,o2,o3,o4,o5,o6,o7,o8,o9,o10,o11,o12,o13,o14,o15}, {b12,b13,b14,b15}, d3, p1, 1, 1, 1;\n"
        "wgmma.mma_async.sync.aligned.m64n32k16.f32.bf16.bf16 {o16,o17,o18,o19,o20,o21,o22,o23,o24,o25,o26,o27,o28,o29,o30,o31}, {b12,b13,b14,b15}, d11, p1, 1, 1, 1;\n"
        "wgmma.mma_async.sync.aligned.m64n32k16.f32.bf16.bf16 {o0,o1,o2,o3,o4,o5,o6,o7,o8,o9,o10,o11,o12,o13,o14,o15}, {b16,b17,b18,b19}, d4, p1, 1, 1, 1;\n"
        "wgmma.mma_async.sync.aligned.m64n32k16.f32.bf16.bf16 {o16,o17,o18,o19,o20,o21,o22,o23,o24,o25,o26,o27,o28,o29,o30,o31}, {b16,b17,b18,b19}, d12, p1, 1, 1, 1;\n"
        "wgmma.mma_async.sync.aligned.m64n32k16.f32.bf16.bf16 {o0,o1,o2,o3,o4,o5,o6,o7,o8,o9,o10,o11,o12,o13,o14,o15}, {b20,b21,b22,b23}, d5, p1, 1, 1, 1;\n"
        "wgmma.mma_async.sync.aligned.m64n32k16.f32.bf16.bf16 {o16,o17,o18,o19,o20,o21,o22,o23,o24,o25,o26,o27,o28,o29,o30,o31}, {b20,b21,b22,b23}, d13, p1, 1, 1, 1;\n"
        "wgmma.mma_async.sync.aligned.m64n32k16.f32.bf16.bf16 {o0,o1,o2,o3,o4,o5,o6,o7,o8,o9,o10,o11,o12,o13,o14,o15}, {b24,b25,b26,b27}, d6, p1, 1, 1, 1;\n"
        "wgmma.mma_async.sync.aligned.m64n32k16.f32.bf16.bf16 {o16,o17,o18,o19,o20,o21,o22,o23,o24,o25,o26,o27,o28,o29,o30,o31}, {b24,b25,b26,b27}, d14, p1, 1, 1, 1;\n"
        "wgmma.mma_async.sync.aligned.m64n32k16.f32.bf16.bf16 {o0,o1,o2,o3,o4,o5,o6,o7,o8,o9,o10,o11,o12,o13,o14,o15}, {b28,b29,b30,b31}, d7, p1, 1, 1, 1;\n"
        "wgmma.mma_async.sync.aligned.m64n32k16.f32.bf16.bf16 {o16,o17,o18,o19,o20,o21,o22,o23,o24,o25,o26,o27,o28,o29,o30,o31}, {b28,b29,b30,b31}, d15, p1, 1, 1, 1;\n"
        "wgmma.commit_group.sync.aligned;\n@nv bra.uni END;\n@s0 st.global.v4.b32 [%49+128], {k0,k1,k2,k3};\n@s1 st.global.v4.b32 [%50+128], {k4,k5,k6,k7};\n"
        "@s0 st.global.v4.b32 [%49+192], {k8,k9,k10,k11};\n@s1 st.global.v4.b32 [%50+192], {k12,k13,k14,k15};\n@nv bra.uni END;\n"
        "wgmma.wait_group.sync.aligned 0;\ncvt.rn.bf16x2.f32 k0, o1, o0;\ncvt.rn.bf16x2.f32 k1, o5, o4;\ncvt.rn.bf16x2.f32 k2, o9, o8;\n"
        "cvt.rn.bf16x2.f32 k3, o13, o12;\ncvt.rn.bf16x2.f32 k8, o17, o16;\ncvt.rn.bf16x2.f32 k9, o21, o20;\ncvt.rn.bf16x2.f32 k10, o25, o24;\n"
        "cvt.rn.bf16x2.f32 k11, o29, o28;\nld.volatile.shared.v2.b32 {c0,c1}, [%48+16];\nld.volatile.shared.v2.b32 {c2,c3}, [%48+4112];\n"
        "ld.volatile.shared.v2.b32 {c4,c5}, [%48+24];\nld.volatile.shared.v2.b32 {c6,c7}, [%48+4120];\ndp2a.lo.u32.u32 t, c0, 0x04000004, 0x200000;\n"
        "mov.b64 d0, {t, h};\ndp2a.hi.u32.u32 t, c0, 0x04000004, 0x200000;\nmov.b64 d1, {t, h};\ndp2a.lo.u32.u32 t, c1, 0x04000004, 0x200000;\n"
        "mov.b64 d2, {t, h};\ndp2a.hi.u32.u32 t, c1, 0x04000004, 0x200000;\nmov.b64 d3, {t, h};\ndp2a.lo.u32.u32 t, c2, 0x04000004, 0x200000;\n"
        "mov.b64 d4, {t, h};\ndp2a.hi.u32.u32 t, c2, 0x04000004, 0x200000;\nmov.b64 d5, {t, h};\ndp2a.lo.u32.u32 t, c3, 0x04000004, 0x200000;\n"
        "mov.b64 d6, {t, h};\ndp2a.hi.u32.u32 t, c3, 0x04000004, 0x200000;\nmov.b64 d7, {t, h};\ndp2a.lo.u32.u32 t, c4, 0x04000004, 0x200000;\n"
        "mov.b64 d8, {t, h};\ndp2a.hi.u32.u32 t, c4, 0x04000004, 0x200000;\nmov.b64 d9, {t, h};\ndp2a.lo.u32.u32 t, c5, 0x04000004, 0x200000;\n"
        "mov.b64 d10, {t, h};\ndp2a.hi.u32.u32 t, c5, 0x04000004, 0x200000;\nmov.b64 d11, {t, h};\ndp2a.lo.u32.u32 t, c6, 0x04000004, 0x200000;\n"
        "mov.b64 d12, {t, h};\ndp2a.hi.u32.u32 t, c6, 0x04000004, 0x200000;\nmov.b64 d13, {t, h};\ndp2a.lo.u32.u32 t, c7, 0x04000004, 0x200000;\n"
        "mov.b64 d14, {t, h};\ndp2a.hi.u32.u32 t, c7, 0x04000004, 0x200000;\nmov.b64 d15, {t, h};\nwgmma.fence.sync.aligned;\n"
        "wgmma.mma_async.sync.aligned.m64n32k16.f32.bf16.bf16 {o0,o1,o2,o3,o4,o5,o6,o7,o8,o9,o10,o11,o12,o13,o14,o15}, {b0,b1,b2,b3}, d0, p0, 1, 1, 1;\n"
        "wgmma.mma_async.sync.aligned.m64n32k16.f32.bf16.bf16 {o16,o17,o18,o19,o20,o21,o22,o23,o24,o25,o26,o27,o28,o29,o30,o31}, {b0,b1,b2,b3}, d8, p0, 1, 1, 1;\n"
        "wgmma.mma_async.sync.aligned.m64n32k16.f32.bf16.bf16 {o0,o1,o2,o3,o4,o5,o6,o7,o8,o9,o10,o11,o12,o13,o14,o15}, {b4,b5,b6,b7}, d1, p1, 1, 1, 1;\n"
        "wgmma.mma_async.sync.aligned.m64n32k16.f32.bf16.bf16 {o16,o17,o18,o19,o20,o21,o22,o23,o24,o25,o26,o27,o28,o29,o30,o31}, {b4,b5,b6,b7}, d9, p1, 1, 1, 1;\n"
        "wgmma.mma_async.sync.aligned.m64n32k16.f32.bf16.bf16 {o0,o1,o2,o3,o4,o5,o6,o7,o8,o9,o10,o11,o12,o13,o14,o15}, {b8,b9,b10,b11}, d2, p1, 1, 1, 1;\n"
        "wgmma.mma_async.sync.aligned.m64n32k16.f32.bf16.bf16 {o16,o17,o18,o19,o20,o21,o22,o23,o24,o25,o26,o27,o28,o29,o30,o31}, {b8,b9,b10,b11}, d10, p1, 1, 1, 1;\n"
        "wgmma.mma_async.sync.aligned.m64n32k16.f32.bf16.bf16 {o0,o1,o2,o3,o4,o5,o6,o7,o8,o9,o10,o11,o12,o13,o14,o15}, {b12,b13,b14,b15}, d3, p1, 1, 1, 1;\n"
        "wgmma.mma_async.sync.aligned.m64n32k16.f32.bf16.bf16 {o16,o17,o18,o19,o20,o21,o22,o23,o24,o25,o26,o27,o28,o29,o30,o31}, {b12,b13,b14,b15}, d11, p1, 1, 1, 1;\n"
        "wgmma.mma_async.sync.aligned.m64n32k16.f32.bf16.bf16 {o0,o1,o2,o3,o4,o5,o6,o7,o8,o9,o10,o11,o12,o13,o14,o15}, {b16,b17,b18,b19}, d4, p1, 1, 1, 1;\n"
        "wgmma.mma_async.sync.aligned.m64n32k16.f32.bf16.bf16 {o16,o17,o18,o19,o20,o21,o22,o23,o24,o25,o26,o27,o28,o29,o30,o31}, {b16,b17,b18,b19}, d12, p1, 1, 1, 1;\n"
        "wgmma.mma_async.sync.aligned.m64n32k16.f32.bf16.bf16 {o0,o1,o2,o3,o4,o5,o6,o7,o8,o9,o10,o11,o12,o13,o14,o15}, {b20,b21,b22,b23}, d5, p1, 1, 1, 1;\n"
        "wgmma.mma_async.sync.aligned.m64n32k16.f32.bf16.bf16 {o16,o17,o18,o19,o20,o21,o22,o23,o24,o25,o26,o27,o28,o29,o30,o31}, {b20,b21,b22,b23}, d13, p1, 1, 1, 1;\n"
        "wgmma.mma_async.sync.aligned.m64n32k16.f32.bf16.bf16 {o0,o1,o2,o3,o4,o5,o6,o7,o8,o9,o10,o11,o12,o13,o14,o15}, {b24,b25,b26,b27}, d6, p1, 1, 1, 1;\n"
        "wgmma.mma_async.sync.aligned.m64n32k16.f32.bf16.bf16 {o16,o17,o18,o19,o20,o21,o22,o23,o24,o25,o26,o27,o28,o29,o30,o31}, {b24,b25,b26,b27}, d14, p1, 1, 1, 1;\n"
        "wgmma.mma_async.sync.aligned.m64n32k16.f32.bf16.bf16 {o0,o1,o2,o3,o4,o5,o6,o7,o8,o9,o10,o11,o12,o13,o14,o15}, {b28,b29,b30,b31}, d7, p1, 1, 1, 1;\n"
        "wgmma.mma_async.sync.aligned.m64n32k16.f32.bf16.bf16 {o16,o17,o18,o19,o20,o21,o22,o23,o24,o25,o26,o27,o28,o29,o30,o31}, {b28,b29,b30,b31}, d15, p1, 1, 1, 1;\n"
        "wgmma.commit_group.sync.aligned;\n@nv bra.uni END;\n@s2 st.global.v4.b32 [%51+0], {k0,k1,k2,k3};\n@s2 st.global.v4.b32 [%51+64], {k8,k9,k10,k11};\n"
        "@nv bra.uni END;\nwgmma.wait_group.sync.aligned 0;\ncvt.rn.bf16x2.f32 k0, o1, o0;\ncvt.rn.bf16x2.f32 k1, o5, o4;\ncvt.rn.bf16x2.f32 k2, o9, o8;\n"
        "cvt.rn.bf16x2.f32 k3, o13, o12;\ncvt.rn.bf16x2.f32 k8, o17, o16;\ncvt.rn.bf16x2.f32 k9, o21, o20;\ncvt.rn.bf16x2.f32 k10, o25, o24;\n"
        "cvt.rn.bf16x2.f32 k11, o29, o28;\n@s2 st.global.v4.b32 [%51+128], {k0,k1,k2,k3};\n@s2 st.global.v4.b32 [%51+192], {k8,k9,k10,k11};\n"
        "END:\n}\n"
        ::"r"(pk[0]), "r"(pk[1]), "r"(pk[2]), "r"(pk[3]), "r"(pk[4]), "r"(pk[5]), "r"(pk[6]), "r"(pk[7]), "r"(pk[8]), "r"(pk[9]), "r"(pk[10]),
          "r"(pk[11]), "r"(pk[12]), "r"(pk[13]), "r"(pk[14]), "r"(pk[15]), "r"(pk[16]), "r"(pk[17]), "r"(pk[18]), "r"(pk[19]), "r"(pk[20]),
          "r"(pk[21]), "r"(pk[22]), "r"(pk[23]), "r"(pk[24]), "r"(pk[25]), "r"(pk[26]), "r"(pk[27]), "r"(pk[28]), "r"(pk[29]), "r"(pk[30]),
          "r"(pk[31]), "r"(pk[32]), "r"(pk[33]), "r"(pk[34]), "r"(pk[35]), "r"(pk[36]), "r"(pk[37]), "r"(pk[38]), "r"(pk[39]), "r"(pk[40]),
          "r"(pk[41]), "r"(pk[42]), "r"(pk[43]), "r"(pk[44]), "r"(pk[45]), "r"(pk[46]), "r"(pk[47]), "r"(ra), "l"(p[0]), "l"(p[1]), "l"(p[2]),
          "r"(v[0]), "r"(v[1]), "r"(v[2]), "r"(ba)
        : "memory");
}
__device__ __forceinline__ int cta_id() {
    int v;
    asm volatile("mov.u32 %0, %ctaid.x;" : "=r"(v));
    return v;
}
__device__ __forceinline__ int thread_id() {
    int v;
    asm volatile("mov.u32 %0, %tid.x;" : "=r"(v));
    return v;
}

__device__ __forceinline__ void slow_edge(int ee, int s, float* accn, const __nv_bfloat16* __restrict__ x,
                                          const __nv_bfloat16* __restrict__ sh, const __nv_bfloat16* __restrict__ ea,
                                          const __nv_bfloat16* __restrict__ cg, const __nv_bfloat16* __restrict__ wr,
                                          int lane) {
    float rwv[4] = {0.f, 0.f, 0.f, 0.f};
#pragma unroll 4
    for (int d = 0; d < 16; d++) {
        const float a = __bfloat162float(ea[(size_t)ee * 16 + d]);
        const uint2 wv = *(const uint2*)(wr + d * 128 + lane * 4);
        rwv[0] += a * __uint_as_float(wv.x << 16);
        rwv[1] += a * __uint_as_float(wv.x & 0xffff0000u);
        rwv[2] += a * __uint_as_float(wv.y << 16);
        rwv[3] += a * __uint_as_float(wv.y & 0xffff0000u);
    }
    float A = 0.f;
#pragma unroll
    for (int v = 0; v < 4; v++)
        A += __bfloat162float(cg[((lane >> 2) & 3) * 16 + v * 4 + (lane & 3)]) * __bfloat162float(sh[(size_t)ee * 4 + v]);
    float m[4][4];
#pragma unroll
    for (int w = 0; w < 4; w++)
#pragma unroll
        for (int j = 0; j < 4; j++) m[w][j] = 0.f;
#pragma unroll
    for (int u = 0; u < 4; u++) {
        const uint2 xv = *(const uint2*)(x + (size_t)s * 512 + u * 128 + lane * 4);
        const float x0 = __uint_as_float(xv.x << 16), x1 = __uint_as_float(xv.x & 0xffff0000u);
        const float x2 = __uint_as_float(xv.y << 16), x3 = __uint_as_float(xv.y & 0xffff0000u);
#pragma unroll
        for (int w = 0; w < 4; w++) {
            const float a = __shfl_sync(0xffffffffu, A, u * 4 + w);
            m[w][0] += a * x0;
            m[w][1] += a * x1;
            m[w][2] += a * x2;
            m[w][3] += a * x3;
        }
    }
#pragma unroll
    for (int w = 0; w < 4; w++)
#pragma unroll
        for (int j = 0; j < 4; j++) atomicAdd(accn + w * 128 + lane * 4 + j, m[w][j] * rwv[j]);
}

__device__ __forceinline__ void slow_out(const float* accn, const __nv_bfloat16* __restrict__ wout,
                                         __nv_bfloat16* __restrict__ outn, int lane) {
    float o[4][4];
#pragma unroll
    for (int w = 0; w < 4; w++)
#pragma unroll
        for (int j = 0; j < 4; j++) o[w][j] = 0.f;
#pragma unroll 2
    for (int c = 0; c < 128; c++) {
        const uint2 wv = *(const uint2*)(wout + c * 128 + lane * 4);
        const float w0 = __uint_as_float(wv.x << 16), w1 = __uint_as_float(wv.x & 0xffff0000u);
        const float w2 = __uint_as_float(wv.y << 16), w3 = __uint_as_float(wv.y & 0xffff0000u);
#pragma unroll
        for (int w = 0; w < 4; w++) {
            const float a = __bfloat162float(__float2bfloat16(accn[w * 128 + c]));
            o[w][0] += a * w0;
            o[w][1] += a * w1;
            o[w][2] += a * w2;
            o[w][3] += a * w3;
        }
    }
#pragma unroll
    for (int w = 0; w < 4; w++)
        *(uint2*)(outn + w * 128 + lane * 4) = make_uint2(pack_bf16(o[w][0], o[w][1]), pack_bf16(o[w][2], o[w][3]));
}

__device__ __forceinline__ void consume4(uint32_t (&pk)[64], const uint32_t (&w)[36], uint32_t olp, uint32_t xa, uint32_t ln,
                                      uint32_t lc, uint32_t linc, uint32_t lt, const __nv_bfloat16* ea, const __nv_bfloat16* sh, const void* wf, uint4 first) {
    ea += lt * 4, sh += lt & 2;
    asm volatile(
        "{\n.reg .pred p, q, psw, prdy, ps1, ps2, ps3, pz, pq, pt, pl;\n.reg .f32 d<40>, fz;\n"
        ".reg .b32 h<64>, x<32>, y<32>, ra<8>, rb<8>, bA0, bA1, bB0, bB1, c0, c1, c2, c3, e0, e1, s0, kept;\n"
        ".reg .b32 olp, v, vB, m, id, ida, bar, xb, pos, t0, t1, t2, t3, n, z<16>, kept2, g<4>, f0, f1, s1;\n.reg .b16 lo, hi, i16;\n.reg .b64 pa, pb;\n"
        "mov.f32 fz, 0f00000000;\nmov.b32 h0, 0;\nmov.b32 h1, 0;\nmov.b32 h2, 0;\nmov.b32 h3, 0;\nmov.b32 h4, 0;\nmov.b32 h5, 0;\nmov.b32 h6, 0;\n"
        "mov.b32 h7, 0;\nmov.b32 h8, 0;\nmov.b32 h9, 0;\nmov.b32 h10, 0;\nmov.b32 h11, 0;\nmov.b32 h12, 0;\nmov.b32 h13, 0;\nmov.b32 h14, 0;\nmov.b32 h15, 0;\n"
        "mov.b32 h16, 0;\nmov.b32 h17, 0;\nmov.b32 h18, 0;\nmov.b32 h19, 0;\nmov.b32 h20, 0;\nmov.b32 h21, 0;\nmov.b32 h22, 0;\nmov.b32 h23, 0;\n"
        "mov.b32 h24, 0;\nmov.b32 h25, 0;\nmov.b32 h26, 0;\nmov.b32 h27, 0;\nmov.b32 h28, 0;\nmov.b32 h29, 0;\nmov.b32 h30, 0;\nmov.b32 h31, 0;\n"
        "mov.b32 h32, 0;\nmov.b32 h33, 0;\nmov.b32 h34, 0;\nmov.b32 h35, 0;\nmov.b32 h36, 0;\nmov.b32 h37, 0;\nmov.b32 h38, 0;\nmov.b32 h39, 0;\n"
        "mov.b32 h40, 0;\nmov.b32 h41, 0;\nmov.b32 h42, 0;\nmov.b32 h43, 0;\nmov.b32 h44, 0;\nmov.b32 h45, 0;\nmov.b32 h46, 0;\nmov.b32 h47, 0;\n"
        "mov.b32 h48, 0;\nmov.b32 h49, 0;\nmov.b32 h50, 0;\nmov.b32 h51, 0;\nmov.b32 h52, 0;\nmov.b32 h53, 0;\nmov.b32 h54, 0;\nmov.b32 h55, 0;\n"
        "mov.b32 h56, 0;\nmov.b32 h57, 0;\nmov.b32 h58, 0;\nmov.b32 h59, 0;\nmov.b32 h60, 0;\nmov.b32 h61, 0;\nmov.b32 h62, 0;\nmov.b32 h63, 0;\n"
        "mov.b32 olp, %64;\nand.b32 t0, %66, 32;\nsetp.ne.u32 psw, t0, 0;\nsetp.eq.u32 pz, %64, 0;\nvote.sync.any.pred pz, pz, 0xffffffff;\nmov.b32 e0, %73;\n"
        "mov.b32 e1, %74;\nmov.b32 s0, %75;\nmov.b32 kept, %76;\nadd.u32 olp, olp, 4;\nsetp.ne.u64 p, %72, 0;\n@p fence.proxy.async.global;\n"
        "@p red.release.gpu.global.add.u32 [%72+12], 1;\nbar.warp.sync 0xffffffff;\nshfl.sync.idx.b32 v, kept, %67, 0x1f, 0xffffffff;\nor.b32 t3, %67, 4;\n"
        "shfl.sync.idx.b32 vB, kept, t3, 0x1f, 0xffffffff;\nld.shared.u16 t0, [olp];\nadd.u32 olp, olp, 4;\nlop3.b32 t1, t0, %66, 0x3ff0, 0xe4;\n"
        "ld.shared.b32 t1, [t1+%77];\nshr.u32 t2, t1, 1;\nlop3.b32 kept, t2, t0, 0xffe, 0xe4;\nlop3.b32 t2, t1, %67, 3, 0x80;\nsetp.ne.u32 pq, t2, 0;\n"
        "shr.u32 t2, t1, 13;\nmad.wide.u32 pa, t2, 32, %70;\nmad.wide.u32 pb, t2, 8, %71;\n"
        "RW:\nmma.sync.aligned.m16n8k8.row.col.f32.bf16.bf16.f32 {d0,d1,d2,d3}, {%114,%115}, {s0}, {fz,fz,fz,fz};\n"
        "mma.sync.aligned.m16n8k8.row.col.f32.bf16.bf16.f32 {d4,d5,d6,d7}, {%116,%117}, {s0}, {fz,fz,fz,fz};\ncvt.rn.bf16x2.f32 c0, d2, d0;\n"
        "cvt.rn.bf16x2.f32 c1, d3, d1;\ncvt.rn.bf16x2.f32 c2, d6, d4;\ncvt.rn.bf16x2.f32 c3, d7, d5;\nselp.b32 bA0, c2, c0, psw;\nselp.b32 bA1, c0, c2, psw;\n"
        "selp.b32 bB0, c3, c1, psw;\nselp.b32 bB1, c1, c3, psw;\n"
        "mma.sync.aligned.m16n8k16.row.col.f32.bf16.bf16.f32 {d0,d1,d2,d3}, {%82,%83,%84,%85}, {e0,e1}, {fz,fz,fz,fz};\ncvt.rn.bf16x2.f32 ra0, d2, d0;\n"
        "cvt.rn.bf16x2.f32 rb0, d3, d1;\nmma.sync.aligned.m16n8k16.row.col.f32.bf16.bf16.f32 {d4,d5,d6,d7}, {%86,%87,%88,%89}, {e0,e1}, {fz,fz,fz,fz};\n"
        "cvt.rn.bf16x2.f32 ra1, d6, d4;\ncvt.rn.bf16x2.f32 rb1, d7, d5;\n"
        "mma.sync.aligned.m16n8k16.row.col.f32.bf16.bf16.f32 {d8,d9,d10,d11}, {%90,%91,%92,%93}, {e0,e1}, {fz,fz,fz,fz};\ncvt.rn.bf16x2.f32 ra2, d10, d8;\n"
        "cvt.rn.bf16x2.f32 rb2, d11, d9;\nmma.sync.aligned.m16n8k16.row.col.f32.bf16.bf16.f32 {d12,d13,d14,d15}, {%94,%95,%96,%97}, {e0,e1}, {fz,fz,fz,fz};\n"
        "cvt.rn.bf16x2.f32 ra3, d14, d12;\ncvt.rn.bf16x2.f32 rb3, d15, d13;\n"
        "mma.sync.aligned.m16n8k16.row.col.f32.bf16.bf16.f32 {d16,d17,d18,d19}, {%98,%99,%100,%101}, {e0,e1}, {fz,fz,fz,fz};\ncvt.rn.bf16x2.f32 ra4, d18, d16;\n"
        "cvt.rn.bf16x2.f32 rb4, d19, d17;\n"
        "mma.sync.aligned.m16n8k16.row.col.f32.bf16.bf16.f32 {d20,d21,d22,d23}, {%102,%103,%104,%105}, {e0,e1}, {fz,fz,fz,fz};\n"
        "cvt.rn.bf16x2.f32 ra5, d22, d20;\ncvt.rn.bf16x2.f32 rb5, d23, d21;\n"
        "mma.sync.aligned.m16n8k16.row.col.f32.bf16.bf16.f32 {d24,d25,d26,d27}, {%106,%107,%108,%109}, {e0,e1}, {fz,fz,fz,fz};\n"
        "cvt.rn.bf16x2.f32 ra6, d26, d24;\ncvt.rn.bf16x2.f32 rb6, d27, d25;\n"
        "mma.sync.aligned.m16n8k16.row.col.f32.bf16.bf16.f32 {d28,d29,d30,d31}, {%110,%111,%112,%113}, {e0,e1}, {fz,fz,fz,fz};\n"
        "cvt.rn.bf16x2.f32 ra7, d30, d28;\ncvt.rn.bf16x2.f32 rb7, d31, d29;\nmov.b32 s0, 0;\nld.global.cg.L2::128B.v2.b32 {e0,e1}, [pa];\n"
        "@pq ld.global.cg.L2::128B.b32 s0, [pb];\nand.b32 bar, v, 0xff8;\nmbarrier.test_wait.parity.shared.b64 pl, [bar+%79], 0;\n"
        "lop3.b32 ida, v, %67, 0xfff, 0xe4;\nld.volatile.shared.u16 id, [ida+%78];\nvote.sync.all.pred prdy, pl, 0xffffffff;\n@!prdy bra.uni WA;\n"
        "HA:\nmad.lo.u32 xb, id, 64, %65;\ncvt.u16.u32 i16, id;\natom.shared.add.u32 pos, [%66+%80], %68;\n"
        "ldmatrix.sync.aligned.m8n8.x4.trans.shared.b16 {x0,x1,x2,x3}, [xb];\nldmatrix.sync.aligned.m8n8.x4.trans.shared.b16 {x24,x25,x26,x27}, [xb+512];\n"
        "xor.b32 t1, xb, 32;\nldmatrix.sync.aligned.m8n8.x4.trans.shared.b16 {x4,x5,x6,x7}, [t1];\n"
        "ldmatrix.sync.aligned.m8n8.x4.trans.shared.b16 {x28,x29,x30,x31}, [t1+512];\nxor.b32 t1, xb, 64;\n"
        "ldmatrix.sync.aligned.m8n8.x4.trans.shared.b16 {x8,x9,x10,x11}, [t1];\nldmatrix.sync.aligned.m8n8.x4.trans.shared.b16 {x16,x17,x18,x19}, [t1+512];\n"
        "xor.b32 t1, xb, 96;\nldmatrix.sync.aligned.m8n8.x4.trans.shared.b16 {x12,x13,x14,x15}, [t1];\n"
        "ldmatrix.sync.aligned.m8n8.x4.trans.shared.b16 {x20,x21,x22,x23}, [t1+512];\nst.volatile.shared.u16 [pos], i16;\nand.b32 t0, v, 16384;\n"
        "setp.ne.u32 ps1, t0, 0;\nvote.sync.any.pred ps1, ps1, 0xffffffff;\nand.b32 t0, v, 32768;\nsetp.ne.u32 ps2, t0, 0;\n"
        "vote.sync.any.pred ps2, ps2, 0xffffffff;\nmov.b32 v, vB;\nand.b32 bar, v, 0xff8;\nmbarrier.test_wait.parity.shared.b64 pl, [bar+%79], 0;\n"
        "lop3.b32 ida, v, %67, 0xfff, 0xe4;\nld.volatile.shared.u16 id, [ida+%78];\nvote.sync.all.pred prdy, pl, 0xffffffff;\nmov.b32 {lo, hi}, ra0;\n"
        "mov.b32 t2, {lo, lo};\nmul.rn.bf16x2 y0, x0, t2;\nmul.rn.bf16x2 y2, x2, t2;\nmov.b32 t2, {hi, hi};\nmul.rn.bf16x2 y1, x1, t2;\n"
        "mul.rn.bf16x2 y3, x3, t2;\nmma.sync.aligned.m16n8k16.row.col.f32.bf16.bf16.f32 {d0,d1,d2,d3}, {y0,y1,y2,y3}, {bA0,bA1}, {fz,fz,fz,fz};\n"
        "cvt.rn.bf16x2.f32 z0, d1, d0;\ncvt.rn.bf16x2.f32 z1, d3, d2;\nmov.b32 {lo, hi}, ra6;\nmov.b32 t2, {lo, lo};\nmul.rn.bf16x2 y24, x24, t2;\n"
        "mul.rn.bf16x2 y26, x26, t2;\nmov.b32 t2, {hi, hi};\nmul.rn.bf16x2 y25, x25, t2;\nmul.rn.bf16x2 y27, x27, t2;\n"
        "mma.sync.aligned.m16n8k16.row.col.f32.bf16.bf16.f32 {d24,d25,d26,d27}, {y24,y25,y26,y27}, {bA0,bA1}, {fz,fz,fz,fz};\ncvt.rn.bf16x2.f32 z12, d25, d24;\n"
        "cvt.rn.bf16x2.f32 z13, d27, d26;\nmov.b32 {lo, hi}, ra1;\nmov.b32 t2, {lo, lo};\nmul.rn.bf16x2 y4, x4, t2;\nmul.rn.bf16x2 y6, x6, t2;\n"
        "mov.b32 t2, {hi, hi};\nmul.rn.bf16x2 y5, x5, t2;\nmul.rn.bf16x2 y7, x7, t2;\n"
        "mma.sync.aligned.m16n8k16.row.col.f32.bf16.bf16.f32 {d4,d5,d6,d7}, {y4,y5,y6,y7}, {bA0,bA1}, {fz,fz,fz,fz};\ncvt.rn.bf16x2.f32 z2, d5, d4;\n"
        "cvt.rn.bf16x2.f32 z3, d7, d6;\nmov.b32 {lo, hi}, ra7;\nmov.b32 t2, {lo, lo};\nmul.rn.bf16x2 y28, x28, t2;\nmul.rn.bf16x2 y30, x30, t2;\n"
        "mov.b32 t2, {hi, hi};\nmul.rn.bf16x2 y29, x29, t2;\nmul.rn.bf16x2 y31, x31, t2;\n"
        "mma.sync.aligned.m16n8k16.row.col.f32.bf16.bf16.f32 {d28,d29,d30,d31}, {y28,y29,y30,y31}, {bA0,bA1}, {fz,fz,fz,fz};\ncvt.rn.bf16x2.f32 z14, d29, d28;\n"
        "cvt.rn.bf16x2.f32 z15, d31, d30;\nmov.b32 {lo, hi}, ra2;\nmov.b32 t2, {lo, lo};\nmul.rn.bf16x2 y8, x8, t2;\nmul.rn.bf16x2 y10, x10, t2;\n"
        "mov.b32 t2, {hi, hi};\nmul.rn.bf16x2 y9, x9, t2;\nmul.rn.bf16x2 y11, x11, t2;\n"
        "mma.sync.aligned.m16n8k16.row.col.f32.bf16.bf16.f32 {d8,d9,d10,d11}, {y8,y9,y10,y11}, {bA0,bA1}, {fz,fz,fz,fz};\ncvt.rn.bf16x2.f32 z4, d9, d8;\n"
        "cvt.rn.bf16x2.f32 z5, d11, d10;\nmov.b32 {lo, hi}, ra4;\nmov.b32 t2, {lo, lo};\nmul.rn.bf16x2 y16, x16, t2;\nmul.rn.bf16x2 y18, x18, t2;\n"
        "mov.b32 t2, {hi, hi};\nmul.rn.bf16x2 y17, x17, t2;\nmul.rn.bf16x2 y19, x19, t2;\n"
        "mma.sync.aligned.m16n8k16.row.col.f32.bf16.bf16.f32 {d16,d17,d18,d19}, {y16,y17,y18,y19}, {bA0,bA1}, {fz,fz,fz,fz};\ncvt.rn.bf16x2.f32 z8, d17, d16;\n"
        "cvt.rn.bf16x2.f32 z9, d19, d18;\nmov.b32 {lo, hi}, ra3;\nmov.b32 t2, {lo, lo};\nmul.rn.bf16x2 y12, x12, t2;\nmul.rn.bf16x2 y14, x14, t2;\n"
        "mov.b32 t2, {hi, hi};\nmul.rn.bf16x2 y13, x13, t2;\nmul.rn.bf16x2 y15, x15, t2;\n"
        "mma.sync.aligned.m16n8k16.row.col.f32.bf16.bf16.f32 {d12,d13,d14,d15}, {y12,y13,y14,y15}, {bA0,bA1}, {fz,fz,fz,fz};\ncvt.rn.bf16x2.f32 z6, d13, d12;\n"
        "cvt.rn.bf16x2.f32 z7, d15, d14;\nmov.b32 {lo, hi}, ra5;\nmov.b32 t2, {lo, lo};\nmul.rn.bf16x2 y20, x20, t2;\nmul.rn.bf16x2 y22, x22, t2;\n"
        "mov.b32 t2, {hi, hi};\nmul.rn.bf16x2 y21, x21, t2;\nmul.rn.bf16x2 y23, x23, t2;\n"
        "mma.sync.aligned.m16n8k16.row.col.f32.bf16.bf16.f32 {d20,d21,d22,d23}, {y20,y21,y22,y23}, {bA0,bA1}, {fz,fz,fz,fz};\ncvt.rn.bf16x2.f32 z10, d21, d20;\n"
        "cvt.rn.bf16x2.f32 z11, d23, d22;\n@ps2 bra.uni TA2;\n@ps1 bra.uni TA1;\n"
        "TA0:\nadd.rn.bf16x2 h0, h0, z0;\nadd.rn.bf16x2 h1, h1, z1;\nadd.rn.bf16x2 h2, h2, z2;\nadd.rn.bf16x2 h3, h3, z3;\nadd.rn.bf16x2 h4, h4, z4;\n"
        "add.rn.bf16x2 h5, h5, z5;\nadd.rn.bf16x2 h6, h6, z6;\nadd.rn.bf16x2 h7, h7, z7;\nadd.rn.bf16x2 h8, h8, z8;\nadd.rn.bf16x2 h9, h9, z9;\n"
        "add.rn.bf16x2 h10, h10, z10;\nadd.rn.bf16x2 h11, h11, z11;\nadd.rn.bf16x2 h12, h12, z12;\nadd.rn.bf16x2 h13, h13, z13;\nadd.rn.bf16x2 h14, h14, z14;\n"
        "add.rn.bf16x2 h15, h15, z15;\n@prdy bra.uni HB;\nbra.uni WB;\n"
        "TA1:\nadd.rn.bf16x2 h16, h16, z0;\nadd.rn.bf16x2 h17, h17, z1;\nadd.rn.bf16x2 h18, h18, z2;\nadd.rn.bf16x2 h19, h19, z3;\nadd.rn.bf16x2 h20, h20, z4;\n"
        "add.rn.bf16x2 h21, h21, z5;\nadd.rn.bf16x2 h22, h22, z6;\nadd.rn.bf16x2 h23, h23, z7;\nadd.rn.bf16x2 h24, h24, z8;\nadd.rn.bf16x2 h25, h25, z9;\n"
        "add.rn.bf16x2 h26, h26, z10;\nadd.rn.bf16x2 h27, h27, z11;\nadd.rn.bf16x2 h28, h28, z12;\nadd.rn.bf16x2 h29, h29, z13;\nadd.rn.bf16x2 h30, h30, z14;\n"
        "add.rn.bf16x2 h31, h31, z15;\n@prdy bra.uni HB;\nbra.uni WB;\n"
        "TA2:\n@ps1 bra.uni TA3;\nadd.rn.bf16x2 h32, h32, z0;\nadd.rn.bf16x2 h33, h33, z1;\nadd.rn.bf16x2 h34, h34, z2;\nadd.rn.bf16x2 h35, h35, z3;\n"
        "add.rn.bf16x2 h36, h36, z4;\nadd.rn.bf16x2 h37, h37, z5;\nadd.rn.bf16x2 h38, h38, z6;\nadd.rn.bf16x2 h39, h39, z7;\nadd.rn.bf16x2 h40, h40, z8;\n"
        "add.rn.bf16x2 h41, h41, z9;\nadd.rn.bf16x2 h42, h42, z10;\nadd.rn.bf16x2 h43, h43, z11;\nadd.rn.bf16x2 h44, h44, z12;\nadd.rn.bf16x2 h45, h45, z13;\n"
        "add.rn.bf16x2 h46, h46, z14;\nadd.rn.bf16x2 h47, h47, z15;\n@prdy bra.uni HB;\nbra.uni WB;\n"
        "TA3:\nadd.rn.bf16x2 h48, h48, z0;\nadd.rn.bf16x2 h49, h49, z1;\nadd.rn.bf16x2 h50, h50, z2;\nadd.rn.bf16x2 h51, h51, z3;\nadd.rn.bf16x2 h52, h52, z4;\n"
        "add.rn.bf16x2 h53, h53, z5;\nadd.rn.bf16x2 h54, h54, z6;\nadd.rn.bf16x2 h55, h55, z7;\nadd.rn.bf16x2 h56, h56, z8;\nadd.rn.bf16x2 h57, h57, z9;\n"
        "add.rn.bf16x2 h58, h58, z10;\nadd.rn.bf16x2 h59, h59, z11;\nadd.rn.bf16x2 h60, h60, z12;\nadd.rn.bf16x2 h61, h61, z13;\nadd.rn.bf16x2 h62, h62, z14;\n"
        "add.rn.bf16x2 h63, h63, z15;\n@prdy bra.uni HB;\nbra.uni WB;\n"
        "HB:\nmad.lo.u32 xb, id, 64, %65;\ncvt.u16.u32 i16, id;\natom.shared.add.u32 pos, [%66+%80], %68;\n"
        "ldmatrix.sync.aligned.m8n8.x4.trans.shared.b16 {x0,x1,x2,x3}, [xb];\nldmatrix.sync.aligned.m8n8.x4.trans.shared.b16 {x24,x25,x26,x27}, [xb+512];\n"
        "xor.b32 t1, xb, 32;\nldmatrix.sync.aligned.m8n8.x4.trans.shared.b16 {x4,x5,x6,x7}, [t1];\n"
        "ldmatrix.sync.aligned.m8n8.x4.trans.shared.b16 {x28,x29,x30,x31}, [t1+512];\nxor.b32 t1, xb, 64;\n"
        "ldmatrix.sync.aligned.m8n8.x4.trans.shared.b16 {x8,x9,x10,x11}, [t1];\nldmatrix.sync.aligned.m8n8.x4.trans.shared.b16 {x16,x17,x18,x19}, [t1+512];\n"
        "xor.b32 t1, xb, 96;\nldmatrix.sync.aligned.m8n8.x4.trans.shared.b16 {x12,x13,x14,x15}, [t1];\n"
        "ldmatrix.sync.aligned.m8n8.x4.trans.shared.b16 {x20,x21,x22,x23}, [t1+512];\nst.volatile.shared.u16 [pos], i16;\nand.b32 t0, v, 16384;\n"
        "setp.ne.u32 ps1, t0, 0;\nvote.sync.any.pred ps1, ps1, 0xffffffff;\nand.b32 t0, v, 32768;\nsetp.ne.u32 ps2, t0, 0;\n"
        "vote.sync.any.pred ps2, ps2, 0xffffffff;\nshfl.sync.idx.b32 v, kept, %67, 0x1f, 0xffffffff;\nor.b32 t3, %67, 4;\n"
        "shfl.sync.idx.b32 vB, kept, t3, 0x1f, 0xffffffff;\nld.shared.u16 t0, [olp];\nadd.u32 olp, olp, 4;\nlop3.b32 t1, t0, %66, 0x3ff0, 0xe4;\n"
        "ld.shared.b32 t1, [t1+%77];\nshr.u32 t2, t1, 1;\nlop3.b32 kept, t2, t0, 0xffe, 0xe4;\nlop3.b32 t2, t1, %67, 3, 0x80;\nsetp.ne.u32 pq, t2, 0;\n"
        "shr.u32 t2, t1, 13;\nmad.wide.u32 pa, t2, 32, %70;\nmad.wide.u32 pb, t2, 8, %71;\nmov.b32 {lo, hi}, rb0;\nmov.b32 t2, {lo, lo};\n"
        "mul.rn.bf16x2 y0, x0, t2;\nmul.rn.bf16x2 y2, x2, t2;\nmov.b32 t2, {hi, hi};\nmul.rn.bf16x2 y1, x1, t2;\nmul.rn.bf16x2 y3, x3, t2;\n"
        "mma.sync.aligned.m16n8k16.row.col.f32.bf16.bf16.f32 {d0,d1,d2,d3}, {y0,y1,y2,y3}, {bB0,bB1}, {fz,fz,fz,fz};\ncvt.rn.bf16x2.f32 z0, d1, d0;\n"
        "cvt.rn.bf16x2.f32 z1, d3, d2;\nmov.b32 {lo, hi}, rb6;\nmov.b32 t2, {lo, lo};\nmul.rn.bf16x2 y24, x24, t2;\nmul.rn.bf16x2 y26, x26, t2;\n"
        "mov.b32 t2, {hi, hi};\nmul.rn.bf16x2 y25, x25, t2;\nmul.rn.bf16x2 y27, x27, t2;\n"
        "mma.sync.aligned.m16n8k16.row.col.f32.bf16.bf16.f32 {d24,d25,d26,d27}, {y24,y25,y26,y27}, {bB0,bB1}, {fz,fz,fz,fz};\ncvt.rn.bf16x2.f32 z12, d25, d24;\n"
        "cvt.rn.bf16x2.f32 z13, d27, d26;\nmov.b32 {lo, hi}, rb1;\nmov.b32 t2, {lo, lo};\nmul.rn.bf16x2 y4, x4, t2;\nmul.rn.bf16x2 y6, x6, t2;\n"
        "mov.b32 t2, {hi, hi};\nmul.rn.bf16x2 y5, x5, t2;\nmul.rn.bf16x2 y7, x7, t2;\n"
        "mma.sync.aligned.m16n8k16.row.col.f32.bf16.bf16.f32 {d4,d5,d6,d7}, {y4,y5,y6,y7}, {bB0,bB1}, {fz,fz,fz,fz};\ncvt.rn.bf16x2.f32 z2, d5, d4;\n"
        "cvt.rn.bf16x2.f32 z3, d7, d6;\nmov.b32 {lo, hi}, rb7;\nmov.b32 t2, {lo, lo};\nmul.rn.bf16x2 y28, x28, t2;\nmul.rn.bf16x2 y30, x30, t2;\n"
        "mov.b32 t2, {hi, hi};\nmul.rn.bf16x2 y29, x29, t2;\nmul.rn.bf16x2 y31, x31, t2;\n"
        "mma.sync.aligned.m16n8k16.row.col.f32.bf16.bf16.f32 {d28,d29,d30,d31}, {y28,y29,y30,y31}, {bB0,bB1}, {fz,fz,fz,fz};\ncvt.rn.bf16x2.f32 z14, d29, d28;\n"
        "cvt.rn.bf16x2.f32 z15, d31, d30;\nmov.b32 {lo, hi}, rb2;\nmov.b32 t2, {lo, lo};\nmul.rn.bf16x2 y8, x8, t2;\nmul.rn.bf16x2 y10, x10, t2;\n"
        "mov.b32 t2, {hi, hi};\nmul.rn.bf16x2 y9, x9, t2;\nmul.rn.bf16x2 y11, x11, t2;\n"
        "mma.sync.aligned.m16n8k16.row.col.f32.bf16.bf16.f32 {d8,d9,d10,d11}, {y8,y9,y10,y11}, {bB0,bB1}, {fz,fz,fz,fz};\ncvt.rn.bf16x2.f32 z4, d9, d8;\n"
        "cvt.rn.bf16x2.f32 z5, d11, d10;\nmov.b32 {lo, hi}, rb4;\nmov.b32 t2, {lo, lo};\nmul.rn.bf16x2 y16, x16, t2;\nmul.rn.bf16x2 y18, x18, t2;\n"
        "mov.b32 t2, {hi, hi};\nmul.rn.bf16x2 y17, x17, t2;\nmul.rn.bf16x2 y19, x19, t2;\n"
        "mma.sync.aligned.m16n8k16.row.col.f32.bf16.bf16.f32 {d16,d17,d18,d19}, {y16,y17,y18,y19}, {bB0,bB1}, {fz,fz,fz,fz};\ncvt.rn.bf16x2.f32 z8, d17, d16;\n"
        "cvt.rn.bf16x2.f32 z9, d19, d18;\nmov.b32 {lo, hi}, rb3;\nmov.b32 t2, {lo, lo};\nmul.rn.bf16x2 y12, x12, t2;\nmul.rn.bf16x2 y14, x14, t2;\n"
        "mov.b32 t2, {hi, hi};\nmul.rn.bf16x2 y13, x13, t2;\nmul.rn.bf16x2 y15, x15, t2;\n"
        "mma.sync.aligned.m16n8k16.row.col.f32.bf16.bf16.f32 {d12,d13,d14,d15}, {y12,y13,y14,y15}, {bB0,bB1}, {fz,fz,fz,fz};\ncvt.rn.bf16x2.f32 z6, d13, d12;\n"
        "cvt.rn.bf16x2.f32 z7, d15, d14;\nmov.b32 {lo, hi}, rb5;\nmov.b32 t2, {lo, lo};\nmul.rn.bf16x2 y20, x20, t2;\nmul.rn.bf16x2 y22, x22, t2;\n"
        "mov.b32 t2, {hi, hi};\nmul.rn.bf16x2 y21, x21, t2;\nmul.rn.bf16x2 y23, x23, t2;\n"
        "mma.sync.aligned.m16n8k16.row.col.f32.bf16.bf16.f32 {d20,d21,d22,d23}, {y20,y21,y22,y23}, {bB0,bB1}, {fz,fz,fz,fz};\ncvt.rn.bf16x2.f32 z10, d21, d20;\n"
        "cvt.rn.bf16x2.f32 z11, d23, d22;\n@ps2 bra.uni TB2;\n@ps1 bra.uni TB1;\n"
        "TB0:\nadd.rn.bf16x2 h0, h0, z0;\nadd.rn.bf16x2 h1, h1, z1;\nadd.rn.bf16x2 h2, h2, z2;\nadd.rn.bf16x2 h3, h3, z3;\nadd.rn.bf16x2 h4, h4, z4;\n"
        "add.rn.bf16x2 h5, h5, z5;\nadd.rn.bf16x2 h6, h6, z6;\nadd.rn.bf16x2 h7, h7, z7;\nadd.rn.bf16x2 h8, h8, z8;\nadd.rn.bf16x2 h9, h9, z9;\n"
        "add.rn.bf16x2 h10, h10, z10;\nadd.rn.bf16x2 h11, h11, z11;\nadd.rn.bf16x2 h12, h12, z12;\nadd.rn.bf16x2 h13, h13, z13;\nadd.rn.bf16x2 h14, h14, z14;\n"
        "add.rn.bf16x2 h15, h15, z15;\nbra.uni RW;\n"
        "TB1:\nadd.rn.bf16x2 h16, h16, z0;\nadd.rn.bf16x2 h17, h17, z1;\nadd.rn.bf16x2 h18, h18, z2;\nadd.rn.bf16x2 h19, h19, z3;\nadd.rn.bf16x2 h20, h20, z4;\n"
        "add.rn.bf16x2 h21, h21, z5;\nadd.rn.bf16x2 h22, h22, z6;\nadd.rn.bf16x2 h23, h23, z7;\nadd.rn.bf16x2 h24, h24, z8;\nadd.rn.bf16x2 h25, h25, z9;\n"
        "add.rn.bf16x2 h26, h26, z10;\nadd.rn.bf16x2 h27, h27, z11;\nadd.rn.bf16x2 h28, h28, z12;\nadd.rn.bf16x2 h29, h29, z13;\nadd.rn.bf16x2 h30, h30, z14;\n"
        "add.rn.bf16x2 h31, h31, z15;\nbra.uni RW;\n"
        "TB2:\n@ps1 bra.uni TB3;\nadd.rn.bf16x2 h32, h32, z0;\nadd.rn.bf16x2 h33, h33, z1;\nadd.rn.bf16x2 h34, h34, z2;\nadd.rn.bf16x2 h35, h35, z3;\n"
        "add.rn.bf16x2 h36, h36, z4;\nadd.rn.bf16x2 h37, h37, z5;\nadd.rn.bf16x2 h38, h38, z6;\nadd.rn.bf16x2 h39, h39, z7;\nadd.rn.bf16x2 h40, h40, z8;\n"
        "add.rn.bf16x2 h41, h41, z9;\nadd.rn.bf16x2 h42, h42, z10;\nadd.rn.bf16x2 h43, h43, z11;\nadd.rn.bf16x2 h44, h44, z12;\nadd.rn.bf16x2 h45, h45, z13;\n"
        "add.rn.bf16x2 h46, h46, z14;\nadd.rn.bf16x2 h47, h47, z15;\nbra.uni RW;\n"
        "TB3:\nadd.rn.bf16x2 h48, h48, z0;\nadd.rn.bf16x2 h49, h49, z1;\nadd.rn.bf16x2 h50, h50, z2;\nadd.rn.bf16x2 h51, h51, z3;\nadd.rn.bf16x2 h52, h52, z4;\n"
        "add.rn.bf16x2 h53, h53, z5;\nadd.rn.bf16x2 h54, h54, z6;\nadd.rn.bf16x2 h55, h55, z7;\nadd.rn.bf16x2 h56, h56, z8;\nadd.rn.bf16x2 h57, h57, z9;\n"
        "add.rn.bf16x2 h58, h58, z10;\nadd.rn.bf16x2 h59, h59, z11;\nadd.rn.bf16x2 h60, h60, z12;\nadd.rn.bf16x2 h61, h61, z13;\nadd.rn.bf16x2 h62, h62, z14;\n"
        "add.rn.bf16x2 h63, h63, z15;\nbra.uni RW;\n"
        "WA:\nand.b32 t2, v, 0xff8;\nredux.sync.max.u32 t1, t2, 0xffffffff;\nmov.b32 n, 0;\nsetp.eq.u32 p, t1, 0;\n@p bra.uni DONE;\n"
        "WA3:\nmbarrier.try_wait.parity.shared.b64 p, [t1+%79], 0;\n@!p bra.uni WA4;\nmbarrier.test_wait.parity.shared.b64 p, [t2+%79], 0;\n"
        "lop3.b32 ida, v, %67, 0xfff, 0xe4;\nld.volatile.shared.u16 id, [ida+%78];\nvote.sync.all.pred p, p, 0xffffffff;\n@p bra.uni HA;\n"
        "WA4:\nadd.u32 n, n, 1;\nsetp.lt.u32 q, n, 1000000;\n@q bra.uni WA3;\nbra.uni DONE;\n"
        "WB:\nand.b32 t2, v, 0xff8;\nredux.sync.max.u32 t1, t2, 0xffffffff;\nmov.b32 n, 0;\nsetp.eq.u32 p, t1, 0;\n@p bra.uni DONE;\n"
        "WB3:\nmbarrier.try_wait.parity.shared.b64 p, [t1+%79], 0;\n@!p bra.uni WB4;\nmbarrier.test_wait.parity.shared.b64 p, [t2+%79], 0;\n"
        "lop3.b32 ida, v, %67, 0xfff, 0xe4;\nld.volatile.shared.u16 id, [ida+%78];\nvote.sync.all.pred p, p, 0xffffffff;\n@p bra.uni HB;\n"
        "WB4:\nadd.u32 n, n, 1;\nsetp.lt.u32 q, n, 1000000;\n@q bra.uni WB3;\nbra.uni DONE;\n"
        "DONE:\nmov.b32 %0, h0;\nmov.b32 %1, h1;\nmov.b32 %2, h2;\nmov.b32 %3, h3;\nmov.b32 %4, h4;\nmov.b32 %5, h5;\nmov.b32 %6, h6;\nmov.b32 %7, h7;\n"
        "mov.b32 %8, h8;\nmov.b32 %9, h9;\nmov.b32 %10, h10;\nmov.b32 %11, h11;\nmov.b32 %12, h12;\nmov.b32 %13, h13;\nmov.b32 %14, h14;\nmov.b32 %15, h15;\n"
        "mov.b32 %16, h16;\nmov.b32 %17, h17;\nmov.b32 %18, h18;\nmov.b32 %19, h19;\nmov.b32 %20, h20;\nmov.b32 %21, h21;\nmov.b32 %22, h22;\nmov.b32 %23, h23;\n"
        "mov.b32 %24, h24;\nmov.b32 %25, h25;\nmov.b32 %26, h26;\nmov.b32 %27, h27;\nmov.b32 %28, h28;\nmov.b32 %29, h29;\nmov.b32 %30, h30;\nmov.b32 %31, h31;\n"
        "mov.b32 %32, h32;\nmov.b32 %33, h33;\nmov.b32 %34, h34;\nmov.b32 %35, h35;\nmov.b32 %36, h36;\nmov.b32 %37, h37;\nmov.b32 %38, h38;\nmov.b32 %39, h39;\n"
        "mov.b32 %40, h40;\nmov.b32 %41, h41;\nmov.b32 %42, h42;\nmov.b32 %43, h43;\nmov.b32 %44, h44;\nmov.b32 %45, h45;\nmov.b32 %46, h46;\nmov.b32 %47, h47;\n"
        "mov.b32 %48, h48;\nmov.b32 %49, h49;\nmov.b32 %50, h50;\nmov.b32 %51, h51;\nmov.b32 %52, h52;\nmov.b32 %53, h53;\nmov.b32 %54, h54;\nmov.b32 %55, h55;\n"
        "mov.b32 %56, h56;\nmov.b32 %57, h57;\nmov.b32 %58, h58;\nmov.b32 %59, h59;\nmov.b32 %60, h60;\nmov.b32 %61, h61;\nmov.b32 %62, h62;\nmov.b32 %63, h63;\n"
        "}\n"
        : "=r"(pk[0]), "=r"(pk[1]), "=r"(pk[2]), "=r"(pk[3]), "=r"(pk[4]), "=r"(pk[5]), "=r"(pk[6]), "=r"(pk[7]), "=r"(pk[8]), "=r"(pk[9]),
          "=r"(pk[10]), "=r"(pk[11]), "=r"(pk[12]), "=r"(pk[13]), "=r"(pk[14]), "=r"(pk[15]), "=r"(pk[16]), "=r"(pk[17]), "=r"(pk[18]), "=r"(pk[19]),
          "=r"(pk[20]), "=r"(pk[21]), "=r"(pk[22]), "=r"(pk[23]), "=r"(pk[24]), "=r"(pk[25]), "=r"(pk[26]), "=r"(pk[27]), "=r"(pk[28]), "=r"(pk[29]),
          "=r"(pk[30]), "=r"(pk[31]), "=r"(pk[32]), "=r"(pk[33]), "=r"(pk[34]), "=r"(pk[35]), "=r"(pk[36]), "=r"(pk[37]), "=r"(pk[38]), "=r"(pk[39]),
          "=r"(pk[40]), "=r"(pk[41]), "=r"(pk[42]), "=r"(pk[43]), "=r"(pk[44]), "=r"(pk[45]), "=r"(pk[46]), "=r"(pk[47]), "=r"(pk[48]), "=r"(pk[49]),
          "=r"(pk[50]), "=r"(pk[51]), "=r"(pk[52]), "=r"(pk[53]), "=r"(pk[54]), "=r"(pk[55]), "=r"(pk[56]), "=r"(pk[57]), "=r"(pk[58]), "=r"(pk[59]),
          "=r"(pk[60]), "=r"(pk[61]), "=r"(pk[62]), "=r"(pk[63])
        : "r"(olp), "r"(xa), "r"(ln), "r"(lc), "r"(linc), "r"(lt), "l"(ea), "l"(sh), "l"(wf), "r"(first.x), "r"(first.y), "r"(first.z), "r"(first.w),
          "n"(sb + SM_REC), "n"(sb + SM_R), "n"(sb + SM_BAR), "n"(sb + SM_CTR), "n"(sb + SM_CGF),
          "r"(w[0]), "r"(w[1]), "r"(w[2]), "r"(w[3]), "r"(w[4]), "r"(w[5]), "r"(w[6]), "r"(w[7]), "r"(w[8]), "r"(w[9]), "r"(w[10]), "r"(w[11]),
          "r"(w[12]), "r"(w[13]), "r"(w[14]), "r"(w[15]), "r"(w[16]), "r"(w[17]), "r"(w[18]), "r"(w[19]), "r"(w[20]), "r"(w[21]), "r"(w[22]),
          "r"(w[23]), "r"(w[24]), "r"(w[25]), "r"(w[26]), "r"(w[27]), "r"(w[28]), "r"(w[29]), "r"(w[30]), "r"(w[31]), "r"(w[32]), "r"(w[33]),
          "r"(w[34]), "r"(w[35])
        : "memory");
}
__device__ __forceinline__ void consume3(uint32_t (&pk)[48], const uint32_t (&w)[36], uint32_t olp, uint32_t xa, uint32_t ln,
                                      uint32_t lc, uint32_t linc, uint32_t lt, const __nv_bfloat16* ea, const __nv_bfloat16* sh, const void* wf, uint4 first) {
    ea += lt * 4, sh += lt & 2;
    asm volatile(
        "{\n.reg .pred p, q, psw, prdy, ps1, ps2, ps3, pz, pq, pt, pl;\n.reg .f32 d<40>, fz;\n"
        ".reg .b32 h<48>, x<32>, y<32>, ra<8>, rb<8>, bA0, bA1, bB0, bB1, c0, c1, c2, c3, e0, e1, s0, kept;\n"
        ".reg .b32 olp, v, vB, m, id, ida, bar, xb, pos, t0, t1, t2, t3, n, z<16>, kept2, g<4>, f0, f1, s1;\n.reg .b16 lo, hi, i16;\n.reg .b64 pa, pb;\n"
        "mov.f32 fz, 0f00000000;\nmov.b32 h0, 0;\nmov.b32 h1, 0;\nmov.b32 h2, 0;\nmov.b32 h3, 0;\nmov.b32 h4, 0;\nmov.b32 h5, 0;\nmov.b32 h6, 0;\n"
        "mov.b32 h7, 0;\nmov.b32 h8, 0;\nmov.b32 h9, 0;\nmov.b32 h10, 0;\nmov.b32 h11, 0;\nmov.b32 h12, 0;\nmov.b32 h13, 0;\nmov.b32 h14, 0;\nmov.b32 h15, 0;\n"
        "mov.b32 h16, 0;\nmov.b32 h17, 0;\nmov.b32 h18, 0;\nmov.b32 h19, 0;\nmov.b32 h20, 0;\nmov.b32 h21, 0;\nmov.b32 h22, 0;\nmov.b32 h23, 0;\n"
        "mov.b32 h24, 0;\nmov.b32 h25, 0;\nmov.b32 h26, 0;\nmov.b32 h27, 0;\nmov.b32 h28, 0;\nmov.b32 h29, 0;\nmov.b32 h30, 0;\nmov.b32 h31, 0;\n"
        "mov.b32 h32, 0;\nmov.b32 h33, 0;\nmov.b32 h34, 0;\nmov.b32 h35, 0;\nmov.b32 h36, 0;\nmov.b32 h37, 0;\nmov.b32 h38, 0;\nmov.b32 h39, 0;\n"
        "mov.b32 h40, 0;\nmov.b32 h41, 0;\nmov.b32 h42, 0;\nmov.b32 h43, 0;\nmov.b32 h44, 0;\nmov.b32 h45, 0;\nmov.b32 h46, 0;\nmov.b32 h47, 0;\n"
        "mov.b32 olp, %48;\nand.b32 t3, %51, 31;\nmad.lo.u32 t3, t3, 0x4001, 4;\nshfl.sync.bfly.b32 t3, t3, 8, 0x1f, 0xffffffff;\nand.b32 t0, %50, 32;\n"
        "setp.ne.u32 psw, t0, 0;\nsetp.eq.u32 pz, %48, 0;\nvote.sync.any.pred pz, pz, 0xffffffff;\nmov.b32 e0, %57;\nmov.b32 e1, %58;\nmov.b32 s0, %59;\n"
        "mov.b32 kept, %60;\nadd.u32 olp, olp, 4;\nsetp.ne.u64 p, %56, 0;\n@p fence.proxy.async.global;\n@p red.release.gpu.global.add.u32 [%56+12], 1;\n"
        "bar.warp.sync 0xffffffff;\nshfl.sync.idx.b32 v, kept, %51, 0x1f, 0xffffffff;\nshfl.sync.idx.b32 vB, kept, t3, 0x1f, 0xffffffff;\n"
        "ld.shared.u16 t0, [olp];\nadd.u32 olp, olp, 4;\nlop3.b32 t1, t0, %50, 0x3ff0, 0xe4;\nld.shared.b32 t1, [t1+%61];\nshr.u32 t2, t1, 1;\n"
        "lop3.b32 kept, t2, t0, 0xffe, 0xe4;\nlop3.b32 t2, t1, %51, 3, 0x80;\nsetp.ne.u32 pq, t2, 0;\nshr.u32 t2, t1, 13;\nmad.wide.u32 pa, t2, 32, %54;\n"
        "mad.wide.u32 pb, t2, 8, %55;\n"
        "RW:\nmma.sync.aligned.m16n8k8.row.col.f32.bf16.bf16.f32 {d0,d1,d2,d3}, {%98,%99}, {s0}, {fz,fz,fz,fz};\n"
        "mma.sync.aligned.m16n8k8.row.col.f32.bf16.bf16.f32 {d4,d5,d6,d7}, {%100,%101}, {s0}, {fz,fz,fz,fz};\ncvt.rn.bf16x2.f32 c0, d2, d0;\n"
        "cvt.rn.bf16x2.f32 c1, d3, d1;\ncvt.rn.bf16x2.f32 c2, d6, d4;\ncvt.rn.bf16x2.f32 c3, d7, d5;\nselp.b32 bA0, c2, c0, psw;\nselp.b32 bA1, c0, c2, psw;\n"
        "selp.b32 bB0, c3, c1, psw;\nselp.b32 bB1, c1, c3, psw;\n"
        "mma.sync.aligned.m16n8k16.row.col.f32.bf16.bf16.f32 {d0,d1,d2,d3}, {%66,%67,%68,%69}, {e0,e1}, {fz,fz,fz,fz};\ncvt.rn.bf16x2.f32 ra0, d2, d0;\n"
        "cvt.rn.bf16x2.f32 rb0, d3, d1;\nmma.sync.aligned.m16n8k16.row.col.f32.bf16.bf16.f32 {d4,d5,d6,d7}, {%70,%71,%72,%73}, {e0,e1}, {fz,fz,fz,fz};\n"
        "cvt.rn.bf16x2.f32 ra1, d6, d4;\ncvt.rn.bf16x2.f32 rb1, d7, d5;\n"
        "mma.sync.aligned.m16n8k16.row.col.f32.bf16.bf16.f32 {d8,d9,d10,d11}, {%74,%75,%76,%77}, {e0,e1}, {fz,fz,fz,fz};\ncvt.rn.bf16x2.f32 ra2, d10, d8;\n"
        "cvt.rn.bf16x2.f32 rb2, d11, d9;\nmma.sync.aligned.m16n8k16.row.col.f32.bf16.bf16.f32 {d12,d13,d14,d15}, {%78,%79,%80,%81}, {e0,e1}, {fz,fz,fz,fz};\n"
        "cvt.rn.bf16x2.f32 ra3, d14, d12;\ncvt.rn.bf16x2.f32 rb3, d15, d13;\n"
        "mma.sync.aligned.m16n8k16.row.col.f32.bf16.bf16.f32 {d16,d17,d18,d19}, {%82,%83,%84,%85}, {e0,e1}, {fz,fz,fz,fz};\ncvt.rn.bf16x2.f32 ra4, d18, d16;\n"
        "cvt.rn.bf16x2.f32 rb4, d19, d17;\nmma.sync.aligned.m16n8k16.row.col.f32.bf16.bf16.f32 {d20,d21,d22,d23}, {%86,%87,%88,%89}, {e0,e1}, {fz,fz,fz,fz};\n"
        "cvt.rn.bf16x2.f32 ra5, d22, d20;\ncvt.rn.bf16x2.f32 rb5, d23, d21;\n"
        "mma.sync.aligned.m16n8k16.row.col.f32.bf16.bf16.f32 {d24,d25,d26,d27}, {%90,%91,%92,%93}, {e0,e1}, {fz,fz,fz,fz};\ncvt.rn.bf16x2.f32 ra6, d26, d24;\n"
        "cvt.rn.bf16x2.f32 rb6, d27, d25;\nmma.sync.aligned.m16n8k16.row.col.f32.bf16.bf16.f32 {d28,d29,d30,d31}, {%94,%95,%96,%97}, {e0,e1}, {fz,fz,fz,fz};\n"
        "cvt.rn.bf16x2.f32 ra7, d30, d28;\ncvt.rn.bf16x2.f32 rb7, d31, d29;\nmov.b32 s0, 0;\nld.global.cg.L2::128B.v2.b32 {e0,e1}, [pa];\n"
        "@pq ld.global.cg.L2::128B.b32 s0, [pb];\nand.b32 bar, v, 0xff8;\nmbarrier.test_wait.parity.shared.b64 pl, [bar+%63], 0;\n"
        "lop3.b32 ida, v, %51, 0xfff, 0xe4;\nld.volatile.shared.u16 id, [ida+%62];\nvote.sync.all.pred prdy, pl, 0xffffffff;\n@!prdy bra.uni WA;\n"
        "HA:\nmad.lo.u32 xb, id, 64, %49;\ncvt.u16.u32 i16, id;\natom.shared.add.u32 pos, [%50+%64], %52;\n"
        "ldmatrix.sync.aligned.m8n8.x4.trans.shared.b16 {x0,x1,x2,x3}, [xb];\nldmatrix.sync.aligned.m8n8.x4.trans.shared.b16 {x24,x25,x26,x27}, [xb+512];\n"
        "xor.b32 t1, xb, 32;\nldmatrix.sync.aligned.m8n8.x4.trans.shared.b16 {x4,x5,x6,x7}, [t1];\n"
        "ldmatrix.sync.aligned.m8n8.x4.trans.shared.b16 {x28,x29,x30,x31}, [t1+512];\nxor.b32 t1, xb, 64;\n"
        "ldmatrix.sync.aligned.m8n8.x4.trans.shared.b16 {x8,x9,x10,x11}, [t1];\nldmatrix.sync.aligned.m8n8.x4.trans.shared.b16 {x16,x17,x18,x19}, [t1+512];\n"
        "xor.b32 t1, xb, 96;\nldmatrix.sync.aligned.m8n8.x4.trans.shared.b16 {x12,x13,x14,x15}, [t1];\n"
        "ldmatrix.sync.aligned.m8n8.x4.trans.shared.b16 {x20,x21,x22,x23}, [t1+512];\nst.volatile.shared.u16 [pos], i16;\nand.b32 t0, v, 16384;\n"
        "setp.ne.u32 ps1, t0, 0;\nvote.sync.any.pred ps1, ps1, 0xffffffff;\nand.b32 t0, v, 32768;\nsetp.ne.u32 ps2, t0, 0;\n"
        "vote.sync.any.pred ps2, ps2, 0xffffffff;\nmov.b32 v, vB;\nand.b32 bar, v, 0xff8;\nmbarrier.test_wait.parity.shared.b64 pl, [bar+%63], 0;\n"
        "lop3.b32 ida, v, %51, 0xfff, 0xe4;\nld.volatile.shared.u16 id, [ida+%62];\nvote.sync.all.pred prdy, pl, 0xffffffff;\nmov.b32 {lo, hi}, ra0;\n"
        "mov.b32 t2, {lo, lo};\nmul.rn.bf16x2 y0, x0, t2;\nmul.rn.bf16x2 y2, x2, t2;\nmov.b32 t2, {hi, hi};\nmul.rn.bf16x2 y1, x1, t2;\n"
        "mul.rn.bf16x2 y3, x3, t2;\nmma.sync.aligned.m16n8k16.row.col.f32.bf16.bf16.f32 {d0,d1,d2,d3}, {y0,y1,y2,y3}, {bA0,bA1}, {fz,fz,fz,fz};\n"
        "cvt.rn.bf16x2.f32 z0, d1, d0;\ncvt.rn.bf16x2.f32 z1, d3, d2;\nmov.b32 {lo, hi}, ra6;\nmov.b32 t2, {lo, lo};\nmul.rn.bf16x2 y24, x24, t2;\n"
        "mul.rn.bf16x2 y26, x26, t2;\nmov.b32 t2, {hi, hi};\nmul.rn.bf16x2 y25, x25, t2;\nmul.rn.bf16x2 y27, x27, t2;\n"
        "mma.sync.aligned.m16n8k16.row.col.f32.bf16.bf16.f32 {d24,d25,d26,d27}, {y24,y25,y26,y27}, {bA0,bA1}, {fz,fz,fz,fz};\ncvt.rn.bf16x2.f32 z12, d25, d24;\n"
        "cvt.rn.bf16x2.f32 z13, d27, d26;\nmov.b32 {lo, hi}, ra1;\nmov.b32 t2, {lo, lo};\nmul.rn.bf16x2 y4, x4, t2;\nmul.rn.bf16x2 y6, x6, t2;\n"
        "mov.b32 t2, {hi, hi};\nmul.rn.bf16x2 y5, x5, t2;\nmul.rn.bf16x2 y7, x7, t2;\n"
        "mma.sync.aligned.m16n8k16.row.col.f32.bf16.bf16.f32 {d4,d5,d6,d7}, {y4,y5,y6,y7}, {bA0,bA1}, {fz,fz,fz,fz};\ncvt.rn.bf16x2.f32 z2, d5, d4;\n"
        "cvt.rn.bf16x2.f32 z3, d7, d6;\nmov.b32 {lo, hi}, ra7;\nmov.b32 t2, {lo, lo};\nmul.rn.bf16x2 y28, x28, t2;\nmul.rn.bf16x2 y30, x30, t2;\n"
        "mov.b32 t2, {hi, hi};\nmul.rn.bf16x2 y29, x29, t2;\nmul.rn.bf16x2 y31, x31, t2;\n"
        "mma.sync.aligned.m16n8k16.row.col.f32.bf16.bf16.f32 {d28,d29,d30,d31}, {y28,y29,y30,y31}, {bA0,bA1}, {fz,fz,fz,fz};\ncvt.rn.bf16x2.f32 z14, d29, d28;\n"
        "cvt.rn.bf16x2.f32 z15, d31, d30;\nmov.b32 {lo, hi}, ra2;\nmov.b32 t2, {lo, lo};\nmul.rn.bf16x2 y8, x8, t2;\nmul.rn.bf16x2 y10, x10, t2;\n"
        "mov.b32 t2, {hi, hi};\nmul.rn.bf16x2 y9, x9, t2;\nmul.rn.bf16x2 y11, x11, t2;\n"
        "mma.sync.aligned.m16n8k16.row.col.f32.bf16.bf16.f32 {d8,d9,d10,d11}, {y8,y9,y10,y11}, {bA0,bA1}, {fz,fz,fz,fz};\ncvt.rn.bf16x2.f32 z4, d9, d8;\n"
        "cvt.rn.bf16x2.f32 z5, d11, d10;\nmov.b32 {lo, hi}, ra4;\nmov.b32 t2, {lo, lo};\nmul.rn.bf16x2 y16, x16, t2;\nmul.rn.bf16x2 y18, x18, t2;\n"
        "mov.b32 t2, {hi, hi};\nmul.rn.bf16x2 y17, x17, t2;\nmul.rn.bf16x2 y19, x19, t2;\n"
        "mma.sync.aligned.m16n8k16.row.col.f32.bf16.bf16.f32 {d16,d17,d18,d19}, {y16,y17,y18,y19}, {bA0,bA1}, {fz,fz,fz,fz};\ncvt.rn.bf16x2.f32 z8, d17, d16;\n"
        "cvt.rn.bf16x2.f32 z9, d19, d18;\nmov.b32 {lo, hi}, ra3;\nmov.b32 t2, {lo, lo};\nmul.rn.bf16x2 y12, x12, t2;\nmul.rn.bf16x2 y14, x14, t2;\n"
        "mov.b32 t2, {hi, hi};\nmul.rn.bf16x2 y13, x13, t2;\nmul.rn.bf16x2 y15, x15, t2;\n"
        "mma.sync.aligned.m16n8k16.row.col.f32.bf16.bf16.f32 {d12,d13,d14,d15}, {y12,y13,y14,y15}, {bA0,bA1}, {fz,fz,fz,fz};\ncvt.rn.bf16x2.f32 z6, d13, d12;\n"
        "cvt.rn.bf16x2.f32 z7, d15, d14;\nmov.b32 {lo, hi}, ra5;\nmov.b32 t2, {lo, lo};\nmul.rn.bf16x2 y20, x20, t2;\nmul.rn.bf16x2 y22, x22, t2;\n"
        "mov.b32 t2, {hi, hi};\nmul.rn.bf16x2 y21, x21, t2;\nmul.rn.bf16x2 y23, x23, t2;\n"
        "mma.sync.aligned.m16n8k16.row.col.f32.bf16.bf16.f32 {d20,d21,d22,d23}, {y20,y21,y22,y23}, {bA0,bA1}, {fz,fz,fz,fz};\ncvt.rn.bf16x2.f32 z10, d21, d20;\n"
        "cvt.rn.bf16x2.f32 z11, d23, d22;\n@ps2 bra.uni TA2;\n@ps1 bra.uni TA1;\n"
        "TA0:\nadd.rn.bf16x2 h0, h0, z0;\nadd.rn.bf16x2 h1, h1, z1;\nadd.rn.bf16x2 h2, h2, z2;\nadd.rn.bf16x2 h3, h3, z3;\nadd.rn.bf16x2 h4, h4, z4;\n"
        "add.rn.bf16x2 h5, h5, z5;\nadd.rn.bf16x2 h6, h6, z6;\nadd.rn.bf16x2 h7, h7, z7;\nadd.rn.bf16x2 h8, h8, z8;\nadd.rn.bf16x2 h9, h9, z9;\n"
        "add.rn.bf16x2 h10, h10, z10;\nadd.rn.bf16x2 h11, h11, z11;\nadd.rn.bf16x2 h12, h12, z12;\nadd.rn.bf16x2 h13, h13, z13;\nadd.rn.bf16x2 h14, h14, z14;\n"
        "add.rn.bf16x2 h15, h15, z15;\n@prdy bra.uni HB;\nbra.uni WB;\n"
        "TA1:\nadd.rn.bf16x2 h16, h16, z0;\nadd.rn.bf16x2 h17, h17, z1;\nadd.rn.bf16x2 h18, h18, z2;\nadd.rn.bf16x2 h19, h19, z3;\nadd.rn.bf16x2 h20, h20, z4;\n"
        "add.rn.bf16x2 h21, h21, z5;\nadd.rn.bf16x2 h22, h22, z6;\nadd.rn.bf16x2 h23, h23, z7;\nadd.rn.bf16x2 h24, h24, z8;\nadd.rn.bf16x2 h25, h25, z9;\n"
        "add.rn.bf16x2 h26, h26, z10;\nadd.rn.bf16x2 h27, h27, z11;\nadd.rn.bf16x2 h28, h28, z12;\nadd.rn.bf16x2 h29, h29, z13;\nadd.rn.bf16x2 h30, h30, z14;\n"
        "add.rn.bf16x2 h31, h31, z15;\n@prdy bra.uni HB;\nbra.uni WB;\n"
        "TA2:\nadd.rn.bf16x2 h32, h32, z0;\nadd.rn.bf16x2 h33, h33, z1;\nadd.rn.bf16x2 h34, h34, z2;\nadd.rn.bf16x2 h35, h35, z3;\nadd.rn.bf16x2 h36, h36, z4;\n"
        "add.rn.bf16x2 h37, h37, z5;\nadd.rn.bf16x2 h38, h38, z6;\nadd.rn.bf16x2 h39, h39, z7;\nadd.rn.bf16x2 h40, h40, z8;\nadd.rn.bf16x2 h41, h41, z9;\n"
        "add.rn.bf16x2 h42, h42, z10;\nadd.rn.bf16x2 h43, h43, z11;\nadd.rn.bf16x2 h44, h44, z12;\nadd.rn.bf16x2 h45, h45, z13;\nadd.rn.bf16x2 h46, h46, z14;\n"
        "add.rn.bf16x2 h47, h47, z15;\n@prdy bra.uni HB;\nbra.uni WB;\n"
        "HB:\nmad.lo.u32 xb, id, 64, %49;\ncvt.u16.u32 i16, id;\natom.shared.add.u32 pos, [%50+%64], %52;\n"
        "ldmatrix.sync.aligned.m8n8.x4.trans.shared.b16 {x0,x1,x2,x3}, [xb];\nldmatrix.sync.aligned.m8n8.x4.trans.shared.b16 {x24,x25,x26,x27}, [xb+512];\n"
        "xor.b32 t1, xb, 32;\nldmatrix.sync.aligned.m8n8.x4.trans.shared.b16 {x4,x5,x6,x7}, [t1];\n"
        "ldmatrix.sync.aligned.m8n8.x4.trans.shared.b16 {x28,x29,x30,x31}, [t1+512];\nxor.b32 t1, xb, 64;\n"
        "ldmatrix.sync.aligned.m8n8.x4.trans.shared.b16 {x8,x9,x10,x11}, [t1];\nldmatrix.sync.aligned.m8n8.x4.trans.shared.b16 {x16,x17,x18,x19}, [t1+512];\n"
        "xor.b32 t1, xb, 96;\nldmatrix.sync.aligned.m8n8.x4.trans.shared.b16 {x12,x13,x14,x15}, [t1];\n"
        "ldmatrix.sync.aligned.m8n8.x4.trans.shared.b16 {x20,x21,x22,x23}, [t1+512];\nst.volatile.shared.u16 [pos], i16;\nand.b32 t0, v, 16384;\n"
        "setp.ne.u32 ps1, t0, 0;\nvote.sync.any.pred ps1, ps1, 0xffffffff;\nand.b32 t0, v, 32768;\nsetp.ne.u32 ps2, t0, 0;\n"
        "vote.sync.any.pred ps2, ps2, 0xffffffff;\nshfl.sync.idx.b32 v, kept, %51, 0x1f, 0xffffffff;\nshfl.sync.idx.b32 vB, kept, t3, 0x1f, 0xffffffff;\n"
        "ld.shared.u16 t0, [olp];\nadd.u32 olp, olp, 4;\nlop3.b32 t1, t0, %50, 0x3ff0, 0xe4;\nld.shared.b32 t1, [t1+%61];\nshr.u32 t2, t1, 1;\n"
        "lop3.b32 kept, t2, t0, 0xffe, 0xe4;\nlop3.b32 t2, t1, %51, 3, 0x80;\nsetp.ne.u32 pq, t2, 0;\nshr.u32 t2, t1, 13;\nmad.wide.u32 pa, t2, 32, %54;\n"
        "mad.wide.u32 pb, t2, 8, %55;\nmov.b32 {lo, hi}, rb0;\nmov.b32 t2, {lo, lo};\nmul.rn.bf16x2 y0, x0, t2;\nmul.rn.bf16x2 y2, x2, t2;\n"
        "mov.b32 t2, {hi, hi};\nmul.rn.bf16x2 y1, x1, t2;\nmul.rn.bf16x2 y3, x3, t2;\n"
        "mma.sync.aligned.m16n8k16.row.col.f32.bf16.bf16.f32 {d0,d1,d2,d3}, {y0,y1,y2,y3}, {bB0,bB1}, {fz,fz,fz,fz};\ncvt.rn.bf16x2.f32 z0, d1, d0;\n"
        "cvt.rn.bf16x2.f32 z1, d3, d2;\nmov.b32 {lo, hi}, rb6;\nmov.b32 t2, {lo, lo};\nmul.rn.bf16x2 y24, x24, t2;\nmul.rn.bf16x2 y26, x26, t2;\n"
        "mov.b32 t2, {hi, hi};\nmul.rn.bf16x2 y25, x25, t2;\nmul.rn.bf16x2 y27, x27, t2;\n"
        "mma.sync.aligned.m16n8k16.row.col.f32.bf16.bf16.f32 {d24,d25,d26,d27}, {y24,y25,y26,y27}, {bB0,bB1}, {fz,fz,fz,fz};\ncvt.rn.bf16x2.f32 z12, d25, d24;\n"
        "cvt.rn.bf16x2.f32 z13, d27, d26;\nmov.b32 {lo, hi}, rb1;\nmov.b32 t2, {lo, lo};\nmul.rn.bf16x2 y4, x4, t2;\nmul.rn.bf16x2 y6, x6, t2;\n"
        "mov.b32 t2, {hi, hi};\nmul.rn.bf16x2 y5, x5, t2;\nmul.rn.bf16x2 y7, x7, t2;\n"
        "mma.sync.aligned.m16n8k16.row.col.f32.bf16.bf16.f32 {d4,d5,d6,d7}, {y4,y5,y6,y7}, {bB0,bB1}, {fz,fz,fz,fz};\ncvt.rn.bf16x2.f32 z2, d5, d4;\n"
        "cvt.rn.bf16x2.f32 z3, d7, d6;\nmov.b32 {lo, hi}, rb7;\nmov.b32 t2, {lo, lo};\nmul.rn.bf16x2 y28, x28, t2;\nmul.rn.bf16x2 y30, x30, t2;\n"
        "mov.b32 t2, {hi, hi};\nmul.rn.bf16x2 y29, x29, t2;\nmul.rn.bf16x2 y31, x31, t2;\n"
        "mma.sync.aligned.m16n8k16.row.col.f32.bf16.bf16.f32 {d28,d29,d30,d31}, {y28,y29,y30,y31}, {bB0,bB1}, {fz,fz,fz,fz};\ncvt.rn.bf16x2.f32 z14, d29, d28;\n"
        "cvt.rn.bf16x2.f32 z15, d31, d30;\nmov.b32 {lo, hi}, rb2;\nmov.b32 t2, {lo, lo};\nmul.rn.bf16x2 y8, x8, t2;\nmul.rn.bf16x2 y10, x10, t2;\n"
        "mov.b32 t2, {hi, hi};\nmul.rn.bf16x2 y9, x9, t2;\nmul.rn.bf16x2 y11, x11, t2;\n"
        "mma.sync.aligned.m16n8k16.row.col.f32.bf16.bf16.f32 {d8,d9,d10,d11}, {y8,y9,y10,y11}, {bB0,bB1}, {fz,fz,fz,fz};\ncvt.rn.bf16x2.f32 z4, d9, d8;\n"
        "cvt.rn.bf16x2.f32 z5, d11, d10;\nmov.b32 {lo, hi}, rb4;\nmov.b32 t2, {lo, lo};\nmul.rn.bf16x2 y16, x16, t2;\nmul.rn.bf16x2 y18, x18, t2;\n"
        "mov.b32 t2, {hi, hi};\nmul.rn.bf16x2 y17, x17, t2;\nmul.rn.bf16x2 y19, x19, t2;\n"
        "mma.sync.aligned.m16n8k16.row.col.f32.bf16.bf16.f32 {d16,d17,d18,d19}, {y16,y17,y18,y19}, {bB0,bB1}, {fz,fz,fz,fz};\ncvt.rn.bf16x2.f32 z8, d17, d16;\n"
        "cvt.rn.bf16x2.f32 z9, d19, d18;\nmov.b32 {lo, hi}, rb3;\nmov.b32 t2, {lo, lo};\nmul.rn.bf16x2 y12, x12, t2;\nmul.rn.bf16x2 y14, x14, t2;\n"
        "mov.b32 t2, {hi, hi};\nmul.rn.bf16x2 y13, x13, t2;\nmul.rn.bf16x2 y15, x15, t2;\n"
        "mma.sync.aligned.m16n8k16.row.col.f32.bf16.bf16.f32 {d12,d13,d14,d15}, {y12,y13,y14,y15}, {bB0,bB1}, {fz,fz,fz,fz};\ncvt.rn.bf16x2.f32 z6, d13, d12;\n"
        "cvt.rn.bf16x2.f32 z7, d15, d14;\nmov.b32 {lo, hi}, rb5;\nmov.b32 t2, {lo, lo};\nmul.rn.bf16x2 y20, x20, t2;\nmul.rn.bf16x2 y22, x22, t2;\n"
        "mov.b32 t2, {hi, hi};\nmul.rn.bf16x2 y21, x21, t2;\nmul.rn.bf16x2 y23, x23, t2;\n"
        "mma.sync.aligned.m16n8k16.row.col.f32.bf16.bf16.f32 {d20,d21,d22,d23}, {y20,y21,y22,y23}, {bB0,bB1}, {fz,fz,fz,fz};\ncvt.rn.bf16x2.f32 z10, d21, d20;\n"
        "cvt.rn.bf16x2.f32 z11, d23, d22;\n@ps2 bra.uni TB2;\n@ps1 bra.uni TB1;\n"
        "TB0:\nadd.rn.bf16x2 h0, h0, z0;\nadd.rn.bf16x2 h1, h1, z1;\nadd.rn.bf16x2 h2, h2, z2;\nadd.rn.bf16x2 h3, h3, z3;\nadd.rn.bf16x2 h4, h4, z4;\n"
        "add.rn.bf16x2 h5, h5, z5;\nadd.rn.bf16x2 h6, h6, z6;\nadd.rn.bf16x2 h7, h7, z7;\nadd.rn.bf16x2 h8, h8, z8;\nadd.rn.bf16x2 h9, h9, z9;\n"
        "add.rn.bf16x2 h10, h10, z10;\nadd.rn.bf16x2 h11, h11, z11;\nadd.rn.bf16x2 h12, h12, z12;\nadd.rn.bf16x2 h13, h13, z13;\nadd.rn.bf16x2 h14, h14, z14;\n"
        "add.rn.bf16x2 h15, h15, z15;\nbra.uni RW;\n"
        "TB1:\nadd.rn.bf16x2 h16, h16, z0;\nadd.rn.bf16x2 h17, h17, z1;\nadd.rn.bf16x2 h18, h18, z2;\nadd.rn.bf16x2 h19, h19, z3;\nadd.rn.bf16x2 h20, h20, z4;\n"
        "add.rn.bf16x2 h21, h21, z5;\nadd.rn.bf16x2 h22, h22, z6;\nadd.rn.bf16x2 h23, h23, z7;\nadd.rn.bf16x2 h24, h24, z8;\nadd.rn.bf16x2 h25, h25, z9;\n"
        "add.rn.bf16x2 h26, h26, z10;\nadd.rn.bf16x2 h27, h27, z11;\nadd.rn.bf16x2 h28, h28, z12;\nadd.rn.bf16x2 h29, h29, z13;\nadd.rn.bf16x2 h30, h30, z14;\n"
        "add.rn.bf16x2 h31, h31, z15;\nbra.uni RW;\n"
        "TB2:\nadd.rn.bf16x2 h32, h32, z0;\nadd.rn.bf16x2 h33, h33, z1;\nadd.rn.bf16x2 h34, h34, z2;\nadd.rn.bf16x2 h35, h35, z3;\nadd.rn.bf16x2 h36, h36, z4;\n"
        "add.rn.bf16x2 h37, h37, z5;\nadd.rn.bf16x2 h38, h38, z6;\nadd.rn.bf16x2 h39, h39, z7;\nadd.rn.bf16x2 h40, h40, z8;\nadd.rn.bf16x2 h41, h41, z9;\n"
        "add.rn.bf16x2 h42, h42, z10;\nadd.rn.bf16x2 h43, h43, z11;\nadd.rn.bf16x2 h44, h44, z12;\nadd.rn.bf16x2 h45, h45, z13;\nadd.rn.bf16x2 h46, h46, z14;\n"
        "add.rn.bf16x2 h47, h47, z15;\nbra.uni RW;\n"
        "WA:\nand.b32 t2, v, 0xff8;\nredux.sync.max.u32 t1, t2, 0xffffffff;\nmov.b32 n, 0;\nsetp.eq.u32 p, t1, 0;\n@p bra.uni DONE;\n"
        "WA3:\nmbarrier.try_wait.parity.shared.b64 p, [t1+%63], 0;\n@!p bra.uni WA4;\nmbarrier.test_wait.parity.shared.b64 p, [t2+%63], 0;\n"
        "lop3.b32 ida, v, %51, 0xfff, 0xe4;\nld.volatile.shared.u16 id, [ida+%62];\nvote.sync.all.pred p, p, 0xffffffff;\n@p bra.uni HA;\n"
        "WA4:\nadd.u32 n, n, 1;\nsetp.lt.u32 q, n, 1000000;\n@q bra.uni WA3;\nbra.uni DONE;\n"
        "WB:\nand.b32 t2, v, 0xff8;\nredux.sync.max.u32 t1, t2, 0xffffffff;\nmov.b32 n, 0;\nsetp.eq.u32 p, t1, 0;\n@p bra.uni DONE;\n"
        "WB3:\nmbarrier.try_wait.parity.shared.b64 p, [t1+%63], 0;\n@!p bra.uni WB4;\nmbarrier.test_wait.parity.shared.b64 p, [t2+%63], 0;\n"
        "lop3.b32 ida, v, %51, 0xfff, 0xe4;\nld.volatile.shared.u16 id, [ida+%62];\nvote.sync.all.pred p, p, 0xffffffff;\n@p bra.uni HB;\n"
        "WB4:\nadd.u32 n, n, 1;\nsetp.lt.u32 q, n, 1000000;\n@q bra.uni WB3;\nbra.uni DONE;\n"
        "DONE:\nmov.b32 %0, h0;\nmov.b32 %1, h1;\nmov.b32 %2, h2;\nmov.b32 %3, h3;\nmov.b32 %4, h4;\nmov.b32 %5, h5;\nmov.b32 %6, h6;\nmov.b32 %7, h7;\n"
        "mov.b32 %8, h8;\nmov.b32 %9, h9;\nmov.b32 %10, h10;\nmov.b32 %11, h11;\nmov.b32 %12, h12;\nmov.b32 %13, h13;\nmov.b32 %14, h14;\nmov.b32 %15, h15;\n"
        "mov.b32 %16, h16;\nmov.b32 %17, h17;\nmov.b32 %18, h18;\nmov.b32 %19, h19;\nmov.b32 %20, h20;\nmov.b32 %21, h21;\nmov.b32 %22, h22;\nmov.b32 %23, h23;\n"
        "mov.b32 %24, h24;\nmov.b32 %25, h25;\nmov.b32 %26, h26;\nmov.b32 %27, h27;\nmov.b32 %28, h28;\nmov.b32 %29, h29;\nmov.b32 %30, h30;\nmov.b32 %31, h31;\n"
        "mov.b32 %32, h32;\nmov.b32 %33, h33;\nmov.b32 %34, h34;\nmov.b32 %35, h35;\nmov.b32 %36, h36;\nmov.b32 %37, h37;\nmov.b32 %38, h38;\nmov.b32 %39, h39;\n"
        "mov.b32 %40, h40;\nmov.b32 %41, h41;\nmov.b32 %42, h42;\nmov.b32 %43, h43;\nmov.b32 %44, h44;\nmov.b32 %45, h45;\nmov.b32 %46, h46;\nmov.b32 %47, h47;\n"
        "}\n"
        : "=r"(pk[0]), "=r"(pk[1]), "=r"(pk[2]), "=r"(pk[3]), "=r"(pk[4]), "=r"(pk[5]), "=r"(pk[6]), "=r"(pk[7]), "=r"(pk[8]), "=r"(pk[9]),
          "=r"(pk[10]), "=r"(pk[11]), "=r"(pk[12]), "=r"(pk[13]), "=r"(pk[14]), "=r"(pk[15]), "=r"(pk[16]), "=r"(pk[17]), "=r"(pk[18]), "=r"(pk[19]),
          "=r"(pk[20]), "=r"(pk[21]), "=r"(pk[22]), "=r"(pk[23]), "=r"(pk[24]), "=r"(pk[25]), "=r"(pk[26]), "=r"(pk[27]), "=r"(pk[28]), "=r"(pk[29]),
          "=r"(pk[30]), "=r"(pk[31]), "=r"(pk[32]), "=r"(pk[33]), "=r"(pk[34]), "=r"(pk[35]), "=r"(pk[36]), "=r"(pk[37]), "=r"(pk[38]), "=r"(pk[39]),
          "=r"(pk[40]), "=r"(pk[41]), "=r"(pk[42]), "=r"(pk[43]), "=r"(pk[44]), "=r"(pk[45]), "=r"(pk[46]), "=r"(pk[47])
        : "r"(olp), "r"(xa), "r"(ln), "r"(lc), "r"(linc), "r"(lt), "l"(ea), "l"(sh), "l"(wf), "r"(first.x), "r"(first.y), "r"(first.z), "r"(first.w),
          "n"(sb + SM_REC), "n"(sb + SM_R), "n"(sb + SM_BAR), "n"(sb + SM_CTR), "n"(sb + SM_CGF),
          "r"(w[0]), "r"(w[1]), "r"(w[2]), "r"(w[3]), "r"(w[4]), "r"(w[5]), "r"(w[6]), "r"(w[7]), "r"(w[8]), "r"(w[9]), "r"(w[10]), "r"(w[11]),
          "r"(w[12]), "r"(w[13]), "r"(w[14]), "r"(w[15]), "r"(w[16]), "r"(w[17]), "r"(w[18]), "r"(w[19]), "r"(w[20]), "r"(w[21]), "r"(w[22]),
          "r"(w[23]), "r"(w[24]), "r"(w[25]), "r"(w[26]), "r"(w[27]), "r"(w[28]), "r"(w[29]), "r"(w[30]), "r"(w[31]), "r"(w[32]), "r"(w[33]),
          "r"(w[34]), "r"(w[35])
        : "memory");
}

__device__ __forceinline__ void wf_done() {
    asm volatile("fence.proxy.async.global;\nred.release.gpu.global.add.u32 [%0+12], 1;" ::"l"(g_sync) : "memory");
}

template <int NS>
__device__ __forceinline__ void consumer(const __nv_bfloat16* __restrict__ sh,
                                         const __nv_bfloat16* __restrict__ ea, __nv_bfloat16* __restrict__ out, int N, int npb, uint4 first) {
    uint32_t pk[NS * 16];
    {
        const int lane = threadIdx.x & 31, warp = threadIdx.x >> 5;
        const int mi = lane >> 3, r = lane & 7, j = r >> 1;
        const int u = 2 * ((mi >> 1) ^ (j >> 1)) + (r & 1), ph = (j ^ (j >> 1)) & 1;
        uint32_t w[36];
        {
            const uint32_t a = sb + SC_WR + (4 * j + (r & 1) + (mi & 2)) * 272 + (mi & 1) * 16;
#pragma unroll
            for (int c = 0; c < 8; c++)
                asm volatile("ldmatrix.sync.aligned.m8n8.x4.trans.shared.b16 {%0,%1,%2,%3}, [%4];"
                             : "=r"(w[4 * c]), "=r"(w[4 * c + 1]), "=r"(w[4 * c + 2]), "=r"(w[4 * c + 3]) : "r"(a + c * 32) : "memory");
            const uint32_t ca = sb + SC_CG + (lane & 2) * 8 + ((lane >> 2) & 3) * 2;
#pragma unroll
            for (int k = 0; k < 4; k++) {
                const uint32_t f = lds16(ca + 32 * k) | (lds16(ca + 32 * k + 8) << 16);
                w[32 + k] = (lane & 1) == (lane >> 4) ? f : 0;
            }
            asm volatile("fence.proxy.async.shared::cta;\nbar.sync 2, %0;" ::"n"(NCW * 32) : "memory");
            if (threadIdx.x < WSL) sts16(sb + SM_R + 0x1000 + (4 + SP - WSL + lane) * 2, (sb + SC_WR) / 64 + lane * 16);
        }
        const uint32_t xa = __shfl_sync(0xffffffffu, u * 128 + (((u + 4 * ph) ^ (mi & 1)) << 4), lane);
        const uint32_t ln = __shfl_sync(0xffffffffu, lane * 16 + (lane >> 3) * 4, lane);
        const uint32_t lc = __shfl_sync(0xffffffffu, j * 8 + (1 << (lane & 1)) + (ph << 12), lane);
        const uint32_t linc = __shfl_sync(0xffffffffu, (lane & 0x19) ? 0 : 4, lane);
        const uint32_t lt = __shfl_sync(0xffffffffu, lane & 3, lane);
        const void* wfp = (threadIdx.x >> 2) == WFT && blockIdx.x < 128 ? g_sync : nullptr;
        const uint32_t olp = sb + SM_OL + warp * (OLN * 2) + ((lane & 4) >> 1);
        if constexpr (NS == 4) consume4(pk, w, olp, xa, ln, lc, linc, lt, ea, sh, wfp, first);
        else consume3(pk, w, olp, xa, ln, lc, linc, lt, ea, sh, wfp, first);
    }
    TLMAX(10);
    const int tid = thread_id(), lane = tid & 31, warp = tid >> 5, g = lane >> 2, t = lane & 3;
    const uint32_t wc = lds32(sb + SM_MISC + 12) + 1;
    const uint32_t inv = lds32(sb + SM_INV + warp * 4);
    const int node0 = cta_id() * npb, nnodes = min(npb, N - node0);
    uint4* op[NS];
    uint32_t on[NS];
#pragma unroll
    for (int s = 0; s < NS; s++) {
        const int nl = ((inv >> (8 * s)) & 255) + (g >> 2) * 40;
        op[s] = (uint4*)(out + ((size_t)(node0 + nl) * 4 + (g & 3)) * 128 + 8 * t);
        on[s] = nl < nnodes;
    }
    if constexpr (NS == 4) project4(pk, sb + SM_R + wc * 8, sb + SM_BAR + (wc + EM3 * t) * 8, op, on);
    else project3(pk, sb + SM_R + wc * 8, sb + SM_BAR + (wc + EM3 * t) * 8, op, on);
}

#define TLHI "shl.b32 d, tb, 16;\n"
#define RAOFF ((threadIdx.x & 96) >> 2)
#define XSTR(x) XSTR2(x)
#define XSTR2(x) #x
__device__ __forceinline__ void producer(const CUtensorMap* tmx, int pw) {
    const uint32_t nch = lds32(sb + SM_MISC + 12), c0 = lds32(sb + SM_MISC + 24);
    asm volatile("bar.sync 1, 512;" ::: "memory");
    if (elect()) {
        asm volatile(
            "{\n.reg .pred p, q, lead, never;\n.reg .b32 ra, oa, off, due, now, a<2>, b<2>, s<4>, d, r, z<8>, bar<4>, t, n, tb, ta, k64, ktx;\n"
            ".reg .b64 lg, t64, tm;\n"
            "mov.b32 ta, %5;\nld.volatile.shared.v4.b32 {z0,z1,z2,z3}, [ta+32];\nld.volatile.shared.v4.b32 {z4,z5,z6,z7}, [ta+32];\n"
            "mov.b32 ra, %9;\nmad.lo.u32 t, %0, 8, %10;\n"
            "add.u32 bar0, t, z0;\nadd.u32 bar1, t, z1;\nadd.u32 bar2, t, z2;\nadd.u32 bar3, t, z3;\nsetp.ne.u32 never, z0, 0;\n"
            "add.u32 k64, z4, 0x40000040;\nadd.u32 ktx, z5, 8192;\ncvt.u64.u32 tm, z6;\nadd.u64 tm, tm, %3;\n"
            "mov.b32 n, 0;\nld.volatile.shared.b32 tb, [ta];\nsetp.eq.u32 lead, %0, 0;\n"
            "mov.u32 due, %%globaltimer_lo;\n"
            "setp.gt.u32 p, ra, %1;\n@p bra.uni END;\nshr.u32 oa, ra, 2;\n"
            "ld.volatile.shared.u16 off, [oa+%11-8];\nadd.u32 due, tb, off;\n"
            "FIRST:\n"
            "mov.u32 now, %%globaltimer_lo;\nsub.u32 t, due, now;\n"
            "setp.gt.s32 p, t, %12;\n@p bra.uni FIRST;\n"
            "GO:\n"
            "ld.volatile.shared.v2.b32 {a0,a1}, [ra];\nld.volatile.shared.v2.b32 {b0,b1}, [ra+0x1000];\n"
            "add.u32 t, ra, ra;\nld.volatile.shared.v4.b32 {s0,s1,s2,s3}, [t+%14];\n"
            "shr.u32 oa, ra, 2;\nld.volatile.shared.u16 off, [oa+%11];\nld.volatile.shared.b32 tb, [z7+%5];\n"
            "mov.u32 now, %%globaltimer_lo;\n"
            "lop3.b32 t, a0, a1, b0, 0xfe;\nor.b32 t, t, b1;\nand.b32 t, t, 0x10001;\n"
            "setp.ne.u32 p, t, 0;\n"
            "@p bra.uni BACK;\n"
            "mbarrier.arrive.expect_tx.shared.b64 _, [ra+%13], ktx;\n"
            "add.u32 bar0, bar0, 32;\nadd.u32 bar1, bar1, 32;\nadd.u32 bar2, bar2, 32;\nadd.u32 bar3, bar3, 32;\n"
            "dp2a.lo.u32.u32 d, a0, k64, 0;\nand.b32 r, s0, 0xffff;\n"
            "cp.async.bulk.tensor.3d.shared::cluster.global.mbarrier::complete_tx::bytes [d], [tm, {z0, r, z1}], [bar0];\n"
            "dp2a.lo.u32.u32 d, b0, k64, 0;\nshr.u32 r, s0, 16;\n"
            "cp.async.bulk.tensor.3d.shared::cluster.global.mbarrier::complete_tx::bytes [d], [tm, {z2, r, z3}], [bar1];\n"
            "dp2a.hi.u32.u32 d, a0, k64, 0;\nand.b32 r, s1, 0xffff;\n"
            "cp.async.bulk.tensor.3d.shared::cluster.global.mbarrier::complete_tx::bytes [d], [tm, {z4, r, z5}], [bar2];\n"
            "dp2a.hi.u32.u32 d, b0, k64, 0;\nshr.u32 r, s1, 16;\n"
            "cp.async.bulk.tensor.3d.shared::cluster.global.mbarrier::complete_tx::bytes [d], [tm, {z6, r, z7}], [bar3];\n"
            "@never bra.uni END;\n"
            "add.u32 ra, ra, 32;\nsub.u32 t, off, now;\nadd.u32 t, t, tb;\nsetp.le.u32 q, t, %2;\n"
            "dp2a.lo.u32.u32 d, a1, k64, 0;\nand.b32 r, s2, 0xffff;\n"
            "cp.async.bulk.tensor.3d.shared::cluster.global.mbarrier::complete_tx::bytes [d], [tm, {z0, r, z1}], [bar0];\n"
            "dp2a.lo.u32.u32 d, b1, k64, 0;\nshr.u32 r, s2, 16;\n"
            "cp.async.bulk.tensor.3d.shared::cluster.global.mbarrier::complete_tx::bytes [d], [tm, {z2, r, z3}], [bar1];\n"
            "dp2a.hi.u32.u32 d, a1, k64, 0;\nand.b32 r, s3, 0xffff;\n"
            "cp.async.bulk.tensor.3d.shared::cluster.global.mbarrier::complete_tx::bytes [d], [tm, {z4, r, z5}], [bar2];\n"
            "dp2a.hi.u32.u32 d, b1, k64, 0;\nshr.u32 r, s3, 16;\n"
            "cp.async.bulk.tensor.3d.shared::cluster.global.mbarrier::complete_tx::bytes [d], [tm, {z6, r, z7}], [bar3];\n"
            "@q bra.uni GO;\n"
            "add.u32 due, t, now;\nsetp.gt.u32 p, ra, %1;\n@p bra.uni END;\n@!lead bra.uni WAIT;\n"
            "add.u32 d, ta, 16;\ncp.async.bulk.shared::cluster.global.mbarrier::complete_tx::bytes [ta], [%4], 16, [d];\n"
            "setp.ge.s32 p, t, 0;\n@p bra.uni WAIT;\n"
            "setp.lt.u32 p, ra, %8;\n@p bra.uni GO;\nadd.u32 r, ra, " XSTR(SLIPEND) ";\nsetp.gt.u32 p, r, %1;\n@p bra.uni GO;\n"
            "ld.volatile.shared.b64 t64, [ta];\ncvt.u32.u64 r, t64;\nsub.u32 r, tb, r;\nsub.u32 d, %7, t;\nadd.s32 d, d, r;\n"
            "cvt.s64.s32 lg, d;\nadd.u64 t64, t64, lg;\n"
            "red.relaxed.gpu.global.max.u64 [%4], t64;\n"
            "bra.uni GO;\n"
            "SLEEP:\n"
            "nanosleep.u32 32;\n"
            "WAIT:\n"
            "mov.u32 now, %%globaltimer_lo;\nsub.u32 t, due, now;\nsetp.gt.s32 p, t, %6;\n@p bra.uni SLEEP;\n"
            "setp.le.s32 p, t, %12;\n@p bra.uni GO;\n"
            "SPIN:\n"
            "mov.u32 now, %%globaltimer_lo;\nsub.u32 t, due, now;\nsetp.gt.s32 p, t, %12;\n@p bra.uni SPIN;\n"
            "bra.uni GO;\n"
            "BACK:\n"
            "nanosleep.u32 32;\nsub.u32 t, now, tb;\nsetp.lt.s32 p, t, 200000000;\n@p bra.uni GO;\n"
            "END:\n}" ::"r"(pw),
            "r"(sb + SM_R + nch * 8), "n"(AHEAD + EARLY + SLIPTH), "l"(tmx), "l"(g_sync), "n"(sb + SM_MISC + 32), "n"(SPINT + SLIPTH), "n"(SLIPADD),
            "n"(sb + SM_R + SLIPFROM * 8), "r"(sb + SM_R + 8 + c0 * 8 + RAOFF), "r"(sb + SM_BAR + 8 - 32 + c0 * 8),
            "n"(sb + SM_OFF + 8 - (sb + SM_R) / 4), "n"(EARLY + SLIPTH), "n"(SM_BAR - SM_R), "n"((int)(sb + SM_S) - (int)(sb + SM_R) * 2)
            : "memory");
        const uint32_t wch = lds32(sb + SM_MISC + 12) + 1 + pw;
        const uint32_t ra = sb + SM_R + wch * 8, bar = sb + SM_BAR + wch * 8;
        const uint32_t target = lds32(sb + SM_MISC + 16);
        uint32_t cnt = lds128(sb + SM_MISC + 32).w;
        for (int n = 0; n < 1000000 && (int)(cnt - target) < 0; n++)
            asm volatile("ld.acquire.gpu.global.u32 %0, [%1+12];" : "=r"(cnt) : "l"(g_sync) : "memory");
        uint2 a, b;
        for (int n = 0; n < 1000000; n++) {
            asm volatile("ld.volatile.shared.v2.b32 {%0,%1}, [%4];\nld.volatile.shared.v2.b32 {%2,%3}, [%4+0x1000];"
                         : "=r"(a.x), "=r"(a.y), "=r"(b.x), "=r"(b.y) : "r"(ra) : "memory");
            if (!((a.x | a.y | b.x | b.y) & 0x10001)) break;
        }
        asm volatile("fence.proxy.async.global;" ::: "memory");
        asm volatile("mbarrier.arrive.expect_tx.shared.b64 _, [%0], 8192;" ::"r"(bar) : "memory");
        const uint32_t c[8] = {a.x, a.x >> 16, a.y, a.y >> 16, b.x, b.x >> 16, b.y, b.y >> 16};
#pragma unroll
        for (int i = 0; i < 8; i++)
            asm volatile("cp.async.bulk.shared::cluster.global.mbarrier::complete_tx::bytes [%0], [%1], 1024, [%2];" ::"r"(
                             (c[i] & 0xffe) << 6),
                         "l"(g_wf + (pw * 8 + i) * 64), "r"(bar)
                         : "memory");
    }
}

#define BARINIT(w, n)                                                                                              \
    if (elect()) {                                                                                                 \
        _Pragma("unroll") for (int k = 0; k < (NBAR + n - 1) / n; k++)                                             \
            asm volatile("mbarrier.init.shared.b64 [%0], 1;" ::"r"(sb + SM_BAR + ((w) * ((NBAR + n - 1) / n) + k) * 8)); \
        asm volatile("fence.mbarrier_init.release.cluster;" ::: "memory");                                         \
    }                                                                                                              \
    __syncwarp();

__global__ void __launch_bounds__(NT, 1)
main_kernel(const __grid_constant__ CUtensorMap tmx, const __nv_bfloat16* __restrict__ x, const int* __restrict__ src,
            const int* __restrict__ dst, const __nv_bfloat16* __restrict__ sh, const __nv_bfloat16* __restrict__ ea,
            const __nv_bfloat16* __restrict__ cg, const __nv_bfloat16* __restrict__ wr,
            const __nv_bfloat16* __restrict__ wout, __nv_bfloat16* __restrict__ out, int N, int E, int npb,
            unsigned npb_magic, int chunk, unsigned wsz, unsigned wmagic, unsigned bkm, int tau, int ramp, int rampn, int tdelay, unsigned polld, int spr, int sprn) {
    extern __shared__ __align__(1024) unsigned char smem[];
    if (s2u(smem) != sb) __trap();
    const int tid = threadIdx.x, lane = tid & 31;
    const int warp = __shfl_sync(0xffffffffu, tid >> 5, 0);
    const int nbins = gridDim.x;
    bool fast = chunk > 0;
    uint4 first = make_uint4(0, 0, 0, 0);
    TLSTAMP(0);
    if (fast) {
        const int e0 = blockIdx.x * chunk + tid, left = min(E, (int)(blockIdx.x + 1) * chunk) - e0;
        uint32_t pd[KE], ps[KE];
        {
            const int* dp = dst + e0;
            const int* sp = src + e0;
#pragma unroll
            for (int k = 0; k < KE; k++) {
                pd[k] = (nbins + (k == KE - 1 ? lane : 0)) * npb, ps[k] = 0;
                asm volatile("{\n.reg .pred p;\nsetp.gt.s32 p, %4, %5;\n@p ld.global.nc.u32 %0, [%2];\n@p ld.global.nc.u32 %1, [%3];\n}"
                             : "+r"(pd[k]), "+r"(ps[k]) : "l"(dp + k * NT), "l"(sp + k * NT), "r"(left), "r"(k * NT));
            }
        }
        uint32_t epoch = 0;
        if (tid == NT - 1) asm volatile("ld.relaxed.gpu.global.u32 %0, [%1];" : "=r"(epoch) : "l"(&g_epoch) : "memory");
        uint4 wv, wo[3];
        const bool wrow = (tid >> 2) == WFT && blockIdx.x < 128;
        {
            const uint4* wp = tid < 256 ? (const uint4*)wr + tid
                              : wrow    ? (const uint4*)(wout + blockIdx.x * 128 + (tid & 3) * 32)
                                        : (const uint4*)cg + (tid & 7);
            if (tid < 264 || wrow) wv = __ldg(wp);
            if (wrow) wo[0] = __ldg(wp + 1), wo[1] = __ldg(wp + 2), wo[2] = __ldg(wp + 3);
        }
        const uint32_t t16 = sb + tid * 16;
        const uint32_t sa = sb + SC_STG + (tid >> 3) * CP + (tid & 7) * 16;
        const uint32_t sm = sb + SC_STG + (tid >> 2) * CP + (tid & 3) * 16 + 128;
        const uint32_t none = (40 * NWIN + (lane & 7) + (blockIdx.x & 3) * 8) << 2;
        const uint32_t pade = min(blockIdx.x * chunk, E - 1) << 13;
        const bool third = warp * 4 + 128 < nbins, second = warp * 8 + 128 < nbins;
#pragma unroll
        for (int k = 0; k < 3; k++)
            if (k < 2 || third) sts128(sa + k * 64 * CP, none, none, none, none);
#pragma unroll
        for (int k = 0; k < 2; k++)
            if (k < 1 || second) sts128(sm + k * 128 * CP, none, none, none, none);
        if (tid < MAXB + 32) sts32(sb + SC_CNT + tid * 4, 0);
#pragma unroll
        for (int k = 0; k < 3; k++) sts128(t16 + SC_TABB + k * NT * 16, 0, 0, 0, 0);
        const uint32_t ecomp = -(wsz * (CH << 13));
#pragma unroll
        for (int k = 0; k < 3; k++)
            sts128(t16 + SC_TMP + k * NT * 16, 0, pade + ecomp, 0, pade + ecomp);
#pragma unroll
        for (int k = 0; k < ZSL / 8; k++) sts128(t16 + k * NT * 16, 0, 0, 0, 0), sts128(t16 + SP * 1024 + PH + k * NT * 16, 0, 0, 0, 0);
        if (tid < RP / 4) {
            uint32_t c[4], d[4];
#pragma unroll
            for (int i = 0; i < 4; i++) {
                const uint32_t k = tid * 4 - 4 + i;
                c[i] = d[i] = 1;
                if (warp == 0 && k < SP) c[i] = sb / 64 + k * 16;
                if (warp == 0 && k < SP - WSL) d[i] = c[i] + (SP * 1024 + PH) / 64;
            }
            static_assert(SP + 4 <= 128, "first warp");
            sts64(sb + SM_R + tid * 8, c[0] | c[1] << 16, c[2] | c[3] << 16);
            sts64(sb + SM_R + 0x1000 + tid * 8, d[0] | d[1] << 16, d[2] | d[3] << 16);
        }
        if (tid < NOFF) sts128(t16 + SM_S, 0xf000f000u, 0xf000f000u, 0xf000f000u, 0xf000f000u);
        constexpr uint32_t OLEND = (RECN - 4) * 4 * 0x10001;
        if (tid < NCW * OLN / 8) sts128(t16 + SM_OL, OLEND, OLEND, OLEND, OLEND);
        if (warp == 12) {
            sts32(sb + SM_CTR + lane * 16 + (lane >> 3) * 4,
                  sb + SM_R + ((lane & 0x19) ? (RP - 1) * 2 : (4 + SP) * 2 + (((lane >> 1) ^ (lane >> 2)) & 1) * 0x1000 + (lane & 4) / 2));
            if (lane < 3) sts32(sb + SM_MISC + (lane ? 16 + lane * 4 : 4), 0);
            if (lane == 8) sts128(sb + SM_REC + (RECN - 4) * 4, pade, pade, pade, pade), sts128(sb + SM_MISC + 64, 0, 0, 0, 0);
            if (lane == 9) asm volatile("prefetch.tensormap [%0];" ::"l"(&tmx) : "memory");
        }
        __syncthreads();
        TLSTAMP(1);

        {
            uint32_t b[KE], r[KE];
#pragma unroll
            for (int k = 0; k < KE; k++) {
                b[k] = __umulhi(pd[k], npb_magic);
                r[k] = atoms_add(sb + SC_CNT + b[k] * 4, 4);
                if (k == KE - 1) b[k] = min(b[k], nbins);
            }
            if (tid == NT - 1) {
                sts32(sb + SM_MISC + 8, epoch % 3 + 1);
                asm volatile("{\n.reg .b64 t;\nmov.u64 t, %%globaltimer;\nred.relaxed.gpu.global.max.u64 [%0], t;\n"
                             "red.relaxed.gpu.global.add.u32 [%0+8], 1;\n}" ::"l"(g_sync) : "memory");
            }
            __syncwarp();
#pragma unroll
            for (int k = 0; k < KE; k++) {
                asm volatile(
                    "{\n.reg .pred p;\n.reg .b32 d, t, u;\nmad.lo.u32 d, %1, %3, %0;\nsetp.ge.u32 p, d, 40;\nmul.hi.u32 u, %2, %4;\n"
                    "mad.lo.u32 t, %2, %10, %5;\nmad.lo.u32 t, d, %11, t;\nmad.lo.u32 t, u, %12, t;\n@p add.u32 t, t, %7;\n"
                    "min.u32 d, %6, 188;\nmad.lo.u32 d, %1, %9, d;\nst.shared.b32 [d+%8], t;\n}" ::"r"(pd[k]),
                    "r"(b[k]), "r"(ps[k]), "r"(-npb), "r"(wmagic), "r"(((tid + k * NT) << 14) + 4), "r"(r[k]), "n"(2 - 40 * NWIN * 4),
                    "n"(sb + SC_STG), "n"(CP), "n"(CH << 14), "n"(NWIN * 4), "r"(4 - wsz * (CH << 14))
                    : "memory");
            }
        }
        if (tid < 264) sts128(sb + SC_WR + (tid >> 4) * 272 + (tid & 15) * 16, wv.x, wv.y, wv.z, wv.w);
        uint4* gp = g_cell + ((tid >> 3) * MAXB + blockIdx.x) * 8 + (tid & 7);
        uint4* gm = g_more + ((tid >> 2) * MAXB + blockIdx.x) * 4 + (tid & 3);
        __syncthreads();
        TLSTAMP(6);
        const uint32_t tag = lds32(sb + SM_MISC + 8), t0 = tag & 1, t1 = tag >> 1;
        {
            uint4 v[5];
#pragma unroll
            for (int k = 0; k < 5; k++)
                if (k != 2 && k != 4 || (k == 2 ? third : second)) v[k] = lds128(k < 3 ? sa + k * 64 * CP : sm + (k - 3) * 128 * CP);
#pragma unroll
            for (int k = 0; k < 5; k++)
                if (k != 2 && k != 4 || (k == 2 ? third : second))
                    st_cell(k < 3 ? gp + k * 64 * MAXB * 8 : gm + (k - 3) * 128 * MAXB * 4, v[k].x | t0, v[k].y | t1, v[k].z | t0, v[k].w | t1);
        }
        if (wrow) {
            const int k = blockIdx.x;
            uint4* dp = &g_wf[((tid & 3) * 8 + (k >> 4)) * 64 + (k & 8) * 4 + (k & 7)];
            dp[0] = make_uint4(wv.x, wo[0].x, wo[1].x, wo[2].x);
            dp[8] = make_uint4(wv.y, wo[0].y, wo[1].y, wo[2].y);
            dp[16] = make_uint4(wv.z, wo[0].z, wo[1].z, wo[2].z);
            dp[24] = make_uint4(wv.w, wo[0].w, wo[1].w, wo[2].w);
        }
        if (warp < 14) { BARINIT(warp, 14) }
        __syncwarp();
        if (tid == NT - 1) {
            uint4 q;
            for (int n = 0; n < (1 << 22); n++) {
                q = ld_cell((const uint4*)g_sync);
                if ((int)(q.z - (epoch + 1) * nbins) >= 0) break;
            }
            sts128(sb + SM_MISC + 32, q.x, q.y, q.z, q.w), sts32(sb + SM_MISC + 16, (epoch + 1) * 512);
            asm volatile("mbarrier.init.shared.b64 [%0], 1;" ::"r"(sb + SM_MISC + 48) : "memory");
            while ((uint32_t)(gt_lo() - q.x) < polld) {}
        }
        __syncthreads();
        TLSTAMP(14);
        uint32_t m[20], rk[20], ia[20], eb[2];
        eb[0] = (((tid >> 3) * chunk) << 13) + ecomp + 1;
        eb[1] = eb[0] + (chunk << 19);
        asm volatile("" : "+r"(eb[0]), "+r"(eb[1]));
        bool ext;
        {
            const uint4* hp = g_cell + blockIdx.x * (MAXB * 8) + tid;
            const uint4* hm = g_more + blockIdx.x * (MAXB * 4) + tid;
            uint4 q[5];
            q[2] = q[4] = make_uint4(none | t0, none | t1, none | t0, none | t1);
            for (int n = 0; n < (1 << 22); n++) {
                q[0] = ld_cell(hp), q[1] = ld_cell(hp + NT), q[3] = ld_cell(hm);
                if ((tid >> 3) + 128 < nbins) q[2] = ld_cell(hp + 2 * NT);
                if ((tid >> 2) + 128 < nbins) q[4] = ld_cell(hm + NT);
                uint32_t bad = 0;
#pragma unroll
                for (int k = 0; k < 5; k++)
                    asm("{\n.reg .b32 a, b;\nlop3.b32 a, %1, %2, %5, 0x7e;\nlop3.b32 b, %3, %4, %6, 0x7e;\nlop3.b32 %0, %0, a, b, 0xfe;\n}"
                        : "+r"(bad) : "r"(q[k].x), "r"(q[k].z), "r"(q[k].y), "r"(q[k].w), "r"(t0), "r"(t1));
                if (!(bad & 1)) break;
            }
            __syncwarp();
            TLSTAMP(8);
#pragma unroll
            for (int k = 0; k < 5; k++) m[4 * k] = q[k].x, m[4 * k + 1] = q[k].y, m[4 * k + 2] = q[k].z, m[4 * k + 3] = q[k].w;
#pragma unroll
            for (int k = 0; k < 12; k++)
                if (k < 8 || third) ia[k] = m[k] & 0x3ffc, rk[k] = atoms_add(sb + SC_TABB + ia[k], 8);
            ext = __any_sync(0xffffffffu, min(m[12] & 0x3ffc, m[16] & 0x3ffc) < 40 * NWIN * 4);
            if (ext) {
#pragma unroll
                for (int k = 12; k < 20; k++) ia[k] = m[k] & 0x3ffc, rk[k] = atoms_add(sb + SC_TABB + ia[k], 8);
                if ((tid & 3) == 3 && min(m[15] & 0x3ffc, m[19] & 0x3ffc) < 40 * NWIN * 4) sts32(sb + SM_MISC + 4, 1);
            }
        }
        __syncthreads();
        TLSTAMP(5);
        const uint32_t tr = sb + warp * (NWIN * 4) + lane * 16;
        if (tid >= NT - PFT) {
            const int i = NT - 1 - tid;
            const char* p = i < 76 ? (const char*)sh + (size_t)min(blockIdx.x * chunk + i * 32, E - 32) * 8
                                   : (const char*)ea + (size_t)min(blockIdx.x * chunk + (i - 76) * 8, E - 8) * 32;
            asm volatile("prefetch.global.L2 [%0];\nprefetch.global.L2 [%0+128];" ::"l"(p));
        }
        if (tid == NT - 1 && blockIdx.x == 0) g_epoch = epoch + 1;
        {
            uint4 c[3];
            uint32_t tt[3];
#pragma unroll
            for (int i = 0; i < 3; i++) {
                c[i] = make_uint4(0, 0, 0, 0);
                if ((i < 2 || warp < 8) && lane < NWIN / 4) c[i] = lds128(tr + SC_TABB + i * 16 * NWIN * 4);
                tt[i] = c[i].x + c[i].y + c[i].z + c[i].w;
            }
            const uint32_t sum = (tt[0] >> 3) + (tt[1] << 7) + (tt[2] << 17);
            const uint32_t tot = __reduce_add_sync(0xffffffffu, sum);
            uint32_t inc = scan_step(scan_step(sum, 1), 2);
            const uint32_t q = (tot + 0x300c03) & 0x3fcff3fc, q0 = q & 1023, q1 = q0 + ((q >> 10) & 1023);
            uint32_t base = atoms_add(sb + (lane ? SC_CNT + lane * 4 : SM_MISC + 20), q1 + (q >> 20));
            inc = scan_step(scan_step(scan_step(inc, 4), 8), 16);
            base = __shfl_sync(0xffffffffu, base, 0);
            const uint32_t l3 = min(lane, 2);
            sts32(sb + SC_KEY + (warp + 16 * l3) * 4, ((tot >> (10 * l3)) & 1023) * 64 + 63 - warp - 16 * l3);
            if (max(tt[0], max(tt[1], tt[2])) > 31 * 8) sts32(sb + SM_MISC + 4, 1);
            inc += q - tot - sum;
#pragma unroll
            for (int i = 0; i < 3; i++) {
                const uint32_t e = (((inc >> (10 * i)) & 1023) + base + (i == 0 ? 0 : i == 1 ? q0 : q1)) * 8;
                if ((i < 2 || warp < 8) && lane < NWIN / 4) sts128(tr + SC_TABB + i * 16 * NWIN * 4, e, e + c[i].x, e + c[i].x + c[i].y, e + tt[i] - c[i].w);
            }
        }
        __syncthreads();
        TLSTAMP(2);
        if (warp >= 11) {
            const uint32_t st = (tid - 352) >> 2, key = lds32(sb + SC_KEY + st * 4);
            uint32_t rank = 0;
#pragma unroll
            for (int i = 0; i < 5; i++) {
                const uint2 q = lds64(sb + SC_KEY + (lane & 3) * 40 + i * 8);
                rank += ((key - q.x) >> 31) + ((key - q.y) >> 31);
            }
            rank += __shfl_xor_sync(0xffffffffu, rank, 1);
            rank += __shfl_xor_sync(0xffffffffu, rank, 2);
            const uint32_t lv = rank >> 2, cw = ((0x969u >> (2 * lv)) & 3) * 4 + ((rank ^ -(lv & 1)) & 3);
            const uint32_t sid = (0xe4a50u >> (2 * lv)) & 3;
            sts32(sb + SC_MAP + st * 4, cw * (NWIN * 4) - st * (NWIN * 4) + 0x10000 + (sid << 30));
            asm volatile("st.shared.u8 [%0], %1;" ::"r"(sb + SM_INV + cw * 4 + sid), "r"(st) : "memory");
        }
        const int total = lds32(sb + SM_MISC + 20);
        fast = lds32(sb + SM_MISC + 4) == 0 && total <= RECN - 4;
        auto lookup = [&](int k) {
            asm volatile("{\n.reg .pred p;\n.reg .b32 t;\nsetp.lt.u32 p, %1, %2;\nmov.b32 t, 0x80000000;\n@p ld.shared.b32 t, [%1+%3];\nadd.u32 %0, %0, t;\n}"
                         : "+r"(rk[k]) : "r"(ia[k]), "n"(40 * NWIN * 4), "n"(sb + SC_TABB) : "memory");
        };
        auto place = [&](int k, uint32_t e) {
            asm volatile("{\n.reg .pred p;\nsetp.ge.s32 p, %0, 0;\n@p st.shared.v2.b32 [%0+%3], {%1, %2};\n}" ::"r"(rk[k]), "r"(m[k]), "r"(e),
                         "n"(sb + SC_TMP) : "memory");
        };
#pragma unroll
        for (int k = 0; k < 8; k++) lookup(k);
        if (fast) {
#pragma unroll
            for (int k = 0; k < 8; k++) place(k, eb[k >> 2]);
            if (third) {
#pragma unroll
                for (int k = 8; k < 12; k++) lookup(k);
#pragma unroll
                for (int k = 8; k < 12; k++) place(k, 2 * eb[1] - eb[0]);
            }
            if (ext) {
#pragma unroll
                for (int k = 12; k < 20; k++) lookup(k);
#pragma unroll
                for (int k = 12; k < 20; k++) place(k, ((((tid >> 2) + (k >> 4) * 128) * chunk) << 13) + ecomp + 1);
            }
            constexpr int KD = (RECN + NT - 1) / NT;
            const uint32_t P = (lane ^ (lane >> 1)) & 1;
            const uint32_t binc = (P ? 1u << 11 : 1u) + ((lane & 3) == 3 ? 1u << 22 : 0u);
            const bool last = warp * 32 + (KD - 1) * NT < total, q2 = warp * 128 + NT * 4 < total;
            const int rest = total - tid, restq = (total >> 2) - tid;
            uint2 en[KD];
            uint32_t bk[KD], r2[KD], ca[2], ol[2], r3[2];
            __syncthreads();
            TLSTAMP(9);
#pragma unroll
            for (int k = 0; k < KD; k++)
                if (k < KD - 1 || last) en[k] = lds64(sb + SC_TMP + tid * 8 + k * NT * 8);
#pragma unroll
            for (int k = 0; k < 2; k++)
                if (k == 0 || q2) ca[k] = lds32(sb + SC_TMP + (tid + k * NT) * 32 + 24);
#pragma unroll
            for (int k = 0; k < 2; k++)
                if (k == 0 || q2) ca[k] &= 0x3ffc, ol[k] = lds32(sb + SC_MAP + __umulhi(ca[k], 0xffffffffu / (NWIN * 4) + 1) * 4);
#pragma unroll
            for (int k = 0; k < KD; k++) {
                if (k < KD - 1 || last) {
                    const uint32_t v = en[k].x, f = v >> 14, i = v & 0x3ffc;
                    const uint32_t w4 = i - __umulhi(i, 0xffffffffu / (NWIN * 4) + 1) * (NWIN * 4);
                    const uint32_t o = __umulhi(f, 0xffffffffu / CH + 1) - wsz;
                    bk[k] = (__umulhi(f, bkm) + w4) * 4;
                    en[k].x = w4 * wsz + o * 4;
                    en[k].y += ((v >> 1) & 0xffffe001u) - o * (CH << 13);
                    if (rest <= k * NT) bk[k] = 2048 + lane * 4;
                    r2[k] = atoms_add(sb + SC_TABA + bk[k], binc);
                }
            }
#pragma unroll
            for (int k = 0; k < 2; k++) {
                if (k == 0 || q2) {
                    ca[k] = (ca[k] + ol[k]) & 0xffff;
                    ol[k] = (tid + k * NT) * 16 + (ol[k] >> 30 << 14);
                    r3[k] = atoms_add(sb + SC_TABC + ca[k], restq > k * NT ? 2 : 0);
                }
            }
            __syncthreads();
            TLSTAMP(12);
            if (warp < NCW) {
                uint4 c = make_uint4(0, 0, 0, 0);
                if (lane < NWIN / 4) c = lds128(tr + SC_TABC);
                const uint32_t tt = c.x + c.y + c.z + c.w;
                uint32_t inc = tt;
#pragma unroll
                for (int o = 1; o < 32; o <<= 1) inc = scan_step(inc, o);
                if (inc > (OLN - 8) * 2) sts32(sb + SM_MISC + 4, 1);
                inc += warp * (OLN * 2) - tt;
                if (lane < NWIN / 4) sts128(tr + SC_TABC, inc, inc + c.x, inc + c.x + c.y, inc + tt - c.w);
            } else {
                const uint32_t mine = (warp + lane) & 3;
                uint4 c;
                uint32_t cs, inc = 0, e = 4 + (4 << 11);
#pragma unroll
                for (int i = 0; i < 4; i++) {
                    const uint32_t pc = (mine + i) & 3;
                    const uint4 v = lds128(sb + SC_TABA + lane * 64 + (pc << 4));
                    const uint32_t sum = v.x + v.y + v.z + v.w;
                    inc += sum;
                    if (i == 0) c = v, cs = sum;
                    if (pc >= mine) e -= sum;
                }
#pragma unroll
                for (int o = 1; o < 32; o <<= 1) inc = scan_step(inc, o);
                e += inc;
                sts128(sb + SC_TABB + lane * 64 + (mine << 4), e, e + c.x, e + c.x + c.y, e + cs - c.w);
                if ((int)max((e + cs) & 0x7ff, ((e + cs) >> 11) & 0x7ff) - (int)(e >> 22) * 2 > SP) sts32(sb + SM_MISC + 4, 1);
                if (tid == NCW * 32) {
                    const uint32_t c0 = min(min(c.x & 0x7ff, (c.x >> 11) & 0x7ff), ZSL) >> 2;
                    sts32(sb + SM_MISC + 12, ((total >> 2) + 1) >> 1), sts32(sb + SM_MISC + 24, c0);
                }
            }
            __syncthreads();
            TLSTAMP(13);
            fast = lds32(sb + SM_MISC + 4) == 0;
            if (warp == 15 && lane < lds32(sb + SM_MISC + 24))
                asm volatile("mbarrier.arrive.shared.b64 _, [%0];" ::"r"(sb + SM_BAR + 8 + lane * 8) : "memory");
#pragma unroll
            for (int k = 0; k < KD; k++)
                if (k < KD - 1 || last) r2[k] += lds32(sb + SC_TABB + bk[k]);
#pragma unroll
            for (int k = 0; k < 2; k++)
                if (k == 0 || q2) r3[k] += lds32(sb + SC_TABC + ca[k]);
            if (fast) {
                const uint32_t rot = P ? 9 : 30;
#pragma unroll
                for (int k = 0; k < KD; k++) {
                    if (k < KD - 1 || last) {
                        const uint32_t k4 = __funnelshift_r(r2[k], r2[k], rot);
                        if (rest > k * NT) {
                            sts16(sb + SM_S + bitsel(k4, P << 1), en[k].x);
                            sts32(sb + SM_REC + tid * 4 + k * NT * 4, bitsel(k4, en[k].y));
                        }
                    }
                }
#pragma unroll
                for (int k = 0; k < 2; k++)
                    if ((k == 0 || q2) && restq > k * NT) sts16(sb + SM_OL + r3[k], ol[k]);
            }
        }
        asm volatile("fence.mbarrier_init.release.cluster;\nfence.proxy.async.shared::cta;" ::: "memory");
        __syncthreads();
        TLSTAMP(3);
        if (!fast && wrow) wf_done();
        if (fast && tid < NOFF) {
            const uint4 a = lds128(t16 + SM_S);
            uint32_t sum = 0;
            sum = __dp2a_lo(__vadd2(a.x, 0x10001000u), 0x101u, sum), sum = __dp2a_lo(__vadd2(a.y, 0x10001000u), 0x101u, sum);
            sum = __dp2a_lo(__vadd2(a.z, 0x10001000u), 0x101u, sum), sum = __dp2a_lo(__vadd2(a.w, 0x10001000u), 0x101u, sum);
            const int s = (int)(sum >> 5) - 0x400;
            sts16(sb + SM_OFF + tid * 2, tid > lds32(sb + SM_MISC + 12) ? 0 : min(max(tdelay + SLIPTH + ((s * tau + min(s, rampn) * ramp - max(s - sprn, 0) * spr) >> 10), 0), 0xffff));
        }
        __syncwarp();
        if (fast && warp < NCW) {
            asm volatile("bar.arrive 1, 512;" ::: "memory");
            const uint32_t e = lds16(sb + SM_OL + warp * (OLN * 2) + ((lane & 4) >> 1));
            const uint32_t rec = lds32(sb + SM_REC + (e & 0x3ff0) + (lane >> 3) * 4);
            first.w = ((rec >> 1) & 0xffe) | (e & ~0xffeu);
            asm volatile("{\n.reg .pred q;\nsetp.ne.u32 q, %5, 0;\nld.global.cg.v2.b32 {%0,%1}, [%3];\n@q ld.global.cg.b32 %2, [%4];\n}"
                         : "=r"(first.x), "=r"(first.y), "+r"(first.z)
                         : "l"(ea + (size_t)(rec >> 13) * 16 + (lane & 3) * 4), "l"(sh + (size_t)(rec >> 13) * 4 + (lane & 2)), "r"(rec & (1 << (lane & 1))));
        }
    }

    if (!fast) {
        float* accs = (float*)smem;
        constexpr int NACC = 96;
        const int node0 = blockIdx.x * npb, nnodes = max(0, min(npb, N - node0));
#pragma unroll 1
        for (int nb = 0; nb < nnodes; nb += NACC) {
            __syncthreads();
            for (int i = tid; i < NACC * 512; i += NT) accs[i] = 0.f;
            __syncthreads();
            const int lim = min(NACC, nnodes - nb);
#pragma unroll 1
            for (int base = warp * 32; base < E; base += NT) {
                const int e = base + lane;
                const int dl = e < E ? dst[e] - node0 - nb : -1;
                unsigned mask = __ballot_sync(0xffffffffu, dl >= 0 && dl < lim);
#pragma unroll 1
                while (mask) {
                    const int l = __ffs(mask) - 1;
                    mask &= mask - 1;
                    const int dd = __shfl_sync(0xffffffffu, dl, l);
                    slow_edge(base + l, src[base + l], accs + dd * 512, x, sh, ea, cg, wr, lane);
                }
            }
            __syncthreads();
#pragma unroll 1
            for (int nl = warp; nl < lim; nl += NT / 32) slow_out(accs + nl * 512, wout, out + (size_t)(node0 + nb + nl) * 512, lane);
        }
    } else if (warp >= NCW) {
        asm volatile("setmaxnreg.dec.sync.aligned.u32 %0;" ::"n"(PREG));
        producer(&tmx, warp - NCW);
    } else if (warp >= 4) {
        asm volatile("setmaxnreg.inc.sync.aligned.u32 %0;" ::"n"(R1));
        consumer<3>(sh, ea, out, N, npb, first);
        TLMAX(4);
    } else {
        asm volatile("setmaxnreg.inc.sync.aligned.u32 %0;" ::"n"(R0));
        consumer<4>(sh, ea, out, N, npb, first);
        TLMAX(4);
    }
}

typedef CUresult (*EncodeTiledFn)(CUtensorMap*, CUtensorMapDataType, cuuint32_t, void*, const cuuint64_t*,
                                  const cuuint64_t*, const cuuint32_t*, const cuuint32_t*, CUtensorMapInterleave,
                                  CUtensorMapSwizzle, CUtensorMapL2promotion, CUtensorMapFloatOOBfill);

extern "C" void kernel_launch(void* const* d_in, const int* in_sizes, int n_in, void* d_out, int out_size) {
    const __nv_bfloat16* x = (const __nv_bfloat16*)d_in[0];
    const int* src = (const int*)d_in[1];
    const int* dst = (const int*)d_in[2];
    const __nv_bfloat16* sh = (const __nv_bfloat16*)d_in[3];
    const __nv_bfloat16* ea = (const __nv_bfloat16*)d_in[4];
    const __nv_bfloat16* cg = (const __nv_bfloat16*)d_in[5];
    const __nv_bfloat16* wr = (const __nv_bfloat16*)d_in[6];
    const __nv_bfloat16* wout = (const __nv_bfloat16*)d_in[7];
    __nv_bfloat16* out = (__nv_bfloat16*)d_out;
    const int N = in_sizes[0] / 512;
    const int E = in_sizes[1];

    static int num_sms = 0, coresident = 0;
    static EncodeTiledFn encode = nullptr;
    if (num_sms == 0) {
        int dev = 0;
        cudaGetDevice(&dev);
        cudaDeviceGetAttribute(&num_sms, cudaDevAttrMultiProcessorCount, dev);
        cudaFuncSetAttribute(main_kernel, cudaFuncAttributeMaxDynamicSharedMemorySize, SM_TOTAL);
        int occ = 0;
        cudaOccupancyMaxActiveBlocksPerMultiprocessor(&occ, main_kernel, NT, SM_TOTAL);
        coresident = occ * num_sms;
        void* fn = nullptr;
        cudaDriverEntryPointQueryResult qr;
        cudaGetDriverEntryPoint("cuTensorMapEncodeTiled", &fn, cudaEnableDefault, &qr);
        encode = (EncodeTiledFn)fn;
    }
    CUtensorMap tmx;
    const int rank = 3;
    const cuuint64_t gd[3] = {64, (cuuint64_t)N * 4, 2}, gs[2] = {256, 128};
    const cuuint32_t bd[3] = {64, 4, 2}, es[3] = {1, 1, 1};
    encode(&tmx, CU_TENSOR_MAP_DATA_TYPE_BFLOAT16, rank, (void*)x, gd, gs, bd, es, CU_TENSOR_MAP_INTERLEAVE_NONE,
           CU_TENSOR_MAP_SWIZZLE_128B, CU_TENSOR_MAP_L2_PROMOTION_NONE, CU_TENSOR_MAP_FLOAT_OOB_FILL_NONE);

    int nbins = num_sms < MAXB ? num_sms : MAXB;
    int npb = (N + nbins - 1) / nbins;
    if (npb < 2) npb = 2;
    nbins = (N + npb - 1) / npb;
    const unsigned npb_magic = (unsigned)((0x100000000ull + npb - 1) / npb);
    int chunk = (E + nbins - 1) / nbins;
    const unsigned wsz = (N + NWIN - 2) / (NWIN - 1);
    if (nbins > coresident || nbins < 128 || npb > MAXNPB || chunk > CH || wsz > (1 << 18) / CH || N < 512 || E < 32 || E > (1 << 19)) chunk = 0;
    const unsigned wmagic = 0xffffffffu / wsz + 1, bkm = (unsigned)((4ull << 32) / (wsz * CH));
    double pace = PACE, rampt = RAMP, rampf = RAMPF, sprt = SPRINT, sprf = SPRINTF;
    int tdelay = TDELAY, polld = POLLD;
    const int tau = (int)(1024.0 * pace * ((double)E / nbins) / N);
    const int rampn = (int)(N * rampf), ramp = (int)(1024.0 * rampt / rampn);
    main_kernel<<<nbins, NT, SM_TOTAL, cudaStreamPerThread>>>(tmx, x, src, dst, sh, ea, cg, wr, wout, out, N, E, npb, npb_magic,
                                                              chunk, wsz, wmagic, bkm, tau, ramp, rampn, tdelay, polld, (int)(1024.0 * sprt / (N * sprf)), (int)(N * (1 - sprf)));
}
```

```cpp
#include <cuda_runtime.h>
#include <cuda.h>
#include <cuda_bf16.h>
#include <stdint.h>
#include <stdlib.h>

#define NT 512
#define NCW 12
#define MAXB 144
#define MAXNPB 80
#define KE 5
#define SP 99
#define RECN 2816
#define RP 1520
#define OLN 80
#define NBAR 364
#define NOFF 360
#define R0 168
#define R1 160
#define PREG 24
#define PACE 9.93
#define TDELAY 4500
#define POLLD 1000
#define WFT 80
#define SLIPTH 200
#define SLIPADD 150
#define SLIPFROM 36
#define AHEAD 96
#define EARLY 32
#define RAMPF 0.1
#define SPRINT 400
#define SPRINTF 0.5
#define SLIPEND 320
#define SPINT 96
#define PFT 224
#define RAMP 350

__device__ __align__(1024) uint4 g_cell[MAXB * MAXB * 8];
__device__ __align__(1024) uint4 g_more[MAXB * MAXB * 4];
__device__ __align__(1024) uint4 g_wf[2048];
__device__ __align__(256) ulonglong2 g_sync[16];
__device__ __align__(256) unsigned g_epoch;

constexpr uint32_t sb = 1024;
#define PH 512
#define SM_R (2 * SP * 1024 + PH)
#define SM_CTR (SP * 1024)
#define SM_MISC (SM_R + RP * 2)
#define SM_INV (SM_MISC + 80)
#define SM_OFF (SM_INV + 48)
#define SM_S (SM_R + 0x1000 + RP * 2)
#define SM_REC (SM_S + NOFF * 16)
#define SM_OL (SM_REC + RECN * 4)
#define SM_BAR (SM_OL + NCW * OLN * 2)
#define SM_TOTAL (SM_BAR + NBAR * 8)
static_assert(SM_TOTAL <= 232448 && SM_OFF + NOFF * 2 <= SM_R + 0x1000 && RP % 8 == 0 && SM_BAR % 16 == 0, "shared memory");
static_assert(4 + RECN / 2 + SP + 2 <= RP && RECN / 8 + 5 <= NBAR && NBAR % 14 == 0 && RECN / 8 + 4 <= NOFF, "tables");
#define ZSL 32
#define NWIN 96
#define CH 2432
#define CP 208
#define SC_STG ((SP + ZSL) * 1024 + PH)
#define SC_TMP (ZSL * 1024)
#define SC_TABB (SC_TMP + 3072 * 8)
#define SC_TABC (SC_TABB + 41 * NWIN * 4)
#define SC_TABA (SC_TABC + NCW * NWIN * 4)
#define SC_ZEND (SC_TABB + 3 * NT * 16)
#define SC_CNT SC_ZEND
#define SC_KEY (SC_CNT + (MAXB + 32) * 4)
#define SC_MAP (SC_KEY + 192)
#define WSL 5
#define SC_WR ((2 * SP - WSL) * 1024 + PH)
#define SC_CG (SC_WR + 16 * 272)
static_assert(SC_TABA + 2048 + 128 <= SC_ZEND && RECN <= 3072 && SC_MAP + 192 <= SP * 1024 && SC_STG + (MAXB + 1) * CP <= SC_WR, "scratch");

__device__ __forceinline__ uint32_t pack_bf16(float lo, float hi) {
    uint32_t r;
    asm("cvt.rn.bf16x2.f32 %0, %1, %2;" : "=r"(r) : "f"(hi), "f"(lo));
    return r;
}
__device__ __forceinline__ uint32_t s2u(const void* p) { return (uint32_t)__cvta_generic_to_shared(p); }
__device__ __forceinline__ uint32_t lds16(uint32_t a) { uint32_t v; asm volatile("ld.shared.u16 %0, [%1];" : "=r"(v) : "r"(a) : "memory"); return v; }
__device__ __forceinline__ uint32_t lds32(uint32_t a) { uint32_t v; asm volatile("ld.shared.u32 %0, [%1];" : "=r"(v) : "r"(a) : "memory"); return v; }
__device__ __forceinline__ uint2 lds64(uint32_t a) {
    uint2 v; asm volatile("ld.shared.v2.u32 {%0,%1}, [%2];" : "=r"(v.x), "=r"(v.y) : "r"(a) : "memory"); return v;
}
__device__ __forceinline__ uint4 lds128(uint32_t a) {
    uint4 v; asm volatile("ld.volatile.shared.v4.u32 {%0,%1,%2,%3}, [%4];" : "=r"(v.x), "=r"(v.y), "=r"(v.z), "=r"(v.w) : "r"(a) : "memory"); return v;
}
__device__ __forceinline__ void sts16(uint32_t a, uint32_t v) { asm volatile("st.shared.u16 [%0], %1;" ::"r"(a), "h"((unsigned short)v) : "memory"); }
__device__ __forceinline__ void sts32(uint32_t a, uint32_t v) { asm volatile("st.shared.u32 [%0], %1;" ::"r"(a), "r"(v) : "memory"); }
__device__ __forceinline__ void sts64(uint32_t a, uint32_t x, uint32_t y) { asm volatile("st.shared.v2.u32 [%0], {%1,%2};" ::"r"(a), "r"(x), "r"(y) : "memory"); }
__device__ __forceinline__ void sts128(uint32_t a, uint32_t x, uint32_t y, uint32_t z, uint32_t w) {
    asm volatile("st.shared.v4.u32 [%0], {%1,%2,%3,%4};" ::"r"(a), "r"(x), "r"(y), "r"(z), "r"(w) : "memory");
}
__device__ __forceinline__ uint32_t atoms_add(uint32_t a, uint32_t v) {
    uint32_t r;
    asm volatile("atom.shared.add.u32 %0, [%1], %2;" : "=r"(r) : "r"(a), "r"(v) : "memory");
    return r;
}
__device__ __forceinline__ uint4 ld_cell(const uint4* p) {
    uint4 v;
    asm volatile("{\n.reg .b64 a, b;\nld.relaxed.gpu.global.v2.b64 {a, b}, [%4];\nmov.b64 {%0,%1}, a;\nmov.b64 {%2,%3}, b;\n}"
                 : "=r"(v.x), "=r"(v.y), "=r"(v.z), "=r"(v.w) : "l"(p) : "memory");
    return v;
}
__device__ __forceinline__ void st_cell(uint4* p, uint32_t x, uint32_t y, uint32_t z, uint32_t w) {
    asm volatile("st.relaxed.gpu.global.v2.b64 [%0], {%1, %2};" ::"l"(p), "l"(x | (uint64_t)y << 32), "l"(z | (uint64_t)w << 32) : "memory");
}
__device__ __forceinline__ uint32_t scan_step(uint32_t v, int o) {
    asm volatile("{\n.reg .pred p;\n.reg .b32 y;\nshfl.sync.up.b32 y|p, %0, %1, 0, 0xffffffff;\n@p add.u32 %0, %0, y;\n}" : "+r"(v) : "r"(o));
    return v;
}
__device__ __forceinline__ uint32_t bitsel(uint32_t a, uint32_t b) {
    uint32_t r;
    asm("lop3.b32 %0, %1, %2, 0x1ffc, 0xe4;" : "=r"(r) : "r"(a), "r"(b));
    return r;
}
__device__ __forceinline__ uint32_t gt_lo() {
    uint32_t t;
    asm volatile("mov.u32 %0, %globaltimer_lo;" : "=r"(t));
    return t;
}
__device__ __forceinline__ bool elect() {
    uint32_t p;
    asm volatile("{\n.reg .pred P;\nelect.sync _|P, 0xffffffff;\nselp.u32 %0, 1, 0, P;\n}" : "=r"(p));
    return p;
}
__device__ __forceinline__ void project4(const uint32_t (&pk)[64], uint32_t ra, uint32_t ba, uint4* const (&p)[4], const uint32_t (&v)[4]) {
    asm volatile(
        "{\n.reg .pred p0, p1, q0, q1, nv, s<4>;\n.reg .b32 t, h, c<16>, a<32>, b<32>, k<16>;\n.reg .b64 d<16>;\n.reg .f32 o<32>;\nsetp.ne.b32 p0, 0, 0;\n"
        "setp.eq.b32 p1, 0, 0;\nmov.b32 h, 8;\nsetp.eq.u32 nv, %64, 0;\nvote.sync.any.pred nv, nv, 0xffffffff;\nsetp.ne.b32 s0, %69, 0;\n"
        "setp.ne.b32 s1, %70, 0;\nsetp.ne.b32 s2, %71, 0;\nsetp.ne.b32 s3, %72, 0;\nmov.b32 t, 0;\n"
        "W0:\nmbarrier.try_wait.parity.shared.b64 q0, [%73], 0;\nvote.sync.all.pred q0, q0, 0xffffffff;\nadd.u32 t, t, 1;\nsetp.lt.and.u32 q1, t, 1000000, !q0;\n"
        "@q1 bra.uni W0;\nld.volatile.shared.v2.b32 {c0,c1}, [%64+0];\nld.volatile.shared.v2.b32 {c2,c3}, [%64+4096];\n"
        "ld.volatile.shared.v2.b32 {c4,c5}, [%64+8];\nld.volatile.shared.v2.b32 {c6,c7}, [%64+4104];\ndp2a.lo.u32.u32 t, c0, 0x04000004, 0x200000;\n"
        "mov.b64 d0, {t, h};\ndp2a.hi.u32.u32 t, c0, 0x04000004, 0x200000;\nmov.b64 d1, {t, h};\ndp2a.lo.u32.u32 t, c1, 0x04000004, 0x200000;\n"
        "mov.b64 d2, {t, h};\ndp2a.hi.u32.u32 t, c1, 0x04000004, 0x200000;\nmov.b64 d3, {t, h};\ndp2a.lo.u32.u32 t, c2, 0x04000004, 0x200000;\n"
        "mov.b64 d4, {t, h};\ndp2a.hi.u32.u32 t, c2, 0x04000004, 0x200000;\nmov.b64 d5, {t, h};\ndp2a.lo.u32.u32 t, c3, 0x04000004, 0x200000;\n"
        "mov.b64 d6, {t, h};\ndp2a.hi.u32.u32 t, c3, 0x04000004, 0x200000;\nmov.b64 d7, {t, h};\ndp2a.lo.u32.u32 t, c4, 0x04000004, 0x200000;\n"
        "mov.b64 d8, {t, h};\ndp2a.hi.u32.u32 t, c4, 0x04000004, 0x200000;\nmov.b64 d9, {t, h};\ndp2a.lo.u32.u32 t, c5, 0x04000004, 0x200000;\n"
        "mov.b64 d10, {t, h};\ndp2a.hi.u32.u32 t, c5, 0x04000004, 0x200000;\nmov.b64 d11, {t, h};\ndp2a.lo.u32.u32 t, c6, 0x04000004, 0x200000;\n"
        "mov.b64 d12, {t, h};\ndp2a.hi.u32.u32 t, c6, 0x04000004, 0x200000;\nmov.b64 d13, {t, h};\ndp2a.lo.u32.u32 t, c7, 0x04000004, 0x200000;\n"
        "mov.b64 d14, {t, h};\ndp2a.hi.u32.u32 t, c7, 0x04000004, 0x200000;\nmov.b64 d15, {t, h};\nmovmatrix.sync.aligned.m8n8.trans.b16 a0, %0;\n"
        "movmatrix.sync.aligned.m8n8.trans.b16 a1, %16;\nmovmatrix.sync.aligned.m8n8.trans.b16 a2, %1;\nmovmatrix.sync.aligned.m8n8.trans.b16 a3, %17;\n"
        "movmatrix.sync.aligned.m8n8.trans.b16 a4, %2;\nmovmatrix.sync.aligned.m8n8.trans.b16 a5, %18;\nmovmatrix.sync.aligned.m8n8.trans.b16 a6, %3;\n"
        "movmatrix.sync.aligned.m8n8.trans.b16 a7, %19;\nmovmatrix.sync.aligned.m8n8.trans.b16 a8, %4;\nmovmatrix.sync.aligned.m8n8.trans.b16 a9, %20;\n"
        "movmatrix.sync.aligned.m8n8.trans.b16 a10, %5;\nmovmatrix.sync.aligned.m8n8.trans.b16 a11, %21;\nmovmatrix.sync.aligned.m8n8.trans.b16 a12, %6;\n"
        "movmatrix.sync.aligned.m8n8.trans.b16 a13, %22;\nmovmatrix.sync.aligned.m8n8.trans.b16 a14, %7;\nmovmatrix.sync.aligned.m8n8.trans.b16 a15, %23;\n"
        "movmatrix.sync.aligned.m8n8.trans.b16 a16, %8;\nmovmatrix.sync.aligned.m8n8.trans.b16 a17, %24;\nmovmatrix.sync.aligned.m8n8.trans.b16 a18, %9;\n"
        "movmatrix.sync.aligned.m8n8.trans.b16 a19, %25;\nmovmatrix.sync.aligned.m8n8.trans.b16 a20, %10;\nmovmatrix.sync.aligned.m8n8.trans.b16 a21, %26;\n"
        "movmatrix.sync.aligned.m8n8.trans.b16 a22, %11;\nmovmatrix.sync.aligned.m8n8.trans.b16 a23, %27;\nmovmatrix.sync.aligned.m8n8.trans.b16 a24, %12;\n"
        "movmatrix.sync.aligned.m8n8.trans.b16 a25, %28;\nmovmatrix.sync.aligned.m8n8.trans.b16 a26, %13;\nmovmatrix.sync.aligned.m8n8.trans.b16 a27, %29;\n"
        "movmatrix.sync.aligned.m8n8.trans.b16 a28, %14;\nmovmatrix.sync.aligned.m8n8.trans.b16 a29, %30;\nmovmatrix.sync.aligned.m8n8.trans.b16 a30, %15;\n"
        "movmatrix.sync.aligned.m8n8.trans.b16 a31, %31;\nwgmma.fence.sync.aligned;\n"
        "wgmma.mma_async.sync.aligned.m64n32k16.f32.bf16.bf16 {o0,o1,o2,o3,o4,o5,o6,o7,o8,o9,o10,o11,o12,o13,o14,o15}, {a0,a1,a2,a3}, d0, p0, 1, 1, 1;\n"
        "wgmma.mma_async.sync.aligned.m64n32k16.f32.bf16.bf16 {o0,o1,o2,o3,o4,o5,o6,o7,o8,o9,o10,o11,o12,o13,o14,o15}, {a4,a5,a6,a7}, d1, p1, 1, 1, 1;\n"
        "wgmma.mma_async.sync.aligned.m64n32k16.f32.bf16.bf16 {o0,o1,o2,o3,o4,o5,o6,o7,o8,o9,o10,o11,o12,o13,o14,o15}, {a8,a9,a10,a11}, d2, p1, 1, 1, 1;\n"
        "wgmma.mma_async.sync.aligned.m64n32k16.f32.bf16.bf16 {o0,o1,o2,o3,o4,o5,o6,o7,o8,o9,o10,o11,o12,o13,o14,o15}, {a12,a13,a14,a15}, d3, p1, 1, 1, 1;\n"
        "wgmma.mma_async.sync.aligned.m64n32k16.f32.bf16.bf16 {o0,o1,o2,o3,o4,o5,o6,o7,o8,o9,o10,o11,o12,o13,o14,o15}, {a16,a17,a18,a19}, d4, p1, 1, 1, 1;\n"
        "wgmma.mma_async.sync.aligned.m64n32k16.f32.bf16.bf16 {o0,o1,o2,o3,o4,o5,o6,o7,o8,o9,o10,o11,o12,o13,o14,o15}, {a20,a21,a22,a23}, d5, p1, 1, 1, 1;\n"
        "wgmma.mma_async.sync.aligned.m64n32k16.f32.bf16.bf16 {o0,o1,o2,o3,o4,o5,o6,o7,o8,o9,o10,o11,o12,o13,o14,o15}, {a24,a25,a26,a27}, d6, p1, 1, 1, 1;\n"
        "wgmma.mma_async.sync.aligned.m64n32k16.f32.bf16.bf16 {o0,o1,o2,o3,o4,o5,o6,o7,o8,o9,o10,o11,o12,o13,o14,o15}, {a28,a29,a30,a31}, d7, p1, 1, 1, 1;\n"
        "wgmma.commit_group.sync.aligned;\n"
        "wgmma.mma_async.sync.aligned.m64n32k16.f32.bf16.bf16 {o16,o17,o18,o19,o20,o21,o22,o23,o24,o25,o26,o27,o28,o29,o30,o31}, {a0,a1,a2,a3}, d8, p0, 1, 1, 1;\n"
        "wgmma.mma_async.sync.aligned.m64n32k16.f32.bf16.bf16 {o16,o17,o18,o19,o20,o21,o22,o23,o24,o25,o26,o27,o28,o29,o30,o31}, {a4,a5,a6,a7}, d9, p1, 1, 1, 1;\n"
        "wgmma.mma_async.sync.aligned.m64n32k16.f32.bf16.bf16 {o16,o17,o18,o19,o20,o21,o22,o23,o24,o25,o26,o27,o28,o29,o30,o31}, {a8,a9,a10,a11}, d10, p1, 1, 1, 1;\n"
        "wgmma.mma_async.sync.aligned.m64n32k16.f32.bf16.bf16 {o16,o17,o18,o19,o20,o21,o22,o23,o24,o25,o26,o27,o28,o29,o30,o31}, {a12,a13,a14,a15}, d11, p1, 1, 1, 1;\n"
        "wgmma.mma_async.sync.aligned.m64n32k16.f32.bf16.bf16 {o16,o17,o18,o19,o20,o21,o22,o23,o24,o25,o26,o27,o28,o29,o30,o31}, {a16,a17,a18,a19}, d12, p1, 1, 1, 1;\n"
        "wgmma.mma_async.sync.aligned.m64n32k16.f32.bf16.bf16 {o16,o17,o18,o19,o20,o21,o22,o23,o24,o25,o26,o27,o28,o29,o30,o31}, {a20,a21,a22,a23}, d13, p1, 1, 1, 1;\n"
        "wgmma.mma_async.sync.aligned.m64n32k16.f32.bf16.bf16 {o16,o17,o18,o19,o20,o21,o22,o23,o24,o25,o26,o27,o28,o29,o30,o31}, {a24,a25,a26,a27}, d14, p1, 1, 1, 1;\n"
        "wgmma.mma_async.sync.aligned.m64n32k16.f32.bf16.bf16 {o16,o17,o18,o19,o20,o21,o22,o23,o24,o25,o26,o27,o28,o29,o30,o31}, {a28,a29,a30,a31}, d15, p1, 1, 1, 1;\n"
        "wgmma.commit_group.sync.aligned;\nwgmma.wait_group.sync.aligned 1;\ncvt.rn.bf16x2.f32 k0, o1, o0;\ncvt.rn.bf16x2.f32 k1, o5, o4;\n"
        "cvt.rn.bf16x2.f32 k2, o9, o8;\ncvt.rn.bf16x2.f32 k3, o13, o12;\n@s0 st.global.v4.b32 [%65+0], {k0,k1,k2,k3};\ncvt.rn.bf16x2.f32 k4, o3, o2;\n"
        "cvt.rn.bf16x2.f32 k5, o7, o6;\ncvt.rn.bf16x2.f32 k6, o11, o10;\ncvt.rn.bf16x2.f32 k7, o15, o14;\n@s1 st.global.v4.b32 [%66+0], {k4,k5,k6,k7};\n"
        "@nv bra.uni END;\nwgmma.wait_group.sync.aligned 0;\ncvt.rn.bf16x2.f32 k8, o17, o16;\ncvt.rn.bf16x2.f32 k9, o21, o20;\ncvt.rn.bf16x2.f32 k10, o25, o24;\n"
        "cvt.rn.bf16x2.f32 k11, o29, o28;\n@s0 st.global.v4.b32 [%65+64], {k8,k9,k10,k11};\ncvt.rn.bf16x2.f32 k12, o19, o18;\ncvt.rn.bf16x2.f32 k13, o23, o22;\n"
        "cvt.rn.bf16x2.f32 k14, o27, o26;\ncvt.rn.bf16x2.f32 k15, o31, o30;\n@s1 st.global.v4.b32 [%66+64], {k12,k13,k14,k15};\n@nv bra.uni END;\n"
        "ld.volatile.shared.v2.b32 {c0,c1}, [%64+16];\nld.volatile.shared.v2.b32 {c2,c3}, [%64+4112];\nld.volatile.shared.v2.b32 {c4,c5}, [%64+24];\n"
        "ld.volatile.shared.v2.b32 {c6,c7}, [%64+4120];\ndp2a.lo.u32.u32 t, c0, 0x04000004, 0x200000;\nmov.b64 d0, {t, h};\n"
        "dp2a.hi.u32.u32 t, c0, 0x04000004, 0x200000;\nmov.b64 d1, {t, h};\ndp2a.lo.u32.u32 t, c1, 0x04000004, 0x200000;\nmov.b64 d2, {t, h};\n"
        "dp2a.hi.u32.u32 t, c1, 0x04000004, 0x200000;\nmov.b64 d3, {t, h};\ndp2a.lo.u32.u32 t, c2, 0x04000004, 0x200000;\nmov.b64 d4, {t, h};\n"
        "dp2a.hi.u32.u32 t, c2, 0x04000004, 0x200000;\nmov.b64 d5, {t, h};\ndp2a.lo.u32.u32 t, c3, 0x04000004, 0x200000;\nmov.b64 d6, {t, h};\n"
        "dp2a.hi.u32.u32 t, c3, 0x04000004, 0x200000;\nmov.b64 d7, {t, h};\ndp2a.lo.u32.u32 t, c4, 0x04000004, 0x200000;\nmov.b64 d8, {t, h};\n"
        "dp2a.hi.u32.u32 t, c4, 0x04000004, 0x200000;\nmov.b64 d9, {t, h};\ndp2a.lo.u32.u32 t, c5, 0x04000004, 0x200000;\nmov.b64 d10, {t, h};\n"
        "dp2a.hi.u32.u32 t, c5, 0x04000004, 0x200000;\nmov.b64 d11, {t, h};\ndp2a.lo.u32.u32 t, c6, 0x04000004, 0x200000;\nmov.b64 d12, {t, h};\n"
        "dp2a.hi.u32.u32 t, c6, 0x04000004, 0x200000;\nmov.b64 d13, {t, h};\ndp2a.lo.u32.u32 t, c7, 0x04000004, 0x200000;\nmov.b64 d14, {t, h};\n"
        "dp2a.hi.u32.u32 t, c7, 0x04000004, 0x200000;\nmov.b64 d15, {t, h};\nwgmma.fence.sync.aligned;\n"
        "wgmma.mma_async.sync.aligned.m64n32k16.f32.bf16.bf16 {o0,o1,o2,o3,o4,o5,o6,o7,o8,o9,o10,o11,o12,o13,o14,o15}, {a0,a1,a2,a3}, d0, p0, 1, 1, 1;\n"
        "wgmma.mma_async.sync.aligned.m64n32k16.f32.bf16.bf16 {o16,o17,o18,o19,o20,o21,o22,o23,o24,o25,o26,o27,o28,o29,o30,o31}, {a0,a1,a2,a3}, d8, p0, 1, 1, 1;\n"
        "wgmma.mma_async.sync.aligned.m64n32k16.f32.bf16.bf16 {o0,o1,o2,o3,o4,o5,o6,o7,o8,o9,o10,o11,o12,o13,o14,o15}, {a4,a5,a6,a7}, d1, p1, 1, 1, 1;\n"
        "wgmma.mma_async.sync.aligned.m64n32k16.f32.bf16.bf16 {o16,o17,o18,o19,o20,o21,o22,o23,o24,o25,o26,o27,o28,o29,o30,o31}, {a4,a5,a6,a7}, d9, p1, 1, 1, 1;\n"
        "wgmma.mma_async.sync.aligned.m64n32k16.f32.bf16.bf16 {o0,o1,o2,o3,o4,o5,o6,o7,o8,o9,o10,o11,o12,o13,o14,o15}, {a8,a9,a10,a11}, d2, p1, 1, 1, 1;\n"
        "wgmma.mma_async.sync.aligned.m64n32k16.f32.bf16.bf16 {o16,o17,o18,o19,o20,o21,o22,o23,o24,o25,o26,o27,o28,o29,o30,o31}, {a8,a9,a10,a11}, d10, p1, 1, 1, 1;\n"
        "wgmma.mma_async.sync.aligned.m64n32k16.f32.bf16.bf16 {o0,o1,o2,o3,o4,o5,o6,o7,o8,o9,o10,o11,o12,o13,o14,o15}, {a12,a13,a14,a15}, d3, p1, 1, 1, 1;\n"
        "wgmma.mma_async.sync.aligned.m64n32k16.f32.bf16.bf16 {o16,o17,o18,o19,o20,o21,o22,o23,o24,o25,o26,o27,o28,o29,o30,o31}, {a12,a13,a14,a15}, d11, p1, 1, 1, 1;\n"
        "wgmma.mma_async.sync.aligned.m64n32k16.f32.bf16.bf16 {o0,o1,o2,o3,o4,o5,o6,o7,o8,o9,o10,o11,o12,o13,o14,o15}, {a16,a17,a18,a19}, d4, p1, 1, 1, 1;\n"
        "wgmma.mma_async.sync.aligned.m64n32k16.f32.bf16.bf16 {o16,o17,o18,o19,o20,o21,o22,o23,o24,o25,o26,o27,o28,o29,o30,o31}, {a16,a17,a18,a19}, d12, p1, 1, 1, 1;\n"
        "wgmma.mma_async.sync.aligned.m64n32k16.f32.bf16.bf16 {o0,o1,o2,o3,o4,o5,o6,o7,o8,o9,o10,o11,o12,o13,o14,o15}, {a20,a21,a22,a23}, d5, p1, 1, 1, 1;\n"
        "wgmma.mma_async.sync.aligned.m64n32k16.f32.bf16.bf16 {o16,o17,o18,o19,o20,o21,o22,o23,o24,o25,o26,o27,o28,o29,o30,o31}, {a20,a21,a22,a23}, d13, p1, 1, 1, 1;\n"
        "wgmma.mma_async.sync.aligned.m64n32k16.f32.bf16.bf16 {o0,o1,o2,o3,o4,o5,o6,o7,o8,o9,o10,o11,o12,o13,o14,o15}, {a24,a25,a26,a27}, d6, p1, 1, 1, 1;\n"
        "wgmma.mma_async.sync.aligned.m64n32k16.f32.bf16.bf16 {o16,o17,o18,o19,o20,o21,o22,o23,o24,o25,o26,o27,o28,o29,o30,o31}, {a24,a25,a26,a27}, d14, p1, 1, 1, 1;\n"
        "wgmma.mma_async.sync.aligned.m64n32k16.f32.bf16.bf16 {o0,o1,o2,o3,o4,o5,o6,o7,o8,o9,o10,o11,o12,o13,o14,o15}, {a28,a29,a30,a31}, d7, p1, 1, 1, 1;\n"
        "wgmma.mma_async.sync.aligned.m64n32k16.f32.bf16.bf16 {o16,o17,o18,o19,o20,o21,o22,o23,o24,o25,o26,o27,o28,o29,o30,o31}, {a28,a29,a30,a31}, d15, p1, 1, 1, 1;\n"
        "wgmma.commit_group.sync.aligned;\n@nv bra.uni END;\nmovmatrix.sync.aligned.m8n8.trans.b16 b0, %32;\nmovmatrix.sync.aligned.m8n8.trans.b16 b1, %48;\n"
        "movmatrix.sync.aligned.m8n8.trans.b16 b2, %33;\nmovmatrix.sync.aligned.m8n8.trans.b16 b3, %49;\nmovmatrix.sync.aligned.m8n8.trans.b16 b4, %34;\n"
        "movmatrix.sync.aligned.m8n8.trans.b16 b5, %50;\nmovmatrix.sync.aligned.m8n8.trans.b16 b6, %35;\nmovmatrix.sync.aligned.m8n8.trans.b16 b7, %51;\n"
        "movmatrix.sync.aligned.m8n8.trans.b16 b8, %36;\nmovmatrix.sync.aligned.m8n8.trans.b16 b9, %52;\nmovmatrix.sync.aligned.m8n8.trans.b16 b10, %37;\n"
        "movmatrix.sync.aligned.m8n8.trans.b16 b11, %53;\nmovmatrix.sync.aligned.m8n8.trans.b16 b12, %38;\nmovmatrix.sync.aligned.m8n8.trans.b16 b13, %54;\n"
        "movmatrix.sync.aligned.m8n8.trans.b16 b14, %39;\nmovmatrix.sync.aligned.m8n8.trans.b16 b15, %55;\nmovmatrix.sync.aligned.m8n8.trans.b16 b16, %40;\n"
        "movmatrix.sync.aligned.m8n8.trans.b16 b17, %56;\nmovmatrix.sync.aligned.m8n8.trans.b16 b18, %41;\nmovmatrix.sync.aligned.m8n8.trans.b16 b19, %57;\n"
        "movmatrix.sync.aligned.m8n8.trans.b16 b20, %42;\nmovmatrix.sync.aligned.m8n8.trans.b16 b21, %58;\nmovmatrix.sync.aligned.m8n8.trans.b16 b22, %43;\n"
        "movmatrix.sync.aligned.m8n8.trans.b16 b23, %59;\nmovmatrix.sync.aligned.m8n8.trans.b16 b24, %44;\nmovmatrix.sync.aligned.m8n8.trans.b16 b25, %60;\n"
        "movmatrix.sync.aligned.m8n8.trans.b16 b26, %45;\nmovmatrix.sync.aligned.m8n8.trans.b16 b27, %61;\nmovmatrix.sync.aligned.m8n8.trans.b16 b28, %46;\n"
        "movmatrix.sync.aligned.m8n8.trans.b16 b29, %62;\nmovmatrix.sync.aligned.m8n8.trans.b16 b30, %47;\nmovmatrix.sync.aligned.m8n8.trans.b16 b31, %63;\n"
        "@nv bra.uni END;\nwgmma.wait_group.sync.aligned 0;\ncvt.rn.bf16x2.f32 k0, o1, o0;\ncvt.rn.bf16x2.f32 k1, o5, o4;\ncvt.rn.bf16x2.f32 k2, o9, o8;\n"
        "cvt.rn.bf16x2.f32 k3, o13, o12;\ncvt.rn.bf16x2.f32 k4, o3, o2;\ncvt.rn.bf16x2.f32 k5, o7, o6;\ncvt.rn.bf16x2.f32 k6, o11, o10;\n"
        "cvt.rn.bf16x2.f32 k7, o15, o14;\ncvt.rn.bf16x2.f32 k8, o17, o16;\ncvt.rn.bf16x2.f32 k9, o21, o20;\ncvt.rn.bf16x2.f32 k10, o25, o24;\n"
        "cvt.rn.bf16x2.f32 k11, o29, o28;\ncvt.rn.bf16x2.f32 k12, o19, o18;\ncvt.rn.bf16x2.f32 k13, o23, o22;\ncvt.rn.bf16x2.f32 k14, o27, o26;\n"
        "cvt.rn.bf16x2.f32 k15, o31, o30;\nld.volatile.shared.v2.b32 {c0,c1}, [%64+0];\nld.volatile.shared.v2.b32 {c2,c3}, [%64+4096];\n"
        "ld.volatile.shared.v2.b32 {c4,c5}, [%64+8];\nld.volatile.shared.v2.b32 {c6,c7}, [%64+4104];\ndp2a.lo.u32.u32 t, c0, 0x04000004, 0x200000;\n"
        "mov.b64 d0, {t, h};\ndp2a.hi.u32.u32 t, c0, 0x04000004, 0x200000;\nmov.b64 d1, {t, h};\ndp2a.lo.u32.u32 t, c1, 0x04000004, 0x200000;\n"
        "mov.b64 d2, {t, h};\ndp2a.hi.u32.u32 t, c1, 0x04000004, 0x200000;\nmov.b64 d3, {t, h};\ndp2a.lo.u32.u32 t, c2, 0x04000004, 0x200000;\n"
        "mov.b64 d4, {t, h};\ndp2a.hi.u32.u32 t, c2, 0x04000004, 0x200000;\nmov.b64 d5, {t, h};\ndp2a.lo.u32.u32 t, c3, 0x04000004, 0x200000;\n"
        "mov.b64 d6, {t, h};\ndp2a.hi.u32.u32 t, c3, 0x04000004, 0x200000;\nmov.b64 d7, {t, h};\ndp2a.lo.u32.u32 t, c4, 0x04000004, 0x200000;\n"
        "mov.b64 d8, {t, h};\ndp2a.hi.u32.u32 t, c4, 0x04000004, 0x200000;\nmov.b64 d9, {t, h};\ndp2a.lo.u32.u32 t, c5, 0x04000004, 0x200000;\n"
        "mov.b64 d10, {t, h};\ndp2a.hi.u32.u32 t, c5, 0x04000004, 0x200000;\nmov.b64 d11, {t, h};\ndp2a.lo.u32.u32 t, c6, 0x04000004, 0x200000;\n"
        "mov.b64 d12, {t, h};\ndp2a.hi.u32.u32 t, c6, 0x04000004, 0x200000;\nmov.b64 d13, {t, h};\ndp2a.lo.u32.u32 t, c7, 0x04000004, 0x200000;\n"
        "mov.b64 d14, {t, h};\ndp2a.hi.u32.u32 t, c7, 0x04000004, 0x200000;\nmov.b64 d15, {t, h};\nwgmma.fence.sync.aligned;\n"
        "wgmma.mma_async.sync.aligned.m64n32k16.f32.bf16.bf16 {o0,o1,o2,o3,o4,o5,o6,o7,o8,o9,o10,o11,o12,o13,o14,o15}, {b0,b1,b2,b3}, d0, p0, 1, 1, 1;\n"
        "wgmma.mma_async.sync.aligned.m64n32k16.f32.bf16.bf16 {o16,o17,o18,o19,o20,o21,o22,o23,o24,o25,o26,o27,o28,o29,o30,o31}, {b0,b1,b2,b3}, d8, p0, 1, 1, 1;\n"
        "wgmma.mma_async.sync.aligned.m64n32k16.f32.bf16.bf16 {o0,o1,o2,o3,o4,o5,o6,o7,o8,o9,o10,o11,o12,o13,o14,o15}, {b4,b5,b6,b7}, d1, p1, 1, 1, 1;\n"
        "wgmma.mma_async.sync.aligned.m64n32k16.f32.bf16.bf16 {o16,o17,o18,o19,o20,o21,o22,o23,o24,o25,o26,o27,o28,o29,o30,o31}, {b4,b5,b6,b7}, d9, p1, 1, 1, 1;\n"
        "wgmma.mma_async.sync.aligned.m64n32k16.f32.bf16.bf16 {o0,o1,o2,o3,o4,o5,o6,o7,o8,o9,o10,o11,o12,o13,o14,o15}, {b8,b9,b10,b11}, d2, p1, 1, 1, 1;\n"
        "wgmma.mma_async.sync.aligned.m64n32k16.f32.bf16.bf16 {o16,o17,o18,o19,o20,o21,o22,o23,o24,o25,o26,o27,o28,o29,o30,o31}, {b8,b9,b10,b11}, d10, p1, 1, 1, 1;\n"
        "wgmma.mma_async.sync.aligned.m64n32k16.f32.bf16.bf16 {o0,o1,o2,o3,o4,o5,o6,o7,o8,o9,o10,o11,o12,o13,o14,o15}, {b12,b13,b14,b15}, d3, p1, 1, 1, 1;\n"
        "wgmma.mma_async.sync.aligned.m64n32k16.f32.bf16.bf16 {o16,o17,o18,o19,o20,o21,o22,o23,o24,o25,o26,o27,o28,o29,o30,o31}, {b12,b13,b14,b15}, d11, p1, 1, 1, 1;\n"
        "wgmma.mma_async.sync.aligned.m64n32k16.f32.bf16.bf16 {o0,o1,o2,o3,o4,o5,o6,o7,o8,o9,o10,o11,o12,o13,o14,o15}, {b16,b17,b18,b19}, d4, p1, 1, 1, 1;\n"
        "wgmma.mma_async.sync.aligned.m64n32k16.f32.bf16.bf16 {o16,o17,o18,o19,o20,o21,o22,o23,o24,o25,o26,o27,o28,o29,o30,o31}, {b16,b17,b18,b19}, d12, p1, 1, 1, 1;\n"
        "wgmma.mma_async.sync.aligned.m64n32k16.f32.bf16.bf16 {o0,o1,o2,o3,o4,o5,o6,o7,o8,o9,o10,o11,o12,o13,o14,o15}, {b20,b21,b22,b23}, d5, p1, 1, 1, 1;\n"
        "wgmma.mma_async.sync.aligned.m64n32k16.f32.bf16.bf16 {o16,o17,o18,o19,o20,o21,o22,o23,o24,o25,o26,o27,o28,o29,o30,o31}, {b20,b21,b22,b23}, d13, p1, 1, 1, 1;\n"
        "wgmma.mma_async.sync.aligned.m64n32k16.f32.bf16.bf16 {o0,o1,o2,o3,o4,o5,o6,o7,o8,o9,o10,o11,o12,o13,o14,o15}, {b24,b25,b26,b27}, d6, p1, 1, 1, 1;\n"
        "wgmma.mma_async.sync.aligned.m64n32k16.f32.bf16.bf16 {o16,o17,o18,o19,o20,o21,o22,o23,o24,o25,o26,o27,o28,o29,o30,o31}, {b24,b25,b26,b27}, d14, p1, 1, 1, 1;\n"
        "wgmma.mma_async.sync.aligned.m64n32k16.f32.bf16.bf16 {o0,o1,o2,o3,o4,o5,o6,o7,o8,o9,o10,o11,o12,o13,o14,o15}, {b28,b29,b30,b31}, d7, p1, 1, 1, 1;\n"
        "wgmma.mma_async.sync.aligned.m64n32k16.f32.bf16.bf16 {o16,o17,o18,o19,o20,o21,o22,o23,o24,o25,o26,o27,o28,o29,o30,o31}, {b28,b29,b30,b31}, d15, p1, 1, 1, 1;\n"
        "wgmma.commit_group.sync.aligned;\n@nv bra.uni END;\n@s0 st.global.v4.b32 [%65+128], {k0,k1,k2,k3};\n@s1 st.global.v4.b32 [%66+128], {k4,k5,k6,k7};\n"
        "@s0 st.global.v4.b32 [%65+192], {k8,k9,k10,k11};\n@s1 st.global.v4.b32 [%66+192], {k12,k13,k14,k15};\n@nv bra.uni END;\n"
        "wgmma.wait_group.sync.aligned 0;\ncvt.rn.bf16x2.f32 k0, o1, o0;\ncvt.rn.bf16x2.f32 k1, o5, o4;\ncvt.rn.bf16x2.f32 k2, o9, o8;\n"
        "cvt.rn.bf16x2.f32 k3, o13, o12;\ncvt.rn.bf16x2.f32 k4, o3, o2;\ncvt.rn.bf16x2.f32 k5, o7, o6;\ncvt.rn.bf16x2.f32 k6, o11, o10;\n"
        "cvt.rn.bf16x2.f32 k7, o15, o14;\ncvt.rn.bf16x2.f32 k8, o17, o16;\ncvt.rn.bf16x2.f32 k9, o21, o20;\ncvt.rn.bf16x2.f32 k10, o25, o24;\n"
        "cvt.rn.bf16x2.f32 k11, o29, o28;\ncvt.rn.bf16x2.f32 k12, o19, o18;\ncvt.rn.bf16x2.f32 k13, o23, o22;\ncvt.rn.bf16x2.f32 k14, o27, o26;\n"
        "cvt.rn.bf16x2.f32 k15, o31, o30;\nld.volatile.shared.v2.b32 {c0,c1}, [%64+16];\nld.volatile.shared.v2.b32 {c2,c3}, [%64+4112];\n"
        "ld.volatile.shared.v2.b32 {c4,c5}, [%64+24];\nld.volatile.shared.v2.b32 {c6,c7}, [%64+4120];\ndp2a.lo.u32.u32 t, c0, 0x04000004, 0x200000;\n"
        "mov.b64 d0, {t, h};\ndp2a.hi.u32.u32 t, c0, 0x04000004, 0x200000;\nmov.b64 d1, {t, h};\ndp2a.lo.u32.u32 t, c1, 0x04000004, 0x200000;\n"
        "mov.b64 d2, {t, h};\ndp2a.hi.u32.u32 t, c1, 0x04000004, 0x200000;\nmov.b64 d3, {t, h};\ndp2a.lo.u32.u32 t, c2, 0x04000004, 0x200000;\n"
        "mov.b64 d4, {t, h};\ndp2a.hi.u32.u32 t, c2, 0x04000004, 0x200000;\nmov.b64 d5, {t, h};\ndp2a.lo.u32.u32 t, c3, 0x04000004, 0x200000;\n"
        "mov.b64 d6, {t, h};\ndp2a.hi.u32.u32 t, c3, 0x04000004, 0x200000;\nmov.b64 d7, {t, h};\ndp2a.lo.u32.u32 t, c4, 0x04000004, 0x200000;\n"
        "mov.b64 d8, {t, h};\ndp2a.hi.u32.u32 t, c4, 0x04000004, 0x200000;\nmov.b64 d9, {t, h};\ndp2a.lo.u32.u32 t, c5, 0x04000004, 0x200000;\n"
        "mov.b64 d10, {t, h};\ndp2a.hi.u32.u32 t, c5, 0x04000004, 0x200000;\nmov.b64 d11, {t, h};\ndp2a.lo.u32.u32 t, c6, 0x04000004, 0x200000;\n"
        "mov.b64 d12, {t, h};\ndp2a.hi.u32.u32 t, c6, 0x04000004, 0x200000;\nmov.b64 d13, {t, h};\ndp2a.lo.u32.u32 t, c7, 0x04000004, 0x200000;\n"
        "mov.b64 d14, {t, h};\ndp2a.hi.u32.u32 t, c7, 0x04000004, 0x200000;\nmov.b64 d15, {t, h};\nwgmma.fence.sync.aligned;\n"
        "wgmma.mma_async.sync.aligned.m64n32k16.f32.bf16.bf16 {o0,o1,o2,o3,o4,o5,o6,o7,o8,o9,o10,o11,o12,o13,o14,o15}, {b0,b1,b2,b3}, d0, p0, 1, 1, 1;\n"
        "wgmma.mma_async.sync.aligned.m64n32k16.f32.bf16.bf16 {o16,o17,o18,o19,o20,o21,o22,o23,o24,o25,o26,o27,o28,o29,o30,o31}, {b0,b1,b2,b3}, d8, p0, 1, 1, 1;\n"
        "wgmma.mma_async.sync.aligned.m64n32k16.f32.bf16.bf16 {o0,o1,o2,o3,o4,o5,o6,o7,o8,o9,o10,o11,o12,o13,o14,o15}, {b4,b5,b6,b7}, d1, p1, 1, 1, 1;\n"
        "wgmma.mma_async.sync.aligned.m64n32k16.f32.bf16.bf16 {o16,o17,o18,o19,o20,o21,o22,o23,o24,o25,o26,o27,o28,o29,o30,o31}, {b4,b5,b6,b7}, d9, p1, 1, 1, 1;\n"
        "wgmma.mma_async.sync.aligned.m64n32k16.f32.bf16.bf16 {o0,o1,o2,o3,o4,o5,o6,o7,o8,o9,o10,o11,o12,o13,o14,o15}, {b8,b9,b10,b11}, d2, p1, 1, 1, 1;\n"
        "wgmma.mma_async.sync.aligned.m64n32k16.f32.bf16.bf16 {o16,o17,o18,o19,o20,o21,o22,o23,o24,o25,o26,o27,o28,o29,o30,o31}, {b8,b9,b10,b11}, d10, p1, 1, 1, 1;\n"
        "wgmma.mma_async.sync.aligned.m64n32k16.f32.bf16.bf16 {o0,o1,o2,o3,o4,o5,o6,o7,o8,o9,o10,o11,o12,o13,o14,o15}, {b12,b13,b14,b15}, d3, p1, 1, 1, 1;\n"
        "wgmma.mma_async.sync.aligned.m64n32k16.f32.bf16.bf16 {o16,o17,o18,o19,o20,o21,o22,o23,o24,o25,o26,o27,o28,o29,o30,o31}, {b12,b13,b14,b15}, d11, p1, 1, 1, 1;\n"
        "wgmma.mma_async.sync.aligned.m64n32k16.f32.bf16.bf16 {o0,o1,o2,o3,o4,o5,o6,o7,o8,o9,o10,o11,o12,o13,o14,o15}, {b16,b17,b18,b19}, d4, p1, 1, 1, 1;\n"
        "wgmma.mma_async.sync.aligned.m64n32k16.f32.bf16.bf16 {o16,o17,o18,o19,o20,o21,o22,o23,o24,o25,o26,o27,o28,o29,o30,o31}, {b16,b17,b18,b19}, d12, p1, 1, 1, 1;\n"
        "wgmma.mma_async.sync.aligned.m64n32k16.f32.bf16.bf16 {o0,o1,o2,o3,o4,o5,o6,o7,o8,o9,o10,o11,o12,o13,o14,o15}, {b20,b21,b22,b23}, d5, p1, 1, 1, 1;\n"
        "wgmma.mma_async.sync.aligned.m64n32k16.f32.bf16.bf16 {o16,o17,o18,o19,o20,o21,o22,o23,o24,o25,o26,o27,o28,o29,o30,o31}, {b20,b21,b22,b23}, d13, p1, 1, 1, 1;\n"
        "wgmma.mma_async.sync.aligned.m64n32k16.f32.bf16.bf16 {o0,o1,o2,o3,o4,o5,o6,o7,o8,o9,o10,o11,o12,o13,o14,o15}, {b24,b25,b26,b27}, d6, p1, 1, 1, 1;\n"
        "wgmma.mma_async.sync.aligned.m64n32k16.f32.bf16.bf16 {o16,o17,o18,o19,o20,o21,o22,o23,o24,o25,o26,o27,o28,o29,o30,o31}, {b24,b25,b26,b27}, d14, p1, 1, 1, 1;\n"
        "wgmma.mma_async.sync.aligned.m64n32k16.f32.bf16.bf16 {o0,o1,o2,o3,o4,o5,o6,o7,o8,o9,o10,o11,o12,o13,o14,o15}, {b28,b29,b30,b31}, d7, p1, 1, 1, 1;\n"
        "wgmma.mma_async.sync.aligned.m64n32k16.f32.bf16.bf16 {o16,o17,o18,o19,o20,o21,o22,o23,o24,o25,o26,o27,o28,o29,o30,o31}, {b28,b29,b30,b31}, d15, p1, 1, 1, 1;\n"
        "wgmma.commit_group.sync.aligned;\n@nv bra.uni END;\n@s2 st.global.v4.b32 [%67+0], {k0,k1,k2,k3};\n@s3 st.global.v4.b32 [%68+0], {k4,k5,k6,k7};\n"
        "@s2 st.global.v4.b32 [%67+64], {k8,k9,k10,k11};\n@s3 st.global.v4.b32 [%68+64], {k12,k13,k14,k15};\n@nv bra.uni END;\nwgmma.wait_group.sync.aligned 0;\n"
        "cvt.rn.bf16x2.f32 k0, o1, o0;\ncvt.rn.bf16x2.f32 k1, o5, o4;\ncvt.rn.bf16x2.f32 k2, o9, o8;\ncvt.rn.bf16x2.f32 k3, o13, o12;\n"
        "cvt.rn.bf16x2.f32 k4, o3, o2;\ncvt.rn.bf16x2.f32 k5, o7, o6;\ncvt.rn.bf16x2.f32 k6, o11, o10;\ncvt.rn.bf16x2.f32 k7, o15, o14;\n"
        "cvt.rn.bf16x2.f32 k8, o17, o16;\ncvt.rn.bf16x2.f32 k9, o21, o20;\ncvt.rn.bf16x2.f32 k10, o25, o24;\ncvt.rn.bf16x2.f32 k11, o29, o28;\n"
        "cvt.rn.bf16x2.f32 k12, o19, o18;\ncvt.rn.bf16x2.f32 k13, o23, o22;\ncvt.rn.bf16x2.f32 k14, o27, o26;\ncvt.rn.bf16x2.f32 k15, o31, o30;\n"
        "@s2 st.global.v4.b32 [%67+128], {k0,k1,k2,k3};\n@s3 st.global.v4.b32 [%68+128], {k4,k5,k6,k7};\n@s2 st.global.v4.b32 [%67+192], {k8,k9,k10,k11};\n"
        "@s3 st.global.v4.b32 [%68+192], {k12,k13,k14,k15};\n"
        "END:\n}\n"
        ::"r"(pk[0]), "r"(pk[1]), "r"(pk[2]), "r"(pk[3]), "r"(pk[4]), "r"(pk[5]), "r"(pk[6]), "r"(pk[7]), "r"(pk[8]), "r"(pk[9]), "r"(pk[10]),
          "r"(pk[11]), "r"(pk[12]), "r"(pk[13]), "r"(pk[14]), "r"(pk[15]), "r"(pk[16]), "r"(pk[17]), "r"(pk[18]), "r"(pk[19]), "r"(pk[20]),
          "r"(pk[21]), "r"(pk[22]), "r"(pk[23]), "r"(pk[24]), "r"(pk[25]), "r"(pk[26]), "r"(pk[27]), "r"(pk[28]), "r"(pk[29]), "r"(pk[30]),
          "r"(pk[31]), "r"(pk[32]), "r"(pk[33]), "r"(pk[34]), "r"(pk[35]), "r"(pk[36]), "r"(pk[37]), "r"(pk[38]), "r"(pk[39]), "r"(pk[40]),
          "r"(pk[41]), "r"(pk[42]), "r"(pk[43]), "r"(pk[44]), "r"(pk[45]), "r"(pk[46]), "r"(pk[47]), "r"(pk[48]), "r"(pk[49]), "r"(pk[50]),
          "r"(pk[51]), "r"(pk[52]), "r"(pk[53]), "r"(pk[54]), "r"(pk[55]), "r"(pk[56]), "r"(pk[57]), "r"(pk[58]), "r"(pk[59]), "r"(pk[60]),
          "r"(pk[61]), "r"(pk[62]), "r"(pk[63]), "r"(ra), "l"(p[0]), "l"(p[1]), "l"(p[2]), "l"(p[3]), "r"(v[0]), "r"(v[1]), "r"(v[2]), "r"(v[3]),
          "r"(ba)
        : "memory");
}
__device__ __forceinline__ void project3(const uint32_t (&pk)[48], uint32_t ra, uint32_t ba, uint4* const (&p)[3], const uint32_t (&v)[3]) {
    asm volatile(
        "{\n.reg .pred p0, p1, q0, q1, nv, s<4>;\n.reg .b32 t, h, c<16>, a<32>, b<32>, k<16>;\n.reg .b64 d<16>;\n.reg .f32 o<32>;\nsetp.ne.b32 p0, 0, 0;\n"
        "setp.eq.b32 p1, 0, 0;\nmov.b32 h, 8;\nsetp.eq.u32 nv, %48, 0;\nvote.sync.any.pred nv, nv, 0xffffffff;\nsetp.ne.b32 s0, %52, 0;\n"
        "setp.ne.b32 s1, %53, 0;\nsetp.ne.b32 s2, %54, 0;\nmov.b32 t, 0;\n"
        "W0:\nmbarrier.try_wait.parity.shared.b64 q0, [%55], 0;\nvote.sync.all.pred q0, q0, 0xffffffff;\nadd.u32 t, t, 1;\nsetp.lt.and.u32 q1, t, 1000000, !q0;\n"
        "@q1 bra.uni W0;\nld.volatile.shared.v2.b32 {c0,c1}, [%48+0];\nld.volatile.shared.v2.b32 {c2,c3}, [%48+4096];\n"
        "ld.volatile.shared.v2.b32 {c4,c5}, [%48+8];\nld.volatile.shared.v2.b32 {c6,c7}, [%48+4104];\ndp2a.lo.u32.u32 t, c0, 0x04000004, 0x200000;\n"
        "mov.b64 d0, {t, h};\ndp2a.hi.u32.u32 t, c0, 0x04000004, 0x200000;\nmov.b64 d1, {t, h};\ndp2a.lo.u32.u32 t, c1, 0x04000004, 0x200000;\n"
        "mov.b64 d2, {t, h};\ndp2a.hi.u32.u32 t, c1, 0x04000004, 0x200000;\nmov.b64 d3, {t, h};\ndp2a.lo.u32.u32 t, c2, 0x04000004, 0x200000;\n"
        "mov.b64 d4, {t, h};\ndp2a.hi.u32.u32 t, c2, 0x04000004, 0x200000;\nmov.b64 d5, {t, h};\ndp2a.lo.u32.u32 t, c3, 0x04000004, 0x200000;\n"
        "mov.b64 d6, {t, h};\ndp2a.hi.u32.u32 t, c3, 0x04000004, 0x200000;\nmov.b64 d7, {t, h};\ndp2a.lo.u32.u32 t, c4, 0x04000004, 0x200000;\n"
        "mov.b64 d8, {t, h};\ndp2a.hi.u32.u32 t, c4, 0x04000004, 0x200000;\nmov.b64 d9, {t, h};\ndp2a.lo.u32.u32 t, c5, 0x04000004, 0x200000;\n"
        "mov.b64 d10, {t, h};\ndp2a.hi.u32.u32 t, c5, 0x04000004, 0x200000;\nmov.b64 d11, {t, h};\ndp2a.lo.u32.u32 t, c6, 0x04000004, 0x200000;\n"
        "mov.b64 d12, {t, h};\ndp2a.hi.u32.u32 t, c6, 0x04000004, 0x200000;\nmov.b64 d13, {t, h};\ndp2a.lo.u32.u32 t, c7, 0x04000004, 0x200000;\n"
        "mov.b64 d14, {t, h};\ndp2a.hi.u32.u32 t, c7, 0x04000004, 0x200000;\nmov.b64 d15, {t, h};\nmovmatrix.sync.aligned.m8n8.trans.b16 a0, %0;\n"
        "movmatrix.sync.aligned.m8n8.trans.b16 a1, %16;\nmovmatrix.sync.aligned.m8n8.trans.b16 a2, %1;\nmovmatrix.sync.aligned.m8n8.trans.b16 a3, %17;\n"
        "movmatrix.sync.aligned.m8n8.trans.b16 a4, %2;\nmovmatrix.sync.aligned.m8n8.trans.b16 a5, %18;\nmovmatrix.sync.aligned.m8n8.trans.b16 a6, %3;\n"
        "movmatrix.sync.aligned.m8n8.trans.b16 a7, %19;\nmovmatrix.sync.aligned.m8n8.trans.b16 a8, %4;\nmovmatrix.sync.aligned.m8n8.trans.b16 a9, %20;\n"
        "movmatrix.sync.aligned.m8n8.trans.b16 a10, %5;\nmovmatrix.sync.aligned.m8n8.trans.b16 a11, %21;\nmovmatrix.sync.aligned.m8n8.trans.b16 a12, %6;\n"
        "movmatrix.sync.aligned.m8n8.trans.b16 a13, %22;\nmovmatrix.sync.aligned.m8n8.trans.b16 a14, %7;\nmovmatrix.sync.aligned.m8n8.trans.b16 a15, %23;\n"
        "movmatrix.sync.aligned.m8n8.trans.b16 a16, %8;\nmovmatrix.sync.aligned.m8n8.trans.b16 a17, %24;\nmovmatrix.sync.aligned.m8n8.trans.b16 a18, %9;\n"
        "movmatrix.sync.aligned.m8n8.trans.b16 a19, %25;\nmovmatrix.sync.aligned.m8n8.trans.b16 a20, %10;\nmovmatrix.sync.aligned.m8n8.trans.b16 a21, %26;\n"
        "movmatrix.sync.aligned.m8n8.trans.b16 a22, %11;\nmovmatrix.sync.aligned.m8n8.trans.b16 a23, %27;\nmovmatrix.sync.aligned.m8n8.trans.b16 a24, %12;\n"
        "movmatrix.sync.aligned.m8n8.trans.b16 a25, %28;\nmovmatrix.sync.aligned.m8n8.trans.b16 a26, %13;\nmovmatrix.sync.aligned.m8n8.trans.b16 a27, %29;\n"
        "movmatrix.sync.aligned.m8n8.trans.b16 a28, %14;\nmovmatrix.sync.aligned.m8n8.trans.b16 a29, %30;\nmovmatrix.sync.aligned.m8n8.trans.b16 a30, %15;\n"
        "movmatrix.sync.aligned.m8n8.trans.b16 a31, %31;\nwgmma.fence.sync.aligned;\n"
        "wgmma.mma_async.sync.aligned.m64n32k16.f32.bf16.bf16 {o0,o1,o2,o3,o4,o5,o6,o7,o8,o9,o10,o11,o12,o13,o14,o15}, {a0,a1,a2,a3}, d0, p0, 1, 1, 1;\n"
        "wgmma.mma_async.sync.aligned.m64n32k16.f32.bf16.bf16 {o0,o1,o2,o3,o4,o5,o6,o7,o8,o9,o10,o11,o12,o13,o14,o15}, {a4,a5,a6,a7}, d1, p1, 1, 1, 1;\n"
        "wgmma.mma_async.sync.aligned.m64n32k16.f32.bf16.bf16 {o0,o1,o2,o3,o4,o5,o6,o7,o8,o9,o10,o11,o12,o13,o14,o15}, {a8,a9,a10,a11}, d2, p1, 1, 1, 1;\n"
        "wgmma.mma_async.sync.aligned.m64n32k16.f32.bf16.bf16 {o0,o1,o2,o3,o4,o5,o6,o7,o8,o9,o10,o11,o12,o13,o14,o15}, {a12,a13,a14,a15}, d3, p1, 1, 1, 1;\n"
        "wgmma.mma_async.sync.aligned.m64n32k16.f32.bf16.bf16 {o0,o1,o2,o3,o4,o5,o6,o7,o8,o9,o10,o11,o12,o13,o14,o15}, {a16,a17,a18,a19}, d4, p1, 1, 1, 1;\n"
        "wgmma.mma_async.sync.aligned.m64n32k16.f32.bf16.bf16 {o0,o1,o2,o3,o4,o5,o6,o7,o8,o9,o10,o11,o12,o13,o14,o15}, {a20,a21,a22,a23}, d5, p1, 1, 1, 1;\n"
        "wgmma.mma_async.sync.aligned.m64n32k16.f32.bf16.bf16 {o0,o1,o2,o3,o4,o5,o6,o7,o8,o9,o10,o11,o12,o13,o14,o15}, {a24,a25,a26,a27}, d6, p1, 1, 1, 1;\n"
        "wgmma.mma_async.sync.aligned.m64n32k16.f32.bf16.bf16 {o0,o1,o2,o3,o4,o5,o6,o7,o8,o9,o10,o11,o12,o13,o14,o15}, {a28,a29,a30,a31}, d7, p1, 1, 1, 1;\n"
        "wgmma.commit_group.sync.aligned;\n"
        "wgmma.mma_async.sync.aligned.m64n32k16.f32.bf16.bf16 {o16,o17,o18,o19,o20,o21,o22,o23,o24,o25,o26,o27,o28,o29,o30,o31}, {a0,a1,a2,a3}, d8, p0, 1, 1, 1;\n"
        "wgmma.mma_async.sync.aligned.m64n32k16.f32.bf16.bf16 {o16,o17,o18,o19,o20,o21,o22,o23,o24,o25,o26,o27,o28,o29,o30,o31}, {a4,a5,a6,a7}, d9, p1, 1, 1, 1;\n"
        "wgmma.mma_async.sync.aligned.m64n32k16.f32.bf16.bf16 {o16,o17,o18,o19,o20,o21,o22,o23,o24,o25,o26,o27,o28,o29,o30,o31}, {a8,a9,a10,a11}, d10, p1, 1, 1, 1;\n"
        "wgmma.mma_async.sync.aligned.m64n32k16.f32.bf16.bf16 {o16,o17,o18,o19,o20,o21,o22,o23,o24,o25,o26,o27,o28,o29,o30,o31}, {a12,a13,a14,a15}, d11, p1, 1, 1, 1;\n"
        "wgmma.mma_async.sync.aligned.m64n32k16.f32.bf16.bf16 {o16,o17,o18,o19,o20,o21,o22,o23,o24,o25,o26,o27,o28,o29,o30,o31}, {a16,a17,a18,a19}, d12, p1, 1, 1, 1;\n"
        "wgmma.mma_async.sync.aligned.m64n32k16.f32.bf16.bf16 {o16,o17,o18,o19,o20,o21,o22,o23,o24,o25,o26,o27,o28,o29,o30,o31}, {a20,a21,a22,a23}, d13, p1, 1, 1, 1;\n"
        "wgmma.mma_async.sync.aligned.m64n32k16.f32.bf16.bf16 {o16,o17,o18,o19,o20,o21,o22,o23,o24,o25,o26,o27,o28,o29,o30,o31}, {a24,a25,a26,a27}, d14, p1, 1, 1, 1;\n"
        "wgmma.mma_async.sync.aligned.m64n32k16.f32.bf16.bf16 {o16,o17,o18,o19,o20,o21,o22,o23,o24,o25,o26,o27,o28,o29,o30,o31}, {a28,a29,a30,a31}, d15, p1, 1, 1, 1;\n"
        "wgmma.commit_group.sync.aligned;\nwgmma.wait_group.sync.aligned 1;\ncvt.rn.bf16x2.f32 k0, o1, o0;\ncvt.rn.bf16x2.f32 k1, o5, o4;\n"
        "cvt.rn.bf16x2.f32 k2, o9, o8;\ncvt.rn.bf16x2.f32 k3, o13, o12;\n@s0 st.global.v4.b32 [%49+0], {k0,k1,k2,k3};\ncvt.rn.bf16x2.f32 k4, o3, o2;\n"
        "cvt.rn.bf16x2.f32 k5, o7, o6;\ncvt.rn.bf16x2.f32 k6, o11, o10;\ncvt.rn.bf16x2.f32 k7, o15, o14;\n@s1 st.global.v4.b32 [%50+0], {k4,k5,k6,k7};\n"
        "@nv bra.uni END;\nwgmma.wait_group.sync.aligned 0;\ncvt.rn.bf16x2.f32 k8, o17, o16;\ncvt.rn.bf16x2.f32 k9, o21, o20;\ncvt.rn.bf16x2.f32 k10, o25, o24;\n"
        "cvt.rn.bf16x2.f32 k11, o29, o28;\n@s0 st.global.v4.b32 [%49+64], {k8,k9,k10,k11};\ncvt.rn.bf16x2.f32 k12, o19, o18;\ncvt.rn.bf16x2.f32 k13, o23, o22;\n"
        "cvt.rn.bf16x2.f32 k14, o27, o26;\ncvt.rn.bf16x2.f32 k15, o31, o30;\n@s1 st.global.v4.b32 [%50+64], {k12,k13,k14,k15};\n@nv bra.uni END;\n"
        "ld.volatile.shared.v2.b32 {c0,c1}, [%48+16];\nld.volatile.shared.v2.b32 {c2,c3}, [%48+4112];\nld.volatile.shared.v2.b32 {c4,c5}, [%48+24];\n"
        "ld.volatile.shared.v2.b32 {c6,c7}, [%48+4120];\ndp2a.lo.u32.u32 t, c0, 0x04000004, 0x200000;\nmov.b64 d0, {t, h};\n"
        "dp2a.hi.u32.u32 t, c0, 0x04000004, 0x200000;\nmov.b64 d1, {t, h};\ndp2a.lo.u32.u32 t, c1, 0x04000004, 0x200000;\nmov.b64 d2, {t, h};\n"
        "dp2a.hi.u32.u32 t, c1, 0x04000004, 0x200000;\nmov.b64 d3, {t, h};\ndp2a.lo.u32.u32 t, c2, 0x04000004, 0x200000;\nmov.b64 d4, {t, h};\n"
        "dp2a.hi.u32.u32 t, c2, 0x04000004, 0x200000;\nmov.b64 d5, {t, h};\ndp2a.lo.u32.u32 t, c3, 0x04000004, 0x200000;\nmov.b64 d6, {t, h};\n"
        "dp2a.hi.u32.u32 t, c3, 0x04000004, 0x200000;\nmov.b64 d7, {t, h};\ndp2a.lo.u32.u32 t, c4, 0x04000004, 0x200000;\nmov.b64 d8, {t, h};\n"
        "dp2a.hi.u32.u32 t, c4, 0x04000004, 0x200000;\nmov.b64 d9, {t, h};\ndp2a.lo.u32.u32 t, c5, 0x04000004, 0x200000;\nmov.b64 d10, {t, h};\n"
        "dp2a.hi.u32.u32 t, c5, 0x04000004, 0x200000;\nmov.b64 d11, {t, h};\ndp2a.lo.u32.u32 t, c6, 0x04000004, 0x200000;\nmov.b64 d12, {t, h};\n"
        "dp2a.hi.u32.u32 t, c6, 0x04000004, 0x200000;\nmov.b64 d13, {t, h};\ndp2a.lo.u32.u32 t, c7, 0x04000004, 0x200000;\nmov.b64 d14, {t, h};\n"
        "dp2a.hi.u32.u32 t, c7, 0x04000004, 0x200000;\nmov.b64 d15, {t, h};\nwgmma.fence.sync.aligned;\n"
        "wgmma.mma_async.sync.aligned.m64n32k16.f32.bf16.bf16 {o0,o1,o2,o3,o4,o5,o6,o7,o8,o9,o10,o11,o12,o13,o14,o15}, {a0,a1,a2,a3}, d0, p0, 1, 1, 1;\n"
        "wgmma.mma_async.sync.aligned.m64n32k16.f32.bf16.bf16 {o16,o17,o18,o19,o20,o21,o22,o23,o24,o25,o26,o27,o28,o29,o30,o31}, {a0,a1,a2,a3}, d8, p0, 1, 1, 1;\n"
        "wgmma.mma_async.sync.aligned.m64n32k16.f32.bf16.bf16 {o0,o1,o2,o3,o4,o5,o6,o7,o8,o9,o10,o11,o12,o13,o14,o15}, {a4,a5,a6,a7}, d1, p1, 1, 1, 1;\n"
        "wgmma.mma_async.sync.aligned.m64n32k16.f32.bf16.bf16 {o16,o17,o18,o19,o20,o21,o22,o23,o24,o25,o26,o27,o28,o29,o30,o31}, {a4,a5,a6,a7}, d9, p1, 1, 1, 1;\n"
        "wgmma.mma_async.sync.aligned.m64n32k16.f32.bf16.bf16 {o0,o1,o2,o3,o4,o5,o6,o7,o8,o9,o10,o11,o12,o13,o14,o15}, {a8,a9,a10,a11}, d2, p1, 1, 1, 1;\n"
        "wgmma.mma_async.sync.aligned.m64n32k16.f32.bf16.bf16 {o16,o17,o18,o19,o20,o21,o22,o23,o24,o25,o26,o27,o28,o29,o30,o31}, {a8,a9,a10,a11}, d10, p1, 1, 1, 1;\n"
        "wgmma.mma_async.sync.aligned.m64n32k16.f32.bf16.bf16 {o0,o1,o2,o3,o4,o5,o6,o7,o8,o9,o10,o11,o12,o13,o14,o15}, {a12,a13,a14,a15}, d3, p1, 1, 1, 1;\n"
        "wgmma.mma_async.sync.aligned.m64n32k16.f32.bf16.bf16 {o16,o17,o18,o19,o20,o21,o22,o23,o24,o25,o26,o27,o28,o29,o30,o31}, {a12,a13,a14,a15}, d11, p1, 1, 1, 1;\n"
        "wgmma.mma_async.sync.aligned.m64n32k16.f32.bf16.bf16 {o0,o1,o2,o3,o4,o5,o6,o7,o8,o9,o10,o11,o12,o13,o14,o15}, {a16,a17,a18,a19}, d4, p1, 1, 1, 1;\n"
        "wgmma.mma_async.sync.aligned.m64n32k16.f32.bf16.bf16 {o16,o17,o18,o19,o20,o21,o22,o23,o24,o25,o26,o27,o28,o29,o30,o31}, {a16,a17,a18,a19}, d12, p1, 1, 1, 1;\n"
        "wgmma.mma_async.sync.aligned.m64n32k16.f32.bf16.bf16 {o0,o1,o2,o3,o4,o5,o6,o7,o8,o9,o10,o11,o12,o13,o14,o15}, {a20,a21,a22,a23}, d5, p1, 1, 1, 1;\n"
        "wgmma.mma_async.sync.aligned.m64n32k16.f32.bf16.bf16 {o16,o17,o18,o19,o20,o21,o22,o23,o24,o25,o26,o27,o28,o29,o30,o31}, {a20,a21,a22,a23}, d13, p1, 1, 1, 1;\n"
        "wgmma.mma_async.sync.aligned.m64n32k16.f32.bf16.bf16 {o0,o1,o2,o3,o4,o5,o6,o7,o8,o9,o10,o11,o12,o13,o14,o15}, {a24,a25,a26,a27}, d6, p1, 1, 1, 1;\n"
        "wgmma.mma_async.sync.aligned.m64n32k16.f32.bf16.bf16 {o16,o17,o18,o19,o20,o21,o22,o23,o24,o25,o26,o27,o28,o29,o30,o31}, {a24,a25,a26,a27}, d14, p1, 1, 1, 1;\n"
        "wgmma.mma_async.sync.aligned.m64n32k16.f32.bf16.bf16 {o0,o1,o2,o3,o4,o5,o6,o7,o8,o9,o10,o11,o12,o13,o14,o15}, {a28,a29,a30,a31}, d7, p1, 1, 1, 1;\n"
        "wgmma.mma_async.sync.aligned.m64n32k16.f32.bf16.bf16 {o16,o17,o18,o19,o20,o21,o22,o23,o24,o25,o26,o27,o28,o29,o30,o31}, {a28,a29,a30,a31}, d15, p1, 1, 1, 1;\n"
        "wgmma.commit_group.sync.aligned;\n@nv bra.uni END;\nmovmatrix.sync.aligned.m8n8.trans.b16 b0, %32;\nmovmatrix.sync.aligned.m8n8.trans.b16 b1, %32;\n"
        "movmatrix.sync.aligned.m8n8.trans.b16 b2, %33;\nmovmatrix.sync.aligned.m8n8.trans.b16 b3, %33;\nmovmatrix.sync.aligned.m8n8.trans.b16 b4, %34;\n"
        "movmatrix.sync.aligned.m8n8.trans.b16 b5, %34;\nmovmatrix.sync.aligned.m8n8.trans.b16 b6, %35;\nmovmatrix.sync.aligned.m8n8.trans.b16 b7, %35;\n"
        "movmatrix.sync.aligned.m8n8.trans.b16 b8, %36;\nmovmatrix.sync.aligned.m8n8.trans.b16 b9, %36;\nmovmatrix.sync.aligned.m8n8.trans.b16 b10, %37;\n"
        "movmatrix.sync.aligned.m8n8.trans.b16 b11, %37;\nmovmatrix.sync.aligned.m8n8.trans.b16 b12, %38;\nmovmatrix.sync.aligned.m8n8.trans.b16 b13, %38;\n"
        "movmatrix.sync.aligned.m8n8.trans.b16 b14, %39;\nmovmatrix.sync.aligned.m8n8.trans.b16 b15, %39;\nmovmatrix.sync.aligned.m8n8.trans.b16 b16, %40;\n"
        "movmatrix.sync.aligned.m8n8.trans.b16 b17, %40;\nmovmatrix.sync.aligned.m8n8.trans.b16 b18, %41;\nmovmatrix.sync.aligned.m8n8.trans.b16 b19, %41;\n"
        "movmatrix.sync.aligned.m8n8.trans.b16 b20, %42;\nmovmatrix.sync.aligned.m8n8.trans.b16 b21, %42;\nmovmatrix.sync.aligned.m8n8.trans.b16 b22, %43;\n"
        "movmatrix.sync.aligned.m8n8.trans.b16 b23, %43;\nmovmatrix.sync.aligned.m8n8.trans.b16 b24, %44;\nmovmatrix.sync.aligned.m8n8.trans.b16 b25, %44;\n"
        "movmatrix.sync.aligned.m8n8.trans.b16 b26, %45;\nmovmatrix.sync.aligned.m8n8.trans.b16 b27, %45;\nmovmatrix.sync.aligned.m8n8.trans.b16 b28, %46;\n"
        "movmatrix.sync.aligned.m8n8.trans.b16 b29, %46;\nmovmatrix.sync.aligned.m8n8.trans.b16 b30, %47;\nmovmatrix.sync.aligned.m8n8.trans.b16 b31, %47;\n"
        "@nv bra.uni END;\nwgmma.wait_group.sync.aligned 0;\ncvt.rn.bf16x2.f32 k0, o1, o0;\ncvt.rn.bf16x2.f32 k1, o5, o4;\ncvt.rn.bf16x2.f32 k2, o9, o8;\n"
        "cvt.rn.bf16x2.f32 k3, o13, o12;\ncvt.rn.bf16x2.f32 k4, o3, o2;\ncvt.rn.bf16x2.f32 k5, o7, o6;\ncvt.rn.bf16x2.f32 k6, o11, o10;\n"
        "cvt.rn.bf16x2.f32 k7, o15, o14;\ncvt.rn.bf16x2.f32 k8, o17, o16;\ncvt.rn.bf16x2.f32 k9, o21, o20;\ncvt.rn.bf16x2.f32 k10, o25, o24;\n"
        "cvt.rn.bf16x2.f32 k11, o29, o28;\ncvt.rn.bf16x2.f32 k12, o19, o18;\ncvt.rn.bf16x2.f32 k13, o23, o22;\ncvt.rn.bf16x2.f32 k14, o27, o26;\n"
        "cvt.rn.bf16x2.f32 k15, o31, o30;\nld.volatile.shared.v2.b32 {c0,c1}, [%48+0];\nld.volatile.shared.v2.b32 {c2,c3}, [%48+4096];\n"
        "ld.volatile.shared.v2.b32 {c4,c5}, [%48+8];\nld.volatile.shared.v2.b32 {c6,c7}, [%48+4104];\ndp2a.lo.u32.u32 t, c0, 0x04000004, 0x200000;\n"
        "mov.b64 d0, {t, h};\ndp2a.hi.u32.u32 t, c0, 0x04000004, 0x200000;\nmov.b64 d1, {t, h};\ndp2a.lo.u32.u32 t, c1, 0x04000004, 0x200000;\n"
        "mov.b64 d2, {t, h};\ndp2a.hi.u32.u32 t, c1, 0x04000004, 0x200000;\nmov.b64 d3, {t, h};\ndp2a.lo.u32.u32 t, c2, 0x04000004, 0x200000;\n"
        "mov.b64 d4, {t, h};\ndp2a.hi.u32.u32 t, c2, 0x04000004, 0x200000;\nmov.b64 d5, {t, h};\ndp2a.lo.u32.u32 t, c3, 0x04000004, 0x200000;\n"
        "mov.b64 d6, {t, h};\ndp2a.hi.u32.u32 t, c3, 0x04000004, 0x200000;\nmov.b64 d7, {t, h};\ndp2a.lo.u32.u32 t, c4, 0x04000004, 0x200000;\n"
        "mov.b64 d8, {t, h};\ndp2a.hi.u32.u32 t, c4, 0x04000004, 0x200000;\nmov.b64 d9, {t, h};\ndp2a.lo.u32.u32 t, c5, 0x04000004, 0x200000;\n"
        "mov.b64 d10, {t, h};\ndp2a.hi.u32.u32 t, c5, 0x04000004, 0x200000;\nmov.b64 d11, {t, h};\ndp2a.lo.u32.u32 t, c6, 0x04000004, 0x200000;\n"
        "mov.b64 d12, {t, h};\ndp2a.hi.u32.u32 t, c6, 0x04000004, 0x200000;\nmov.b64 d13, {t, h};\ndp2a.lo.u32.u32 t, c7, 0x04000004, 0x200000;\n"
        "mov.b64 d14, {t, h};\ndp2a.hi.u32.u32 t, c7, 0x04000004, 0x200000;\nmov.b64 d15, {t, h};\nwgmma.fence.sync.aligned;\n"
        "wgmma.mma_async.sync.aligned.m64n32k16.f32.bf16.bf16 {o0,o1,o2,o3,o4,o5,o6,o7,o8,o9,o10,o11,o12,o13,o14,o15}, {b0,b1,b2,b3}, d0, p0, 1, 1, 1;\n"
        "wgmma.mma_async.sync.aligned.m64n32k16.f32.bf16.bf16 {o16,o17,o18,o19,o20,o21,o22,o23,o24,o25,o26,o27,o28,o29,o30,o31}, {b0,b1,b2,b3}, d8, p0, 1, 1, 1;\n"
        "wgmma.mma_async.sync.aligned.m64n32k16.f32.bf16.bf16 {o0,o1,o2,o3,o4,o5,o6,o7,o8,o9,o10,o11,o12,o13,o14,o15}, {b4,b5,b6,b7}, d1, p1, 1, 1, 1;\n"
        "wgmma.mma_async.sync.aligned.m64n32k16.f32.bf16.bf16 {o16,o17,o18,o19,o20,o21,o22,o23,o24,o25,o26,o27,o28,o29,o30,o31}, {b4,b5,b6,b7}, d9, p1, 1, 1, 1;\n"
        "wgmma.mma_async.sync.aligned.m64n32k16.f32.bf16.bf16 {o0,o1,o2,o3,o4,o5,o6,o7,o8,o9,o10,o11,o12,o13,o14,o15}, {b8,b9,b10,b11}, d2, p1, 1, 1, 1;\n"
        "wgmma.mma_async.sync.aligned.m64n32k16.f32.bf16.bf16 {o16,o17,o18,o19,o20,o21,o22,o23,o24,o25,o26,o27,o28,o29,o30,o31}, {b8,b9,b10,b11}, d10, p1, 1, 1, 1;\n"
        "wgmma.mma_async.sync.aligned.m64n32k16.f32.bf16.bf16 {o0,o1,o2,o3,o4,o5,o6,o7,o8,o9,o10,o11,o12,o13,o14,o15}, {b12,b13,b14,b15}, d3, p1, 1, 1, 1;\n"
        "wgmma.mma_async.sync.aligned.m64n32k16.f32.bf16.bf16 {o16,o17,o18,o19,o20,o21,o22,o23,o24,o25,o26,o27,o28,o29,o30,o31}, {b12,b13,b14,b15}, d11, p1, 1, 1, 1;\n"
        "wgmma.mma_async.sync.aligned.m64n32k16.f32.bf16.bf16 {o0,o1,o2,o3,o4,o5,o6,o7,o8,o9,o10,o11,o12,o13,o14,o15}, {b16,b17,b18,b19}, d4, p1, 1, 1, 1;\n"
        "wgmma.mma_async.sync.aligned.m64n32k16.f32.bf16.bf16 {o16,o17,o18,o19,o20,o21,o22,o23,o24,o25,o26,o27,o28,o29,o30,o31}, {b16,b17,b18,b19}, d12, p1, 1, 1, 1;\n"
        "wgmma.mma_async.sync.aligned.m64n32k16.f32.bf16.bf16 {o0,o1,o2,o3,o4,o5,o6,o7,o8,o9,o10,o11,o12,o13,o14,o15}, {b20,b21,b22,b23}, d5, p1, 1, 1, 1;\n"
        "wgmma.mma_async.sync.aligned.m64n32k16.f32.bf16.bf16 {o16,o17,o18,o19,o20,o21,o22,o23,o24,o25,o26,o27,o28,o29,o30,o31}, {b20,b21,b22,b23}, d13, p1, 1, 1, 1;\n"
        "wgmma.mma_async.sync.aligned.m64n32k16.f32.bf16.bf16 {o0,o1,o2,o3,o4,o5,o6,o7,o8,o9,o10,o11,o12,o13,o14,o15}, {b24,b25,b26,b27}, d6, p1, 1, 1, 1;\n"
        "wgmma.mma_async.sync.aligned.m64n32k16.f32.bf16.bf16 {o16,o17,o18,o19,o20,o21,o22,o23,o24,o25,o26,o27,o28,o29,o30,o31}, {b24,b25,b26,b27}, d14, p1, 1, 1, 1;\n"
        "wgmma.mma_async.sync.aligned.m64n32k16.f32.bf16.bf16 {o0,o1,o2,o3,o4,o5,o6,o7,o8,o9,o10,o11,o12,o13,o14,o15}, {b28,b29,b30,b31}, d7, p1, 1, 1, 1;\n"
        "wgmma.mma_async.sync.aligned.m64n32k16.f32.bf16.bf16 {o16,o17,o18,o19,o20,o21,o22,o23,o24,o25,o26,o27,o28,o29,o30,o31}, {b28,b29,b30,b31}, d15, p1, 1, 1, 1;\n"
        "wgmma.commit_group.sync.aligned;\n@nv bra.uni END;\n@s0 st.global.v4.b32 [%49+128], {k0,k1,k2,k3};\n@s1 st.global.v4.b32 [%50+128], {k4,k5,k6,k7};\n"
        "@s0 st.global.v4.b32 [%49+192], {k8,k9,k10,k11};\n@s1 st.global.v4.b32 [%50+192], {k12,k13,k14,k15};\n@nv bra.uni END;\n"
        "wgmma.wait_group.sync.aligned 0;\ncvt.rn.bf16x2.f32 k0, o1, o0;\ncvt.rn.bf16x2.f32 k1, o5, o4;\ncvt.rn.bf16x2.f32 k2, o9, o8;\n"
        "cvt.rn.bf16x2.f32 k3, o13, o12;\ncvt.rn.bf16x2.f32 k8, o17, o16;\ncvt.rn.bf16x2.f32 k9, o21, o20;\ncvt.rn.bf16x2.f32 k10, o25, o24;\n"
        "cvt.rn.bf16x2.f32 k11, o29, o28;\nld.volatile.shared.v2.b32 {c0,c1}, [%48+16];\nld.volatile.shared.v2.b32 {c2,c3}, [%48+4112];\n"
        "ld.volatile.shared.v2.b32 {c4,c5}, [%48+24];\nld.volatile.shared.v2.b32 {c6,c7}, [%48+4120];\ndp2a.lo.u32.u32 t, c0, 0x04000004, 0x200000;\n"
        "mov.b64 d0, {t, h};\ndp2a.hi.u32.u32 t, c0, 0x04000004, 0x200000;\nmov.b64 d1, {t, h};\ndp2a.lo.u32.u32 t, c1, 0x04000004, 0x200000;\n"
        "mov.b64 d2, {t, h};\ndp2a.hi.u32.u32 t, c1, 0x04000004, 0x200000;\nmov.b64 d3, {t, h};\ndp2a.lo.u32.u32 t, c2, 0x04000004, 0x200000;\n"
        "mov.b64 d4, {t, h};\ndp2a.hi.u32.u32 t, c2, 0x04000004, 0x200000;\nmov.b64 d5, {t, h};\ndp2a.lo.u32.u32 t, c3, 0x04000004, 0x200000;\n"
        "mov.b64 d6, {t, h};\ndp2a.hi.u32.u32 t, c3, 0x04000004, 0x200000;\nmov.b64 d7, {t, h};\ndp2a.lo.u32.u32 t, c4, 0x04000004, 0x200000;\n"
        "mov.b64 d8, {t, h};\ndp2a.hi.u32.u32 t, c4, 0x04000004, 0x200000;\nmov.b64 d9, {t, h};\ndp2a.lo.u32.u32 t, c5, 0x04000004, 0x200000;\n"
        "mov.b64 d10, {t, h};\ndp2a.hi.u32.u32 t, c5, 0x04000004, 0x200000;\nmov.b64 d11, {t, h};\ndp2a.lo.u32.u32 t, c6, 0x04000004, 0x200000;\n"
        "mov.b64 d12, {t, h};\ndp2a.hi.u32.u32 t, c6, 0x04000004, 0x200000;\nmov.b64 d13, {t, h};\ndp2a.lo.u32.u32 t, c7, 0x04000004, 0x200000;\n"
        "mov.b64 d14, {t, h};\ndp2a.hi.u32.u32 t, c7, 0x04000004, 0x200000;\nmov.b64 d15, {t, h};\nwgmma.fence.sync.aligned;\n"
        "wgmma.mma_async.sync.aligned.m64n32k16.f32.bf16.bf16 {o0,o1,o2,o3,o4,o5,o6,o7,o8,o9,o10,o11,o12,o13,o14,o15}, {b0,b1,b2,b3}, d0, p0, 1, 1, 1;\n"
        "wgmma.mma_async.sync.aligned.m64n32k16.f32.bf16.bf16 {o16,o17,o18,o19,o20,o21,o22,o23,o24,o25,o26,o27,o28,o29,o30,o31}, {b0,b1,b2,b3}, d8, p0, 1, 1, 1;\n"
        "wgmma.mma_async.sync.aligned.m64n32k16.f32.bf16.bf16 {o0,o1,o2,o3,o4,o5,o6,o7,o8,o9,o10,o11,o12,o13,o14,o15}, {b4,b5,b6,b7}, d1, p1, 1, 1, 1;\n"
        "wgmma.mma_async.sync.aligned.m64n32k16.f32.bf16.bf16 {o16,o17,o18,o19,o20,o21,o22,o23,o24,o25,o26,o27,o28,o29,o30,o31}, {b4,b5,b6,b7}, d9, p1, 1, 1, 1;\n"
        "wgmma.mma_async.sync.aligned.m64n32k16.f32.bf16.bf16 {o0,o1,o2,o3,o4,o5,o6,o7,o8,o9,o10,o11,o12,o13,o14,o15}, {b8,b9,b10,b11}, d2, p1, 1, 1, 1;\n"
        "wgmma.mma_async.sync.aligned.m64n32k16.f32.bf16.bf16 {o16,o17,o18,o19,o20,o21,o22,o23,o24,o25,o26,o27,o28,o29,o30,o31}, {b8,b9,b10,b11}, d10, p1, 1, 1, 1;\n"
        "wgmma.mma_async.sync.aligned.m64n32k16.f32.bf16.bf16 {o0,o1,o2,o3,o4,o5,o6,o7,o8,o9,o10,o11,o12,o13,o14,o15}, {b12,b13,b14,b15}, d3, p1, 1, 1, 1;\n"
        "wgmma.mma_async.sync.aligned.m64n32k16.f32.bf16.bf16 {o16,o17,o18,o19,o20,o21,o22,o23,o24,o25,o26,o27,o28,o29,o30,o31}, {b12,b13,b14,b15}, d11, p1, 1, 1, 1;\n"
        "wgmma.mma_async.sync.aligned.m64n32k16.f32.bf16.bf16 {o0,o1,o2,o3,o4,o5,o6,o7,o8,o9,o10,o11,o12,o13,o14,o15}, {b16,b17,b18,b19}, d4, p1, 1, 1, 1;\n"
        "wgmma.mma_async.sync.aligned.m64n32k16.f32.bf16.bf16 {o16,o17,o18,o19,o20,o21,o22,o23,o24,o25,o26,o27,o28,o29,o30,o31}, {b16,b17,b18,b19}, d12, p1, 1, 1, 1;\n"
        "wgmma.mma_async.sync.aligned.m64n32k16.f32.bf16.bf16 {o0,o1,o2,o3,o4,o5,o6,o7,o8,o9,o10,o11,o12,o13,o14,o15}, {b20,b21,b22,b23}, d5, p1, 1, 1, 1;\n"
        "wgmma.mma_async.sync.aligned.m64n32k16.f32.bf16.bf16 {o16,o17,o18,o19,o20,o21,o22,o23,o24,o25,o26,o27,o28,o29,o30,o31}, {b20,b21,b22,b23}, d13, p1, 1, 1, 1;\n"
        "wgmma.mma_async.sync.aligned.m64n32k16.f32.bf16.bf16 {o0,o1,o2,o3,o4,o5,o6,o7,o8,o9,o10,o11,o12,o13,o14,o15}, {b24,b25,b26,b27}, d6, p1, 1, 1, 1;\n"
        "wgmma.mma_async.sync.aligned.m64n32k16.f32.bf16.bf16 {o16,o17,o18,o19,o20,o21,o22,o23,o24,o25,o26,o27,o28,o29,o30,o31}, {b24,b25,b26,b27}, d14, p1, 1, 1, 1;\n"
        "wgmma.mma_async.sync.aligned.m64n32k16.f32.bf16.bf16 {o0,o1,o2,o3,o4,o5,o6,o7,o8,o9,o10,o11,o12,o13,o14,o15}, {b28,b29,b30,b31}, d7, p1, 1, 1, 1;\n"
        "wgmma.mma_async.sync.aligned.m64n32k16.f32.bf16.bf16 {o16,o17,o18,o19,o20,o21,o22,o23,o24,o25,o26,o27,o28,o29,o30,o31}, {b28,b29,b30,b31}, d15, p1, 1, 1, 1;\n"
        "wgmma.commit_group.sync.aligned;\n@nv bra.uni END;\n@s2 st.global.v4.b32 [%51+0], {k0,k1,k2,k3};\n@s2 st.global.v4.b32 [%51+64], {k8,k9,k10,k11};\n"
        "@nv bra.uni END;\nwgmma.wait_group.sync.aligned 0;\ncvt.rn.bf16x2.f32 k0, o1, o0;\ncvt.rn.bf16x2.f32 k1, o5, o4;\ncvt.rn.bf16x2.f32 k2, o9, o8;\n"
        "cvt.rn.bf16x2.f32 k3, o13, o12;\ncvt.rn.bf16x2.f32 k8, o17, o16;\ncvt.rn.bf16x2.f32 k9, o21, o20;\ncvt.rn.bf16x2.f32 k10, o25, o24;\n"
        "cvt.rn.bf16x2.f32 k11, o29, o28;\n@s2 st.global.v4.b32 [%51+128], {k0,k1,k2,k3};\n@s2 st.global.v4.b32 [%51+192], {k8,k9,k10,k11};\n"
        "END:\n}\n"
        ::"r"(pk[0]), "r"(pk[1]), "r"(pk[2]), "r"(pk[3]), "r"(pk[4]), "r"(pk[5]), "r"(pk[6]), "r"(pk[7]), "r"(pk[8]), "r"(pk[9]), "r"(pk[10]),
          "r"(pk[11]), "r"(pk[12]), "r"(pk[13]), "r"(pk[14]), "r"(pk[15]), "r"(pk[16]), "r"(pk[17]), "r"(pk[18]), "r"(pk[19]), "r"(pk[20]),
          "r"(pk[21]), "r"(pk[22]), "r"(pk[23]), "r"(pk[24]), "r"(pk[25]), "r"(pk[26]), "r"(pk[27]), "r"(pk[28]), "r"(pk[29]), "r"(pk[30]),
          "r"(pk[31]), "r"(pk[32]), "r"(pk[33]), "r"(pk[34]), "r"(pk[35]), "r"(pk[36]), "r"(pk[37]), "r"(pk[38]), "r"(pk[39]), "r"(pk[40]),
          "r"(pk[41]), "r"(pk[42]), "r"(pk[43]), "r"(pk[44]), "r"(pk[45]), "r"(pk[46]), "r"(pk[47]), "r"(ra), "l"(p[0]), "l"(p[1]), "l"(p[2]),
          "r"(v[0]), "r"(v[1]), "r"(v[2]), "r"(ba)
        : "memory");
}
__device__ __forceinline__ int cta_id() {
    int v;
    asm volatile("mov.u32 %0, %ctaid.x;" : "=r"(v));
    return v;
}
__device__ __forceinline__ int thread_id() {
    int v;
    asm volatile("mov.u32 %0, %tid.x;" : "=r"(v));
    return v;
}

__device__ __forceinline__ void slow_edge(int ee, int s, float* accn, const __nv_bfloat16* __restrict__ x,
                                          const __nv_bfloat16* __restrict__ sh, const __nv_bfloat16* __restrict__ ea,
                                          const __nv_bfloat16* __restrict__ cg, const __nv_bfloat16* __restrict__ wr,
                                          int lane) {
    float rwv[4] = {0.f, 0.f, 0.f, 0.f};
#pragma unroll 4
    for (int d = 0; d < 16; d++) {
        const float a = __bfloat162float(ea[(size_t)ee * 16 + d]);
        const uint2 wv = *(const uint2*)(wr + d * 128 + lane * 4);
        rwv[0] += a * __uint_as_float(wv.x << 16);
        rwv[1] += a * __uint_as_float(wv.x & 0xffff0000u);
        rwv[2] += a * __uint_as_float(wv.y << 16);
        rwv[3] += a * __uint_as_float(wv.y & 0xffff0000u);
    }
    float A = 0.f;
#pragma unroll
    for (int v = 0; v < 4; v++)
        A += __bfloat162float(cg[((lane >> 2) & 3) * 16 + v * 4 + (lane & 3)]) * __bfloat162float(sh[(size_t)ee * 4 + v]);
    float m[4][4];
#pragma unroll
    for (int w = 0; w < 4; w++)
#pragma unroll
        for (int j = 0; j < 4; j++) m[w][j] = 0.f;
#pragma unroll
    for (int u = 0; u < 4; u++) {
        const uint2 xv = *(const uint2*)(x + (size_t)s * 512 + u * 128 + lane * 4);
        const float x0 = __uint_as_float(xv.x << 16), x1 = __uint_as_float(xv.x & 0xffff0000u);
        const float x2 = __uint_as_float(xv.y << 16), x3 = __uint_as_float(xv.y & 0xffff0000u);
#pragma unroll
        for (int w = 0; w < 4; w++) {
            const float a = __shfl_sync(0xffffffffu, A, u * 4 + w);
            m[w][0] += a * x0;
            m[w][1] += a * x1;
            m[w][2] += a * x2;
            m[w][3] += a * x3;
        }
    }
#pragma unroll
    for (int w = 0; w < 4; w++)
#pragma unroll
        for (int j = 0; j < 4; j++) atomicAdd(accn + w * 128 + lane * 4 + j, m[w][j] * rwv[j]);
}

__device__ __forceinline__ void slow_out(const float* accn, const __nv_bfloat16* __restrict__ wout,
                                         __nv_bfloat16* __restrict__ outn, int lane) {
    float o[4][4];
#pragma unroll
    for (int w = 0; w < 4; w++)
#pragma unroll
        for (int j = 0; j < 4; j++) o[w][j] = 0.f;
#pragma unroll 2
    for (int c = 0; c < 128; c++) {
        const uint2 wv = *(const uint2*)(wout + c * 128 + lane * 4);
        const float w0 = __uint_as_float(wv.x << 16), w1 = __uint_as_float(wv.x & 0xffff0000u);
        const float w2 = __uint_as_float(wv.y << 16), w3 = __uint_as_float(wv.y & 0xffff0000u);
#pragma unroll
        for (int w = 0; w < 4; w++) {
            const float a = __bfloat162float(__float2bfloat16(accn[w * 128 + c]));
            o[w][0] += a * w0;
            o[w][1] += a * w1;
            o[w][2] += a * w2;
            o[w][3] += a * w3;
        }
    }
#pragma unroll
    for (int w = 0; w < 4; w++)
        *(uint2*)(outn + w * 128 + lane * 4) = make_uint2(pack_bf16(o[w][0], o[w][1]), pack_bf16(o[w][2], o[w][3]));
}


__device__ __forceinline__ void consume4(uint32_t (&pk)[64], const uint32_t (&w)[36], uint32_t olp, uint32_t xa, uint32_t ln,
                                      uint32_t lc, uint32_t linc, uint32_t lt, const __nv_bfloat16* ea, const __nv_bfloat16* sh, const void* wf, uint4 first) {
    ea += lt * 4, sh += lt & 2;
    asm volatile(
        "{\n.reg .pred p, q, psw, prdy, ps1, ps2, ps3, pz, pq, pt, pl;\n.reg .f32 d<40>, fz;\n"
        ".reg .b32 h<64>, x<32>, y<32>, ra<8>, rb<8>, bA0, bA1, bB0, bB1, c0, c1, c2, c3, e0, e1, s0, kept;\n"
        ".reg .b32 olp, v, vB, m, id, ida, bar, xb, pos, t0, t1, t2, t3, n, z<16>, kept2, g<4>, f0, f1, s1;\n.reg .b16 lo, hi, i16;\n.reg .b64 pa, pb;\n"
        "mov.f32 fz, 0f00000000;\nmov.b32 h0, 0;\nmov.b32 h1, 0;\nmov.b32 h2, 0;\nmov.b32 h3, 0;\nmov.b32 h4, 0;\nmov.b32 h5, 0;\nmov.b32 h6, 0;\n"
        "mov.b32 h7, 0;\nmov.b32 h8, 0;\nmov.b32 h9, 0;\nmov.b32 h10, 0;\nmov.b32 h11, 0;\nmov.b32 h12, 0;\nmov.b32 h13, 0;\nmov.b32 h14, 0;\nmov.b32 h15, 0;\n"
        "mov.b32 h16, 0;\nmov.b32 h17, 0;\nmov.b32 h18, 0;\nmov.b32 h19, 0;\nmov.b32 h20, 0;\nmov.b32 h21, 0;\nmov.b32 h22, 0;\nmov.b32 h23, 0;\n"
        "mov.b32 h24, 0;\nmov.b32 h25, 0;\nmov.b32 h26, 0;\nmov.b32 h27, 0;\nmov.b32 h28, 0;\nmov.b32 h29, 0;\nmov.b32 h30, 0;\nmov.b32 h31, 0;\n"
        "mov.b32 h32, 0;\nmov.b32 h33, 0;\nmov.b32 h34, 0;\nmov.b32 h35, 0;\nmov.b32 h36, 0;\nmov.b32 h37, 0;\nmov.b32 h38, 0;\nmov.b32 h39, 0;\n"
        "mov.b32 h40, 0;\nmov.b32 h41, 0;\nmov.b32 h42, 0;\nmov.b32 h43, 0;\nmov.b32 h44, 0;\nmov.b32 h45, 0;\nmov.b32 h46, 0;\nmov.b32 h47, 0;\n"
        "mov.b32 h48, 0;\nmov.b32 h49, 0;\nmov.b32 h50, 0;\nmov.b32 h51, 0;\nmov.b32 h52, 0;\nmov.b32 h53, 0;\nmov.b32 h54, 0;\nmov.b32 h55, 0;\n"
        "mov.b32 h56, 0;\nmov.b32 h57, 0;\nmov.b32 h58, 0;\nmov.b32 h59, 0;\nmov.b32 h60, 0;\nmov.b32 h61, 0;\nmov.b32 h62, 0;\nmov.b32 h63, 0;\n"
        "mov.b32 olp, %64;\nand.b32 t0, %66, 32;\nsetp.ne.u32 psw, t0, 0;\nsetp.eq.u32 pz, %64, 0;\nvote.sync.any.pred pz, pz, 0xffffffff;\nmov.b32 e0, %73;\n"
        "mov.b32 e1, %74;\nmov.b32 s0, %75;\nmov.b32 kept, %76;\nadd.u32 olp, olp, 4;\nsetp.ne.u64 p, %72, 0;\n@p fence.proxy.async.global;\n"
        "@p red.release.gpu.global.add.u32 [%72+12], 1;\nbar.warp.sync 0xffffffff;\nshfl.sync.idx.b32 v, kept, %67, 0x1f, 0xffffffff;\nor.b32 t3, %67, 4;\n"
        "shfl.sync.idx.b32 vB, kept, t3, 0x1f, 0xffffffff;\nld.shared.u16 t0, [olp];\nadd.u32 olp, olp, 4;\nlop3.b32 t1, t0, %66, 0x3ff0, 0xe4;\n"
        "ld.shared.b32 t1, [t1+%77];\nshr.u32 t2, t1, 1;\nlop3.b32 kept, t2, t0, 0xffe, 0xe4;\nlop3.b32 t2, t1, %67, 3, 0x80;\nsetp.ne.u32 pq, t2, 0;\n"
        "shr.u32 t2, t1, 13;\nmad.wide.u32 pa, t2, 32, %70;\nmad.wide.u32 pb, t2, 8, %71;\n"
        "RW:\nmma.sync.aligned.m16n8k8.row.col.f32.bf16.bf16.f32 {d0,d1,d2,d3}, {%114,%115}, {s0}, {fz,fz,fz,fz};\n"
        "mma.sync.aligned.m16n8k8.row.col.f32.bf16.bf16.f32 {d4,d5,d6,d7}, {%116,%117}, {s0}, {fz,fz,fz,fz};\ncvt.rn.bf16x2.f32 c0, d2, d0;\n"
        "cvt.rn.bf16x2.f32 c1, d3, d1;\ncvt.rn.bf16x2.f32 c2, d6, d4;\ncvt.rn.bf16x2.f32 c3, d7, d5;\nselp.b32 bA0, c2, c0, psw;\nselp.b32 bA1, c0, c2, psw;\n"
        "selp.b32 bB0, c3, c1, psw;\nselp.b32 bB1, c1, c3, psw;\n"
        "mma.sync.aligned.m16n8k16.row.col.f32.bf16.bf16.f32 {d0,d1,d2,d3}, {%82,%83,%84,%85}, {e0,e1}, {fz,fz,fz,fz};\ncvt.rn.bf16x2.f32 ra0, d2, d0;\n"
        "cvt.rn.bf16x2.f32 rb0, d3, d1;\nmma.sync.aligned.m16n8k16.row.col.f32.bf16.bf16.f32 {d4,d5,d6,d7}, {%86,%87,%88,%89}, {e0,e1}, {fz,fz,fz,fz};\n"
        "cvt.rn.bf16x2.f32 ra1, d6, d4;\ncvt.rn.bf16x2.f32 rb1, d7, d5;\n"
        "mma.sync.aligned.m16n8k16.row.col.f32.bf16.bf16.f32 {d8,d9,d10,d11}, {%90,%91,%92,%93}, {e0,e1}, {fz,fz,fz,fz};\ncvt.rn.bf16x2.f32 ra2, d10, d8;\n"
        "cvt.rn.bf16x2.f32 rb2, d11, d9;\nmma.sync.aligned.m16n8k16.row.col.f32.bf16.bf16.f32 {d12,d13,d14,d15}, {%94,%95,%96,%97}, {e0,e1}, {fz,fz,fz,fz};\n"
        "cvt.rn.bf16x2.f32 ra3, d14, d12;\ncvt.rn.bf16x2.f32 rb3, d15, d13;\n"
        "mma.sync.aligned.m16n8k16.row.col.f32.bf16.bf16.f32 {d16,d17,d18,d19}, {%98,%99,%100,%101}, {e0,e1}, {fz,fz,fz,fz};\ncvt.rn.bf16x2.f32 ra4, d18, d16;\n"
        "cvt.rn.bf16x2.f32 rb4, d19, d17;\n"
        "mma.sync.aligned.m16n8k16.row.col.f32.bf16.bf16.f32 {d20,d21,d22,d23}, {%102,%103,%104,%105}, {e0,e1}, {fz,fz,fz,fz};\n"
        "cvt.rn.bf16x2.f32 ra5, d22, d20;\ncvt.rn.bf16x2.f32 rb5, d23, d21;\n"
        "mma.sync.aligned.m16n8k16.row.col.f32.bf16.bf16.f32 {d24,d25,d26,d27}, {%106,%107,%108,%109}, {e0,e1}, {fz,fz,fz,fz};\n"
        "cvt.rn.bf16x2.f32 ra6, d26, d24;\ncvt.rn.bf16x2.f32 rb6, d27, d25;\n"
        "mma.sync.aligned.m16n8k16.row.col.f32.bf16.bf16.f32 {d28,d29,d30,d31}, {%110,%111,%112,%113}, {e0,e1}, {fz,fz,fz,fz};\n"
        "cvt.rn.bf16x2.f32 ra7, d30, d28;\ncvt.rn.bf16x2.f32 rb7, d31, d29;\nmov.b32 s0, 0;\nld.global.cg.L2::128B.v2.b32 {e0,e1}, [pa];\n"
        "@pq ld.global.cg.L2::128B.b32 s0, [pb];\nand.b32 bar, v, 0xff8;\nmbarrier.test_wait.parity.shared.b64 pl, [bar+%79], 0;\n"
        "lop3.b32 ida, v, %67, 0xfff, 0xe4;\nld.volatile.shared.u16 id, [ida+%78];\nvote.sync.all.pred prdy, pl, 0xffffffff;\n@!prdy bra.uni WA;\n"
        "HA:\nmad.lo.u32 xb, id, 64, %65;\ncvt.u16.u32 i16, id;\natom.shared.add.u32 pos, [%66+%80], %68;\n"
        "ldmatrix.sync.aligned.m8n8.x4.trans.shared.b16 {x0,x1,x2,x3}, [xb];\nldmatrix.sync.aligned.m8n8.x4.trans.shared.b16 {x24,x25,x26,x27}, [xb+512];\n"
        "xor.b32 t1, xb, 32;\nldmatrix.sync.aligned.m8n8.x4.trans.shared.b16 {x4,x5,x6,x7}, [t1];\n"
        "ldmatrix.sync.aligned.m8n8.x4.trans.shared.b16 {x28,x29,x30,x31}, [t1+512];\nxor.b32 t1, xb, 64;\n"
        "ldmatrix.sync.aligned.m8n8.x4.trans.shared.b16 {x8,x9,x10,x11}, [t1];\nldmatrix.sync.aligned.m8n8.x4.trans.shared.b16 {x16,x17,x18,x19}, [t1+512];\n"
        "xor.b32 t1, xb, 96;\nldmatrix.sync.aligned.m8n8.x4.trans.shared.b16 {x12,x13,x14,x15}, [t1];\n"
        "ldmatrix.sync.aligned.m8n8.x4.trans.shared.b16 {x20,x21,x22,x23}, [t1+512];\nst.volatile.shared.u16 [pos], i16;\nand.b32 t0, v, 16384;\n"
        "setp.ne.u32 ps1, t0, 0;\nvote.sync.any.pred ps1, ps1, 0xffffffff;\nand.b32 t0, v, 32768;\nsetp.ne.u32 ps2, t0, 0;\n"
        "vote.sync.any.pred ps2, ps2, 0xffffffff;\nmov.b32 v, vB;\nand.b32 bar, v, 0xff8;\nmbarrier.test_wait.parity.shared.b64 pl, [bar+%79], 0;\n"
        "lop3.b32 ida, v, %67, 0xfff, 0xe4;\nld.volatile.shared.u16 id, [ida+%78];\nvote.sync.all.pred prdy, pl, 0xffffffff;\nmov.b32 {lo, hi}, ra0;\n"
        "mov.b32 t2, {lo, lo};\nmul.rn.bf16x2 y0, x0, t2;\nmul.rn.bf16x2 y2, x2, t2;\nmov.b32 t2, {hi, hi};\nmul.rn.bf16x2 y1, x1, t2;\n"
        "mul.rn.bf16x2 y3, x3, t2;\nmma.sync.aligned.m16n8k16.row.col.f32.bf16.bf16.f32 {d0,d1,d2,d3}, {y0,y1,y2,y3}, {bA0,bA1}, {fz,fz,fz,fz};\n"
        "cvt.rn.bf16x2.f32 z0, d1, d0;\ncvt.rn.bf16x2.f32 z1, d3, d2;\nmov.b32 {lo, hi}, ra6;\nmov.b32 t2, {lo, lo};\nmul.rn.bf16x2 y24, x24, t2;\n"
        "mul.rn.bf16x2 y26, x26, t2;\nmov.b32 t2, {hi, hi};\nmul.rn.bf16x2 y25, x25, t2;\nmul.rn.bf16x2 y27, x27, t2;\n"
        "mma.sync.aligned.m16n8k16.row.col.f32.bf16.bf16.f32 {d24,d25,d26,d27}, {y24,y25,y26,y27}, {bA0,bA1}, {fz,fz,fz,fz};\ncvt.rn.bf16x2.f32 z12, d25, d24;\n"
        "cvt.rn.bf16x2.f32 z13, d27, d26;\nmov.b32 {lo, hi}, ra1;\nmov.b32 t2, {lo, lo};\nmul.rn.bf16x2 y4, x4, t2;\nmul.rn.bf16x2 y6, x6, t2;\n"
        "mov.b32 t2, {hi, hi};\nmul.rn.bf16x2 y5, x5, t2;\nmul.rn.bf16x2 y7, x7, t2;\n"
        "mma.sync.aligned.m16n8k16.row.col.f32.bf16.bf16.f32 {d4,d5,d6,d7}, {y4,y5,y6,y7}, {bA0,bA1}, {fz,fz,fz,fz};\ncvt.rn.bf16x2.f32 z2, d5, d4;\n"
        "cvt.rn.bf16x2.f32 z3, d7, d6;\nmov.b32 {lo, hi}, ra7;\nmov.b32 t2, {lo, lo};\nmul.rn.bf16x2 y28, x28, t2;\nmul.rn.bf16x2 y30, x30, t2;\n"
        "mov.b32 t2, {hi, hi};\nmul.rn.bf16x2 y29, x29, t2;\nmul.rn.bf16x2 y31, x31, t2;\n"
        "mma.sync.aligned.m16n8k16.row.col.f32.bf16.bf16.f32 {d28,d29,d30,d31}, {y28,y29,y30,y31}, {bA0,bA1}, {fz,fz,fz,fz};\ncvt.rn.bf16x2.f32 z14, d29, d28;\n"
        "cvt.rn.bf16x2.f32 z15, d31, d30;\nmov.b32 {lo, hi}, ra2;\nmov.b32 t2, {lo, lo};\nmul.rn.bf16x2 y8, x8, t2;\nmul.rn.bf16x2 y10, x10, t2;\n"
        "mov.b32 t2, {hi, hi};\nmul.rn.bf16x2 y9, x9, t2;\nmul.rn.bf16x2 y11, x11, t2;\n"
        "mma.sync.aligned.m16n8k16.row.col.f32.bf16.bf16.f32 {d8,d9,d10,d11}, {y8,y9,y10,y11}, {bA0,bA1}, {fz,fz,fz,fz};\ncvt.rn.bf16x2.f32 z4, d9, d8;\n"
        "cvt.rn.bf16x2.f32 z5, d11, d10;\nmov.b32 {lo, hi}, ra4;\nmov.b32 t2, {lo, lo};\nmul.rn.bf16x2 y16, x16, t2;\nmul.rn.bf16x2 y18, x18, t2;\n"
        "mov.b32 t2, {hi, hi};\nmul.rn.bf16x2 y17, x17, t2;\nmul.rn.bf16x2 y19, x19, t2;\n"
        "mma.sync.aligned.m16n8k16.row.col.f32.bf16.bf16.f32 {d16,d17,d18,d19}, {y16,y17,y18,y19}, {bA0,bA1}, {fz,fz,fz,fz};\ncvt.rn.bf16x2.f32 z8, d17, d16;\n"
        "cvt.rn.bf16x2.f32 z9, d19, d18;\nmov.b32 {lo, hi}, ra3;\nmov.b32 t2, {lo, lo};\nmul.rn.bf16x2 y12, x12, t2;\nmul.rn.bf16x2 y14, x14, t2;\n"
        "mov.b32 t2, {hi, hi};\nmul.rn.bf16x2 y13, x13, t2;\nmul.rn.bf16x2 y15, x15, t2;\n"
        "mma.sync.aligned.m16n8k16.row.col.f32.bf16.bf16.f32 {d12,d13,d14,d15}, {y12,y13,y14,y15}, {bA0,bA1}, {fz,fz,fz,fz};\ncvt.rn.bf16x2.f32 z6, d13, d12;\n"
        "cvt.rn.bf16x2.f32 z7, d15, d14;\nmov.b32 {lo, hi}, ra5;\nmov.b32 t2, {lo, lo};\nmul.rn.bf16x2 y20, x20, t2;\nmul.rn.bf16x2 y22, x22, t2;\n"
        "mov.b32 t2, {hi, hi};\nmul.rn.bf16x2 y21, x21, t2;\nmul.rn.bf16x2 y23, x23, t2;\n"
        "mma.sync.aligned.m16n8k16.row.col.f32.bf16.bf16.f32 {d20,d21,d22,d23}, {y20,y21,y22,y23}, {bA0,bA1}, {fz,fz,fz,fz};\ncvt.rn.bf16x2.f32 z10, d21, d20;\n"
        "cvt.rn.bf16x2.f32 z11, d23, d22;\n@ps2 bra.uni TA2;\n@ps1 bra.uni TA1;\n"
        "TA0:\nadd.rn.bf16x2 h0, h0, z0;\nadd.rn.bf16x2 h1, h1, z1;\nadd.rn.bf16x2 h2, h2, z2;\nadd.rn.bf16x2 h3, h3, z3;\nadd.rn.bf16x2 h4, h4, z4;\n"
        "add.rn.bf16x2 h5, h5, z5;\nadd.rn.bf16x2 h6, h6, z6;\nadd.rn.bf16x2 h7, h7, z7;\nadd.rn.bf16x2 h8, h8, z8;\nadd.rn.bf16x2 h9, h9, z9;\n"
        "add.rn.bf16x2 h10, h10, z10;\nadd.rn.bf16x2 h11, h11, z11;\nadd.rn.bf16x2 h12, h12, z12;\nadd.rn.bf16x2 h13, h13, z13;\nadd.rn.bf16x2 h14, h14, z14;\n"
        "add.rn.bf16x2 h15, h15, z15;\n@prdy bra.uni HB;\nbra.uni WB;\n"
        "TA1:\nadd.rn.bf16x2 h16, h16, z0;\nadd.rn.bf16x2 h17, h17, z1;\nadd.rn.bf16x2 h18, h18, z2;\nadd.rn.bf16x2 h19, h19, z3;\nadd.rn.bf16x2 h20, h20, z4;\n"
        "add.rn.bf16x2 h21, h21, z5;\nadd.rn.bf16x2 h22, h22, z6;\nadd.rn.bf16x2 h23, h23, z7;\nadd.rn.bf16x2 h24, h24, z8;\nadd.rn.bf16x2 h25, h25, z9;\n"
        "add.rn.bf16x2 h26, h26, z10;\nadd.rn.bf16x2 h27, h27, z11;\nadd.rn.bf16x2 h28, h28, z12;\nadd.rn.bf16x2 h29, h29, z13;\nadd.rn.bf16x2 h30, h30, z14;\n"
        "add.rn.bf16x2 h31, h31, z15;\n@prdy bra.uni HB;\nbra.uni WB;\n"
        "TA2:\n@ps1 bra.uni TA3;\nadd.rn.bf16x2 h32, h32, z0;\nadd.rn.bf16x2 h33, h33, z1;\nadd.rn.bf16x2 h34, h34, z2;\nadd.rn.bf16x2 h35, h35, z3;\n"
        "add.rn.bf16x2 h36, h36, z4;\nadd.rn.bf16x2 h37, h37, z5;\nadd.rn.bf16x2 h38, h38, z6;\nadd.rn.bf16x2 h39, h39, z7;\nadd.rn.bf16x2 h40, h40, z8;\n"
        "add.rn.bf16x2 h41, h41, z9;\nadd.rn.bf16x2 h42, h42, z10;\nadd.rn.bf16x2 h43, h43, z11;\nadd.rn.bf16x2 h44, h44, z12;\nadd.rn.bf16x2 h45, h45, z13;\n"
        "add.rn.bf16x2 h46, h46, z14;\nadd.rn.bf16x2 h47, h47, z15;\n@prdy bra.uni HB;\nbra.uni WB;\n"
        "TA3:\nadd.rn.bf16x2 h48, h48, z0;\nadd.rn.bf16x2 h49, h49, z1;\nadd.rn.bf16x2 h50, h50, z2;\nadd.rn.bf16x2 h51, h51, z3;\nadd.rn.bf16x2 h52, h52, z4;\n"
        "add.rn.bf16x2 h53, h53, z5;\nadd.rn.bf16x2 h54, h54, z6;\nadd.rn.bf16x2 h55, h55, z7;\nadd.rn.bf16x2 h56, h56, z8;\nadd.rn.bf16x2 h57, h57, z9;\n"
        "add.rn.bf16x2 h58, h58, z10;\nadd.rn.bf16x2 h59, h59, z11;\nadd.rn.bf16x2 h60, h60, z12;\nadd.rn.bf16x2 h61, h61, z13;\nadd.rn.bf16x2 h62, h62, z14;\n"
        "add.rn.bf16x2 h63, h63, z15;\n@prdy bra.uni HB;\nbra.uni WB;\n"
        "HB:\nmad.lo.u32 xb, id, 64, %65;\ncvt.u16.u32 i16, id;\natom.shared.add.u32 pos, [%66+%80], %68;\n"
        "ldmatrix.sync.aligned.m8n8.x4.trans.shared.b16 {x0,x1,x2,x3}, [xb];\nldmatrix.sync.aligned.m8n8.x4.trans.shared.b16 {x24,x25,x26,x27}, [xb+512];\n"
        "xor.b32 t1, xb, 32;\nldmatrix.sync.aligned.m8n8.x4.trans.shared.b16 {x4,x5,x6,x7}, [t1];\n"
        "ldmatrix.sync.aligned.m8n8.x4.trans.shared.b16 {x28,x29,x30,x31}, [t1+512];\nxor.b32 t1, xb, 64;\n"
        "ldmatrix.sync.aligned.m8n8.x4.trans.shared.b16 {x8,x9,x10,x11}, [t1];\nldmatrix.sync.aligned.m8n8.x4.trans.shared.b16 {x16,x17,x18,x19}, [t1+512];\n"
        "xor.b32 t1, xb, 96;\nldmatrix.sync.aligned.m8n8.x4.trans.shared.b16 {x12,x13,x14,x15}, [t1];\n"
        "ldmatrix.sync.aligned.m8n8.x4.trans.shared.b16 {x20,x21,x22,x23}, [t1+512];\nst.volatile.shared.u16 [pos], i16;\nand.b32 t0, v, 16384;\n"
        "setp.ne.u32 ps1, t0, 0;\nvote.sync.any.pred ps1, ps1, 0xffffffff;\nand.b32 t0, v, 32768;\nsetp.ne.u32 ps2, t0, 0;\n"
        "vote.sync.any.pred ps2, ps2, 0xffffffff;\nshfl.sync.idx.b32 v, kept, %67, 0x1f, 0xffffffff;\nor.b32 t3, %67, 4;\n"
        "shfl.sync.idx.b32 vB, kept, t3, 0x1f, 0xffffffff;\nld.shared.u16 t0, [olp];\nadd.u32 olp, olp, 4;\nlop3.b32 t1, t0, %66, 0x3ff0, 0xe4;\n"
        "ld.shared.b32 t1, [t1+%77];\nshr.u32 t2, t1, 1;\nlop3.b32 kept, t2, t0, 0xffe, 0xe4;\nlop3.b32 t2, t1, %67, 3, 0x80;\nsetp.ne.u32 pq, t2, 0;\n"
        "shr.u32 t2, t1, 13;\nmad.wide.u32 pa, t2, 32, %70;\nmad.wide.u32 pb, t2, 8, %71;\nmov.b32 {lo, hi}, rb0;\nmov.b32 t2, {lo, lo};\n"
        "mul.rn.bf16x2 y0, x0, t2;\nmul.rn.bf16x2 y2, x2, t2;\nmov.b32 t2, {hi, hi};\nmul.rn.bf16x2 y1, x1, t2;\nmul.rn.bf16x2 y3, x3, t2;\n"
        "mma.sync.aligned.m16n8k16.row.col.f32.bf16.bf16.f32 {d0,d1,d2,d3}, {y0,y1,y2,y3}, {bB0,bB1}, {fz,fz,fz,fz};\ncvt.rn.bf16x2.f32 z0, d1, d0;\n"
        "cvt.rn.bf16x2.f32 z1, d3, d2;\nmov.b32 {lo, hi}, rb6;\nmov.b32 t2, {lo, lo};\nmul.rn.bf16x2 y24, x24, t2;\nmul.rn.bf16x2 y26, x26, t2;\n"
        "mov.b32 t2, {hi, hi};\nmul.rn.bf16x2 y25, x25, t2;\nmul.rn.bf16x2 y27, x27, t2;\n"
        "mma.sync.aligned.m16n8k16.row.col.f32.bf16.bf16.f32 {d24,d25,d26,d27}, {y24,y25,y26,y27}, {bB0,bB1}, {fz,fz,fz,fz};\ncvt.rn.bf16x2.f32 z12, d25, d24;\n"
        "cvt.rn.bf16x2.f32 z13, d27, d26;\nmov.b32 {lo, hi}, rb1;\nmov.b32 t2, {lo, lo};\nmul.rn.bf16x2 y4, x4, t2;\nmul.rn.bf16x2 y6, x6, t2;\n"
        "mov.b32 t2, {hi, hi};\nmul.rn.bf16x2 y5, x5, t2;\nmul.rn.bf16x2 y7, x7, t2;\n"
        "mma.sync.aligned.m16n8k16.row.col.f32.bf16.bf16.f32 {d4,d5,d6,d7}, {y4,y5,y6,y7}, {bB0,bB1}, {fz,fz,fz,fz};\ncvt.rn.bf16x2.f32 z2, d5, d4;\n"
        "cvt.rn.bf16x2.f32 z3, d7, d6;\nmov.b32 {lo, hi}, rb7;\nmov.b32 t2, {lo, lo};\nmul.rn.bf16x2 y28, x28, t2;\nmul.rn.bf16x2 y30, x30, t2;\n"
        "mov.b32 t2, {hi, hi};\nmul.rn.bf16x2 y29, x29, t2;\nmul.rn.bf16x2 y31, x31, t2;\n"
        "mma.sync.aligned.m16n8k16.row.col.f32.bf16.bf16.f32 {d28,d29,d30,d31}, {y28,y29,y30,y31}, {bB0,bB1}, {fz,fz,fz,fz};\ncvt.rn.bf16x2.f32 z14, d29, d28;\n"
        "cvt.rn.bf16x2.f32 z15, d31, d30;\nmov.b32 {lo, hi}, rb2;\nmov.b32 t2, {lo, lo};\nmul.rn.bf16x2 y8, x8, t2;\nmul.rn.bf16x2 y10, x10, t2;\n"
        "mov.b32 t2, {hi, hi};\nmul.rn.bf16x2 y9, x9, t2;\nmul.rn.bf16x2 y11, x11, t2;\n"
        "mma.sync.aligned.m16n8k16.row.col.f32.bf16.bf16.f32 {d8,d9,d10,d11}, {y8,y9,y10,y11}, {bB0,bB1}, {fz,fz,fz,fz};\ncvt.rn.bf16x2.f32 z4, d9, d8;\n"
        "cvt.rn.bf16x2.f32 z5, d11, d10;\nmov.b32 {lo, hi}, rb4;\nmov.b32 t2, {lo, lo};\nmul.rn.bf16x2 y16, x16, t2;\nmul.rn.bf16x2 y18, x18, t2;\n"
        "mov.b32 t2, {hi, hi};\nmul.rn.bf16x2 y17, x17, t2;\nmul.rn.bf16x2 y19, x19, t2;\n"
        "mma.sync.aligned.m16n8k16.row.col.f32.bf16.bf16.f32 {d16,d17,d18,d19}, {y16,y17,y18,y19}, {bB0,bB1}, {fz,fz,fz,fz};\ncvt.rn.bf16x2.f32 z8, d17, d16;\n"
        "cvt.rn.bf16x2.f32 z9, d19, d18;\nmov.b32 {lo, hi}, rb3;\nmov.b32 t2, {lo, lo};\nmul.rn.bf16x2 y12, x12, t2;\nmul.rn.bf16x2 y14, x14, t2;\n"
        "mov.b32 t2, {hi, hi};\nmul.rn.bf16x2 y13, x13, t2;\nmul.rn.bf16x2 y15, x15, t2;\n"
        "mma.sync.aligned.m16n8k16.row.col.f32.bf16.bf16.f32 {d12,d13,d14,d15}, {y12,y13,y14,y15}, {bB0,bB1}, {fz,fz,fz,fz};\ncvt.rn.bf16x2.f32 z6, d13, d12;\n"
        "cvt.rn.bf16x2.f32 z7, d15, d14;\nmov.b32 {lo, hi}, rb5;\nmov.b32 t2, {lo, lo};\nmul.rn.bf16x2 y20, x20, t2;\nmul.rn.bf16x2 y22, x22, t2;\n"
        "mov.b32 t2, {hi, hi};\nmul.rn.bf16x2 y21, x21, t2;\nmul.rn.bf16x2 y23, x23, t2;\n"
        "mma.sync.aligned.m16n8k16.row.col.f32.bf16.bf16.f32 {d20,d21,d22,d23}, {y20,y21,y22,y23}, {bB0,bB1}, {fz,fz,fz,fz};\ncvt.rn.bf16x2.f32 z10, d21, d20;\n"
        "cvt.rn.bf16x2.f32 z11, d23, d22;\n@ps2 bra.uni TB2;\n@ps1 bra.uni TB1;\n"
        "TB0:\nadd.rn.bf16x2 h0, h0, z0;\nadd.rn.bf16x2 h1, h1, z1;\nadd.rn.bf16x2 h2, h2, z2;\nadd.rn.bf16x2 h3, h3, z3;\nadd.rn.bf16x2 h4, h4, z4;\n"
        "add.rn.bf16x2 h5, h5, z5;\nadd.rn.bf16x2 h6, h6, z6;\nadd.rn.bf16x2 h7, h7, z7;\nadd.rn.bf16x2 h8, h8, z8;\nadd.rn.bf16x2 h9, h9, z9;\n"
        "add.rn.bf16x2 h10, h10, z10;\nadd.rn.bf16x2 h11, h11, z11;\nadd.rn.bf16x2 h12, h12, z12;\nadd.rn.bf16x2 h13, h13, z13;\nadd.rn.bf16x2 h14, h14, z14;\n"
        "add.rn.bf16x2 h15, h15, z15;\nbra.uni RW;\n"
        "TB1:\nadd.rn.bf16x2 h16, h16, z0;\nadd.rn.bf16x2 h17, h17, z1;\nadd.rn.bf16x2 h18, h18, z2;\nadd.rn.bf16x2 h19, h19, z3;\nadd.rn.bf16x2 h20, h20, z4;\n"
        "add.rn.bf16x2 h21, h21, z5;\nadd.rn.bf16x2 h22, h22, z6;\nadd.rn.bf16x2 h23, h23, z7;\nadd.rn.bf16x2 h24, h24, z8;\nadd.rn.bf16x2 h25, h25, z9;\n"
        "add.rn.bf16x2 h26, h26, z10;\nadd.rn.bf16x2 h27, h27, z11;\nadd.rn.bf16x2 h28, h28, z12;\nadd.rn.bf16x2 h29, h29, z13;\nadd.rn.bf16x2 h30, h30, z14;\n"
        "add.rn.bf16x2 h31, h31, z15;\nbra.uni RW;\n"
        "TB2:\n@ps1 bra.uni TB3;\nadd.rn.bf16x2 h32, h32, z0;\nadd.rn.bf16x2 h33, h33, z1;\nadd.rn.bf16x2 h34, h34, z2;\nadd.rn.bf16x2 h35, h35, z3;\n"
        "add.rn.bf16x2 h36, h36, z4;\nadd.rn.bf16x2 h37, h37, z5;\nadd.rn.bf16x2 h38, h38, z6;\nadd.rn.bf16x2 h39, h39, z7;\nadd.rn.bf16x2 h40, h40, z8;\n"
        "add.rn.bf16x2 h41, h41, z9;\nadd.rn.bf16x2 h42, h42, z10;\nadd.rn.bf16x2 h43, h43, z11;\nadd.rn.bf16x2 h44, h44, z12;\nadd.rn.bf16x2 h45, h45, z13;\n"
        "add.rn.bf16x2 h46, h46, z14;\nadd.rn.bf16x2 h47, h47, z15;\nbra.uni RW;\n"
        "TB3:\nadd.rn.bf16x2 h48, h48, z0;\nadd.rn.bf16x2 h49, h49, z1;\nadd.rn.bf16x2 h50, h50, z2;\nadd.rn.bf16x2 h51, h51, z3;\nadd.rn.bf16x2 h52, h52, z4;\n"
        "add.rn.bf16x2 h53, h53, z5;\nadd.rn.bf16x2 h54, h54, z6;\nadd.rn.bf16x2 h55, h55, z7;\nadd.rn.bf16x2 h56, h56, z8;\nadd.rn.bf16x2 h57, h57, z9;\n"
        "add.rn.bf16x2 h58, h58, z10;\nadd.rn.bf16x2 h59, h59, z11;\nadd.rn.bf16x2 h60, h60, z12;\nadd.rn.bf16x2 h61, h61, z13;\nadd.rn.bf16x2 h62, h62, z14;\n"
        "add.rn.bf16x2 h63, h63, z15;\nbra.uni RW;\n"
        "WA:\nand.b32 t2, v, 0xff8;\nredux.sync.max.u32 t1, t2, 0xffffffff;\nmov.b32 n, 0;\nsetp.eq.u32 p, t1, 0;\n@p bra.uni DONE;\n"
        "WA3:\nmbarrier.try_wait.parity.shared.b64 p, [t1+%79], 0;\n@!p bra.uni WA4;\nmbarrier.test_wait.parity.shared.b64 p, [t2+%79], 0;\n"
        "lop3.b32 ida, v, %67, 0xfff, 0xe4;\nld.volatile.shared.u16 id, [ida+%78];\nvote.sync.all.pred p, p, 0xffffffff;\n@p bra.uni HA;\n"
        "WA4:\nadd.u32 n, n, 1;\nsetp.lt.u32 q, n, 1000000;\n@q bra.uni WA3;\nbra.uni DONE;\n"
        "WB:\nand.b32 t2, v, 0xff8;\nredux.sync.max.u32 t1, t2, 0xffffffff;\nmov.b32 n, 0;\nsetp.eq.u32 p, t1, 0;\n@p bra.uni DONE;\n"
        "WB3:\nmbarrier.try_wait.parity.shared.b64 p, [t1+%79], 0;\n@!p bra.uni WB4;\nmbarrier.test_wait.parity.shared.b64 p, [t2+%79], 0;\n"
        "lop3.b32 ida, v, %67, 0xfff, 0xe4;\nld.volatile.shared.u16 id, [ida+%78];\nvote.sync.all.pred p, p, 0xffffffff;\n@p bra.uni HB;\n"
        "WB4:\nadd.u32 n, n, 1;\nsetp.lt.u32 q, n, 1000000;\n@q bra.uni WB3;\nbra.uni DONE;\n"
        "DONE:\nmov.b32 %0, h0;\nmov.b32 %1, h1;\nmov.b32 %2, h2;\nmov.b32 %3, h3;\nmov.b32 %4, h4;\nmov.b32 %5, h5;\nmov.b32 %6, h6;\nmov.b32 %7, h7;\n"
        "mov.b32 %8, h8;\nmov.b32 %9, h9;\nmov.b32 %10, h10;\nmov.b32 %11, h11;\nmov.b32 %12, h12;\nmov.b32 %13, h13;\nmov.b32 %14, h14;\nmov.b32 %15, h15;\n"
        "mov.b32 %16, h16;\nmov.b32 %17, h17;\nmov.b32 %18, h18;\nmov.b32 %19, h19;\nmov.b32 %20, h20;\nmov.b32 %21, h21;\nmov.b32 %22, h22;\nmov.b32 %23, h23;\n"
        "mov.b32 %24, h24;\nmov.b32 %25, h25;\nmov.b32 %26, h26;\nmov.b32 %27, h27;\nmov.b32 %28, h28;\nmov.b32 %29, h29;\nmov.b32 %30, h30;\nmov.b32 %31, h31;\n"
        "mov.b32 %32, h32;\nmov.b32 %33, h33;\nmov.b32 %34, h34;\nmov.b32 %35, h35;\nmov.b32 %36, h36;\nmov.b32 %37, h37;\nmov.b32 %38, h38;\nmov.b32 %39, h39;\n"
        "mov.b32 %40, h40;\nmov.b32 %41, h41;\nmov.b32 %42, h42;\nmov.b32 %43, h43;\nmov.b32 %44, h44;\nmov.b32 %45, h45;\nmov.b32 %46, h46;\nmov.b32 %47, h47;\n"
        "mov.b32 %48, h48;\nmov.b32 %49, h49;\nmov.b32 %50, h50;\nmov.b32 %51, h51;\nmov.b32 %52, h52;\nmov.b32 %53, h53;\nmov.b32 %54, h54;\nmov.b32 %55, h55;\n"
        "mov.b32 %56, h56;\nmov.b32 %57, h57;\nmov.b32 %58, h58;\nmov.b32 %59, h59;\nmov.b32 %60, h60;\nmov.b32 %61, h61;\nmov.b32 %62, h62;\nmov.b32 %63, h63;\n"
        "}\n"
        : "=r"(pk[0]), "=r"(pk[1]), "=r"(pk[2]), "=r"(pk[3]), "=r"(pk[4]), "=r"(pk[5]), "=r"(pk[6]), "=r"(pk[7]), "=r"(pk[8]), "=r"(pk[9]),
          "=r"(pk[10]), "=r"(pk[11]), "=r"(pk[12]), "=r"(pk[13]), "=r"(pk[14]), "=r"(pk[15]), "=r"(pk[16]), "=r"(pk[17]), "=r"(pk[18]), "=r"(pk[19]),
          "=r"(pk[20]), "=r"(pk[21]), "=r"(pk[22]), "=r"(pk[23]), "=r"(pk[24]), "=r"(pk[25]), "=r"(pk[26]), "=r"(pk[27]), "=r"(pk[28]), "=r"(pk[29]),
          "=r"(pk[30]), "=r"(pk[31]), "=r"(pk[32]), "=r"(pk[33]), "=r"(pk[34]), "=r"(pk[35]), "=r"(pk[36]), "=r"(pk[37]), "=r"(pk[38]), "=r"(pk[39]),
          "=r"(pk[40]), "=r"(pk[41]), "=r"(pk[42]), "=r"(pk[43]), "=r"(pk[44]), "=r"(pk[45]), "=r"(pk[46]), "=r"(pk[47]), "=r"(pk[48]), "=r"(pk[49]),
          "=r"(pk[50]), "=r"(pk[51]), "=r"(pk[52]), "=r"(pk[53]), "=r"(pk[54]), "=r"(pk[55]), "=r"(pk[56]), "=r"(pk[57]), "=r"(pk[58]), "=r"(pk[59]),
          "=r"(pk[60]), "=r"(pk[61]), "=r"(pk[62]), "=r"(pk[63])
        : "r"(olp), "r"(xa), "r"(ln), "r"(lc), "r"(linc), "r"(lt), "l"(ea), "l"(sh), "l"(wf), "r"(first.x), "r"(first.y), "r"(first.z), "r"(first.w),
          "n"(sb + SM_REC), "n"(sb + SM_R), "n"(sb + SM_BAR), "n"(sb + SM_CTR), "n"(0),
          "r"(w[0]), "r"(w[1]), "r"(w[2]), "r"(w[3]), "r"(w[4]), "r"(w[5]), "r"(w[6]), "r"(w[7]), "r"(w[8]), "r"(w[9]), "r"(w[10]), "r"(w[11]),
          "r"(w[12]), "r"(w[13]), "r"(w[14]), "r"(w[15]), "r"(w[16]), "r"(w[17]), "r"(w[18]), "r"(w[19]), "r"(w[20]), "r"(w[21]), "r"(w[22]),
          "r"(w[23]), "r"(w[24]), "r"(w[25]), "r"(w[26]), "r"(w[27]), "r"(w[28]), "r"(w[29]), "r"(w[30]), "r"(w[31]), "r"(w[32]), "r"(w[33]),
          "r"(w[34]), "r"(w[35])
        : "memory");
}
__device__ __forceinline__ void consume3(uint32_t (&pk)[48], const uint32_t (&w)[36], uint32_t olp, uint32_t xa, uint32_t ln,
                                      uint32_t lc, uint32_t linc, uint32_t lt, const __nv_bfloat16* ea, const __nv_bfloat16* sh, const void* wf, uint4 first) {
    ea += lt * 4, sh += lt & 2;
    asm volatile(
        "{\n.reg .pred p, q, psw, prdy, ps1, ps2, ps3, pz, pq, pt, pl;\n.reg .f32 d<40>, fz;\n"
        ".reg .b32 h<48>, x<32>, y<32>, ra<8>, rb<8>, bA0, bA1, bB0, bB1, c0, c1, c2, c3, e0, e1, s0, kept;\n"
        ".reg .b32 olp, v, vB, m, id, ida, bar, xb, pos, t0, t1, t2, t3, n, z<16>, kept2, g<4>, f0, f1, s1;\n.reg .b16 lo, hi, i16;\n.reg .b64 pa, pb;\n"
        "mov.f32 fz, 0f00000000;\nmov.b32 h0, 0;\nmov.b32 h1, 0;\nmov.b32 h2, 0;\nmov.b32 h3, 0;\nmov.b32 h4, 0;\nmov.b32 h5, 0;\nmov.b32 h6, 0;\n"
        "mov.b32 h7, 0;\nmov.b32 h8, 0;\nmov.b32 h9, 0;\nmov.b32 h10, 0;\nmov.b32 h11, 0;\nmov.b32 h12, 0;\nmov.b32 h13, 0;\nmov.b32 h14, 0;\nmov.b32 h15, 0;\n"
        "mov.b32 h16, 0;\nmov.b32 h17, 0;\nmov.b32 h18, 0;\nmov.b32 h19, 0;\nmov.b32 h20, 0;\nmov.b32 h21, 0;\nmov.b32 h22, 0;\nmov.b32 h23, 0;\n"
        "mov.b32 h24, 0;\nmov.b32 h25, 0;\nmov.b32 h26, 0;\nmov.b32 h27, 0;\nmov.b32 h28, 0;\nmov.b32 h29, 0;\nmov.b32 h30, 0;\nmov.b32 h31, 0;\n"
        "mov.b32 h32, 0;\nmov.b32 h33, 0;\nmov.b32 h34, 0;\nmov.b32 h35, 0;\nmov.b32 h36, 0;\nmov.b32 h37, 0;\nmov.b32 h38, 0;\nmov.b32 h39, 0;\n"
        "mov.b32 h40, 0;\nmov.b32 h41, 0;\nmov.b32 h42, 0;\nmov.b32 h43, 0;\nmov.b32 h44, 0;\nmov.b32 h45, 0;\nmov.b32 h46, 0;\nmov.b32 h47, 0;\n"
        "mov.b32 olp, %48;\nand.b32 t3, %51, 31;\nmad.lo.u32 t3, t3, 0x4001, 4;\nshfl.sync.bfly.b32 t3, t3, 8, 0x1f, 0xffffffff;\nand.b32 t0, %50, 32;\n"
        "setp.ne.u32 psw, t0, 0;\nsetp.eq.u32 pz, %48, 0;\nvote.sync.any.pred pz, pz, 0xffffffff;\nmov.b32 e0, %57;\nmov.b32 e1, %58;\nmov.b32 s0, %59;\n"
        "mov.b32 kept, %60;\nadd.u32 olp, olp, 4;\nsetp.ne.u64 p, %56, 0;\n@p fence.proxy.async.global;\n@p red.release.gpu.global.add.u32 [%56+12], 1;\n"
        "bar.warp.sync 0xffffffff;\nshfl.sync.idx.b32 v, kept, %51, 0x1f, 0xffffffff;\nshfl.sync.idx.b32 vB, kept, t3, 0x1f, 0xffffffff;\n"
        "ld.shared.u16 t0, [olp];\nadd.u32 olp, olp, 4;\nlop3.b32 t1, t0, %50, 0x3ff0, 0xe4;\nld.shared.b32 t1, [t1+%61];\nshr.u32 t2, t1, 1;\n"
        "lop3.b32 kept, t2, t0, 0xffe, 0xe4;\nlop3.b32 t2, t1, %51, 3, 0x80;\nsetp.ne.u32 pq, t2, 0;\nshr.u32 t2, t1, 13;\nmad.wide.u32 pa, t2, 32, %54;\n"
        "mad.wide.u32 pb, t2, 8, %55;\n"
        "RW:\nmma.sync.aligned.m16n8k8.row.col.f32.bf16.bf16.f32 {d0,d1,d2,d3}, {%98,%99}, {s0}, {fz,fz,fz,fz};\n"
        "mma.sync.aligned.m16n8k8.row.col.f32.bf16.bf16.f32 {d4,d5,d6,d7}, {%100,%101}, {s0}, {fz,fz,fz,fz};\ncvt.rn.bf16x2.f32 c0, d2, d0;\n"
        "cvt.rn.bf16x2.f32 c1, d3, d1;\ncvt.rn.bf16x2.f32 c2, d6, d4;\ncvt.rn.bf16x2.f32 c3, d7, d5;\nselp.b32 bA0, c2, c0, psw;\nselp.b32 bA1, c0, c2, psw;\n"
        "selp.b32 bB0, c3, c1, psw;\nselp.b32 bB1, c1, c3, psw;\n"
        "mma.sync.aligned.m16n8k16.row.col.f32.bf16.bf16.f32 {d0,d1,d2,d3}, {%66,%67,%68,%69}, {e0,e1}, {fz,fz,fz,fz};\ncvt.rn.bf16x2.f32 ra0, d2, d0;\n"
        "cvt.rn.bf16x2.f32 rb0, d3, d1;\nmma.sync.aligned.m16n8k16.row.col.f32.bf16.bf16.f32 {d4,d5,d6,d7}, {%70,%71,%72,%73}, {e0,e1}, {fz,fz,fz,fz};\n"
        "cvt.rn.bf16x2.f32 ra1, d6, d4;\ncvt.rn.bf16x2.f32 rb1, d7, d5;\n"
        "mma.sync.aligned.m16n8k16.row.col.f32.bf16.bf16.f32 {d8,d9,d10,d11}, {%74,%75,%76,%77}, {e0,e1}, {fz,fz,fz,fz};\ncvt.rn.bf16x2.f32 ra2, d10, d8;\n"
        "cvt.rn.bf16x2.f32 rb2, d11, d9;\nmma.sync.aligned.m16n8k16.row.col.f32.bf16.bf16.f32 {d12,d13,d14,d15}, {%78,%79,%80,%81}, {e0,e1}, {fz,fz,fz,fz};\n"
        "cvt.rn.bf16x2.f32 ra3, d14, d12;\ncvt.rn.bf16x2.f32 rb3, d15, d13;\n"
        "mma.sync.aligned.m16n8k16.row.col.f32.bf16.bf16.f32 {d16,d17,d18,d19}, {%82,%83,%84,%85}, {e0,e1}, {fz,fz,fz,fz};\ncvt.rn.bf16x2.f32 ra4, d18, d16;\n"
        "cvt.rn.bf16x2.f32 rb4, d19, d17;\nmma.sync.aligned.m16n8k16.row.col.f32.bf16.bf16.f32 {d20,d21,d22,d23}, {%86,%87,%88,%89}, {e0,e1}, {fz,fz,fz,fz};\n"
        "cvt.rn.bf16x2.f32 ra5, d22, d20;\ncvt.rn.bf16x2.f32 rb5, d23, d21;\n"
        "mma.sync.aligned.m16n8k16.row.col.f32.bf16.bf16.f32 {d24,d25,d26,d27}, {%90,%91,%92,%93}, {e0,e1}, {fz,fz,fz,fz};\ncvt.rn.bf16x2.f32 ra6, d26, d24;\n"
        "cvt.rn.bf16x2.f32 rb6, d27, d25;\nmma.sync.aligned.m16n8k16.row.col.f32.bf16.bf16.f32 {d28,d29,d30,d31}, {%94,%95,%96,%97}, {e0,e1}, {fz,fz,fz,fz};\n"
        "cvt.rn.bf16x2.f32 ra7, d30, d28;\ncvt.rn.bf16x2.f32 rb7, d31, d29;\nmov.b32 s0, 0;\nld.global.cg.L2::128B.v2.b32 {e0,e1}, [pa];\n"
        "@pq ld.global.cg.L2::128B.b32 s0, [pb];\nand.b32 bar, v, 0xff8;\nmbarrier.test_wait.parity.shared.b64 pl, [bar+%63], 0;\n"
        "lop3.b32 ida, v, %51, 0xfff, 0xe4;\nld.volatile.shared.u16 id, [ida+%62];\nvote.sync.all.pred prdy, pl, 0xffffffff;\n@!prdy bra.uni WA;\n"
        "HA:\nmad.lo.u32 xb, id, 64, %49;\ncvt.u16.u32 i16, id;\natom.shared.add.u32 pos, [%50+%64], %52;\n"
        "ldmatrix.sync.aligned.m8n8.x4.trans.shared.b16 {x0,x1,x2,x3}, [xb];\nldmatrix.sync.aligned.m8n8.x4.trans.shared.b16 {x24,x25,x26,x27}, [xb+512];\n"
        "xor.b32 t1, xb, 32;\nldmatrix.sync.aligned.m8n8.x4.trans.shared.b16 {x4,x5,x6,x7}, [t1];\n"
        "ldmatrix.sync.aligned.m8n8.x4.trans.shared.b16 {x28,x29,x30,x31}, [t1+512];\nxor.b32 t1, xb, 64;\n"
        "ldmatrix.sync.aligned.m8n8.x4.trans.shared.b16 {x8,x9,x10,x11}, [t1];\nldmatrix.sync.aligned.m8n8.x4.trans.shared.b16 {x16,x17,x18,x19}, [t1+512];\n"
        "xor.b32 t1, xb, 96;\nldmatrix.sync.aligned.m8n8.x4.trans.shared.b16 {x12,x13,x14,x15}, [t1];\n"
        "ldmatrix.sync.aligned.m8n8.x4.trans.shared.b16 {x20,x21,x22,x23}, [t1+512];\nst.volatile.shared.u16 [pos], i16;\nand.b32 t0, v, 16384;\n"
        "setp.ne.u32 ps1, t0, 0;\nvote.sync.any.pred ps1, ps1, 0xffffffff;\nand.b32 t0, v, 32768;\nsetp.ne.u32 ps2, t0, 0;\n"
        "vote.sync.any.pred ps2, ps2, 0xffffffff;\nmov.b32 v, vB;\nand.b32 bar, v, 0xff8;\nmbarrier.test_wait.parity.shared.b64 pl, [bar+%63], 0;\n"
        "lop3.b32 ida, v, %51, 0xfff, 0xe4;\nld.volatile.shared.u16 id, [ida+%62];\nvote.sync.all.pred prdy, pl, 0xffffffff;\nmov.b32 {lo, hi}, ra0;\n"
        "mov.b32 t2, {lo, lo};\nmul.rn.bf16x2 y0, x0, t2;\nmul.rn.bf16x2 y2, x2, t2;\nmov.b32 t2, {hi, hi};\nmul.rn.bf16x2 y1, x1, t2;\n"
        "mul.rn.bf16x2 y3, x3, t2;\nmma.sync.aligned.m16n8k16.row.col.f32.bf16.bf16.f32 {d0,d1,d2,d3}, {y0,y1,y2,y3}, {bA0,bA1}, {fz,fz,fz,fz};\n"
        "cvt.rn.bf16x2.f32 z0, d1, d0;\ncvt.rn.bf16x2.f32 z1, d3, d2;\nmov.b32 {lo, hi}, ra6;\nmov.b32 t2, {lo, lo};\nmul.rn.bf16x2 y24, x24, t2;\n"
        "mul.rn.bf16x2 y26, x26, t2;\nmov.b32 t2, {hi, hi};\nmul.rn.bf16x2 y25, x25, t2;\nmul.rn.bf16x2 y27, x27, t2;\n"
        "mma.sync.aligned.m16n8k16.row.col.f32.bf16.bf16.f32 {d24,d25,d26,d27}, {y24,y25,y26,y27}, {bA0,bA1}, {fz,fz,fz,fz};\ncvt.rn.bf16x2.f32 z12, d25, d24;\n"
        "cvt.rn.bf16x2.f32 z13, d27, d26;\nmov.b32 {lo, hi}, ra1;\nmov.b32 t2, {lo, lo};\nmul.rn.bf16x2 y4, x4, t2;\nmul.rn.bf16x2 y6, x6, t2;\n"
        "mov.b32 t2, {hi, hi};\nmul.rn.bf16x2 y5, x5, t2;\nmul.rn.bf16x2 y7, x7, t2;\n"
        "mma.sync.aligned.m16n8k16.row.col.f32.bf16.bf16.f32 {d4,d5,d6,d7}, {y4,y5,y6,y7}, {bA0,bA1}, {fz,fz,fz,fz};\ncvt.rn.bf16x2.f32 z2, d5, d4;\n"
        "cvt.rn.bf16x2.f32 z3, d7, d6;\nmov.b32 {lo, hi}, ra7;\nmov.b32 t2, {lo, lo};\nmul.rn.bf16x2 y28, x28, t2;\nmul.rn.bf16x2 y30, x30, t2;\n"
        "mov.b32 t2, {hi, hi};\nmul.rn.bf16x2 y29, x29, t2;\nmul.rn.bf16x2 y31, x31, t2;\n"
        "mma.sync.aligned.m16n8k16.row.col.f32.bf16.bf16.f32 {d28,d29,d30,d31}, {y28,y29,y30,y31}, {bA0,bA1}, {fz,fz,fz,fz};\ncvt.rn.bf16x2.f32 z14, d29, d28;\n"
        "cvt.rn.bf16x2.f32 z15, d31, d30;\nmov.b32 {lo, hi}, ra2;\nmov.b32 t2, {lo, lo};\nmul.rn.bf16x2 y8, x8, t2;\nmul.rn.bf16x2 y10, x10, t2;\n"
        "mov.b32 t2, {hi, hi};\nmul.rn.bf16x2 y9, x9, t2;\nmul.rn.bf16x2 y11, x11, t2;\n"
        "mma.sync.aligned.m16n8k16.row.col.f32.bf16.bf16.f32 {d8,d9,d10,d11}, {y8,y9,y10,y11}, {bA0,bA1}, {fz,fz,fz,fz};\ncvt.rn.bf16x2.f32 z4, d9, d8;\n"
        "cvt.rn.bf16x2.f32 z5, d11, d10;\nmov.b32 {lo, hi}, ra4;\nmov.b32 t2, {lo, lo};\nmul.rn.bf16x2 y16, x16, t2;\nmul.rn.bf16x2 y18, x18, t2;\n"
        "mov.b32 t2, {hi, hi};\nmul.rn.bf16x2 y17, x17, t2;\nmul.rn.bf16x2 y19, x19, t2;\n"
        "mma.sync.aligned.m16n8k16.row.col.f32.bf16.bf16.f32 {d16,d17,d18,d19}, {y16,y17,y18,y19}, {bA0,bA1}, {fz,fz,fz,fz};\ncvt.rn.bf16x2.f32 z8, d17, d16;\n"
        "cvt.rn.bf16x2.f32 z9, d19, d18;\nmov.b32 {lo, hi}, ra3;\nmov.b32 t2, {lo, lo};\nmul.rn.bf16x2 y12, x12, t2;\nmul.rn.bf16x2 y14, x14, t2;\n"
        "mov.b32 t2, {hi, hi};\nmul.rn.bf16x2 y13, x13, t2;\nmul.rn.bf16x2 y15, x15, t2;\n"
        "mma.sync.aligned.m16n8k16.row.col.f32.bf16.bf16.f32 {d12,d13,d14,d15}, {y12,y13,y14,y15}, {bA0,bA1}, {fz,fz,fz,fz};\ncvt.rn.bf16x2.f32 z6, d13, d12;\n"
        "cvt.rn.bf16x2.f32 z7, d15, d14;\nmov.b32 {lo, hi}, ra5;\nmov.b32 t2, {lo, lo};\nmul.rn.bf16x2 y20, x20, t2;\nmul.rn.bf16x2 y22, x22, t2;\n"
        "mov.b32 t2, {hi, hi};\nmul.rn.bf16x2 y21, x21, t2;\nmul.rn.bf16x2 y23, x23, t2;\n"
        "mma.sync.aligned.m16n8k16.row.col.f32.bf16.bf16.f32 {d20,d21,d22,d23}, {y20,y21,y22,y23}, {bA0,bA1}, {fz,fz,fz,fz};\ncvt.rn.bf16x2.f32 z10, d21, d20;\n"
        "cvt.rn.bf16x2.f32 z11, d23, d22;\n@ps2 bra.uni TA2;\n@ps1 bra.uni TA1;\n"
        "TA0:\nadd.rn.bf16x2 h0, h0, z0;\nadd.rn.bf16x2 h1, h1, z1;\nadd.rn.bf16x2 h2, h2, z2;\nadd.rn.bf16x2 h3, h3, z3;\nadd.rn.bf16x2 h4, h4, z4;\n"
        "add.rn.bf16x2 h5, h5, z5;\nadd.rn.bf16x2 h6, h6, z6;\nadd.rn.bf16x2 h7, h7, z7;\nadd.rn.bf16x2 h8, h8, z8;\nadd.rn.bf16x2 h9, h9, z9;\n"
        "add.rn.bf16x2 h10, h10, z10;\nadd.rn.bf16x2 h11, h11, z11;\nadd.rn.bf16x2 h12, h12, z12;\nadd.rn.bf16x2 h13, h13, z13;\nadd.rn.bf16x2 h14, h14, z14;\n"
        "add.rn.bf16x2 h15, h15, z15;\n@prdy bra.uni HB;\nbra.uni WB;\n"
        "TA1:\nadd.rn.bf16x2 h16, h16, z0;\nadd.rn.bf16x2 h17, h17, z1;\nadd.rn.bf16x2 h18, h18, z2;\nadd.rn.bf16x2 h19, h19, z3;\nadd.rn.bf16x2 h20, h20, z4;\n"
        "add.rn.bf16x2 h21, h21, z5;\nadd.rn.bf16x2 h22, h22, z6;\nadd.rn.bf16x2 h23, h23, z7;\nadd.rn.bf16x2 h24, h24, z8;\nadd.rn.bf16x2 h25, h25, z9;\n"
        "add.rn.bf16x2 h26, h26, z10;\nadd.rn.bf16x2 h27, h27, z11;\nadd.rn.bf16x2 h28, h28, z12;\nadd.rn.bf16x2 h29, h29, z13;\nadd.rn.bf16x2 h30, h30, z14;\n"
        "add.rn.bf16x2 h31, h31, z15;\n@prdy bra.uni HB;\nbra.uni WB;\n"
        "TA2:\nadd.rn.bf16x2 h32, h32, z0;\nadd.rn.bf16x2 h33, h33, z1;\nadd.rn.bf16x2 h34, h34, z2;\nadd.rn.bf16x2 h35, h35, z3;\nadd.rn.bf16x2 h36, h36, z4;\n"
        "add.rn.bf16x2 h37, h37, z5;\nadd.rn.bf16x2 h38, h38, z6;\nadd.rn.bf16x2 h39, h39, z7;\nadd.rn.bf16x2 h40, h40, z8;\nadd.rn.bf16x2 h41, h41, z9;\n"
        "add.rn.bf16x2 h42, h42, z10;\nadd.rn.bf16x2 h43, h43, z11;\nadd.rn.bf16x2 h44, h44, z12;\nadd.rn.bf16x2 h45, h45, z13;\nadd.rn.bf16x2 h46, h46, z14;\n"
        "add.rn.bf16x2 h47, h47, z15;\n@prdy bra.uni HB;\nbra.uni WB;\n"
        "HB:\nmad.lo.u32 xb, id, 64, %49;\ncvt.u16.u32 i16, id;\natom.shared.add.u32 pos, [%50+%64], %52;\n"
        "ldmatrix.sync.aligned.m8n8.x4.trans.shared.b16 {x0,x1,x2,x3}, [xb];\nldmatrix.sync.aligned.m8n8.x4.trans.shared.b16 {x24,x25,x26,x27}, [xb+512];\n"
        "xor.b32 t1, xb, 32;\nldmatrix.sync.aligned.m8n8.x4.trans.shared.b16 {x4,x5,x6,x7}, [t1];\n"
        "ldmatrix.sync.aligned.m8n8.x4.trans.shared.b16 {x28,x29,x30,x31}, [t1+512];\nxor.b32 t1, xb, 64;\n"
        "ldmatrix.sync.aligned.m8n8.x4.trans.shared.b16 {x8,x9,x10,x11}, [t1];\nldmatrix.sync.aligned.m8n8.x4.trans.shared.b16 {x16,x17,x18,x19}, [t1+512];\n"
        "xor.b32 t1, xb, 96;\nldmatrix.sync.aligned.m8n8.x4.trans.shared.b16 {x12,x13,x14,x15}, [t1];\n"
        "ldmatrix.sync.aligned.m8n8.x4.trans.shared.b16 {x20,x21,x22,x23}, [t1+512];\nst.volatile.shared.u16 [pos], i16;\nand.b32 t0, v, 16384;\n"
        "setp.ne.u32 ps1, t0, 0;\nvote.sync.any.pred ps1, ps1, 0xffffffff;\nand.b32 t0, v, 32768;\nsetp.ne.u32 ps2, t0, 0;\n"
        "vote.sync.any.pred ps2, ps2, 0xffffffff;\nshfl.sync.idx.b32 v, kept, %51, 0x1f, 0xffffffff;\nshfl.sync.idx.b32 vB, kept, t3, 0x1f, 0xffffffff;\n"
        "ld.shared.u16 t0, [olp];\nadd.u32 olp, olp, 4;\nlop3.b32 t1, t0, %50, 0x3ff0, 0xe4;\nld.shared.b32 t1, [t1+%61];\nshr.u32 t2, t1, 1;\n"
        "lop3.b32 kept, t2, t0, 0xffe, 0xe4;\nlop3.b32 t2, t1, %51, 3, 0x80;\nsetp.ne.u32 pq, t2, 0;\nshr.u32 t2, t1, 13;\nmad.wide.u32 pa, t2, 32, %54;\n"
        "mad.wide.u32 pb, t2, 8, %55;\nmov.b32 {lo, hi}, rb0;\nmov.b32 t2, {lo, lo};\nmul.rn.bf16x2 y0, x0, t2;\nmul.rn.bf16x2 y2, x2, t2;\n"
        "mov.b32 t2, {hi, hi};\nmul.rn.bf16x2 y1, x1, t2;\nmul.rn.bf16x2 y3, x3, t2;\n"
        "mma.sync.aligned.m16n8k16.row.col.f32.bf16.bf16.f32 {d0,d1,d2,d3}, {y0,y1,y2,y3}, {bB0,bB1}, {fz,fz,fz,fz};\ncvt.rn.bf16x2.f32 z0, d1, d0;\n"
        "cvt.rn.bf16x2.f32 z1, d3, d2;\nmov.b32 {lo, hi}, rb6;\nmov.b32 t2, {lo, lo};\nmul.rn.bf16x2 y24, x24, t2;\nmul.rn.bf16x2 y26, x26, t2;\n"
        "mov.b32 t2, {hi, hi};\nmul.rn.bf16x2 y25, x25, t2;\nmul.rn.bf16x2 y27, x27, t2;\n"
        "mma.sync.aligned.m16n8k16.row.col.f32.bf16.bf16.f32 {d24,d25,d26,d27}, {y24,y25,y26,y27}, {bB0,bB1}, {fz,fz,fz,fz};\ncvt.rn.bf16x2.f32 z12, d25, d24;\n"
        "cvt.rn.bf16x2.f32 z13, d27, d26;\nmov.b32 {lo, hi}, rb1;\nmov.b32 t2, {lo, lo};\nmul.rn.bf16x2 y4, x4, t2;\nmul.rn.bf16x2 y6, x6, t2;\n"
        "mov.b32 t2, {hi, hi};\nmul.rn.bf16x2 y5, x5, t2;\nmul.rn.bf16x2 y7, x7, t2;\n"
        "mma.sync.aligned.m16n8k16.row.col.f32.bf16.bf16.f32 {d4,d5,d6,d7}, {y4,y5,y6,y7}, {bB0,bB1}, {fz,fz,fz,fz};\ncvt.rn.bf16x2.f32 z2, d5, d4;\n"
        "cvt.rn.bf16x2.f32 z3, d7, d6;\nmov.b32 {lo, hi}, rb7;\nmov.b32 t2, {lo, lo};\nmul.rn.bf16x2 y28, x28, t2;\nmul.rn.bf16x2 y30, x30, t2;\n"
        "mov.b32 t2, {hi, hi};\nmul.rn.bf16x2 y29, x29, t2;\nmul.rn.bf16x2 y31, x31, t2;\n"
        "mma.sync.aligned.m16n8k16.row.col.f32.bf16.bf16.f32 {d28,d29,d30,d31}, {y28,y29,y30,y31}, {bB0,bB1}, {fz,fz,fz,fz};\ncvt.rn.bf16x2.f32 z14, d29, d28;\n"
        "cvt.rn.bf16x2.f32 z15, d31, d30;\nmov.b32 {lo, hi}, rb2;\nmov.b32 t2, {lo, lo};\nmul.rn.bf16x2 y8, x8, t2;\nmul.rn.bf16x2 y10, x10, t2;\n"
        "mov.b32 t2, {hi, hi};\nmul.rn.bf16x2 y9, x9, t2;\nmul.rn.bf16x2 y11, x11, t2;\n"
        "mma.sync.aligned.m16n8k16.row.col.f32.bf16.bf16.f32 {d8,d9,d10,d11}, {y8,y9,y10,y11}, {bB0,bB1}, {fz,fz,fz,fz};\ncvt.rn.bf16x2.f32 z4, d9, d8;\n"
        "cvt.rn.bf16x2.f32 z5, d11, d10;\nmov.b32 {lo, hi}, rb4;\nmov.b32 t2, {lo, lo};\nmul.rn.bf16x2 y16, x16, t2;\nmul.rn.bf16x2 y18, x18, t2;\n"
        "mov.b32 t2, {hi, hi};\nmul.rn.bf16x2 y17, x17, t2;\nmul.rn.bf16x2 y19, x19, t2;\n"
        "mma.sync.aligned.m16n8k16.row.col.f32.bf16.bf16.f32 {d16,d17,d18,d19}, {y16,y17,y18,y19}, {bB0,bB1}, {fz,fz,fz,fz};\ncvt.rn.bf16x2.f32 z8, d17, d16;\n"
        "cvt.rn.bf16x2.f32 z9, d19, d18;\nmov.b32 {lo, hi}, rb3;\nmov.b32 t2, {lo, lo};\nmul.rn.bf16x2 y12, x12, t2;\nmul.rn.bf16x2 y14, x14, t2;\n"
        "mov.b32 t2, {hi, hi};\nmul.rn.bf16x2 y13, x13, t2;\nmul.rn.bf16x2 y15, x15, t2;\n"
        "mma.sync.aligned.m16n8k16.row.col.f32.bf16.bf16.f32 {d12,d13,d14,d15}, {y12,y13,y14,y15}, {bB0,bB1}, {fz,fz,fz,fz};\ncvt.rn.bf16x2.f32 z6, d13, d12;\n"
        "cvt.rn.bf16x2.f32 z7, d15, d14;\nmov.b32 {lo, hi}, rb5;\nmov.b32 t2, {lo, lo};\nmul.rn.bf16x2 y20, x20, t2;\nmul.rn.bf16x2 y22, x22, t2;\n"
        "mov.b32 t2, {hi, hi};\nmul.rn.bf16x2 y21, x21, t2;\nmul.rn.bf16x2 y23, x23, t2;\n"
        "mma.sync.aligned.m16n8k16.row.col.f32.bf16.bf16.f32 {d20,d21,d22,d23}, {y20,y21,y22,y23}, {bB0,bB1}, {fz,fz,fz,fz};\ncvt.rn.bf16x2.f32 z10, d21, d20;\n"
        "cvt.rn.bf16x2.f32 z11, d23, d22;\n@ps2 bra.uni TB2;\n@ps1 bra.uni TB1;\n"
        "TB0:\nadd.rn.bf16x2 h0, h0, z0;\nadd.rn.bf16x2 h1, h1, z1;\nadd.rn.bf16x2 h2, h2, z2;\nadd.rn.bf16x2 h3, h3, z3;\nadd.rn.bf16x2 h4, h4, z4;\n"
        "add.rn.bf16x2 h5, h5, z5;\nadd.rn.bf16x2 h6, h6, z6;\nadd.rn.bf16x2 h7, h7, z7;\nadd.rn.bf16x2 h8, h8, z8;\nadd.rn.bf16x2 h9, h9, z9;\n"
        "add.rn.bf16x2 h10, h10, z10;\nadd.rn.bf16x2 h11, h11, z11;\nadd.rn.bf16x2 h12, h12, z12;\nadd.rn.bf16x2 h13, h13, z13;\nadd.rn.bf16x2 h14, h14, z14;\n"
        "add.rn.bf16x2 h15, h15, z15;\nbra.uni RW;\n"
        "TB1:\nadd.rn.bf16x2 h16, h16, z0;\nadd.rn.bf16x2 h17, h17, z1;\nadd.rn.bf16x2 h18, h18, z2;\nadd.rn.bf16x2 h19, h19, z3;\nadd.rn.bf16x2 h20, h20, z4;\n"
        "add.rn.bf16x2 h21, h21, z5;\nadd.rn.bf16x2 h22, h22, z6;\nadd.rn.bf16x2 h23, h23, z7;\nadd.rn.bf16x2 h24, h24, z8;\nadd.rn.bf16x2 h25, h25, z9;\n"
        "add.rn.bf16x2 h26, h26, z10;\nadd.rn.bf16x2 h27, h27, z11;\nadd.rn.bf16x2 h28, h28, z12;\nadd.rn.bf16x2 h29, h29, z13;\nadd.rn.bf16x2 h30, h30, z14;\n"
        "add.rn.bf16x2 h31, h31, z15;\nbra.uni RW;\n"
        "TB2:\nadd.rn.bf16x2 h32, h32, z0;\nadd.rn.bf16x2 h33, h33, z1;\nadd.rn.bf16x2 h34, h34, z2;\nadd.rn.bf16x2 h35, h35, z3;\nadd.rn.bf16x2 h36, h36, z4;\n"
        "add.rn.bf16x2 h37, h37, z5;\nadd.rn.bf16x2 h38, h38, z6;\nadd.rn.bf16x2 h39, h39, z7;\nadd.rn.bf16x2 h40, h40, z8;\nadd.rn.bf16x2 h41, h41, z9;\n"
        "add.rn.bf16x2 h42, h42, z10;\nadd.rn.bf16x2 h43, h43, z11;\nadd.rn.bf16x2 h44, h44, z12;\nadd.rn.bf16x2 h45, h45, z13;\nadd.rn.bf16x2 h46, h46, z14;\n"
        "add.rn.bf16x2 h47, h47, z15;\nbra.uni RW;\n"
        "WA:\nand.b32 t2, v, 0xff8;\nredux.sync.max.u32 t1, t2, 0xffffffff;\nmov.b32 n, 0;\nsetp.eq.u32 p, t1, 0;\n@p bra.uni DONE;\n"
        "WA3:\nmbarrier.try_wait.parity.shared.b64 p, [t1+%63], 0;\n@!p bra.uni WA4;\nmbarrier.test_wait.parity.shared.b64 p, [t2+%63], 0;\n"
        "lop3.b32 ida, v, %51, 0xfff, 0xe4;\nld.volatile.shared.u16 id, [ida+%62];\nvote.sync.all.pred p, p, 0xffffffff;\n@p bra.uni HA;\n"
        "WA4:\nadd.u32 n, n, 1;\nsetp.lt.u32 q, n, 1000000;\n@q bra.uni WA3;\nbra.uni DONE;\n"
        "WB:\nand.b32 t2, v, 0xff8;\nredux.sync.max.u32 t1, t2, 0xffffffff;\nmov.b32 n, 0;\nsetp.eq.u32 p, t1, 0;\n@p bra.uni DONE;\n"
        "WB3:\nmbarrier.try_wait.parity.shared.b64 p, [t1+%63], 0;\n@!p bra.uni WB4;\nmbarrier.test_wait.parity.shared.b64 p, [t2+%63], 0;\n"
        "lop3.b32 ida, v, %51, 0xfff, 0xe4;\nld.volatile.shared.u16 id, [ida+%62];\nvote.sync.all.pred p, p, 0xffffffff;\n@p bra.uni HB;\n"
        "WB4:\nadd.u32 n, n, 1;\nsetp.lt.u32 q, n, 1000000;\n@q bra.uni WB3;\nbra.uni DONE;\n"
        "DONE:\nmov.b32 %0, h0;\nmov.b32 %1, h1;\nmov.b32 %2, h2;\nmov.b32 %3, h3;\nmov.b32 %4, h4;\nmov.b32 %5, h5;\nmov.b32 %6, h6;\nmov.b32 %7, h7;\n"
        "mov.b32 %8, h8;\nmov.b32 %9, h9;\nmov.b32 %10, h10;\nmov.b32 %11, h11;\nmov.b32 %12, h12;\nmov.b32 %13, h13;\nmov.b32 %14, h14;\nmov.b32 %15, h15;\n"
        "mov.b32 %16, h16;\nmov.b32 %17, h17;\nmov.b32 %18, h18;\nmov.b32 %19, h19;\nmov.b32 %20, h20;\nmov.b32 %21, h21;\nmov.b32 %22, h22;\nmov.b32 %23, h23;\n"
        "mov.b32 %24, h24;\nmov.b32 %25, h25;\nmov.b32 %26, h26;\nmov.b32 %27, h27;\nmov.b32 %28, h28;\nmov.b32 %29, h29;\nmov.b32 %30, h30;\nmov.b32 %31, h31;\n"
        "mov.b32 %32, h32;\nmov.b32 %33, h33;\nmov.b32 %34, h34;\nmov.b32 %35, h35;\nmov.b32 %36, h36;\nmov.b32 %37, h37;\nmov.b32 %38, h38;\nmov.b32 %39, h39;\n"
        "mov.b32 %40, h40;\nmov.b32 %41, h41;\nmov.b32 %42, h42;\nmov.b32 %43, h43;\nmov.b32 %44, h44;\nmov.b32 %45, h45;\nmov.b32 %46, h46;\nmov.b32 %47, h47;\n"
        "}\n"
        : "=r"(pk[0]), "=r"(pk[1]), "=r"(pk[2]), "=r"(pk[3]), "=r"(pk[4]), "=r"(pk[5]), "=r"(pk[6]), "=r"(pk[7]), "=r"(pk[8]), "=r"(pk[9]),
          "=r"(pk[10]), "=r"(pk[11]), "=r"(pk[12]), "=r"(pk[13]), "=r"(pk[14]), "=r"(pk[15]), "=r"(pk[16]), "=r"(pk[17]), "=r"(pk[18]), "=r"(pk[19]),
          "=r"(pk[20]), "=r"(pk[21]), "=r"(pk[22]), "=r"(pk[23]), "=r"(pk[24]), "=r"(pk[25]), "=r"(pk[26]), "=r"(pk[27]), "=r"(pk[28]), "=r"(pk[29]),
          "=r"(pk[30]), "=r"(pk[31]), "=r"(pk[32]), "=r"(pk[33]), "=r"(pk[34]), "=r"(pk[35]), "=r"(pk[36]), "=r"(pk[37]), "=r"(pk[38]), "=r"(pk[39]),
          "=r"(pk[40]), "=r"(pk[41]), "=r"(pk[42]), "=r"(pk[43]), "=r"(pk[44]), "=r"(pk[45]), "=r"(pk[46]), "=r"(pk[47])
        : "r"(olp), "r"(xa), "r"(ln), "r"(lc), "r"(linc), "r"(lt), "l"(ea), "l"(sh), "l"(wf), "r"(first.x), "r"(first.y), "r"(first.z), "r"(first.w),
          "n"(sb + SM_REC), "n"(sb + SM_R), "n"(sb + SM_BAR), "n"(sb + SM_CTR), "n"(0),
          "r"(w[0]), "r"(w[1]), "r"(w[2]), "r"(w[3]), "r"(w[4]), "r"(w[5]), "r"(w[6]), "r"(w[7]), "r"(w[8]), "r"(w[9]), "r"(w[10]), "r"(w[11]),
          "r"(w[12]), "r"(w[13]), "r"(w[14]), "r"(w[15]), "r"(w[16]), "r"(w[17]), "r"(w[18]), "r"(w[19]), "r"(w[20]), "r"(w[21]), "r"(w[22]),
          "r"(w[23]), "r"(w[24]), "r"(w[25]), "r"(w[26]), "r"(w[27]), "r"(w[28]), "r"(w[29]), "r"(w[30]), "r"(w[31]), "r"(w[32]), "r"(w[33]),
          "r"(w[34]), "r"(w[35])
        : "memory");
}

__device__ __forceinline__ void wf_done() {
    asm volatile("fence.proxy.async.global;\nred.release.gpu.global.add.u32 [%0+12], 1;" ::"l"(g_sync) : "memory");
}

template <int NS>
__device__ __forceinline__ void consumer(const __nv_bfloat16* __restrict__ sh,
                                         const __nv_bfloat16* __restrict__ ea, __nv_bfloat16* __restrict__ out, int N, int npb, uint4 first) {
    uint32_t pk[NS * 16];
    {
        const int lane = threadIdx.x & 31, warp = threadIdx.x >> 5;
        const int mi = lane >> 3, r = lane & 7, j = r >> 1;
        const int u = 2 * ((mi >> 1) ^ (j >> 1)) + (r & 1), ph = (j ^ (j >> 1)) & 1;
        uint32_t w[36];
        {
            const uint32_t a = sb + SC_WR + (4 * j + (r & 1) + (mi & 2)) * 272 + (mi & 1) * 16;
#pragma unroll
            for (int c = 0; c < 8; c++)
                asm volatile("ldmatrix.sync.aligned.m8n8.x4.trans.shared.b16 {%0,%1,%2,%3}, [%4];"
                             : "=r"(w[4 * c]), "=r"(w[4 * c + 1]), "=r"(w[4 * c + 2]), "=r"(w[4 * c + 3]) : "r"(a + c * 32) : "memory");
            const uint32_t ca = sb + SC_CG + (lane & 2) * 8 + ((lane >> 2) & 3) * 2;
#pragma unroll
            for (int k = 0; k < 4; k++) {
                const uint32_t f = lds16(ca + 32 * k) | (lds16(ca + 32 * k + 8) << 16);
                w[32 + k] = (lane & 1) == (lane >> 4) ? f : 0;
            }
            asm volatile("fence.proxy.async.shared::cta;\nbar.sync 2, %0;" ::"n"(NCW * 32) : "memory");
            if (threadIdx.x < WSL) sts16(sb + SM_R + 0x1000 + (4 + SP - WSL + lane) * 2, (sb + SC_WR) / 64 + lane * 16);
        }
        const uint32_t xa = __shfl_sync(0xffffffffu, u * 128 + (((u + 4 * ph) ^ (mi & 1)) << 4), lane);
        const uint32_t ln = __shfl_sync(0xffffffffu, lane * 16 + (lane >> 3) * 4, lane);
        const uint32_t lc = __shfl_sync(0xffffffffu, j * 8 + (1 << (lane & 1)) + (ph << 12), lane);
        const uint32_t linc = __shfl_sync(0xffffffffu, (lane & 0x19) ? 0 : 4, lane);
        const uint32_t lt = __shfl_sync(0xffffffffu, lane & 3, lane);
        const void* wfp = (threadIdx.x >> 2) == WFT && blockIdx.x < 128 ? g_sync : nullptr;
        const uint32_t olp = sb + SM_OL + warp * (OLN * 2) + ((lane & 4) >> 1);
        if constexpr (NS == 4) consume4(pk, w, olp, xa, ln, lc, linc, lt, ea, sh, wfp, first);
        else consume3(pk, w, olp, xa, ln, lc, linc, lt, ea, sh, wfp, first);
    }
    const int tid = thread_id(), lane = tid & 31, warp = tid >> 5, g = lane >> 2, t = lane & 3;
    const uint32_t wc = lds32(sb + SM_MISC + 12) + 1;
    const uint32_t inv = lds32(sb + SM_INV + warp * 4);
    const int node0 = cta_id() * npb, nnodes = min(npb, N - node0);
    uint4* op[NS];
    uint32_t on[NS];
#pragma unroll
    for (int s = 0; s < NS; s++) {
        const int nl = ((inv >> (8 * s)) & 255) + (g >> 2) * 40;
        op[s] = (uint4*)(out + ((size_t)(node0 + nl) * 4 + (g & 3)) * 128 + 8 * t);
        on[s] = nl < nnodes;
    }
    if constexpr (NS == 4) project4(pk, sb + SM_R + wc * 8, sb + SM_BAR + (wc + t) * 8, op, on);
    else project3(pk, sb + SM_R + wc * 8, sb + SM_BAR + (wc + t) * 8, op, on);
}

#define RAOFF ((threadIdx.x & 96) >> 2)
#define XSTR(x) XSTR2(x)
#define XSTR2(x) #x
__device__ __forceinline__ void producer(const CUtensorMap* tmx, int pw) {
    const uint32_t nch = lds32(sb + SM_MISC + 12), c0 = lds32(sb + SM_MISC + 24);
    asm volatile("bar.sync 1, 512;" ::: "memory");
    if (elect()) {
        asm volatile(
            "{\n.reg .pred p, q, lead, never;\n.reg .b32 ra, oa, off, due, now, a<2>, b<2>, s<4>, d, r, z<8>, bar<4>, t, n, tb, ta, k64, ktx;\n"
            ".reg .b64 lg, t64, tm;\n"
            "mov.b32 ta, %5;\nld.volatile.shared.v4.b32 {z0,z1,z2,z3}, [ta+32];\nld.volatile.shared.v4.b32 {z4,z5,z6,z7}, [ta+32];\n"
            "mov.b32 ra, %9;\nmad.lo.u32 t, %0, 8, %10;\n"
            "add.u32 bar0, t, z0;\nadd.u32 bar1, t, z1;\nadd.u32 bar2, t, z2;\nadd.u32 bar3, t, z3;\nsetp.ne.u32 never, z0, 0;\n"
            "add.u32 k64, z4, 0x40000040;\nadd.u32 ktx, z5, 8192;\ncvt.u64.u32 tm, z6;\nadd.u64 tm, tm, %3;\n"
            "mov.b32 n, 0;\nld.volatile.shared.b32 tb, [ta];\nsetp.eq.u32 lead, %0, 0;\n"
            "mov.u32 due, %%globaltimer_lo;\n"
            "setp.gt.u32 p, ra, %1;\n@p bra.uni END;\nshr.u32 oa, ra, 2;\n"
            "ld.volatile.shared.u16 off, [oa+%11-8];\nadd.u32 due, tb, off;\n"
            "FIRST:\n"
            "mov.u32 now, %%globaltimer_lo;\nsub.u32 t, due, now;\n"
            "setp.gt.s32 p, t, %12;\n@p bra.uni FIRST;\n"
            "GO:\n"
            "ld.volatile.shared.v2.b32 {a0,a1}, [ra];\nld.volatile.shared.v2.b32 {b0,b1}, [ra+0x1000];\n"
            "add.u32 t, ra, ra;\nld.volatile.shared.v4.b32 {s0,s1,s2,s3}, [t+%14];\n"
            "shr.u32 oa, ra, 2;\nld.volatile.shared.u16 off, [oa+%11];\nld.volatile.shared.b32 tb, [z7+%5];\n"
            "mov.u32 now, %%globaltimer_lo;\n"
            "lop3.b32 t, a0, a1, b0, 0xfe;\nor.b32 t, t, b1;\nand.b32 t, t, 0x10001;\n"
            "setp.ne.u32 p, t, 0;\n"
            "@p bra.uni BACK;\n"
            "mbarrier.arrive.expect_tx.shared.b64 _, [ra+%13], ktx;\n"
            "add.u32 bar0, bar0, 32;\nadd.u32 bar1, bar1, 32;\nadd.u32 bar2, bar2, 32;\nadd.u32 bar3, bar3, 32;\n"
            "dp2a.lo.u32.u32 d, a0, k64, 0;\nand.b32 r, s0, 0xffff;\n"
            "cp.async.bulk.tensor.3d.shared::cluster.global.mbarrier::complete_tx::bytes [d], [tm, {z0, r, z1}], [bar0];\n"
            "dp2a.lo.u32.u32 d, b0, k64, 0;\nshr.u32 r, s0, 16;\n"
            "cp.async.bulk.tensor.3d.shared::cluster.global.mbarrier::complete_tx::bytes [d], [tm, {z2, r, z3}], [bar1];\n"
            "dp2a.hi.u32.u32 d, a0, k64, 0;\nand.b32 r, s1, 0xffff;\n"
            "cp.async.bulk.tensor.3d.shared::cluster.global.mbarrier::complete_tx::bytes [d], [tm, {z4, r, z5}], [bar2];\n"
            "dp2a.hi.u32.u32 d, b0, k64, 0;\nshr.u32 r, s1, 16;\n"
            "cp.async.bulk.tensor.3d.shared::cluster.global.mbarrier::complete_tx::bytes [d], [tm, {z6, r, z7}], [bar3];\n"
            "@never bra.uni END;\n"
            "add.u32 ra, ra, 32;\nsub.u32 t, off, now;\nadd.u32 t, t, tb;\n"
            "setp.le.u32 q, t, %2;\n"
            "dp2a.lo.u32.u32 d, a1, k64, 0;\nand.b32 r, s2, 0xffff;\n"
            "cp.async.bulk.tensor.3d.shared::cluster.global.mbarrier::complete_tx::bytes [d], [tm, {z0, r, z1}], [bar0];\n"
            "dp2a.lo.u32.u32 d, b1, k64, 0;\nshr.u32 r, s2, 16;\n"
            "cp.async.bulk.tensor.3d.shared::cluster.global.mbarrier::complete_tx::bytes [d], [tm, {z2, r, z3}], [bar1];\n"
            "dp2a.hi.u32.u32 d, a1, k64, 0;\nand.b32 r, s3, 0xffff;\n"
            "cp.async.bulk.tensor.3d.shared::cluster.global.mbarrier::complete_tx::bytes [d], [tm, {z4, r, z5}], [bar2];\n"
            "dp2a.hi.u32.u32 d, b1, k64, 0;\nshr.u32 r, s3, 16;\n"
            "cp.async.bulk.tensor.3d.shared::cluster.global.mbarrier::complete_tx::bytes [d], [tm, {z6, r, z7}], [bar3];\n"
            "@q bra.uni GO;\n"
            "add.u32 due, t, now;\nsetp.gt.u32 p, ra, %1;\n@p bra.uni END;\n@!lead bra.uni WAIT;\n"
            "and.b32 d, ra, 32;\nsetp.ne.u32 p, d, 0;\n@p bra.uni NOCP;\n"
            "add.u32 d, ta, 16;\ncp.async.bulk.shared::cluster.global.mbarrier::complete_tx::bytes [ta], [%4], 16, [d];\n"
            "NOCP:\n"
            "setp.ge.s32 p, t, 0;\n@p bra.uni WAIT;\n"
            "setp.lt.u32 p, ra, %8;\n@p bra.uni GO;\nadd.u32 r, ra, " XSTR(SLIPEND) ";\nsetp.gt.u32 p, r, %1;\n@p bra.uni GO;\n"
            "ld.volatile.shared.b64 t64, [ta];\ncvt.u32.u64 r, t64;\nsub.u32 r, tb, r;\nsub.u32 d, %7, t;\nadd.s32 d, d, r;\n"
            "cvt.s64.s32 lg, d;\nadd.u64 t64, t64, lg;\n"
            "red.relaxed.gpu.global.max.u64 [%4], t64;\n"
            "bra.uni GO;\n"
            "SLEEP:\n"
            "nanosleep.u32 32;\n"
            "WAIT:\n"
            "mov.u32 now, %%globaltimer_lo;\nsub.u32 t, due, now;\nsetp.gt.s32 p, t, %6;\n@p bra.uni SLEEP;\n"
            "setp.le.s32 p, t, %12;\n@p bra.uni GO;\n"
            "SPIN:\n"
            "mov.u32 now, %%globaltimer_lo;\nsub.u32 t, due, now;\nsetp.gt.s32 p, t, %12;\n@p bra.uni SPIN;\n"
            "bra.uni GO;\n"
            "BACK:\n"
            "nanosleep.u32 32;\nsub.u32 t, now, tb;\nsetp.lt.s32 p, t, 200000000;\n@p bra.uni GO;\n"
            "END:\n}" ::"r"(pw),
            "r"(sb + SM_R + nch * 8), "n"(AHEAD + EARLY + SLIPTH), "l"(tmx), "l"(g_sync), "n"(sb + SM_MISC + 32), "n"(SPINT + SLIPTH), "n"(SLIPADD),
            "n"(sb + SM_R + SLIPFROM * 8), "r"(sb + SM_R + 8 + c0 * 8 + RAOFF), "r"(sb + SM_BAR + 8 - 32 + c0 * 8),
            "n"(sb + SM_OFF + 8 - (sb + SM_R) / 4), "n"(EARLY + SLIPTH), "n"(SM_BAR - SM_R), "n"((int)(sb + SM_S) - (int)(sb + SM_R) * 2)
            : "memory");
        const uint32_t wch = lds32(sb + SM_MISC + 12) + 1 + pw;
        const uint32_t ra = sb + SM_R + wch * 8, bar = sb + SM_BAR + wch * 8;
        const uint32_t target = lds32(sb + SM_MISC + 16);
        uint32_t cnt = lds128(sb + SM_MISC + 32).w;
        for (int n = 0; n < 1000000 && (int)(cnt - target) < 0; n++)
            asm volatile("ld.acquire.gpu.global.u32 %0, [%1+12];" : "=r"(cnt) : "l"(g_sync) : "memory");
        uint2 a, b;
        for (int n = 0; n < 1000000; n++) {
            asm volatile("ld.volatile.shared.v2.b32 {%0,%1}, [%4];\nld.volatile.shared.v2.b32 {%2,%3}, [%4+0x1000];"
                         : "=r"(a.x), "=r"(a.y), "=r"(b.x), "=r"(b.y) : "r"(ra) : "memory");
            if (!((a.x | a.y | b.x | b.y) & 0x10001)) break;
        }
        asm volatile("fence.proxy.async.global;" ::: "memory");
        asm volatile("mbarrier.arrive.expect_tx.shared.b64 _, [%0], 8192;" ::"r"(bar) : "memory");
        const uint32_t c[8] = {a.x, a.x >> 16, a.y, a.y >> 16, b.x, b.x >> 16, b.y, b.y >> 16};
#pragma unroll
        for (int i = 0; i < 8; i++)
            asm volatile("cp.async.bulk.shared::cluster.global.mbarrier::complete_tx::bytes [%0], [%1], 1024, [%2];" ::"r"(
                             (c[i] & 0xffe) << 6),
                         "l"(g_wf + (pw * 8 + i) * 64), "r"(bar)
                         : "memory");
    }
}

#define BARINIT(w, n)                                                                                              \
    if (elect()) {                                                                                                 \
        _Pragma("unroll") for (int k = 0; k < (NBAR + n - 1) / n; k++)                                             \
            asm volatile("mbarrier.init.shared.b64 [%0], 1;" ::"r"(sb + SM_BAR + ((w) * ((NBAR + n - 1) / n) + k) * 8)); \
        asm volatile("fence.mbarrier_init.release.cluster;" ::: "memory");                                         \
    }                                                                                                              \
    __syncwarp();

__global__ void __launch_bounds__(NT, 1)
main_kernel(const __grid_constant__ CUtensorMap tmx, const __nv_bfloat16* __restrict__ x, const int* __restrict__ src,
            const int* __restrict__ dst, const __nv_bfloat16* __restrict__ sh, const __nv_bfloat16* __restrict__ ea,
            const __nv_bfloat16* __restrict__ cg, const __nv_bfloat16* __restrict__ wr,
            const __nv_bfloat16* __restrict__ wout, __nv_bfloat16* __restrict__ out, int N, int E, int npb,
            unsigned npb_magic, int chunk, unsigned wsz, unsigned wmagic, unsigned bkm, int tau, int ramp, int rampn, int tdelay, unsigned polld, int spr, int sprn) {
    extern __shared__ __align__(1024) unsigned char smem[];
    if (s2u(smem) != sb) __trap();
    const int tid = threadIdx.x, lane = tid & 31;
    const int warp = __shfl_sync(0xffffffffu, tid >> 5, 0);
    const int nbins = gridDim.x;
    bool fast = chunk > 0;
    uint4 first = make_uint4(0, 0, 0, 0);
    if (fast) {
        const int e0 = blockIdx.x * chunk + tid, left = min(E, (int)(blockIdx.x + 1) * chunk) - e0;
        uint32_t pd[KE], ps[KE];
        {
            const int* dp = dst + e0;
            const int* sp = src + e0;
#pragma unroll
            for (int k = 0; k < KE; k++) {
                pd[k] = (nbins + (k == KE - 1 ? lane : 0)) * npb, ps[k] = 0;
                asm volatile("{\n.reg .pred p;\nsetp.gt.s32 p, %4, %5;\n@p ld.global.nc.u32 %0, [%2];\n@p ld.global.nc.u32 %1, [%3];\n}"
                             : "+r"(pd[k]), "+r"(ps[k]) : "l"(dp + k * NT), "l"(sp + k * NT), "r"(left), "r"(k * NT));
            }
        }
        uint32_t epoch = 0;
        if (tid == NT - 1) asm volatile("ld.relaxed.gpu.global.u32 %0, [%1];" : "=r"(epoch) : "l"(&g_epoch) : "memory");
        uint4 wv, wo[3];
        const bool wrow = (tid >> 2) == WFT && blockIdx.x < 128;
        {
            const uint4* wp = tid < 256 ? (const uint4*)wr + tid
                              : wrow    ? (const uint4*)(wout + blockIdx.x * 128 + (tid & 3) * 32)
                                        : (const uint4*)cg + (tid & 7);
            if (tid < 264 || wrow) wv = __ldg(wp);
            if (wrow) wo[0] = __ldg(wp + 1), wo[1] = __ldg(wp + 2), wo[2] = __ldg(wp + 3);
        }
        const uint32_t t16 = sb + tid * 16;
        const uint32_t sa = sb + SC_STG + (tid >> 3) * CP + (tid & 7) * 16;
        const uint32_t sm = sb + SC_STG + (tid >> 2) * CP + (tid & 3) * 16 + 128;
        const uint32_t none = (40 * NWIN + (lane & 7) + (blockIdx.x & 3) * 8) << 2;
        const uint32_t pade = min(blockIdx.x * chunk, E - 1) << 13;
        const bool third = warp * 4 + 128 < nbins, second = warp * 8 + 128 < nbins;
#pragma unroll
        for (int k = 0; k < 3; k++)
            if (k < 2 || third) sts128(sa + k * 64 * CP, none, none, none, none);
#pragma unroll
        for (int k = 0; k < 2; k++)
            if (k < 1 || second) sts128(sm + k * 128 * CP, none, none, none, none);
        if (tid < MAXB + 32) sts32(sb + SC_CNT + tid * 4, 0);
#pragma unroll
        for (int k = 0; k < 3; k++) sts128(t16 + SC_TABB + k * NT * 16, 0, 0, 0, 0);
        const uint32_t ecomp = -(wsz * (CH << 13));
#pragma unroll
        for (int k = 0; k < 3; k++)
            sts128(t16 + SC_TMP + k * NT * 16, 0, pade + ecomp, 0, pade + ecomp);
#pragma unroll
        for (int k = 0; k < ZSL / 8; k++) sts128(t16 + k * NT * 16, 0, 0, 0, 0), sts128(t16 + SP * 1024 + PH + k * NT * 16, 0, 0, 0, 0);
        if (tid < RP / 4) {
            uint32_t c[4], d[4];
#pragma unroll
            for (int i = 0; i < 4; i++) {
                const uint32_t k = tid * 4 - 4 + i;
                c[i] = d[i] = 1;
                if (warp == 0 && k < SP) c[i] = sb / 64 + k * 16;
                if (warp == 0 && k < SP - WSL) d[i] = c[i] + (SP * 1024 + PH) / 64;
            }
            static_assert(SP + 4 <= 128, "first warp");
            sts64(sb + SM_R + tid * 8, c[0] | c[1] << 16, c[2] | c[3] << 16);
            sts64(sb + SM_R + 0x1000 + tid * 8, d[0] | d[1] << 16, d[2] | d[3] << 16);
        }
        if (tid < NOFF) sts128(t16 + SM_S, 0xf000f000u, 0xf000f000u, 0xf000f000u, 0xf000f000u);
        constexpr uint32_t OLEND = (RECN - 4) * 4 * 0x10001;
        if (tid < NCW * OLN / 8) sts128(t16 + SM_OL, OLEND, OLEND, OLEND, OLEND);
        if (warp == 12) {
            sts32(sb + SM_CTR + lane * 16 + (lane >> 3) * 4,
                  sb + SM_R + ((lane & 0x19) ? (RP - 1) * 2 : (4 + SP) * 2 + (((lane >> 1) ^ (lane >> 2)) & 1) * 0x1000 + (lane & 4) / 2));
            if (lane < 3) sts32(sb + SM_MISC + (lane ? 16 + lane * 4 : 4), 0);
            if (lane == 8) sts128(sb + SM_REC + (RECN - 4) * 4, pade, pade, pade, pade), sts128(sb + SM_MISC + 64, 0, 0, 0, 0);
            if (lane == 9) asm volatile("prefetch.tensormap [%0];" ::"l"(&tmx) : "memory");
        }
        __syncthreads();

        {
            uint32_t b[KE], r[KE];
#pragma unroll
            for (int k = 0; k < KE; k++) {
                b[k] = __umulhi(pd[k], npb_magic);
                r[k] = atoms_add(sb + SC_CNT + b[k] * 4, 4);
                if (k == KE - 1) b[k] = min(b[k], nbins);
            }
            if (tid == NT - 1) {
                sts32(sb + SM_MISC + 8, epoch % 3 + 1);
                asm volatile("{\n.reg .b64 t;\nmov.u64 t, %%globaltimer;\nred.relaxed.gpu.global.max.u64 [%0], t;\n"
                             "red.relaxed.gpu.global.add.u32 [%0+8], 1;\n}" ::"l"(g_sync) : "memory");
            }
            __syncwarp();
#pragma unroll
            for (int k = 0; k < KE; k++) {
                asm volatile(
                    "{\n.reg .pred p;\n.reg .b32 d, t, u;\nmad.lo.u32 d, %1, %3, %0;\nsetp.ge.u32 p, d, 40;\nmul.hi.u32 u, %2, %4;\n"
                    "mad.lo.u32 t, %2, %10, %5;\nmad.lo.u32 t, d, %11, t;\nmad.lo.u32 t, u, %12, t;\n@p add.u32 t, t, %7;\n"
                    "min.u32 d, %6, 188;\nmad.lo.u32 d, %1, %9, d;\nst.shared.b32 [d+%8], t;\n}" ::"r"(pd[k]),
                    "r"(b[k]), "r"(ps[k]), "r"(-npb), "r"(wmagic), "r"(((tid + k * NT) << 14) + 4), "r"(r[k]), "n"(2 - 40 * NWIN * 4),
                    "n"(sb + SC_STG), "n"(CP), "n"(CH << 14), "n"(NWIN * 4), "r"(4 - wsz * (CH << 14))
                    : "memory");
            }
        }
        if (tid < 264) sts128(sb + SC_WR + (tid >> 4) * 272 + (tid & 15) * 16, wv.x, wv.y, wv.z, wv.w);
        uint4* gp = g_cell + ((tid >> 3) * MAXB + blockIdx.x) * 8 + (tid & 7);
        uint4* gm = g_more + ((tid >> 2) * MAXB + blockIdx.x) * 4 + (tid & 3);
        __syncthreads();
        const uint32_t tag = lds32(sb + SM_MISC + 8), t0 = tag & 1, t1 = tag >> 1;
        {
            uint4 v[5];
#pragma unroll
            for (int k = 0; k < 5; k++)
                if (k != 2 && k != 4 || (k == 2 ? third : second)) v[k] = lds128(k < 3 ? sa + k * 64 * CP : sm + (k - 3) * 128 * CP);
#pragma unroll
            for (int k = 0; k < 5; k++)
                if (k != 2 && k != 4 || (k == 2 ? third : second))
                    st_cell(k < 3 ? gp + k * 64 * MAXB * 8 : gm + (k - 3) * 128 * MAXB * 4, v[k].x | t0, v[k].y | t1, v[k].z | t0, v[k].w | t1);
        }
        if (wrow) {
            const int k = blockIdx.x;
            uint4* dp = &g_wf[((tid & 3) * 8 + (k >> 4)) * 64 + (k & 8) * 4 + (k & 7)];
            dp[0] = make_uint4(wv.x, wo[0].x, wo[1].x, wo[2].x);
            dp[8] = make_uint4(wv.y, wo[0].y, wo[1].y, wo[2].y);
            dp[16] = make_uint4(wv.z, wo[0].z, wo[1].z, wo[2].z);
            dp[24] = make_uint4(wv.w, wo[0].w, wo[1].w, wo[2].w);
        }
        if (warp < 14) { BARINIT(warp, 14) }
        __syncwarp();
        if (tid == NT - 1) {
            uint4 q;
            for (int n = 0; n < (1 << 22); n++) {
                q = ld_cell((const uint4*)g_sync);
                if ((int)(q.z - (epoch + 1) * nbins) >= 0) break;
            }
            sts128(sb + SM_MISC + 32, q.x, q.y, q.z, q.w), sts32(sb + SM_MISC + 16, (epoch + 1) * 512);
            asm volatile("mbarrier.init.shared.b64 [%0], 1;" ::"r"(sb + SM_MISC + 48) : "memory");
            while ((uint32_t)(gt_lo() - q.x) < polld) {}
        }
        __syncthreads();
        uint32_t m[20], rk[20], ia[20], eb[2];
        eb[0] = (((tid >> 3) * chunk) << 13) + ecomp + 1;
        eb[1] = eb[0] + (chunk << 19);
        asm volatile("" : "+r"(eb[0]), "+r"(eb[1]));
        bool ext;
        {
            const uint4* hp = g_cell + blockIdx.x * (MAXB * 8) + tid;
            const uint4* hm = g_more + blockIdx.x * (MAXB * 4) + tid;
            uint4 q[5];
            q[2] = q[4] = make_uint4(none | t0, none | t1, none | t0, none | t1);
            for (int n = 0; n < (1 << 22); n++) {
                q[0] = ld_cell(hp), q[1] = ld_cell(hp + NT), q[3] = ld_cell(hm);
                if ((tid >> 3) + 128 < nbins) q[2] = ld_cell(hp + 2 * NT);
                if ((tid >> 2) + 128 < nbins) q[4] = ld_cell(hm + NT);
                uint32_t bad = 0;
#pragma unroll
                for (int k = 0; k < 5; k++)
                    asm("{\n.reg .b32 a, b;\nlop3.b32 a, %1, %2, %5, 0x7e;\nlop3.b32 b, %3, %4, %6, 0x7e;\nlop3.b32 %0, %0, a, b, 0xfe;\n}"
                        : "+r"(bad) : "r"(q[k].x), "r"(q[k].z), "r"(q[k].y), "r"(q[k].w), "r"(t0), "r"(t1));
                if (!(bad & 1)) break;
            }
            __syncwarp();
#pragma unroll
            for (int k = 0; k < 5; k++) m[4 * k] = q[k].x, m[4 * k + 1] = q[k].y, m[4 * k + 2] = q[k].z, m[4 * k + 3] = q[k].w;
#pragma unroll
            for (int k = 0; k < 12; k++)
                if (k < 8 || third) ia[k] = m[k] & 0x3ffc, rk[k] = atoms_add(sb + SC_TABB + ia[k], 8);
            ext = __any_sync(0xffffffffu, min(m[12] & 0x3ffc, m[16] & 0x3ffc) < 40 * NWIN * 4);
            if (ext) {
#pragma unroll
                for (int k = 12; k < 20; k++) ia[k] = m[k] & 0x3ffc, rk[k] = atoms_add(sb + SC_TABB + ia[k], 8);
                if ((tid & 3) == 3 && min(m[15] & 0x3ffc, m[19] & 0x3ffc) < 40 * NWIN * 4) sts32(sb + SM_MISC + 4, 1);
            }
        }
        __syncthreads();
        const uint32_t tr = sb + warp * (NWIN * 4) + lane * 16;
        if (tid >= NT - PFT) {
            const int i = NT - 1 - tid;
            const char* p = i < 76 ? (const char*)sh + (size_t)min(blockIdx.x * chunk + i * 32, E - 32) * 8
                                   : (const char*)ea + (size_t)min(blockIdx.x * chunk + (i - 76) * 8, E - 8) * 32;
            asm volatile("prefetch.global.L2 [%0];\nprefetch.global.L2 [%0+128];" ::"l"(p));
        }
        if (tid == NT - 1 && blockIdx.x == 0) g_epoch = epoch + 1;
        {
            uint4 c[3];
            uint32_t tt[3];
#pragma unroll
            for (int i = 0; i < 3; i++) {
                c[i] = make_uint4(0, 0, 0, 0);
                if ((i < 2 || warp < 8) && lane < NWIN / 4) c[i] = lds128(tr + SC_TABB + i * 16 * NWIN * 4);
                tt[i] = c[i].x + c[i].y + c[i].z + c[i].w;
            }
            const uint32_t sum = (tt[0] >> 3) + (tt[1] << 7) + (tt[2] << 17);
            const uint32_t tot = __reduce_add_sync(0xffffffffu, sum);
            uint32_t inc = scan_step(scan_step(sum, 1), 2);
            const uint32_t q = (tot + 0x300c03) & 0x3fcff3fc, q0 = q & 1023, q1 = q0 + ((q >> 10) & 1023);
            uint32_t base = atoms_add(sb + (lane ? SC_CNT + lane * 4 : SM_MISC + 20), q1 + (q >> 20));
            inc = scan_step(scan_step(scan_step(inc, 4), 8), 16);
            base = __shfl_sync(0xffffffffu, base, 0);
            const uint32_t l3 = min(lane, 2);
            sts32(sb + SC_KEY + (warp + 16 * l3) * 4, ((tot >> (10 * l3)) & 1023) * 64 + 63 - warp - 16 * l3);
            if (max(tt[0], max(tt[1], tt[2])) > 31 * 8) sts32(sb + SM_MISC + 4, 1);
            inc += q - tot - sum;
#pragma unroll
            for (int i = 0; i < 3; i++) {
                const uint32_t e = (((inc >> (10 * i)) & 1023) + base + (i == 0 ? 0 : i == 1 ? q0 : q1)) * 8;
                if ((i < 2 || warp < 8) && lane < NWIN / 4) sts128(tr + SC_TABB + i * 16 * NWIN * 4, e, e + c[i].x, e + c[i].x + c[i].y, e + tt[i] - c[i].w);
            }
        }
        __syncthreads();
        if (warp >= 11) {
            const uint32_t st = (tid - 352) >> 2, key = lds32(sb + SC_KEY + st * 4);
            uint32_t rank = 0;
#pragma unroll
            for (int i = 0; i < 5; i++) {
                const uint2 q = lds64(sb + SC_KEY + (lane & 3) * 40 + i * 8);
                rank += ((key - q.x) >> 31) + ((key - q.y) >> 31);
            }
            rank += __shfl_xor_sync(0xffffffffu, rank, 1);
            rank += __shfl_xor_sync(0xffffffffu, rank, 2);
            const uint32_t lv = rank >> 2, cw = ((0x969u >> (2 * lv)) & 3) * 4 + ((rank ^ -(lv & 1)) & 3);
            const uint32_t sid = (0xe4a50u >> (2 * lv)) & 3;
            sts32(sb + SC_MAP + st * 4, cw * (NWIN * 4) - st * (NWIN * 4) + 0x10000 + (sid << 30));
            asm volatile("st.shared.u8 [%0], %1;" ::"r"(sb + SM_INV + cw * 4 + sid), "r"(st) : "memory");
        }
        const int total = lds32(sb + SM_MISC + 20);
        fast = lds32(sb + SM_MISC + 4) == 0 && total <= RECN - 4;
        auto lookup = [&](int k) {
            asm volatile("{\n.reg .pred p;\n.reg .b32 t;\nsetp.lt.u32 p, %1, %2;\nmov.b32 t, 0x80000000;\n@p ld.shared.b32 t, [%1+%3];\nadd.u32 %0, %0, t;\n}"
                         : "+r"(rk[k]) : "r"(ia[k]), "n"(40 * NWIN * 4), "n"(sb + SC_TABB) : "memory");
        };
        auto place = [&](int k, uint32_t e) {
            asm volatile("{\n.reg .pred p;\nsetp.ge.s32 p, %0, 0;\n@p st.shared.v2.b32 [%0+%3], {%1, %2};\n}" ::"r"(rk[k]), "r"(m[k]), "r"(e),
                         "n"(sb + SC_TMP) : "memory");
        };
#pragma unroll
        for (int k = 0; k < 8; k++) lookup(k);
        if (fast) {
#pragma unroll
            for (int k = 0; k < 8; k++) place(k, eb[k >> 2]);
            if (third) {
#pragma unroll
                for (int k = 8; k < 12; k++) lookup(k);
#pragma unroll
                for (int k = 8; k < 12; k++) place(k, 2 * eb[1] - eb[0]);
            }
            if (ext) {
#pragma unroll
                for (int k = 12; k < 20; k++) lookup(k);
#pragma unroll
                for (int k = 12; k < 20; k++) place(k, ((((tid >> 2) + (k >> 4) * 128) * chunk) << 13) + ecomp + 1);
            }
            constexpr int KD = (RECN + NT - 1) / NT;
            const uint32_t P = (lane ^ (lane >> 1)) & 1;
            const uint32_t binc = (P ? 1u << 11 : 1u) + ((lane & 3) == 3 ? 1u << 22 : 0u);
            const bool last = warp * 32 + (KD - 1) * NT < total, q2 = warp * 128 + NT * 4 < total;
            const int rest = total - tid, restq = (total >> 2) - tid;
            uint2 en[KD];
            uint32_t bk[KD], r2[KD], ca[2], ol[2], r3[2];
            __syncthreads();
#pragma unroll
            for (int k = 0; k < KD; k++)
                if (k < KD - 1 || last) en[k] = lds64(sb + SC_TMP + tid * 8 + k * NT * 8);
#pragma unroll
            for (int k = 0; k < 2; k++)
                if (k == 0 || q2) ca[k] = lds32(sb + SC_TMP + (tid + k * NT) * 32 + 24);
#pragma unroll
            for (int k = 0; k < 2; k++)
                if (k == 0 || q2) ca[k] &= 0x3ffc, ol[k] = lds32(sb + SC_MAP + __umulhi(ca[k], 0xffffffffu / (NWIN * 4) + 1) * 4);
#pragma unroll
            for (int k = 0; k < KD; k++) {
                if (k < KD - 1 || last) {
                    const uint32_t v = en[k].x, f = v >> 14, i = v & 0x3ffc;
                    const uint32_t w4 = i - __umulhi(i, 0xffffffffu / (NWIN * 4) + 1) * (NWIN * 4);
                    const uint32_t o = __umulhi(f, 0xffffffffu / CH + 1) - wsz;
                    bk[k] = (__umulhi(f, bkm) + w4) * 4;
                    en[k].x = w4 * wsz + o * 4;
                    en[k].y += ((v >> 1) & 0xffffe001u) - o * (CH << 13);
                    if (rest <= k * NT) bk[k] = 2048 + lane * 4;
                    r2[k] = atoms_add(sb + SC_TABA + bk[k], binc);
                }
            }
#pragma unroll
            for (int k = 0; k < 2; k++) {
                if (k == 0 || q2) {
                    ca[k] = (ca[k] + ol[k]) & 0xffff;
                    ol[k] = (tid + k * NT) * 16 + (ol[k] >> 30 << 14);
                    r3[k] = atoms_add(sb + SC_TABC + ca[k], restq > k * NT ? 2 : 0);
                }
            }
            __syncthreads();
            if (warp < NCW) {
                uint4 c = make_uint4(0, 0, 0, 0);
                if (lane < NWIN / 4) c = lds128(tr + SC_TABC);
                const uint32_t tt = c.x + c.y + c.z + c.w;
                uint32_t inc = tt;
#pragma unroll
                for (int o = 1; o < 32; o <<= 1) inc = scan_step(inc, o);
                if (inc > (OLN - 8) * 2) sts32(sb + SM_MISC + 4, 1);
                inc += warp * (OLN * 2) - tt;
                if (lane < NWIN / 4) sts128(tr + SC_TABC, inc, inc + c.x, inc + c.x + c.y, inc + tt - c.w);
            } else {
                const uint32_t mine = (warp + lane) & 3;
                uint4 c;
                uint32_t cs, inc = 0, e = 4 + (4 << 11);
#pragma unroll
                for (int i = 0; i < 4; i++) {
                    const uint32_t pc = (mine + i) & 3;
                    const uint4 v = lds128(sb + SC_TABA + lane * 64 + (pc << 4));
                    const uint32_t sum = v.x + v.y + v.z + v.w;
                    inc += sum;
                    if (i == 0) c = v, cs = sum;
                    if (pc >= mine) e -= sum;
                }
#pragma unroll
                for (int o = 1; o < 32; o <<= 1) inc = scan_step(inc, o);
                e += inc;
                sts128(sb + SC_TABB + lane * 64 + (mine << 4), e, e + c.x, e + c.x + c.y, e + cs - c.w);
                if ((int)max((e + cs) & 0x7ff, ((e + cs) >> 11) & 0x7ff) - (int)(e >> 22) * 2 > SP) sts32(sb + SM_MISC + 4, 1);
                if (tid == NCW * 32) {
                    const uint32_t c0 = min(min(c.x & 0x7ff, (c.x >> 11) & 0x7ff), ZSL) >> 2;
                    sts32(sb + SM_MISC + 12, ((total >> 2) + 1) >> 1), sts32(sb + SM_MISC + 24, c0);
                }
            }
            __syncthreads();
            fast = lds32(sb + SM_MISC + 4) == 0;
            if (warp == 15 && lane < lds32(sb + SM_MISC + 24))
                asm volatile("mbarrier.arrive.shared.b64 _, [%0];" ::"r"(sb + SM_BAR + 8 + lane * 8) : "memory");
#pragma unroll
            for (int k = 0; k < KD; k++)
                if (k < KD - 1 || last) r2[k] += lds32(sb + SC_TABB + bk[k]);
#pragma unroll
            for (int k = 0; k < 2; k++)
                if (k == 0 || q2) r3[k] += lds32(sb + SC_TABC + ca[k]);
            if (fast) {
                const uint32_t rot = P ? 9 : 30;
#pragma unroll
                for (int k = 0; k < KD; k++) {
                    if (k < KD - 1 || last) {
                        const uint32_t k4 = __funnelshift_r(r2[k], r2[k], rot);
                        if (rest > k * NT) {
                            sts16(sb + SM_S + bitsel(k4, P << 1), en[k].x);
                            sts32(sb + SM_REC + tid * 4 + k * NT * 4, bitsel(k4, en[k].y));
                        }
                    }
                }
#pragma unroll
                for (int k = 0; k < 2; k++)
                    if ((k == 0 || q2) && restq > k * NT) sts16(sb + SM_OL + r3[k], ol[k]);
            }
        }
        asm volatile("fence.mbarrier_init.release.cluster;\nfence.proxy.async.shared::cta;" ::: "memory");
        __syncthreads();
        if (!fast && wrow) wf_done();
        if (fast && tid < NOFF) {
            const uint4 a = lds128(t16 + SM_S);
            uint32_t sum = 0;
            sum = __dp2a_lo(__vadd2(a.x, 0x10001000u), 0x101u, sum), sum = __dp2a_lo(__vadd2(a.y, 0x10001000u), 0x101u, sum);
            sum = __dp2a_lo(__vadd2(a.z, 0x10001000u), 0x101u, sum), sum = __dp2a_lo(__vadd2(a.w, 0x10001000u), 0x101u, sum);
            const int s = (int)(sum >> 5) - 0x400;
            sts16(sb + SM_OFF + tid * 2, tid > lds32(sb + SM_MISC + 12) ? 0 : min(max(tdelay + SLIPTH + ((s * tau + min(s, rampn) * ramp - max(s - sprn, 0) * spr) >> 10), 0), 0xffff));
        }
        __syncwarp();
        if (fast && warp < NCW) {
            asm volatile("bar.arrive 1, 512;" ::: "memory");
            const uint32_t e = lds16(sb + SM_OL + warp * (OLN * 2) + ((lane & 4) >> 1));
            const uint32_t rec = lds32(sb + SM_REC + (e & 0x3ff0) + (lane >> 3) * 4);
            first.w = ((rec >> 1) & 0xffe) | (e & ~0xffeu);
            asm volatile("{\n.reg .pred q;\nsetp.ne.u32 q, %5, 0;\nld.global.cg.v2.b32 {%0,%1}, [%3];\n@q ld.global.cg.b32 %2, [%4];\n}"
                         : "=r"(first.x), "=r"(first.y), "+r"(first.z)
                         : "l"(ea + (size_t)(rec >> 13) * 16 + (lane & 3) * 4), "l"(sh + (size_t)(rec >> 13) * 4 + (lane & 2)), "r"(rec & (1 << (lane & 1))));
        }
    }

    if (!fast) {
        float* accs = (float*)smem;
        constexpr int NACC = 96;
        const int node0 = blockIdx.x * npb, nnodes = max(0, min(npb, N - node0));
#pragma unroll 1
        for (int nb = 0; nb < nnodes; nb += NACC) {
            __syncthreads();
            for (int i = tid; i < NACC * 512; i += NT) accs[i] = 0.f;
            __syncthreads();
            const int lim = min(NACC, nnodes - nb);
#pragma unroll 1
            for (int base = warp * 32; base < E; base += NT) {
                const int e = base + lane;
                const int dl = e < E ? dst[e] - node0 - nb : -1;
                unsigned mask = __ballot_sync(0xffffffffu, dl >= 0 && dl < lim);
#pragma unroll 1
                while (mask) {
                    const int l = __ffs(mask) - 1;
                    mask &= mask - 1;
                    const int dd = __shfl_sync(0xffffffffu, dl, l);
                    slow_edge(base + l, src[base + l], accs + dd * 512, x, sh, ea, cg, wr, lane);
                }
            }
            __syncthreads();
#pragma unroll 1
            for (int nl = warp; nl < lim; nl += NT / 32) slow_out(accs + nl * 512, wout, out + (size_t)(node0 + nb + nl) * 512, lane);
        }
    } else if (warp >= NCW) {
        asm volatile("setmaxnreg.dec.sync.aligned.u32 %0;" ::"n"(PREG));
        producer(&tmx, warp - NCW);
    } else if (warp >= 4) {
        asm volatile("setmaxnreg.inc.sync.aligned.u32 %0;" ::"n"(R1));
        consumer<3>(sh, ea, out, N, npb, first);
    } else {
        asm volatile("setmaxnreg.inc.sync.aligned.u32 %0;" ::"n"(R0));
        consumer<4>(sh, ea, out, N, npb, first);
    }
}

typedef CUresult (*EncodeTiledFn)(CUtensorMap*, CUtensorMapDataType, cuuint32_t, void*, const cuuint64_t*,
                                  const cuuint64_t*, const cuuint32_t*, const cuuint32_t*, CUtensorMapInterleave,
                                  CUtensorMapSwizzle, CUtensorMapL2promotion, CUtensorMapFloatOOBfill);

extern "C" void kernel_launch(void* const* d_in, const int* in_sizes, int n_in, void* d_out, int out_size) {
    const __nv_bfloat16* x = (const __nv_bfloat16*)d_in[0];
    const int* src = (const int*)d_in[1];
    const int* dst = (const int*)d_in[2];
    const __nv_bfloat16* sh = (const __nv_bfloat16*)d_in[3];
    const __nv_bfloat16* ea = (const __nv_bfloat16*)d_in[4];
    const __nv_bfloat16* cg = (const __nv_bfloat16*)d_in[5];
    const __nv_bfloat16* wr = (const __nv_bfloat16*)d_in[6];
    const __nv_bfloat16* wout = (const __nv_bfloat16*)d_in[7];
    __nv_bfloat16* out = (__nv_bfloat16*)d_out;
    const int N = in_sizes[0] / 512;
    const int E = in_sizes[1];

    static int num_sms = 0, coresident = 0;
    static EncodeTiledFn encode = nullptr;
    if (num_sms == 0) {
        int dev = 0;
        cudaGetDevice(&dev);
        cudaDeviceGetAttribute(&num_sms, cudaDevAttrMultiProcessorCount, dev);
        cudaFuncSetAttribute(main_kernel, cudaFuncAttributeMaxDynamicSharedMemorySize, SM_TOTAL);
        int occ = 0;
        cudaOccupancyMaxActiveBlocksPerMultiprocessor(&occ, main_kernel, NT, SM_TOTAL);
        coresident = occ * num_sms;
        void* fn = nullptr;
        cudaDriverEntryPointQueryResult qr;
        cudaGetDriverEntryPoint("cuTensorMapEncodeTiled", &fn, cudaEnableDefault, &qr);
        encode = (EncodeTiledFn)fn;
    }
    CUtensorMap tmx;
    const int rank = 3;
    const cuuint64_t gd[3] = {64, (cuuint64_t)N * 4, 2}, gs[2] = {256, 128};
    const cuuint32_t bd[3] = {64, 4, 2}, es[3] = {1, 1, 1};
    encode(&tmx, CU_TENSOR_MAP_DATA_TYPE_BFLOAT16, rank, (void*)x, gd, gs, bd, es, CU_TENSOR_MAP_INTERLEAVE_NONE,
           CU_TENSOR_MAP_SWIZZLE_128B, CU_TENSOR_MAP_L2_PROMOTION_NONE, CU_TENSOR_MAP_FLOAT_OOB_FILL_NONE);

    int nbins = num_sms < MAXB ? num_sms : MAXB;
    int npb = (N + nbins - 1) / nbins;
    if (npb < 2) npb = 2;
    nbins = (N + npb - 1) / npb;
    const unsigned npb_magic = (unsigned)((0x100000000ull + npb - 1) / npb);
    int chunk = (E + nbins - 1) / nbins;
    const unsigned wsz = (N + NWIN - 2) / (NWIN - 1);
    if (nbins > coresident || nbins < 128 || npb > MAXNPB || chunk > CH || wsz > (1 << 18) / CH || N < 512 || E < 32 || E > (1 << 19)) chunk = 0;
    const unsigned wmagic = 0xffffffffu / wsz + 1, bkm = (unsigned)((4ull << 32) / (wsz * CH));
    double pace = PACE, rampt = RAMP, rampf = RAMPF, sprt = SPRINT, sprf = SPRINTF;
    int tdelay = TDELAY, polld = POLLD;
    const int tau = (int)(1024.0 * pace * ((double)E / nbins) / N);
    const int rampn = (int)(N * rampf), ramp = (int)(1024.0 * rampt / rampn);
    main_kernel<<<nbins, NT, SM_TOTAL, cudaStreamPerThread>>>(tmx, x, src, dst, sh, ea, cg, wr, wout, out, N, E, npb, npb_magic,
                                                              chunk, wsz, wmagic, bkm, tau, ramp, rampn, tdelay, polld, (int)(1024.0 * sprt / (N * sprf)), (int)(N * (1 - sprf)));
}
```
